```python
import torch

def _softmax(x, axis=-1):
    return torch.softmax(x, dim=axis)

def _gelu(x):
    return torch.nn.functional.gelu(x, approximate='tanh')

def _silu(x):
    return torch.nn.functional.silu(x)

def _sigmoid(x):
    return torch.sigmoid(x)

def _layernorm(x, axis=-1, eps=1e-05):
    m = x.mean(dim=axis, keepdim=True)
    v = x.var(dim=axis, keepdim=True, unbiased=False)
    return (x - m) / torch.sqrt(v + eps)

def _scatter_add(tgt, idx, src, axis=0):
    return tgt.clone().index_add_(axis, idx, src)

def _segment_sum(src, seg, n):
    out = torch.zeros((n,) + src.shape[1:], dtype=src.dtype)
    return out.index_add_(0, seg, src)

def _pad(x, pw):
    flat = tuple((v for pair in reversed(pw) for v in pair))
    return torch.nn.functional.pad(x, flat)
kernel_name = 'interleave_layers__spectral_gfnet__memory_aug_recurrent_mem_tr__prompt'

def setup_inputs():

    _w = lambda a: (lambda t: t.to(torch.bfloat16) if t.is_floating_point() else t)(torch.as_tensor(a))

    def _A_setup():
        B, S, D = (1, 2048, 640)
        Df = D // 2 + 1
        return {'x': _w((lambda *s: torch.randn(*s, dtype=torch.bfloat16) * 0.05)(B, S, D)), 'w_r': _w((lambda *s: torch.randn(*s, dtype=torch.bfloat16) * 0.4)(S, Df) * 0.02), 'w_i': _w((lambda *s: torch.randn(*s, dtype=torch.bfloat16) * 0.4)(S, Df) * 0.02)}
    _A_in = _A_setup()

    def _B_setup():
        B, S, Dm = (1, 2048, 640)
        H, Dh = (32, 128)
        M, seg = (8, 32)
        seg = min(seg, S)
        S = S // seg * seg
        return {'x': _w((lambda *s: torch.randn(*s, dtype=torch.bfloat16) * 0.05)(B, S, Dm)), 'mem0': _w((lambda *s: torch.randn(*s, dtype=torch.bfloat16) * 0.2)(B, M, Dm)), 'Wq': _w((lambda *s: torch.randn(*s, dtype=torch.bfloat16) * 1.6)(Dm, H, Dh) * Dm ** (-0.5)), 'Wk': _w((lambda *s: torch.randn(*s, dtype=torch.bfloat16) * 1.6)(Dm, H, Dh) * Dm ** (-0.5)), 'Wv': _w((lambda *s: torch.randn(*s, dtype=torch.bfloat16) * 0.2)(Dm, H, Dh) * Dm ** (-0.5)), 'Wo': _w((lambda *s: torch.randn(*s, dtype=torch.bfloat16) * 0.2)(H, Dh, Dm) * (H * Dh) ** (-0.5)), 'seg_len': seg}
    _B_in = _B_setup()
    return {'A_x': _A_in['x'], 'A_w_r': _A_in['w_r'], 'A_w_i': _A_in['w_i'], 'B_x': _B_in['x'], 'B_mem0': _B_in['mem0'], 'B_Wq': _B_in['Wq'], 'B_Wk': _B_in['Wk'], 'B_Wv': _B_in['Wv'], 'B_Wo': _B_in['Wo'], 'B_seg_len': _B_in['seg_len']}

def reference(A_x, A_w_r, A_w_i, B_x, B_mem0, B_Wq, B_Wk, B_Wv, B_Wo, B_seg_len):

    def _A_ref(x, w_r, w_i):
        B, S, D = x.shape
        X = (lambda x, axes=(-2, -1): torch.fft.rfft2(x.float(), dim=axes))(x, axes=(-2, -1))
        W = w_r + 1j * w_i
        X = X * W
        y = (lambda x, s, axes=(-2, -1): torch.fft.irfft2(x, s=s, dim=axes).to(torch.bfloat16))(X, (S, D), axes=(-2, -1))
        return y

    def _B_ref(x, mem0, Wq, Wk, Wv, Wo, seg_len):
        B, S, Dm = x.shape
        H, Dh = (Wq.shape[1], Wq.shape[2])
        M = mem0.shape[1]
        scale = Dh ** (-0.5)
        n_seg = S // seg_len
        L = M + seg_len
        idx = torch.arange(L)
        mask = (idx[:, None] < M) | (idx[:, None] >= idx[None, :])
        mem = mem0
        outs = []
        for s in range(n_seg):
            xs = x[:, s * seg_len:(s + 1) * seg_len, :].clone()
            h = torch.concatenate([mem, xs], axis=1)
            q = torch.einsum('btd,dhe->bhte', h, Wq)
            k = torch.einsum('btd,dhe->bhte', h, Wk)
            v = torch.einsum('btd,dhe->bhte', h, Wv)
            scores = torch.einsum('bhqe,bhke->bhqk', q, k) * scale
            scores = torch.where(mask[None, None], scores, -1000000000.0)
            p = _softmax(scores, axis=-1)
            o = torch.einsum('bhqk,bhke->bhqe', p, v)
            o = torch.einsum('bhte,hed->btd', o, Wo)
            mem = o[:, :M, :].clone()
            outs.append(o[:, M:, :])
        return torch.concatenate(outs, axis=1)
    x = A_x
    x = x + _A_ref(_layernorm(x, axis=-1), A_w_r, A_w_i)
    x = x + _B_ref(_layernorm(x, axis=-1), B_mem0, B_Wq, B_Wk, B_Wv, B_Wo, B_seg_len)
    x = x + _A_ref(_layernorm(x, axis=-1), A_w_r, A_w_i)
    x = x + _B_ref(_layernorm(x, axis=-1), B_mem0, B_Wq, B_Wk, B_Wv, B_Wo, B_seg_len)
    return x
```

```cpp
#include <cuda_runtime.h>
#include <cuda_bf16.h>
#include <cuda.h>
#include <stdint.h>
typedef __nv_bfloat16 bf16;
constexpr int S_ = 2048, D_ = 640, H_ = 32, DH = 128, NSEG = 64;

__device__ __forceinline__ uint32_t smem_u32(const void* p) { return (uint32_t)__cvta_generic_to_shared(p); }
__device__ __forceinline__ uint32_t pack_bf16(float lo, float hi) { uint32_t r; asm("cvt.rn.bf16x2.f32 %0, %1, %2;" : "=r"(r) : "f"(hi), "f"(lo)); return r; }
__device__ __forceinline__ float bf_lo(uint32_t v) { return __uint_as_float(v << 16); }
__device__ __forceinline__ float bf_hi(uint32_t v) { return __uint_as_float(v & 0xFFFF0000u); }
__device__ __forceinline__ void ldsm4t(uint32_t& r0, uint32_t& r1, uint32_t& r2, uint32_t& r3, uint32_t a) {
  asm volatile("ldmatrix.sync.aligned.m8n8.x4.trans.shared.b16 {%0,%1,%2,%3}, [%4];" : "=r"(r0), "=r"(r1), "=r"(r2), "=r"(r3) : "r"(a) : "memory");
}
__device__ __forceinline__ void ldsm4(uint32_t& r0, uint32_t& r1, uint32_t& r2, uint32_t& r3, uint32_t a) {
  asm volatile("ldmatrix.sync.aligned.m8n8.x4.shared.b16 {%0,%1,%2,%3}, [%4];" : "=r"(r0), "=r"(r1), "=r"(r2), "=r"(r3) : "r"(a) : "memory");
}
__device__ __forceinline__ void mma16816(float* d, uint32_t a0, uint32_t a1, uint32_t a2, uint32_t a3, uint32_t b0, uint32_t b1) {
  asm volatile("mma.sync.aligned.m16n8k16.row.col.f32.bf16.bf16.f32 {%0,%1,%2,%3}, {%4,%5,%6,%7}, {%8,%9}, {%0,%1,%2,%3};"
    : "+f"(d[0]), "+f"(d[1]), "+f"(d[2]), "+f"(d[3]) : "r"(a0), "r"(a1), "r"(a2), "r"(a3), "r"(b0), "r"(b1));
}
__device__ __forceinline__ void mma16816z(float* d, uint32_t a0, uint32_t a1, uint32_t a2, uint32_t a3, uint32_t b0, uint32_t b1) {
  asm volatile("mma.sync.aligned.m16n8k16.row.col.f32.bf16.bf16.f32 {%0,%1,%2,%3}, {%4,%5,%6,%7}, {%8,%9}, {%10,%10,%10,%10};"
    : "=f"(d[0]), "=f"(d[1]), "=f"(d[2]), "=f"(d[3]) : "r"(a0), "r"(a1), "r"(a2), "r"(a3), "r"(b0), "r"(b1), "f"(0.f));
}
__device__ __forceinline__ void mma1688z(float* d, uint32_t a0, uint32_t a1, uint32_t b0) {
  asm volatile("mma.sync.aligned.m16n8k8.row.col.f32.bf16.bf16.f32 {%0,%1,%2,%3}, {%4,%5}, {%6}, {%7,%7,%7,%7};"
    : "=f"(d[0]), "=f"(d[1]), "=f"(d[2]), "=f"(d[3]) : "r"(a0), "r"(a1), "r"(b0), "f"(0.f));
}
__device__ __forceinline__ void mma1688(float* d, uint32_t a0, uint32_t a1, uint32_t b0) {
  asm volatile("mma.sync.aligned.m16n8k8.row.col.f32.bf16.bf16.f32 {%0,%1,%2,%3}, {%4,%5}, {%6}, {%0,%1,%2,%3};"
    : "+f"(d[0]), "+f"(d[1]), "+f"(d[2]), "+f"(d[3]) : "r"(a0), "r"(a1), "r"(b0));
}
__device__ __forceinline__ void mmaA(float* d, const uint32_t* a, uint32_t b0, uint32_t b1) { mma16816(d, a[0], a[1], a[2], a[3], b0, b1); }
__device__ __forceinline__ void mmaZ(float* d, const uint32_t* a, uint32_t b0, uint32_t b1) { mma16816z(d, a[0], a[1], a[2], a[3], b0, b1); }
__device__ __forceinline__ uint32_t movm(uint32_t a) { uint32_t d; asm volatile("movmatrix.sync.aligned.m8n8.trans.b16 %0, %1;" : "=r"(d) : "r"(a)); return d; }
__device__ __forceinline__ void cp_async16(uint32_t dst, const void* src) { asm volatile("cp.async.cg.shared.global [%0], [%1], 16;" :: "r"(dst), "l"(src) : "memory"); }
__device__ __forceinline__ void cp_commit() { asm volatile("cp.async.commit_group;" ::: "memory"); }
template <int N> __device__ __forceinline__ void cp_wait() { asm volatile("cp.async.wait_group %0;" :: "n"(N) : "memory"); }
__device__ __forceinline__ void lds128(uint32_t* r, uint32_t a) { asm volatile("ld.shared.v4.b32 {%0,%1,%2,%3}, [%4];" : "=r"(r[0]), "=r"(r[1]), "=r"(r[2]), "=r"(r[3]) : "r"(a) : "memory"); }
__device__ __forceinline__ void sts128(uint32_t a, uint32_t r0, uint32_t r1, uint32_t r2, uint32_t r3) { asm volatile("st.shared.v4.b32 [%0], {%1,%2,%3,%4};" :: "r"(a), "r"(r0), "r"(r1), "r"(r2), "r"(r3) : "memory"); }
__device__ __forceinline__ void stg128(void* p, uint32_t r0, uint32_t r1, uint32_t r2, uint32_t r3) { asm volatile("st.global.v4.b32 [%0], {%1,%2,%3,%4};" :: "l"(p), "r"(r0), "r"(r1), "r"(r2), "r"(r3) : "memory"); }
template <int ID, int N> __device__ __forceinline__ void bar_sync() { asm volatile("bar.sync %0, %1;" :: "n"(ID), "n"(N) : "memory"); }
template <int ID, int N> __device__ __forceinline__ void bar_arrive() { asm volatile("bar.arrive %0, %1;" :: "n"(ID), "n"(N) : "memory"); }
__device__ __forceinline__ void mbar_wait(uint32_t bar, uint32_t parity) {
  asm volatile("{\n.reg .pred p, pq;\n.reg .u32 n;\nmov.u32 n, 0;\nLW%=:\nmbarrier.try_wait.parity.shared::cta.b64 p, [%0], %1;\n@p bra.uni LD%=;\nadd.u32 n, n, 1;\nsetp.lt.u32 pq, n, 20000;\n@pq bra.uni LW%=;\nLD%=:\n}" :: "r"(bar), "r"(parity) : "memory");
}
#define mbar_wait_long mbar_wait
__device__ __forceinline__ void mbar_init(uint32_t bar, int n) { asm volatile("mbarrier.init.shared.b64 [%0], %1;" :: "r"(bar), "r"(n) : "memory"); }
__device__ __forceinline__ void mbar_expect(uint32_t bar, int bytes) { asm volatile("mbarrier.arrive.expect_tx.shared.b64 _, [%0], %1;" :: "r"(bar), "r"(bytes) : "memory"); }
__device__ __forceinline__ void mbar_arrive(uint32_t bar) { asm volatile("mbarrier.arrive.shared.b64 _, [%0];" :: "r"(bar) : "memory"); }
__device__ __forceinline__ void l2_prefetch(const void* p, int bytes) { asm volatile("cp.async.bulk.prefetch.L2.global [%0], %1;" :: "l"(p), "r"(bytes) : "memory"); }
__device__ __forceinline__ float ex2(float x) { float y; asm("ex2.approx.ftz.f32 %0, %1;" : "=f"(y) : "f"(x)); return y; }
__device__ __forceinline__ void pdl_wait() { asm volatile("griddepcontrol.wait;" ::: "memory"); }
__device__ __forceinline__ void pdl_launch() { asm volatile("griddepcontrol.launch_dependents;" ::: "memory"); }
template <int N> __device__ __forceinline__ void cs2pi(int idx, float& c, float& s) {
  int r = (int)((unsigned)idx % N); if (r > N / 2) r -= N;
  const float a = (float)r * (6.283185307179586f / N);
  asm volatile("cos.approx.ftz.f32 %0, %1;" : "=f"(c) : "f"(a)); asm volatile("sin.approx.ftz.f32 %0, %1;" : "=f"(s) : "f"(a));
}
__device__ __forceinline__ void sched_fence() { asm volatile("{\n.reg .pred p;\n.reg .u32 t;\nLF%=:\nmov.u32 t, %%clock;\nsetp.eq.u32 p, t, %0;\n@p bra.uni LF%=;\n}" :: "n"(12345) : "memory"); }
#define TL_MIN(id, k)
#define TL_MAX(id, k)
#define TLP
#define TLA(x)

template <int SG> __device__ __forceinline__ void f16_frags(int g, int q, uint32_t* fr, uint32_t* fi, uint32_t* nfi) {
#pragma unroll
  for (int i = 0; i < 4; i++) {
    const int k = g + 8 * (i & 1), a = 2 * q + 8 * (i >> 1);
    float c0, s0, c1, s1; cs2pi<16>(k * a, c0, s0); cs2pi<16>(k * (a + 1), c1, s1);
    fr[i] = pack_bf16(c0, c1); fi[i] = pack_bf16(SG * s0, SG * s1); nfi[i] = fi[i] ^ 0x80008000u;
  }
}
template <int SG> __device__ __forceinline__ void f40_table(uint2* tab, int tid) {
  for (int i = tid; i < 800; i += 256) {
    const int lane = i & 31, tu = i >> 5, t = tu / 5, u = tu % 5, b = 8 * t + 2 * (lane & 3), k = 8 * u + (lane >> 2);
    float c0, s0, c1, s1; cs2pi<40>(b * k, c0, s0); cs2pi<40>((b + 1) * k, c1, s1);
    tab[i] = make_uint2(pack_bf16(c0, c1), pack_bf16(-SG * s0, -SG * s1));
  }
}
template <int SG> __device__ __forceinline__ void fft640(uint32_t plane, uint32_t tab, int lane, const uint32_t* fr, const uint32_t* fi, const uint32_t* nfi,
                                                         const float (*tc)[4], const float (*ts)[4], float (*xr)[4], float (*xi)[4]) {
  uint32_t A1[5][4], A2[5][4];
  const uint32_t la = plane + (lane >> 4) * 1280 + (lane & 15) * 80;
#pragma unroll
  for (int j = 0; j < 5; j++) {
    uint32_t r0, r1, i0, i1; ldsm4t(r0, r1, i0, i1, la + j * 16);
    float yr[4], yi[4];
    mmaZ(yr, fr, r0, r1); mmaZ(yi, fi, r0, r1); mmaA(yr, nfi, i0, i1); mmaA(yi, fr, i0, i1);
    float zr[4], zi[4];
#pragma unroll
    for (int e = 0; e < 4; e++) { zr[e] = yr[e] * tc[j][e] - yi[e] * ts[j][e]; zi[e] = yr[e] * ts[j][e] + yi[e] * tc[j][e]; }
    A1[j][0] = pack_bf16(zr[0], zr[1]); A1[j][1] = pack_bf16(zr[2], zr[3]); A1[j][2] = pack_bf16(zi[0], zi[1]); A1[j][3] = pack_bf16(zi[2], zi[3]);
    A2[j][0] = A1[j][2]; A2[j][1] = A1[j][3]; A2[j][2] = A1[j][0] ^ 0x80008000u; A2[j][3] = A1[j][1] ^ 0x80008000u;
  }
#pragma unroll
  for (int t = 0; t < 5; t++) {
#pragma unroll
    for (int u = 0; u < 5; u++) {
      uint32_t b0, b1; asm volatile("ld.shared.v2.b32 {%0,%1}, [%2];" : "=r"(b0), "=r"(b1) : "r"(tab + (t * 5 + u) * 256 + lane * 8));
      if (t == 0) { mmaZ(xr[u], A1[t], b0, b1); mmaZ(xi[u], A2[t], b0, b1); } else { mmaA(xr[u], A1[t], b0, b1); mmaA(xi[u], A2[t], b0, b1); }
    }
  }
}
template <int SG> __device__ __forceinline__ void tw640(int g, int q, float (*tc)[4], float (*ts)[4]) {
#pragma unroll
  for (int j = 0; j < 5; j++)
#pragma unroll
    for (int e = 0; e < 4; e++) { float s; cs2pi<640>((g + 8 * (e >> 1)) * (8 * j + 2 * q + (e & 1)), tc[j][e], s); ts[j][e] = SG * s; }
}
__device__ __forceinline__ void ln_row(float* v) {
  float s = 0.f;
#pragma unroll
  for (int i = 0; i < 20; i++) s += v[i];
#pragma unroll
  for (int o = 16; o; o >>= 1) s += __shfl_xor_sync(~0u, s, o);
  const float mean = s * (1.f / D_);
  float qv = 0.f;
#pragma unroll
  for (int i = 0; i < 20; i++) { v[i] -= mean; qv += v[i] * v[i]; }
#pragma unroll
  for (int o = 16; o; o >>= 1) qv += __shfl_xor_sync(~0u, qv, o);
  const float rs = rsqrtf(qv * (1.f / D_) + 1e-5f);
#pragma unroll
  for (int i = 0; i < 20; i++) v[i] *= rs;
}

constexpr int KA_TR_STRIDE = 804;
__global__ void __launch_bounds__(256) ka1_kernel(const bf16* __restrict__ x, uint32_t* __restrict__ ZT, const bf16* pf0, const bf16* pf1 TLP) {
  __shared__ __align__(16) uint2 tab[800];
  __shared__ __align__(16) uint32_t buf[8 * KA_TR_STRIDE];
  const int tid = threadIdx.x, lane = tid & 31, w = tid >> 5, g = lane >> 2, q = lane & 3;
  if (tid == 0) { TL_MIN(tlid, 0); TL_MAX(tlid, 4); }
  pdl_launch();
  uint32_t fr[4], fi[4], nfi[4]; f16_frags<-1>(g, q, fr, fi, nfi);
  float tc[5][4], ts[5][4]; tw640<-1>(g, q, tc, ts);
  f40_table<-1>(tab, tid);
  sched_fence();
  pdl_wait();
  if (tid == 0) TL_MIN(tlid, 1);
  const uint32_t plane = smem_u32(buf) + w * (KA_TR_STRIDE * 4);
  {
    uint2 raw[2][5];
#pragma unroll
    for (int r = 0; r < 2; r++)
#pragma unroll
      for (int i = 0; i < 5; i++) raw[r][i] = *(const uint2*)(x + (size_t)(blockIdx.x * 16 + 2 * w + r) * D_ + i * 128 + lane * 4);
#pragma unroll
    for (int r = 0; r < 2; r++) {
      float v[20];
#pragma unroll
      for (int i = 0; i < 5; i++) { v[4 * i] = bf_lo(raw[r][i].x); v[4 * i + 1] = bf_hi(raw[r][i].x); v[4 * i + 2] = bf_lo(raw[r][i].y); v[4 * i + 3] = bf_hi(raw[r][i].y); }
      ln_row(v);
#pragma unroll
      for (int i = 0; i < 5; i++) asm volatile("st.shared.v2.b32 [%0], {%1,%2};" :: "r"(plane + r * 1280 + i * 256 + lane * 8), "r"(pack_bf16(v[4 * i], v[4 * i + 1])), "r"(pack_bf16(v[4 * i + 2], v[4 * i + 3])) : "memory");
    }
  }
  __syncthreads();
  if (tid < 20) l2_prefetch((tid < 10 ? pf0 : pf1) + (blockIdx.x * 10 + tid % 10) * 2048, 4096);
  float xr[5][4], xi[5][4];
  fft640<-1>(plane, smem_u32(tab), lane, fr, fi, nfi, tc, ts, xr, xi);
  __syncwarp();
#pragma unroll
  for (int u = 0; u < 5; u++)
#pragma unroll
    for (int e = 0; e < 4; e++) { const int f = g + 8 * (e >> 1) + 16 * (8 * u + 2 * q + (e & 1)); buf[w * KA_TR_STRIDE + f + 8 * (f >> 5)] = pack_bf16(xr[u][e], xi[u][e]); }
  __syncthreads();
  uint32_t ov[5][4];
#pragma unroll
  for (int it = 0; it < 5; it++) {
    const int f = it * 128 + (tid >> 1);
#pragma unroll
    for (int k = 0; k < 4; k++) ov[it][k] = buf[((tid & 1) * 4 + k) * KA_TR_STRIDE + f + 8 * (f >> 5)];
  }
#pragma unroll
  for (int it = 0; it < 5; it++) stg128(ZT + (size_t)(it * 128 + (tid >> 1)) * 1024 + blockIdx.x * 8 + (tid & 1) * 4, ov[it][0], ov[it][1], ov[it][2], ov[it][3]);
  if (tid == 0) TL_MAX(tlid, 2);
}

__global__ void __launch_bounds__(256) ka3_kernel(const uint32_t* __restrict__ ZT, const bf16* __restrict__ x, bf16* __restrict__ x1, bf16* __restrict__ hN, const bf16* pf0, const bf16* pf1 TLP) {
  __shared__ __align__(16) uint2 tab[800];
  __shared__ __align__(16) uint32_t buf[8 * KA_TR_STRIDE];
  const int tid = threadIdx.x, lane = tid & 31, w = tid >> 5, g = lane >> 2, q = lane & 3;
  if (tid == 0) { TL_MIN(tlid, 0); TL_MAX(tlid, 4); }
  uint32_t fr[4], fi[4], nfi[4]; f16_frags<1>(g, q, fr, fi, nfi);
  float tc[5][4], ts[5][4]; tw640<1>(g, q, tc, ts);
  f40_table<1>(tab, tid);
  sched_fence();
  pdl_wait();
  pdl_launch();
  if (tid == 0) TL_MIN(tlid, 1);
  uint4 za[3], zb[3];
#pragma unroll
  for (int it = 0; it < 3; it++) if (it < 2 || tid < 128) {
    const int i = it * 256 + tid; const uint32_t* s = ZT + (size_t)(i & ~1) * 1024 + blockIdx.x * 8 + (i & 1) * 4;
    za[it] = *(const uint4*)s; zb[it] = *(const uint4*)(s + 1024);
  }
  uint2 raw[2][5];
#pragma unroll
  for (int r = 0; r < 2; r++)
#pragma unroll
    for (int i = 0; i < 5; i++) raw[r][i] = *(const uint2*)(x + (size_t)(blockIdx.x * 16 + 2 * w + r) * D_ + i * 128 + lane * 4);
  sched_fence();
#pragma unroll
  for (int it = 0; it < 3; it++) if (it < 2 || tid < 128) {
    const int i = it * 256 + tid; const uint4 a = za[it], b = zb[it];
    uint32_t* d = buf + (i & 1) * 4 * KA_TR_STRIDE + (i >> 1);
    d[0] = __byte_perm(a.x, b.x, 0x5410); d[320] = __byte_perm(a.x, b.x, 0x7632); d += KA_TR_STRIDE;
    d[0] = __byte_perm(a.y, b.y, 0x5410); d[320] = __byte_perm(a.y, b.y, 0x7632); d += KA_TR_STRIDE;
    d[0] = __byte_perm(a.z, b.z, 0x5410); d[320] = __byte_perm(a.z, b.z, 0x7632); d += KA_TR_STRIDE;
    d[0] = __byte_perm(a.w, b.w, 0x5410); d[320] = __byte_perm(a.w, b.w, 0x7632);
  }
  __syncthreads();
  if (tid < 20) l2_prefetch((tid < 10 ? pf0 : pf1) + (blockIdx.x * 10 + tid % 10) * 2048, 4096);
  float xr[5][4], xi[5][4];
  fft640<1>(smem_u32(buf) + w * (KA_TR_STRIDE * 4), smem_u32(tab), lane, fr, fi, nfi, tc, ts, xr, xi);
  __syncwarp();
#pragma unroll
  for (int u = 0; u < 5; u++)
#pragma unroll
    for (int e = 0; e < 4; e++) { const int d = g + 8 * (e >> 1) + 16 * (8 * u + 2 * q + (e & 1)); buf[w * KA_TR_STRIDE + d + 8 * (d >> 5)] = pack_bf16(xr[u][e], xi[u][e]); }
  __syncwarp();
  float v[2][20];
#pragma unroll
  for (int i = 0; i < 5; i++) {
    const int d = i * 128 + lane * 4;
    const uint4 y = *(const uint4*)(buf + w * KA_TR_STRIDE + d + 8 * (d >> 5));
    const uint32_t p0 = pack_bf16(bf_lo(raw[0][i].x) + bf_lo(y.x), bf_hi(raw[0][i].x) + bf_lo(y.y)), p1 = pack_bf16(bf_lo(raw[0][i].y) + bf_lo(y.z), bf_hi(raw[0][i].y) + bf_lo(y.w));
    const uint32_t p2 = pack_bf16(bf_lo(raw[1][i].x) + bf_hi(y.x), bf_hi(raw[1][i].x) + bf_hi(y.y)), p3 = pack_bf16(bf_lo(raw[1][i].y) + bf_hi(y.z), bf_hi(raw[1][i].y) + bf_hi(y.w));
    const size_t o = (size_t)(blockIdx.x * 16 + 2 * w) * D_ + d;
    *(uint2*)(x1 + o) = make_uint2(p0, p1); *(uint2*)(x1 + o + D_) = make_uint2(p2, p3);
    v[0][4 * i] = bf_lo(p0); v[0][4 * i + 1] = bf_hi(p0); v[0][4 * i + 2] = bf_lo(p1); v[0][4 * i + 3] = bf_hi(p1);
    v[1][4 * i] = bf_lo(p2); v[1][4 * i + 1] = bf_hi(p2); v[1][4 * i + 2] = bf_lo(p3); v[1][4 * i + 3] = bf_hi(p3);
  }
#pragma unroll
  for (int r = 0; r < 2; r++) {
    ln_row(v[r]);
#pragma unroll
    for (int i = 0; i < 5; i++) *(uint2*)(hN + (size_t)(blockIdx.x * 16 + 2 * w + r) * D_ + i * 128 + lane * 4) = make_uint2(pack_bf16(v[r][4 * i], v[r][4 * i + 1]), pack_bf16(v[r][4 * i + 2], v[r][4 * i + 3]));
  }
  if (tid == 0) TL_MAX(tlid, 2);
}

__global__ void __launch_bounds__(256) kprep_kernel(const bf16* __restrict__ wr, const bf16* __restrict__ wi, uint32_t* __restrict__ WT, uint32_t* __restrict__ comm TLP) {
  __shared__ uint32_t t[64][33];
  const int tid = threadIdx.x;
  if (tid == 0) { TL_MIN(tlid, 0); TL_MAX(tlid, 4); }
  pdl_launch();
  const int ft = blockIdx.x % 11, kg = blockIdx.x / 11;
  const int g = kg >> 2, q = kg & 3;
  for (int i = tid; i < 64 * 32; i += 256) {
    const int fl = i & 31, j = i >> 5, r = j >> 4, u = (j >> 2) & 3, e = j & 3, f = ft * 32 + fl;
    const int k = 4 * (g + 8 * (e >> 1) + 16 * (8 * u + 2 * q + (e & 1))) + r;
    uint32_t v = 0;
    if (f < 321) v = (uint32_t)__bfloat16_as_ushort(wr[k * 321 + f]) | ((uint32_t)__bfloat16_as_ushort(wi[k * 321 + f]) << 16);
    t[j][fl] = v;
  }
  __syncthreads();
  for (int i = tid; i < 64 * 32; i += 256) {
    const int j = i & 63, fl = i >> 6, f = ft * 32 + fl;
    if (f < 321) WT[(size_t)f * 2048 + (j >> 4) * 512 + kg * 16 + (j & 15)] = t[j][fl];
  }
  const int nthr = gridDim.x * 256, gid = blockIdx.x * 256 + tid;
  for (int i = gid; i < 2 * 416 * 256; i += nthr) {
    const int L = i / (416 * 256), o = i % (416 * 256); const uint32_t v = (o >= 162 * 256 && o < 256 * 256) ? ~0u : 0u;
    if (o >= 188 * 256 && o < 256 * 256) continue;
    ((uint4*)comm)[L * (512 * 256) + o] = make_uint4(v, v, v, v);
  }
  if (tid == 0) TL_MAX(tlid, 2);
  pdl_wait();
}

__global__ void __launch_bounds__(128, 3) ka2_kernel(uint32_t* __restrict__ ZT, const uint32_t* __restrict__ WT TLP) {
  __shared__ __align__(16) float buf[4 * 2 * 16 * 40];
  const int tid = threadIdx.x, lane = tid & 31, w = tid >> 5, g = lane >> 2, q = lane & 3;
  const int f = blockIdx.x, f2 = (640 - f) % 640;
  if (tid == 0) { TL_MIN(tlid, 0); TL_MAX(tlid, 4); }
  pdl_launch();
  uint32_t fr[4], fi[4], nfi[4]; f16_frags<-1>(g, q, fr, fi, nfi);
  uint32_t br[4][4], bi[4][4];
#pragma unroll
  for (int t = 0; t < 4; t++)
#pragma unroll
    for (int u = 0; u < 4; u++) { float c0, s0, c1, s1; cs2pi<32>((8 * t + 2 * q) * (8 * u + g), c0, s0); cs2pi<32>((8 * t + 2 * q + 1) * (8 * u + g), c1, s1); br[t][u] = pack_bf16(c0, c1); bi[t][u] = pack_bf16(s0, s1); }
  float tc[4][4], ts[4][4];
#pragma unroll
  for (int j = 0; j < 4; j++)
#pragma unroll
    for (int e = 0; e < 4; e++) cs2pi<512>((g + 8 * (e >> 1)) * (8 * j + 2 * q + (e & 1)), tc[j][e], ts[j][e]);
  float wc[4], ws[4];
#pragma unroll
  for (int i = 0; i < 4; i++) cs2pi<2048>(4 * tid + i, wc[i], ws[i]);
  sched_fence();
  pdl_wait();
  if (tid == 0) TL_MIN(tlid, 1);
  uint4 wt[4];
#pragma unroll
  for (int u = 0; u < 4; u++) wt[u] = *(const uint4*)(WT + (size_t)f * 2048 + w * 512 + lane * 16 + u * 4);
  const uint32_t sbuf = smem_u32(buf);
  {
    uint2 P[4], Q[4];
#pragma unroll
    for (int j = 0; j < 4; j++) { P[j] = *(const uint2*)(ZT + (size_t)f * 1024 + j * 256 + 2 * tid); Q[j] = *(const uint2*)(ZT + (size_t)f2 * 1024 + j * 256 + 2 * tid); }
    float ur[4][4], ui[4][4];
#pragma unroll
    for (int i = 0; i < 4; i++) {
      float ar[4], ai[4];
#pragma unroll
      for (int j = 0; j < 4; j++) {
        const uint32_t p = (i >> 1) ? P[j].y : P[j].x, z = (i >> 1) ? Q[j].y : Q[j].x;
        if (!(i & 1)) { ar[j] = bf_lo(p) + bf_lo(z); ai[j] = bf_hi(p) - bf_hi(z); }
        else { ar[j] = bf_hi(p) + bf_hi(z); ai[j] = bf_lo(z) - bf_lo(p); }
      }
      const float s0r = ar[0] + ar[2], s0i = ai[0] + ai[2], d0r = ar[0] - ar[2], d0i = ai[0] - ai[2];
      const float s1r = ar[1] + ar[3], s1i = ai[1] + ai[3], d1r = ar[1] - ar[3], d1i = ai[1] - ai[3];
      ur[0][i] = s0r + s1r; ui[0][i] = s0i + s1i;
      const float vr[3] = {d0r + d1i, s0r - s1r, d0r - d1i}, vi[3] = {d0i - d1r, s0i - s1i, d0i + d1r};
      const float c2 = wc[i] * wc[i] - ws[i] * ws[i], s2 = 2.f * wc[i] * ws[i];
      const float twc[4] = {1.f, wc[i], c2, c2 * wc[i] - s2 * ws[i]}, tws[4] = {0.f, ws[i], s2, s2 * wc[i] + c2 * ws[i]};
#pragma unroll
      for (int r = 1; r < 4; r++) { const float c = twc[r], s = tws[r]; ur[r][i] = vr[r - 1] * c + vi[r - 1] * s; ui[r][i] = vi[r - 1] * c - vr[r - 1] * s; }
    }
    const uint32_t o = sbuf + (tid >> 3) * 80 + (tid & 7) * 8;
#pragma unroll
    for (int r = 0; r < 4; r++) {
      asm volatile("st.shared.v2.b32 [%0], {%1,%2};" :: "r"(o + r * 5120), "r"(pack_bf16(ur[r][0], ur[r][1])), "r"(pack_bf16(ur[r][2], ur[r][3])) : "memory");
      asm volatile("st.shared.v2.b32 [%0], {%1,%2};" :: "r"(o + r * 5120 + 1280), "r"(pack_bf16(ui[r][0], ui[r][1])), "r"(pack_bf16(ui[r][2], ui[r][3])) : "memory");
    }
  }
  __syncthreads();
  {
    uint32_t A1[4][4], A2[4][4];
    const uint32_t la = sbuf + w * 5120 + (lane >> 4) * 1280 + (lane & 15) * 80;
#pragma unroll
    for (int j = 0; j < 4; j++) {
      uint32_t r0, r1, i0, i1; ldsm4t(r0, r1, i0, i1, la + j * 16);
      float yr[4], yi[4];
      mmaZ(yr, fr, r0, r1); mmaZ(yi, fi, r0, r1); mmaA(yr, nfi, i0, i1); mmaA(yi, fr, i0, i1);
      float zr[4], zi[4];
#pragma unroll
      for (int e = 0; e < 4; e++) { zr[e] = yr[e] * tc[j][e] + yi[e] * ts[j][e]; zi[e] = yi[e] * tc[j][e] - yr[e] * ts[j][e]; }
      A1[j][0] = pack_bf16(zr[0], zr[1]); A1[j][1] = pack_bf16(zr[2], zr[3]); A1[j][2] = pack_bf16(zi[0], zi[1]); A1[j][3] = pack_bf16(zi[2], zi[3]);
      A2[j][0] = A1[j][2]; A2[j][1] = A1[j][3]; A2[j][2] = A1[j][0] ^ 0x80008000u; A2[j][3] = A1[j][1] ^ 0x80008000u;
    }
    float xr[4][4], xi[4][4];
#pragma unroll
    for (int t = 0; t < 4; t++)
#pragma unroll
      for (int u = 0; u < 4; u++) {
        if (t == 0) { mmaZ(xr[u], A1[t], br[t][u], bi[t][u]); mmaZ(xi[u], A2[t], br[t][u], bi[t][u]); } else { mmaA(xr[u], A1[t], br[t][u], bi[t][u]); mmaA(xi[u], A2[t], br[t][u], bi[t][u]); }
      }
#pragma unroll
    for (int u = 0; u < 4; u++) {
      const uint32_t wv[4] = {wt[u].x, wt[u].y, wt[u].z, wt[u].w};
      float zr[4], zi[4];
#pragma unroll
      for (int e = 0; e < 4; e++) { const float a = bf_lo(wv[e]), b = bf_hi(wv[e]); zr[e] = xr[u][e] * a - xi[u][e] * b; zi[e] = xr[u][e] * b + xi[u][e] * a; }
      A2[u][2] = pack_bf16(zr[0], zr[1]); A2[u][3] = pack_bf16(zr[2], zr[3]); A2[u][0] = pack_bf16(zi[0], zi[1]); A2[u][1] = pack_bf16(zi[2], zi[3]);
      A1[u][0] = A2[u][2]; A1[u][1] = A2[u][3]; A1[u][2] = A2[u][0] ^ 0x80008000u; A1[u][3] = A2[u][1] ^ 0x80008000u;
    }
#pragma unroll
    for (int t = 0; t < 4; t++)
#pragma unroll
      for (int u = 0; u < 4; u++) {
        if (t == 0) { mmaZ(xr[u], A1[t], br[t][u], bi[t][u]); mmaZ(xi[u], A2[t], br[t][u], bi[t][u]); } else { mmaA(xr[u], A1[t], br[t][u], bi[t][u]); mmaA(xi[u], A2[t], br[t][u], bi[t][u]); }
      }
    __syncwarp();
    float* pl = buf + w * 1280;
    const float nrm = 0.5f / (2048.f * 640.f);
#pragma unroll
    for (int j = 0; j < 4; j++) {
      float zr[4], zi[4];
#pragma unroll
      for (int e = 0; e < 4; e++) { zr[e] = xr[j][e] * tc[j][e] - xi[j][e] * ts[j][e]; zi[e] = xi[j][e] * tc[j][e] + xr[j][e] * ts[j][e]; }
      const uint32_t r0 = movm(pack_bf16(zr[0], zr[1])), r1 = movm(pack_bf16(zr[2], zr[3])), i0 = movm(pack_bf16(zi[0], zi[1])), i1 = movm(pack_bf16(zi[2], zi[3]));
      float yr[4], yi[4];
      mmaZ(yr, fr, r0, r1); mmaZ(yi, nfi, r0, r1); mmaA(yr, fi, i0, i1); mmaA(yi, fr, i0, i1);
      *(float2*)(pl + g * 40 + 8 * j + 2 * q) = make_float2(yr[0] * nrm, yr[1] * nrm); *(float2*)(pl + (g + 8) * 40 + 8 * j + 2 * q) = make_float2(yr[2] * nrm, yr[3] * nrm);
      *(float2*)(pl + 640 + g * 40 + 8 * j + 2 * q) = make_float2(yi[0] * nrm, yi[1] * nrm); *(float2*)(pl + 640 + (g + 8) * 40 + 8 * j + 2 * q) = make_float2(yi[2] * nrm, yi[3] * nrm);
    }
  }
  __syncthreads();
  {
    float4 Ur[4], Ui[4];
#pragma unroll
    for (int r = 0; r < 4; r++) { Ur[r] = *(const float4*)(buf + r * 1280 + (tid >> 3) * 40 + (tid & 7) * 4); Ui[r] = *(const float4*)(buf + r * 1280 + 640 + (tid >> 3) * 40 + (tid & 7) * 4); }
    float yr[4][4], yi[4][4];
#pragma unroll
    for (int i = 0; i < 4; i++) {
      float ar[4], ai[4];
      const float c2 = wc[i] * wc[i] - ws[i] * ws[i], s2 = 2.f * wc[i] * ws[i];
      const float twc[4] = {1.f, wc[i], c2, c2 * wc[i] - s2 * ws[i]}, tws[4] = {0.f, ws[i], s2, s2 * wc[i] + c2 * ws[i]};
#pragma unroll
      for (int r = 0; r < 4; r++) {
        const float a = i == 0 ? Ur[r].x : i == 1 ? Ur[r].y : i == 2 ? Ur[r].z : Ur[r].w, b = i == 0 ? Ui[r].x : i == 1 ? Ui[r].y : i == 2 ? Ui[r].z : Ui[r].w;
        if (r == 0) { ar[r] = a; ai[r] = b; } else { const float c = twc[r], s = tws[r]; ar[r] = a * c - b * s; ai[r] = b * c + a * s; }
      }
      const float s0r = ar[0] + ar[2], s0i = ai[0] + ai[2], d0r = ar[0] - ar[2], d0i = ai[0] - ai[2];
      const float s1r = ar[1] + ar[3], s1i = ai[1] + ai[3], d1r = ar[1] - ar[3], d1i = ai[1] - ai[3];
      yr[0][i] = s0r + s1r; yi[0][i] = s0i + s1i; yr[2][i] = s0r - s1r; yi[2][i] = s0i - s1i;
      yr[1][i] = d0r - d1i; yi[1][i] = d0i + d1r; yr[3][i] = d0r + d1i; yi[3][i] = d0i - d1r;
    }
    const float im = (f == f2) ? 0.f : 1.f;
#pragma unroll
    for (int j = 0; j < 4; j++) {
      *(uint2*)(ZT + (size_t)f * 1024 + j * 256 + 2 * tid) = make_uint2(pack_bf16(yr[j][0] - im * yi[j][1], yr[j][1] + im * yi[j][0]), pack_bf16(yr[j][2] - im * yi[j][3], yr[j][3] + im * yi[j][2]));
      if (f != f2) *(uint2*)(ZT + (size_t)f2 * 1024 + j * 256 + 2 * tid) = make_uint2(pack_bf16(yr[j][0] + yi[j][1], yr[j][1] - yi[j][0]), pack_bf16(yr[j][2] + yi[j][3], yr[j][3] - yi[j][2]));
    }
  }
  if (tid == 0) TL_MAX(tlid, 2);
}

__device__ __forceinline__ void tma2d(uint32_t dst, const CUtensorMap* tm, int c0, int c1, uint32_t bar) {
  asm volatile("cp.async.bulk.tensor.2d.shared::cluster.global.mbarrier::complete_tx::bytes [%0], [%1, {%3, %4}], [%2];" :: "r"(dst), "l"(tm), "r"(bar), "r"(c0), "r"(c1) : "memory");
}
__device__ __forceinline__ void bulk_g2s(uint32_t dst, const void* src, int bytes, uint32_t bar) {
  asm volatile("cp.async.bulk.shared::cluster.global.mbarrier::complete_tx::bytes [%0], [%1], %2, [%3];" :: "r"(dst), "l"(src), "r"(bytes), "r"(bar) : "memory");
}
__device__ __forceinline__ uint64_t desc128(uint32_t a) { return (uint64_t)((a & 0x3FFFF) >> 4) | (1ull << 16) | (64ull << 32) | (1ull << 62); }
#define WG_FENCE() asm volatile("wgmma.fence.sync.aligned;" ::: "memory")
#define WG_COMMIT() asm volatile("wgmma.commit_group.sync.aligned;" ::: "memory")
#define WG_WAIT(n) asm volatile("wgmma.wait_group.sync.aligned " #n ";" ::: "memory")
__device__ __forceinline__ void wg_rs_n64(float* d, const uint32_t* a, uint64_t db, int acc) {
  asm volatile("{.reg .pred p; setp.ne.b32 p, %37, 0;\n"
    "wgmma.mma_async.sync.aligned.m64n64k16.f32.bf16.bf16 {%0,%1,%2,%3,%4,%5,%6,%7,%8,%9,%10,%11,%12,%13,%14,%15,%16,%17,%18,%19,%20,%21,%22,%23,%24,%25,%26,%27,%28,%29,%30,%31}, {%32,%33,%34,%35}, %36, p, 1, 1, 0;}"
    : "+f"(d[0]), "+f"(d[1]), "+f"(d[2]), "+f"(d[3]), "+f"(d[4]), "+f"(d[5]), "+f"(d[6]), "+f"(d[7]), "+f"(d[8]), "+f"(d[9]), "+f"(d[10]), "+f"(d[11]), "+f"(d[12]), "+f"(d[13]), "+f"(d[14]), "+f"(d[15]),
      "+f"(d[16]), "+f"(d[17]), "+f"(d[18]), "+f"(d[19]), "+f"(d[20]), "+f"(d[21]), "+f"(d[22]), "+f"(d[23]), "+f"(d[24]), "+f"(d[25]), "+f"(d[26]), "+f"(d[27]), "+f"(d[28]), "+f"(d[29]), "+f"(d[30]), "+f"(d[31])
    : "r"(a[0]), "r"(a[1]), "r"(a[2]), "r"(a[3]), "l"(db), "r"(acc));
}
__device__ __forceinline__ void wg_rs_n32(float* d, const uint32_t* a, uint64_t db, int acc) {
  asm volatile("{.reg .pred p; setp.ne.b32 p, %21, 0;\n"
    "wgmma.mma_async.sync.aligned.m64n32k16.f32.bf16.bf16 {%0,%1,%2,%3,%4,%5,%6,%7,%8,%9,%10,%11,%12,%13,%14,%15}, {%16,%17,%18,%19}, %20, p, 1, 1, 0;}"
    : "+f"(d[0]), "+f"(d[1]), "+f"(d[2]), "+f"(d[3]), "+f"(d[4]), "+f"(d[5]), "+f"(d[6]), "+f"(d[7]), "+f"(d[8]), "+f"(d[9]), "+f"(d[10]), "+f"(d[11]), "+f"(d[12]), "+f"(d[13]), "+f"(d[14]), "+f"(d[15])
    : "r"(a[0]), "r"(a[1]), "r"(a[2]), "r"(a[3]), "l"(db), "r"(acc));
}
__device__ __forceinline__ void wg_ss_n40_tt(float* d, uint64_t da, uint64_t db, int acc) {
  asm volatile("{.reg .pred p; setp.ne.b32 p, %22, 0;\n"
    "wgmma.mma_async.sync.aligned.m64n40k16.f32.bf16.bf16 {%0,%1,%2,%3,%4,%5,%6,%7,%8,%9,%10,%11,%12,%13,%14,%15,%16,%17,%18,%19}, %20, %21, p, 1, 1, 1, 1;}"
    : "+f"(d[0]), "+f"(d[1]), "+f"(d[2]), "+f"(d[3]), "+f"(d[4]), "+f"(d[5]), "+f"(d[6]), "+f"(d[7]), "+f"(d[8]), "+f"(d[9]), "+f"(d[10]), "+f"(d[11]), "+f"(d[12]), "+f"(d[13]), "+f"(d[14]), "+f"(d[15]),
      "+f"(d[16]), "+f"(d[17]), "+f"(d[18]), "+f"(d[19])
    : "l"(da), "l"(db), "r"(acc));
}
__device__ __forceinline__ void wg_ss_n32_ta(float* d, uint64_t da, uint64_t db, int acc) {
  asm volatile("{.reg .pred p; setp.ne.b32 p, %18, 0;\n"
    "wgmma.mma_async.sync.aligned.m64n32k16.f32.bf16.bf16 {%0,%1,%2,%3,%4,%5,%6,%7,%8,%9,%10,%11,%12,%13,%14,%15}, %16, %17, p, 1, 1, 1, 0;}"
    : "+f"(d[0]), "+f"(d[1]), "+f"(d[2]), "+f"(d[3]), "+f"(d[4]), "+f"(d[5]), "+f"(d[6]), "+f"(d[7]), "+f"(d[8]), "+f"(d[9]), "+f"(d[10]), "+f"(d[11]), "+f"(d[12]), "+f"(d[13]), "+f"(d[14]), "+f"(d[15])
    : "l"(da), "l"(db), "r"(acc));
}
__device__ __forceinline__ uint64_t desc_ns(uint32_t a, uint32_t lbo, uint32_t sbo) { return (uint64_t)((a & 0x3FFFF) >> 4) | ((uint64_t)(lbo >> 4) << 16) | ((uint64_t)(sbo >> 4) << 32); }
__device__ __forceinline__ uint32_t ld_acquire(const void* p) { uint32_t v; asm volatile("ld.acquire.gpu.global.u32 %0, [%1];" : "=r"(v) : "l"(p) : "memory"); return v; }
__device__ __forceinline__ void wait_count(const uint32_t* p, uint32_t n) { int guard = 0; while (ld_acquire(p) < n && ++guard < 200000) __nanosleep(40); }

constexpr int SD_WS = 0, SD_REC = 16384, SD_O = SD_REC + 2 * 30720, SD_OI = SD_O + 2 * 8192, SD_OUT = SD_OI + 2 * 40960, SD_FIN = SD_OUT + 8192, SD_BAR = SD_FIN + 10240;
constexpr int SD_SMEM = SD_BAR + 256 + 1024;
constexpr int ORING = 4, PRING = 2 * ORING;
constexpr int FL_MEM = 160 * 1024, FL_RDY = 161 * 1024;
struct SideParams { CUtensorMap tmWo, tmP; const char* QKV; char *O, *part; const bf16* x1; bf16* out; uint32_t* comm; int dbgf; };
#define DBGF(m) false
#define ELECT "{.reg .pred p; elect.sync _|p, 0xffffffff;\n"
#define ATS(i)
__global__ void __launch_bounds__(512, 1) side_kernel(const __grid_constant__ SideParams p TLP) {
  extern __shared__ __align__(1024) char smem_raw[];
  const uint32_t sb = (smem_u32(smem_raw) + 1023) & ~1023u, wfull = sb + SD_BAR, rland = wfull + 8, ofull = wfull + 16, ofree = wfull + 32,
    ifull = wfull + 48, ifree = wfull + 64, rfull = wfull + 80, rfree = wfull + 96, fdone = wfull + 112, ffull = wfull + 128;
  const int tid = threadIdx.x, lane = tid & 31, w = tid >> 5, h = blockIdx.x;
  const int cb = h % 5, ks = h / 5, h0 = ks < 4 ? 5 * ks : 4 + 4 * ks, nh = ks < 4 ? 5 : 4;
  if (tid == 0) { TL_MIN(tlid, 0); TL_MAX(tlid, 4); }
  pdl_launch();
  if (tid == 0) {
    mbar_init(wfull, 1); mbar_init(rland, 1); mbar_init(ffull, 1);
    for (int i = 0; i < 2; i++) { mbar_init(ofull + i * 8, 2); mbar_init(ofree + i * 8, 1); mbar_init(ifull + i * 8, 1); mbar_init(ifree + i * 8, 8); mbar_init(rfull + i * 8, 1); mbar_init(rfree + i * 8, 4); }
    sts128(fdone, 0, 0, 0, 0);
    asm volatile("fence.proxy.async.shared::cta;" ::: "memory");
    mbar_expect(wfull, nh * 32768);
    for (int b = 0; b < 4 * nh; b++) tma2d(sb + ((b + 2) % 20) * 8192, &p.tmWo, cb * 128 + (b & 1) * 64, h0 * 128 + (b >> 1) * 64, wfull);
  }
  __syncthreads();
  if (w < 8) {
    asm volatile("setmaxnreg.inc.sync.aligned.u32 192;");
    const int c = __shfl_sync(~0u, w >> 2, 0), mg = w & 3;
    const uint32_t boxoff = (((lane >> 4) << 3) + (lane & 7)) * 128 + (((2 * mg + ((lane >> 3) & 1)) ^ (lane & 7)) << 4);
    uint32_t A[36][4];
    mbar_wait(wfull, 0);
#pragma unroll
    for (int f = 0; f < 36; f++) ldsm4t(A[f][0], A[f][1], A[f][2], A[f][3], sb + 16384 + c * 8192 + boxoff + (f >> 2) * 16384 + (f & 3) * 2048);
    asm volatile("fence.proxy.async.shared::cta;" ::: "memory");
    bar_sync<1, 320>();
    if (tid == 0) TL_MAX(tlid, 3);
    const uint32_t oa = sb + SD_OUT + c * 4096 + boxoff;
#pragma unroll 1
    for (int s = 0; s < NSEG; s++) {
      const int b = s & 1;
      const uint64_t db = desc128(sb + SD_OI + b * 40960), da = desc128(sb + SD_WS + c * 8192);
      float acc[16];
      mbar_wait_long(ifull + b * 8, (s >> 1) & 1);
      ATS(0)
      WG_FENCE();
#pragma unroll
      for (int k = 0; k < 32; k++) wg_rs_n32(acc, A[k], db + (k >> 2) * 256 + (k & 3) * 2, k);
      if (nh == 5) {
#pragma unroll
        for (int k = 32; k < 36; k++) wg_rs_n32(acc, A[k], db + 2048 + (k & 3) * 2, 1);
#pragma unroll
        for (int k = 0; k < 4; k++) wg_ss_n32_ta(acc, da + k * 128, db + 2304 + k * 2, 1);
      }
      WG_COMMIT();
      bar_sync<2, 256>();
      WG_WAIT(0);
      ATS(1)
      if (lane == 0) mbar_arrive(ifree + b * 8);
#pragma unroll
      for (int u = 0; u < 2; u++)
        asm volatile("stmatrix.sync.aligned.m8n8.x4.trans.shared.b16 [%0], {%1,%2,%3,%4};" :: "r"(oa + u * 2048),
          "r"(pack_bf16(acc[8 * u], acc[8 * u + 1])), "r"(pack_bf16(acc[8 * u + 2], acc[8 * u + 3])), "r"(pack_bf16(acc[8 * u + 4], acc[8 * u + 5])), "r"(pack_bf16(acc[8 * u + 6], acc[8 * u + 7])) : "memory");
      asm volatile("fence.proxy.async.shared::cta;" ::: "memory");
      if (w > 0) bar_arrive<4, 256>();
      else {
        bar_sync<4, 256>();
        asm volatile(ELECT "@p cp.async.bulk.tensor.3d.global.shared::cta.bulk_group [%0, {%2, %3, %4}], [%1];\n"
          "cp.async.bulk.commit_group;\ncp.async.bulk.wait_group 0;\n@p red.relaxed.gpu.global.add.u32 [%5], 1;}"
          :: "l"(&p.tmP), "r"(sb + SD_OUT), "r"(0), "r"((s % PRING) * 32), "r"(ks * 10 + cb * 2), "l"(p.comm + FL_RDY + s * 16 + 8) : "memory");
        ATS(2)
      }
    }
    if (tid == 0) TL_MAX(tlid, 6);
  } else if (w < 12) {
    asm volatile("setmaxnreg.dec.sync.aligned.u32 72;");
    const int a = __shfl_sync(~0u, w - 8, 0), g = lane >> 2, q = lane & 3;
    const float sc2 = 0.08838834764831845f * 1.4426950408889634f;
#pragma unroll 1
    for (int s = 0; s < (h < 32 ? NSEG : 0); s++) {
      const int b = s & 1;
      const uint32_t rec = sb + SD_REC + b * 30720;
      mbar_wait_long(rfull + b * 8, (s >> 1) & 1);
      ATS(1)
      if (s == 0 && tid == 256) TL_MIN(tlid, 1);
      uint32_t P[3][4]; float inv[2];
      {
        float sc[20];
        const uint64_t dq = desc_ns(rec + 1024, 128, 1024), dk = desc_ns(rec + 5120, 128, 1024);
        WG_FENCE();
#pragma unroll
        for (int k = 0; k < 8; k++) wg_ss_n40_tt(sc, dq + (k >> 2) * 640 + (k & 3) * 16, dk + (k >> 2) * 640 + (k & 3) * 16, k);
        WG_COMMIT(); WG_WAIT(0);
        ATS(2)
#pragma unroll
        for (int rh = 0; rh < 2; rh++) {
          const int row = 16 * a + 8 * rh + g;
          float v[5][2], mx = -3.0e38f;
#pragma unroll
          for (int n = 0; n < 5; n++)
#pragma unroll
            for (int e = 0; e < 2; e++) {
              const bool ok = n == 0 || (8 * (n - 1) + 2 * q + e) <= row;
              v[n][e] = ok ? sc[4 * n + 2 * rh + e] * sc2 : -1.0e9f * 1.4426950408889634f; mx = fmaxf(mx, v[n][e]);
            }
          mx = fmaxf(mx, __shfl_xor_sync(~0u, mx, 1)); mx = fmaxf(mx, __shfl_xor_sync(~0u, mx, 2));
          float sum = 0.f;
#pragma unroll
          for (int n = 0; n < 5; n++) { const float e0 = ex2(v[n][0] - mx), e1 = ex2(v[n][1] - mx); sum += e0 + e1; P[n >> 1][(n & 1) * 2 + rh] = pack_bf16(e0, e1); }
          P[2][2 + rh] = 0u;
          sum += __shfl_xor_sync(~0u, sum, 1); sum += __shfl_xor_sync(~0u, sum, 2);
          asm("rcp.approx.ftz.f32 %0, %1;" : "=f"(inv[rh]) : "f"(sum));
        }
      }
      ATS(3)
      mbar_wait_long(ofree + b * 8, ((s >> 1) & 1) ^ 1);
      ATS(4)
      const uint32_t od = sb + SD_O + b * 8192 + (16 * a + (lane & 15)) * 128;
#pragma unroll
      for (int hf = 0; hf < 2; hf++) {
        float o[32];
        const uint64_t dv = desc_ns(rec + 20480 + hf * 5120, 1024, 128);
        WG_FENCE();
        wg_rs_n64(o, P[0], dv, 0); wg_rs_n64(o, P[1], dv + 128, 1); wg_rs_n64(o, P[2], desc_ns(rec + 20480 + hf * 5120 + 4096, 0, 128), 1);
        WG_COMMIT(); WG_WAIT(0);
        if (a < 2) {
#pragma unroll
          for (int n = 0; n < 8; n += 2) {
            const float* x = o + 4 * n;
            asm volatile("stmatrix.sync.aligned.m8n8.x4.shared.b16 [%0], {%1,%2,%3,%4};" :: "r"(od + hf * 4096 + (((n + (lane >> 4)) ^ (lane & 7)) << 4)),
              "r"(pack_bf16(x[0] * inv[0], x[1] * inv[0])), "r"(pack_bf16(x[2] * inv[1], x[3] * inv[1])), "r"(pack_bf16(x[4] * inv[0], x[5] * inv[0])), "r"(pack_bf16(x[6] * inv[1], x[7] * inv[1])) : "memory");
          }
        }
      }
      if (a < 2) {
        asm volatile("fence.proxy.async.shared::cta;" ::: "memory");
        __syncwarp();
        if (lane == 0) mbar_arrive(ofull + b * 8);
      }
      if (lane == 0) mbar_arrive(rfree + b * 8);
      ATS(5)
    }
    if (tid == 256) TL_MAX(tlid, 5);
  } else {
    asm volatile("setmaxnreg.dec.sync.aligned.u32 56;");
    if (w == 13) {
      bar_sync<1, 320>();
#pragma unroll 1
      for (int s = 0; s < NSEG; s++) {
        mbar_wait_long(ifree + (s & 1) * 8, ((s >> 1) & 1) ^ 1);
        wait_count(p.comm + FL_RDY + s * 16 + ks, nh);
        ATS(0)
        asm volatile(ELECT "@p mbarrier.arrive.expect_tx.shared.b64 _, [%2], %3;\n@p cp.async.bulk.shared::cluster.global.mbarrier::complete_tx::bytes [%0], [%1], %3, [%2];}"
          :: "r"(sb + SD_OI + (s & 1) * 40960), "l"(p.O + (size_t)((s % ORING) * 32 + h0) * 8192), "r"(ifull + (s & 1) * 8), "r"(nh * 8192) : "memory");
      }
    } else if (h >= 32) {
      if (w == 15) bar_sync<1, 320>();
    } else if (w == 12) {
#pragma unroll 1
      for (int s = 0; s < NSEG; s++) {
        mbar_wait_long(ofull + (s & 1) * 8, (s >> 1) & 1);
        int fin, guard = 0;
        do { asm volatile("ld.volatile.shared.b32 %0, [%1];" : "=r"(fin) : "r"(fdone) : "memory"); } while (fin + ORING <= s && ++guard < 1000000);
        ATS(0)
        asm volatile(ELECT "@p cp.async.bulk.global.shared::cta.bulk_group [%0], [%1], 8192;\n"
          "cp.async.bulk.commit_group;\ncp.async.bulk.wait_group 0;\n@p red.relaxed.gpu.global.add.u32 [%2], 1;\n@p mbarrier.arrive.shared.b64 _, [%3];}"
          :: "l"(p.O + (size_t)((s % ORING) * 32 + h) * 8192), "r"(sb + SD_O + (s & 1) * 8192), "l"(p.comm + FL_RDY + s * 16 + (h < 20 ? h / 5 : (h - 4) >> 2)), "r"(ofree + (s & 1) * 8) : "memory");
        ATS(1)
      }
      if (lane == 0) TL_MAX(tlid, 7);
    } else if (w == 14) {
      mbar_wait_long(ofull, 0);
#pragma unroll 1
      for (int s = 0; s < NSEG; s++) {
        asm volatile("fence.proxy.async.shared::cta;" ::: "memory");
        __syncwarp();
        asm volatile(ELECT "@p mbarrier.arrive.expect_tx.shared.b64 _, [%2], 10240;\n@p cp.async.bulk.shared::cluster.global.mbarrier::complete_tx::bytes [%0], [%1], 1280, [%2];}"
          :: "r"(sb + SD_FIN + 8960), "l"(p.x1 + (size_t)(s * 32 + h) * D_), "r"(ffull) : "memory");
        wait_count(p.comm + FL_RDY + s * 16 + 8, 35);
        ATS(0)
        asm volatile(ELECT "@p cp.async.bulk.shared::cluster.global.mbarrier::complete_tx::bytes [%0], [%1], 8960, [%2];}"
          :: "r"(sb + SD_FIN), "l"(p.part + (size_t)((s % PRING) * 32 + h) * 8960), "r"(ffull) : "memory");
        mbar_wait_long(ffull, s & 1);
        ATS(1)
        asm volatile("st.volatile.shared.b32 [%0], %1;" :: "r"(fdone), "r"(s + 1) : "memory");
#pragma unroll
        for (int i = 0; i < 5; i++) {
          uint32_t v[8][2];
#pragma unroll
          for (int u = 0; u < 8; u++) asm volatile("ld.shared.v2.b32 {%0,%1}, [%2];" : "=r"(v[u][0]), "=r"(v[u][1]) : "r"(sb + SD_FIN + u * 1280 + i * 256 + lane * 8) : "memory");
          uint32_t y[2];
#pragma unroll
          for (int k = 0; k < 2; k++) {
            y[k] = pack_bf16(((bf_lo(v[0][k]) + bf_lo(v[1][k])) + (bf_lo(v[2][k]) + bf_lo(v[3][k]))) + ((bf_lo(v[4][k]) + bf_lo(v[5][k])) + bf_lo(v[6][k])),
                             ((bf_hi(v[0][k]) + bf_hi(v[1][k])) + (bf_hi(v[2][k]) + bf_hi(v[3][k]))) + ((bf_hi(v[4][k]) + bf_hi(v[5][k])) + bf_hi(v[6][k])));
            asm("add.rn.bf16x2 %0, %0, %1;" : "+r"(y[k]) : "r"(v[7][k]));
          }
          *(uint2*)(p.out + (size_t)(s * 32 + h) * D_ + i * 128 + lane * 4) = make_uint2(y[0], y[1]);
        }
        ATS(2)
      }
    } else {
      uint32_t lp = 0, known = 0;
      bar_sync<1, 320>();
#pragma unroll 1
      for (int s = 0; s < NSEG; s++) {
        const int b = s & 1;
        const uint32_t rec = sb + SD_REC + b * 30720;
        mbar_wait_long(rfree + b * 8, ((s >> 1) & 1) ^ 1);
        for (int tries = 0; tries < 2000; tries++) {
          int guard = 0;
          while (known <= (uint32_t)s && ++guard < 100000) {
            uint32_t f = ~0u;
            if (lane < 3) asm volatile("ld.relaxed.gpu.global.u32 %0, [%1];" : "=r"(f) : "l"(p.comm + FL_MEM + h * 32 + lane * 8) : "memory");
            known = __reduce_min_sync(~0u, f);
          }
          ATS(0)
          if (lane == 0) {
            asm volatile("fence.proxy.async.shared::cta;" ::: "memory");
            mbar_expect(rland, 30720);
            bulk_g2s(rec, p.QKV + (size_t)(s * 32 + h) * 30720, 30720, rland);
          }
          __syncwarp();
          mbar_wait_long(rland, lp); lp ^= 1;
          uint32_t mx = 0;
#pragma unroll
          for (int k = 0; k < 4; k++) { uint32_t v; asm volatile("ld.shared.b32 %0, [%1];" : "=r"(v) : "r"(rec + (k == 0 ? 5120 : 10240 + k * 5120) + lane * 32 + (lane >> 2) * 4) : "memory"); mx = max(mx, v); }
          if (__all_sync(~0u, mx != ~0u)) break;
        }
        if (lane == 0) mbar_arrive(rfull + b * 8);
      }
    }
    if (lane == 0) TL_MAX(tlid, 2);
    pdl_wait();
  }
}

__device__ __forceinline__ uint32_t ld_relaxed(const void* p) { uint32_t v; asm volatile("ld.relaxed.gpu.global.u32 %0, [%1];" : "=r"(v) : "l"(p) : "memory"); return v; }
__device__ __forceinline__ void st_relaxed(void* p, uint32_t v) { asm volatile("st.relaxed.gpu.global.u32 [%0], %1;" :: "l"(p), "r"(v) : "memory"); }
__device__ __forceinline__ void st_relaxed_if(void* p, uint32_t v, uint32_t c) { asm volatile("{.reg .pred p; setp.ne.u32 p, %2, 0; @p st.relaxed.gpu.global.u32 [%0], %1;}" :: "l"(p), "r"(v), "r"(c) : "memory"); }
__device__ __forceinline__ uint32_t clk32() { uint32_t c; asm volatile("mov.u32 %0, %%clock;" : "=r"(c) :: "memory"); return c; }
__device__ __forceinline__ uint32_t gt32() { uint64_t c; asm volatile("mov.u64 %0, %%globaltimer;" : "=l"(c) :: "memory"); return (uint32_t)c; }
__device__ __forceinline__ void wait_gt(uint32_t T) {
  asm volatile("{\n.reg .pred p;\n.reg .u64 t;\n.reg .u32 lo, hi;\nLG%=:\nmov.u64 t, %%globaltimer;\nmov.b64 {lo, hi}, t;\nsub.u32 lo, lo, %0;\nsetp.lt.s32 p, lo, 0;\n@p bra.uni LG%=;\n}" :: "r"(T) : "memory");
}
template <int LUT> __device__ __forceinline__ uint32_t lop3(uint32_t a, uint32_t b, uint32_t c) { uint32_t r; asm("lop3.b32 %0, %1, %2, %3, %4;" : "=r"(r) : "r"(a), "r"(b), "r"(c), "n"(LUT)); return r; }
__device__ __forceinline__ void mma_h(float* d, uint32_t a0, uint32_t a2, uint32_t b0, uint32_t b1) {
  asm volatile("{.reg .b32 u0, u1; mma.sync.aligned.m16n8k16.row.col.f32.bf16.bf16.f32 {%0,%1,%2,%3}, {%4,u0,%5,u1}, {%6,%7}, {%0,%1,%2,%3};}"
    : "+f"(d[0]), "+f"(d[1]), "+f"(d[2]), "+f"(d[3]) : "r"(a0), "r"(a2), "r"(b0), "r"(b1));
}
__device__ __forceinline__ void mma_hz(float* d, uint32_t a0, uint32_t a2, uint32_t b0, uint32_t b1) {
  asm volatile("{.reg .b32 u0, u1; mma.sync.aligned.m16n8k16.row.col.f32.bf16.bf16.f32 {%0,%1,%2,%3}, {%4,u0,%5,u1}, {%6,%7}, {%8,%8,%8,%8};}"
    : "=f"(d[0]), "=f"(d[1]), "=f"(d[2]), "=f"(d[3]) : "r"(a0), "r"(a2), "r"(b0), "r"(b1), "f"(0.f));
}
__device__ __forceinline__ void mma8_h(float* d, uint32_t a0, uint32_t b0) {
  asm volatile("{.reg .b32 u0; mma.sync.aligned.m16n8k8.row.col.f32.bf16.bf16.f32 {%0,%1,%2,%3}, {%4,u0}, {%5}, {%0,%1,%2,%3};}"
    : "+f"(d[0]), "+f"(d[1]), "+f"(d[2]), "+f"(d[3]) : "r"(a0), "r"(b0));
}
__device__ __forceinline__ uint32_t ldsm1t(uint32_t a) { uint32_t r; asm volatile("ldmatrix.sync.aligned.m8n8.x1.trans.shared.b16 {%0}, [%1];" : "=r"(r) : "r"(a) : "memory"); return r; }
__device__ __forceinline__ uint32_t hadd2(uint32_t a, uint32_t b) { uint32_t r; asm("add.rn.bf16x2 %0, %1, %2;" : "=r"(r) : "r"(a), "r"(b)); return r; }
__device__ __forceinline__ uint32_t hmax2(uint32_t a, uint32_t b) { uint32_t r; asm("max.bf16x2 %0, %1, %2;" : "=r"(r) : "r"(a), "r"(b)); return r; }
__device__ __forceinline__ uint32_t lds32(uint32_t a) { uint32_t v; asm volatile("ld.shared.b32 %0, [%1];" : "=r"(v) : "r"(a) : "memory"); return v; }
__device__ __forceinline__ void sts32(uint32_t a, uint32_t v) { asm volatile("st.shared.b32 [%0], %1;" :: "r"(a), "r"(v) : "memory"); }
__device__ __forceinline__ uint32_t mapa(uint32_t a, int rank) { uint32_t r; asm("mapa.shared::cluster.u32 %0, %1, %2;" : "=r"(r) : "r"(a), "r"(rank)); return r; }
template <int OFF> __device__ __forceinline__ void stas32(uint32_t a, uint32_t v, uint32_t bar) {
  asm volatile("st.async.weak.shared::cluster.mbarrier::complete_tx::bytes.b32 [%0+%3], %1, [%2];" :: "r"(a), "r"(v), "r"(bar), "n"(OFF) : "memory");
}
#define OPAQUE(x) x = __shfl_sync(~0u, x, lane)
#define CLUSTER_SYNC() asm volatile("barrier.cluster.arrive.release.aligned; barrier.cluster.wait.acquire.aligned;" ::: "memory")

constexpr int SM_X = 0;
constexpr int SM_AT = 40960;
constexpr int SM_WO = 94208;
constexpr int SM_MEMT = 147456;
constexpr int SM_QK = 157696;
constexpr int SM_SC = 161792;
constexpr int SM_WST = 163840;
constexpr int SM_OX = 163840;
constexpr int SM_VM = 167936;
constexpr int SM_RED = 172032;
constexpr int SM_ST = 180224;
constexpr int SM_VR = 190464;
constexpr int SM_BAR = 229376;
constexpr int REC_SMEM = SM_BAR + 2048 + 1024;
constexpr int MB_A = 0, MB_QK = 24, MB_V = 56, MB_KV = 64, MB_X = 80, MB_IA = 88, MB_IC = 96, MB_XE = 104, MB_TK = 112, MB_PRB = 120, MB_DP = 128, MB_TAB = 256, MB_T2 = 512;
#define NTQ 11
#define NTV 5
#define NB0 4
#define PINK 14
#define NB1 8
#define PINT 5
#define GATEK 6
#define TOLQ 96
#define TOLV 160
constexpr int POLL_LIMIT = 20000;
constexpr int CM_X3 = 162, CM_MISC = 186;
__device__ __forceinline__ int near_page(int pg, int side) { return pg + ((__popc(pg & 0xB3) ^ side) & 1); }
__device__ __forceinline__ int mem_line(int jb) { const int ks = jb >> 1, c = ks >= 20, kk = ks - 20 * c; return (kk >> 2) * 16 + c * 8 + (kk & 3) * 2 + (jb & 1); }

struct RecParams {
  CUtensorMap tmW[3], tmWo, tmX;
  const bf16* mem0;
  char* QKV;
  uint32_t* comm;
  int period, c3, slack, xlate, gap, zero, dbgf;
  uint32_t *dbg, *log;
};
#define PRB(k)
#define LDW(d, a) ldsm4t(d[0], d[1], d[2], d[3], a)

#define PRBASE dpa
#define PRIMM (1024 - MB_DP)
#define PROFF 0
template <bool VR>
__device__ __forceinline__ void rec_gemm_warps(const RecParams& p, const uint32_t sb, const int h, const int r TLP) {
  const int tid = threadIdx.x, lane = tid & 31, w = tid >> 5, q = lane & 3;
  const int mg = w & 3, c = w >> 2;
  constexpr int NT = VR ? NTV : NTQ, NW = VR ? 8 : 16;
  uint32_t R[20][4], P[20][4], Wr[NW - NT][4];
  const uint32_t mbar = sb + SM_BAR;
  uint32_t l16 = sb + lane * 16, wl16 = l16 + w * 512, memaddr = l16 + SM_MEMT + c * 1024, redw = l16 + (w ^ 4) * 512;
  uint32_t qoff = sb + SM_QK + c * 2048 + ((lane >> 4) ^ c) * 1024 + mg * 256 + (lane & 15) * 16;
  {
    const uint32_t boxoff = (((lane >> 4) << 3) + (lane & 7)) * 128 + (((2 * mg + ((lane >> 3) & 1)) ^ (lane & 7)) << 4);
    {
      const int job = 2 * (16 * r + ((lane & 2) && !VR ? w + 8 : w)) + (lane & 1);
      uint32_t side; int guard = 0;
      do { side = ld_relaxed(p.comm + CM_MISC * 1024 + job); } while (side == 0xFFFFFFFFu && ++guard < 1000000);
      if (lane < 4) sts32(mbar + MB_DP + w * 16 + lane * 4, near_page(2 * job, side) * 4096 + h * 128);
      __syncwarp();
    }
    mbar_wait(mbar + MB_IA, 0);
    if (tid == 0) TL_MAX(tlid, 5);
    const uint32_t wa = sb + c * 81920 + boxoff;
#pragma unroll
    for (int k = 0; k < 20; k++) { LDW(R[k], wa + c * 8192 + (k >> 2) * 16384 + (k & 3) * 2048); LDW(P[k], wa + (c ^ 1) * 8192 + (k >> 2) * 16384 + (k & 3) * 2048); }
    bar_sync<1, 384>();
#pragma unroll
    for (int i = 0; i < NT; i++) sts128(wl16 + SM_AT + i * 4096, P[i][0], P[i][1], P[i][2], P[i][3]);
    mbar_wait(mbar + MB_IC, 0);
    if (tid == 0) TL_MAX(tlid, 6);
    const uint32_t woa = sb + SM_WST + c * 16384 + boxoff;
#pragma unroll
    for (int i = 0; i < NW; i++) {
      uint32_t t[4]; LDW(t, woa + (VR ? i * 2048 : (i & 1) * 32768 + (i >> 1) * 2048));
      if (i >= 4 && i < 4 + NW - NT) { Wr[i - 4][0] = t[0]; Wr[i - 4][1] = t[1]; Wr[i - 4][2] = t[2]; Wr[i - 4][3] = t[3]; }
      else sts128(wl16 + SM_WO + (i < 4 ? i : i - (NW - NT)) * 4096, t[0], t[1], t[2], t[3]);
    }
    asm volatile("fence.proxy.async.shared::cta;" ::: "memory");
    bar_sync<1, 384>();
    asm volatile("barrier.cluster.arrive.relaxed.aligned;" ::: "memory");
  }
  uint32_t kvo = (h * 3 + r) * 10240 + c * 5120 + mg * 256 + lane * 4;
  uint32_t fmask = q == 0 ? 1u : 0u, dpa = mbar + MB_DP + w * 16;
  uint32_t sta = sb + SM_ST + (c ^ 1) * 5120 + 1024 + (lane >> 4) * 1024 + mg * 256 + (lane & 15) * 16;
  OPAQUE(wl16); OPAQUE(l16); OPAQUE(kvo); OPAQUE(fmask); OPAQUE(dpa); OPAQUE(memaddr); OPAQUE(redw); OPAQUE(qoff); OPAQUE(sta);
  const int cu = __shfl_sync(~0u, c, 0);
#define LDT(i) lds128(P[i], wl16 + SM_AT + (i) * 4096)
  uint32_t w0, w1;
#define MEMKV() if (VR || cu) { st_relaxed(p.QKV + kvo, w0); st_relaxed(p.QKV + kvo + 128, w1); }
  auto stream = [&](int n, bool gate) {
    float ta[16], tb[16];
    const uint32_t dR = (((sb + SM_X + cu * 20480) >> 4) | 0x10000) + (n & p.zero), dP = dR + (~n & p.zero);
#define WGX(acc, A, ks, sc) wg_rs_n32(acc, A[ks], (uint64_t)(d##A + ((ks) >> 2) * 256 + ((ks) & 3) * 2) | (0x40000040ull << 32), sc)
    WG_FENCE();
    constexpr int NE = NT - 4;
#pragma unroll
    for (int k = 0; k < 20; k++) {
      WGX(ta, R, k, k); if ((k & 1) && k / 2 < NE) LDT(k / 2);
      if (!VR && k == 3 && gate) { st_relaxed_if(p.QKV + kvo, w0, cu); st_relaxed_if(p.QKV + kvo + 128, w1, cu); kvo += 96 * 10240; }
    }
    WG_COMMIT();
    constexpr int K2 = VR ? NT + 2 : 16;
#pragma unroll
    for (int k = K2; k < 20; k++) {
      if (VR && k == K2 + GATEK && gate) asm volatile("bar.sync 12, %0;" :: "r"((h & 1) ? 320 : 352) : "memory");
      WGX(tb, P, k, k - K2);
    }
    WG_COMMIT();
    WG_WAIT(1);
#pragma unroll
    for (int i = 0; i < 2; i++)
      sts128(redw + SM_RED + i * 4096, pack_bf16(ta[8 * i], ta[8 * i + 1]), pack_bf16(ta[8 * i + 2], ta[8 * i + 3]), pack_bf16(ta[8 * i + 4], ta[8 * i + 5]), pack_bf16(ta[8 * i + 6], ta[8 * i + 7]));
#pragma unroll
    for (int i = NE; i < NT; i++) LDT(i);
#pragma unroll
    for (int k = NT; k < K2; k++) WGX(tb, P, k, 1);
    WG_FENCE();
#pragma unroll
    for (int k = 0; k < NE; k++) WGX(tb, P, k, 1);
    bar_sync<11, 384>();
    uint32_t o[2][4];
    lds128(o[0], wl16 + SM_RED); lds128(o[1], wl16 + SM_RED + 4096);
    WG_FENCE();
#pragma unroll
    for (int k = NE; k < NT; k++) WGX(tb, P, k, 1);
    WG_COMMIT();
    WG_WAIT(0);
#pragma unroll
    for (int i = 0; i < 2; i++)
      asm volatile("stmatrix.sync.aligned.m8n8.x4.shared.b16 [%0], {%1,%2,%3,%4};" :: "r"(sta + i * 2048),
        "r"(hadd2(pack_bf16(tb[8 * i], tb[8 * i + 1]), o[i][0])), "r"(hadd2(pack_bf16(tb[8 * i + 2], tb[8 * i + 3]), o[i][1])),
        "r"(hadd2(pack_bf16(tb[8 * i + 4], tb[8 * i + 5]), o[i][2])), "r"(hadd2(pack_bf16(tb[8 * i + 6], tb[8 * i + 7]), o[i][3])) : "memory");
    bar_arrive<14, 384>();
  };
#pragma unroll 1
  for (int n = 0; n < 2; n++) { mbar_wait(mbar + MB_X, n); stream(n, false); }
  if (tid == 0) TL_MAX(tlid, 7);
  asm volatile("barrier.cluster.wait.aligned;" ::: "memory");
  int s = 0, att = 0;
#pragma unroll 1
  while (true) {
    uint32_t B[10][4], Wf[NT][4], dp[4];
    float ap[2][4], ar[2][4];
#define LDO(i, base) lds128(Wf[i], (base) + SM_WO + (i) * 4096)
#define LDB(k2) ldsm4t(B[k2][0], B[k2][1], B[k2][2], B[k2][3], memaddr + ((k2) >> 1) * 2048 + ((k2) & 1) * 512)
#define BK(k) B[(k) >> 1][((k) & 1) * 2], B[(k) >> 1][((k) & 1) * 2 + 1]
    mbar_wait(mbar + MB_A, att & 1);
    PRB(0)
    LDB(0); LDB(1);
#pragma unroll
    for (int k = 0; k < 20; k++) {
      if (!(k & 1) && k < 16) LDB(k / 2 + 2);
      if (k == PINK) {
        const uint32_t wb = lop3<0xF8>(wl16, __float_as_uint(ap[0][0]), p.zero);
#pragma unroll
        for (int u = 0; u < NB0 && u < NT; u++) LDO(u, wb);
      }
      if (k < 2) { mmaZ(ap[k], P[k], BK(k)); mmaZ(ar[k], R[k], BK(k)); } else { mmaA(ap[k & 1], P[k], BK(k)); mmaA(ar[k & 1], R[k], BK(k)); }
    }
    w0 = pack_bf16(ar[0][0] + ar[1][0], ar[0][1] + ar[1][1]); w1 = pack_bf16(ar[0][2] + ar[1][2], ar[0][3] + ar[1][3]);
    asm volatile("stmatrix.sync.aligned.m8n8.x4.shared.b16 [%0], {%1,%2,%3,%4};" :: "r"(qoff), "r"(w0), "r"(w1),
      "r"(pack_bf16(ap[0][0] + ap[1][0], ap[0][1] + ap[1][1])), "r"(pack_bf16(ap[0][2] + ap[1][2], ap[0][3] + ap[1][3])) : "memory");
    bar_arrive<9, 384>();
    PRB(1)
    att++;
    uint32_t bad;
    asm volatile("{.reg .pred p; setp.ne.u32 p, 0, 0; bar.red.or.pred p, 8, 384, p; selp.u32 %0, 1, 0, p;}" : "=r"(bad) :: "memory");
    if (bad) {
#pragma unroll
      for (int i = 0; i < NT; i++) LDT(i);
      continue;
    }
    lds128(dp, dpa);
    { const uint32_t pa = sb + SM_QK + 2048 - cu * 1024 + (kvo & 1023); w0 = hadd2(w0, lds32(pa)); w1 = hadd2(w1, lds32(pa + 128)); }
#pragma unroll
    for (int i = NB0; i < NT && (VR || i < NB1); i++) LDO(i, wl16);
    if (s == NSEG - 1) { MEMKV(); break; }
    uint32_t bit = ((s >> 1) & 1) ? 0u : fmask;
    char* cb = (char*)p.comm + ((s & 1) * (256 * 4096) + (kvo & 127));
    char *d0 = cb + dp[0], *d1 = cb + dp[1], *d2 = cb + dp[2], *d3 = cb + dp[3];
    if (VR) { MEMKV(); kvo += 96 * 10240; asm volatile("" : "+l"(d0), "+l"(d1), "+r"(bit)); }
    else asm volatile("" : "+l"(d0), "+l"(d1), "+l"(d2), "+l"(d3), "+r"(bit), "+r"(w0), "+r"(w1));
    sched_fence();
    if (!VR) {
      bar_sync<2, 384>();
#pragma unroll
      for (int i = NB1; i < NT; i++) LDO(i, wl16);
    }
    bar_sync<3, 384>();
    PRB(2)
    uint32_t ob[4][4];
    float z0, z1;
#pragma unroll
    for (int i = 0; i < 4; i++) LDW(ob[i], l16 + SM_OX + i * 512);
    asm volatile("ld.shared.v2.f32 {%0,%1}, [%2];" : "=f"(z0), "=f"(z1) : "r"(l16 + SM_OX + 2048) : "memory");
#define WO(i) ((i) >= 4 && (i) < 4 + NW - NT ? Wr[(i) >= 4 && (i) < 4 + NW - NT ? (i) - 4 : 0] : Wf[(i) < 4 ? (i) : (i) < 4 + NW - NT ? 0 : (i) - (NW - NT)])
    float ga[4][4];
#pragma unroll
    for (int i = 0; i < NW; i++) {
      const int ks = VR ? i : i >> 1;
      if (i < 4) mmaZ(ga[i], WO(i), ob[ks >> 1][(ks & 1) * 2], ob[ks >> 1][(ks & 1) * 2 + 1]); else mmaA(ga[i & 3], WO(i), ob[ks >> 1][(ks & 1) * 2], ob[ks >> 1][(ks & 1) * 2 + 1]);
    }
    asm("rcp.approx.ftz.f32 %0, %0;" : "+f"(z0)); asm("rcp.approx.ftz.f32 %0, %0;" : "+f"(z1));
#pragma unroll
    for (int i = 0; i < 4; i++) { ga[0][i] += ga[2][i]; ga[1][i] += ga[3][i]; if (VR) ga[0][i] += ga[1][i]; }
#pragma unroll
    for (int t = 0; t < NW / 8; t++) {
      st_relaxed(t ? d2 : d0, lop3<0xF4>(bit, pack_bf16(ga[t][0] * z0, ga[t][1] * z1), fmask));
      st_relaxed(t ? d3 : d1, lop3<0xF4>(bit, pack_bf16(ga[t][2] * z0, ga[t][3] * z1), fmask));
    }
    PRB(3)
    bar_sync<1, 384>();
    stream(s, true);
    PRB(4)
    s++;
  }
  bar_arrive<10, 384>();
  CLUSTER_SYNC();
}

#undef PRBASE
#undef PRIMM
#undef PROFF
#define PRBASE (mbar + j * 16)
#define PRIMM (1024 + 4)
#define PROFF 8
template <bool VR>
__device__ __forceinline__ void rec_attn_warps(const RecParams& p, const uint32_t sb, char* smem, const int h, const int r TLP) {
  const int lane = threadIdx.x & 31, g = lane >> 2, q = lane & 3;
  const int j = __shfl_sync(~0u, (int)(threadIdx.x >> 5) - 8, 0);
  int ct = threadIdx.x - 256;
  OPAQUE(ct);
  const uint32_t mbar = sb + SM_BAR;
  const bool is_red = VR && (j < 2 || (j == 2 && !(h & 1)));
  if (lane == 0) {
    const uint32_t* best = (const uint32_t*)(smem + SM_BAR + MB_PRB);
    const int side = ((best[1] < best[0]) ^ __popc(CM_MISC & 0xB3)) & 1;
    const int jb = j < 2 ? 2 * h + j : 64 + (h >> 1), ln = mem_line(jb) + 16, pi = ln >> 5;
    if (is_red) st_relaxed(p.comm + CM_MISC * 1024 + jb, side);
    for (int k = 0; k < 4; k++) {
      const int sl = (k + 1) & 3;
      uint32_t* t = (uint32_t*)(smem + SM_BAR + MB_TAB) + j * 16 + k * 4;
      if (j == 3) { for (int i = 0; i < 3; i++) t[i] = near_page(CM_X3 + 2 * (sl * 3 + i), side) * 4096 + (i == 0 ? 2048 : 0); t[3] = 0; }
      else {
        t[0] = near_page(2 * jb + (k & 1) * 256, side) * 4096;
        t[1] = near_page(CM_X3 + 2 * (sl * 3 + pi), side ^ 1) * 4096 + (ln & 31) * 128; t[2] = near_page(CM_X3 + 2 * (sl * 3 + pi), side) * 4096 + (ln & 31) * 128;
        t[3] = (CM_X3 + 2 * (((k + 3) & 3) * 3 + pi)) * 4096 + (ln & 31) * 128;
      }
    }
  }
  __syncwarp();
  {
    uint4 m0v[5];
#pragma unroll
    for (int i = 0; i < 5; i++) { const int v = ct + i * 128; m0v[i] = *(const uint4*)(p.mem0 + (v & 7) * D_ + (v >> 3) * 8); }
    bar_sync<1, 384>();
#pragma unroll
    for (int i = 0; i < 5; i++) {
      const int v = ct + i * 128; unsigned short* d = (unsigned short*)(smem + SM_MEMT) + mem_line(v >> 3) * 64 + (v & 7);
      d[0] = m0v[i].x; d[8] = m0v[i].x >> 16; d[16] = m0v[i].y; d[24] = m0v[i].y >> 16; d[32] = m0v[i].z; d[40] = m0v[i].z >> 16; d[48] = m0v[i].w; d[56] = m0v[i].w >> 16;
    }
    bar_sync<1, 384>();
    asm volatile("barrier.cluster.arrive.relaxed.aligned;" ::: "memory");
    sts128(sb + SM_ST + (ct >> 6) * 5120 + (ct & 63) * 16, ~0u, ~0u, ~0u, ~0u);
  }
  if (ct == 0) TL_MIN(tlid, 1);
  const int mi = lane >> 3;
  uint32_t l16 = sb + lane * 16, wr16 = l16 + j * 512;
  uint32_t ka = j < 2 ? sb + SM_ST + 6144 + (2 * j + (mi & 1)) * 1024 + ((mi >> 1) * 8 + (lane & 7)) * 16 : sb + SM_QK + j * 512 + ((mi & 1) * 16 + (mi >> 1) * 8 + (lane & 7)) * 16;
  uint32_t va = sb + SM_VR + (j >> 1) * 4096 + (mi >> 1) * 1024 + ((j & 1) * 32 + (mi & 1) * 8 + (lane & 7)) * 16;
  uint32_t own = sb + SM_SC + (r & 1) * 1024 + (j < 2 ? j * 256 : 256 + j * 128) + lane * 4, ps[2], pb[2];
#pragma unroll
  for (int i = 0; i < 2; i++) {
    const int peer = VR ? i : i == 0 ? r ^ 1 : 2;
    ps[i] = mapa(VR ? wr16 + SM_VM : own, peer); pb[i] = mapa(mbar + (VR ? MB_V : MB_QK), peer);
    OPAQUE(ps[i]); OPAQUE(pb[i]);
  }
  if (!VR) { OPAQUE(ka); OPAQUE(own); }
  OPAQUE(va); OPAQUE(wr16); OPAQUE(l16);
  const char* comm = (const char*)p.comm;
  uint32_t s0 = (g >> 1) != q ? 0u : (g & 1) ? 0x3F800000u : 0x00003F80u, s1 = s0 | (p.zero & 0x40000000), fm = (lane & 1) == 0 ? 1u : 0u;
  uint32_t ones0 = 0x3F803F80u | (p.zero & 0x40000000), ones1 = 0x3F803F80u | (p.zero & 0x40);
  if (VR) { OPAQUE(s0); OPAQUE(s1); OPAQUE(fm); }
  OPAQUE(ones0); OPAQUE(ones1);
  const float sc2 = 0.08838834764831845f * 1.4426950408889634f;
  uint32_t kf[4][4], vf[4][4];
  auto load_k = [&]() {
    if (!VR) {
#pragma unroll
      for (int i = 0; i < 4; i++) LDW(kf[i], ka + i * 256);
    }
  };
  auto load_v = [&](int n) {
    mbar_wait(mbar + MB_KV + (n & 1) * 8, (n >> 1) & 1);
#pragma unroll
    for (int i = 0; i < 4; i++) ldsm4(vf[i][0], vf[i][1], vf[i][2], vf[i][3], va + (n & 1) * 8192 + (i >> 1) * 2048 + (i & 1) * 256);
  };
  auto v_load = [&](int n) {
    asm volatile("cp.async.bulk.wait_group 0;" ::: "memory");
    if (VR) asm volatile(ELECT
      "@p cp.async.bulk.shared::cluster.global.mbarrier::complete_tx::bytes.multicast::cluster [%0], [%1], 4096, [%2], %3;\n"
      "@p cp.async.bulk.shared::cluster.global.mbarrier::complete_tx::bytes.multicast::cluster [%0+4096], [%1+5120], 4096, [%2], %3;}"
        :: "r"(sb + SM_VR + (n & 1) * 8192), "l"(p.QKV + ((size_t)(n * 32 + h) * 3 + 2) * 10240 + 1024), "r"(mbar + MB_KV + (n & 1) * 8), "h"((unsigned short)7) : "memory");
  };
  auto x_load = [&](int n) {
    if (DBGF(32)) { if (lane == 0) mbar_arrive(mbar + MB_X); return; }
    asm volatile(ELECT "@p mbarrier.arrive.expect_tx.shared.b64 _, [%2], 40960;\n"
      "@p cp.async.bulk.tensor.3d.shared::cluster.global.mbarrier::complete_tx::bytes [%0], [%1, {%3, %4, %3}], [%2];}"
        :: "r"(sb + SM_X), "l"(&p.tmX), "r"(mbar + MB_X), "r"(0), "r"(n * 32) : "memory");
  };
  auto t_store = [&](int n) {
    if (DBGF(64)) return;
    asm volatile("fence.proxy.async.shared::cta;" ::: "memory");
    asm volatile(ELECT "@p cp.async.bulk.global.shared::cta.bulk_group [%0], [%1], 10240;}" :: "l"(p.QKV + ((size_t)(n * 32 + h) * 3 + r) * 10240), "r"(sb + SM_ST) : "memory");
    asm volatile("cp.async.bulk.commit_group;" ::: "memory");
  };
  auto publish = [&](int n) {
    if (ct == 32) st_relaxed(p.comm + FL_MEM + h * 32 + r * 8, n);
  };
  if (j == 3) x_load(0);
  bar_arrive<11, 384>();
  bar_sync<14, 384>();
  asm volatile("barrier.cluster.wait.aligned;" ::: "memory");
  if (j == 3) x_load(1);
  if (j == 2) { t_store(0); v_load(0); }
  load_k();
  bar_arrive<11, 384>();
  load_v(0);
  uint32_t Tk = gt32() - p.period;
  if (ct == 96) { sts32(mbar + MB_TK, Tk); mbar_arrive(mbar + MB_A); }
  bar_sync<14, 384>();
  if (j == 3) x_load(2);
  if (j == 2) t_store(1);
  if (ct == 0) TL_MAX(tlid, 3);
  int att = 1;
#define VERDICT(bad) asm volatile("{.reg .pred p; setp.ne.u32 p, %0, 0; bar.red.or.pred p, 8, 384, p;}" :: "n"(bad) : "memory")
#pragma unroll 1
  for (int s = 0; s < NSEG - 1; s++) {
    const uint32_t par = s & 1;
    uint32_t su[6], sw[6], vm[4];
#define LDSM2T(d, a) asm volatile("ldmatrix.sync.aligned.m8n8.x2.trans.shared.b16 {%0,%1}, [%2];" : "=r"(d[4]), "=r"(d[5]) : "r"(a) : "memory")
#define HADD4(a, b) { a[0] = hadd2(a[0], b[0]); a[1] = hadd2(a[1], b[1]); a[2] = hadd2(a[2], b[2]); a[3] = hadd2(a[3], b[3]); }
    bar_sync<9, 384>();
    PRB(0)
    if (!VR) {
      uint32_t qf[2][4], qg[2][4];
      float sa[4][4];
      if (j < 2) {
        LDW(qf[0], l16 + SM_QK); LDW(qg[0], l16 + SM_QK + 2048); LDW(qf[1], l16 + SM_QK + 512); LDW(qg[1], l16 + SM_QK + 2560);
        HADD4(qf[0], qg[0]); HADD4(qf[1], qg[1]);
#pragma unroll
        for (int i = 0; i < 4; i++) mmaZ(sa[i], kf[i], qf[i >> 1][(i & 1) * 2], qf[i >> 1][(i & 1) * 2 + 1]);
        const uint32_t t0 = pack_bf16((sa[0][0] + sa[1][0]) + (sa[2][0] + sa[3][0]), (sa[0][1] + sa[1][1]) + (sa[2][1] + sa[3][1]));
        const uint32_t t1 = pack_bf16((sa[0][2] + sa[1][2]) + (sa[2][2] + sa[3][2]), (sa[0][3] + sa[1][3]) + (sa[2][3] + sa[3][3]));
        stas32<0>(ps[0], t0, pb[0]); stas32<0>(ps[1], t0, pb[1]); stas32<128>(ps[0], t1, pb[0]); stas32<128>(ps[1], t1, pb[1]);
        sts32(own, t0); sts32(own + 128, t1);
      } else {
        LDW(qf[0], wr16 + SM_QK - 1024); LDW(qg[0], wr16 + SM_QK + 1024); LDW(qf[1], ka); LDW(qg[1], ka + 2048);
        HADD4(qf[0], qg[0]); HADD4(qf[1], qg[1]);
        mmaZ(sa[0], qf[1], qf[0][0], qf[0][1]); mmaZ(sa[1], qf[1], qf[0][2], qf[0][3]);
        const uint32_t t0 = pack_bf16(sa[0][0] + sa[1][2], sa[0][1] + sa[1][3]);
        stas32<0>(ps[0], t0, pb[0]); stas32<0>(ps[1], t0, pb[1]);
        sts32(own, t0);
      }
      PRB(1)
      VERDICT(0);
      LDW(su, l16 + SM_SC + r * 1024); LDSM2T(su, l16 + SM_SC + 512 + r * 1024);
      su[4] = hadd2(su[4], su[5]);
      mbar_wait(mbar + MB_QK, par);
      PRB(2)
      LDW(sw, l16 + SM_SC + 1024 - r * 1024); LDSM2T(sw, l16 + SM_SC + 1536 - r * 1024);
    } else {
      ldsm4(vm[0], vm[1], vm[2], vm[3], wr16 + SM_QK); ldsm4(su[0], su[1], su[2], su[3], wr16 + SM_QK + 2048);
      HADD4(vm, su);
#pragma unroll
      for (int i = 0; i < 2; i++)
        asm volatile("st.async.weak.shared::cluster.mbarrier::complete_tx::bytes.v4.b32 [%0], {%1,%2,%3,%4}, [%5];" :: "r"(ps[i]), "r"(vm[0]), "r"(vm[1]), "r"(vm[2]), "r"(vm[3]), "r"(pb[i]) : "memory");
      PRB(1)
      VERDICT(0);
      mbar_wait(mbar + MB_QK, par);
      PRB(2)
      LDW(su, l16 + SM_SC); LDW(sw, l16 + SM_SC + 1024); LDSM2T(su, l16 + SM_SC + 512); LDSM2T(sw, l16 + SM_SC + 1536);
      su[4] = hadd2(su[4], su[5]);
    }
    {
      HADD4(su, sw); su[4] = hadd2(su[4], hadd2(sw[4], sw[5]));
      uint32_t m = hmax2(hmax2(hmax2(su[0], su[1]), hmax2(su[2], su[3])), su[4]);
      const uint32_t m1 = __shfl_xor_sync(~0u, m, 1), m2 = __shfl_xor_sync(~0u, m, 2), m3 = __shfl_xor_sync(~0u, m, 3);
      float t[10];
#pragma unroll
      for (int i = 0; i < 5; i++) { t[2 * i] = bf_lo(su[i]) * sc2; t[2 * i + 1] = bf_hi(su[i]) * sc2; }
      if (!VR) {
        asm volatile("" : "+f"(t[0]), "+f"(t[1]), "+f"(t[2]), "+f"(t[3]), "+f"(t[4]), "+f"(t[5]), "+f"(t[6]), "+f"(t[7]), "+f"(t[8]), "+f"(t[9]));
        mbar_wait(mbar + MB_V, par); bar_arrive<2, 384>(); lds128(vm, wr16 + SM_VM);
      }
      if (!VR) t[PINT] = __uint_as_float(lop3<0xF8>(__float_as_uint(t[PINT]), vm[0], p.zero));
      m = hmax2(hmax2(m, m1), hmax2(m2, m3));
      const float mx = fmaxf(bf_lo(m), bf_hi(m));
#define EX(i) ex2(fmaf(mx, -sc2, t[i]))
      float o1[2][4], z[4];
      const uint32_t P0 = pack_bf16(EX(0), EX(1)), P1 = pack_bf16(EX(2), EX(3));
      mmaZ(o1[0], vf[0], P0, P1); mmaZ(o1[1], vf[1], P0, P1); mma_hz(z, ones0, ones1, P0, P1);
      const float e4 = EX(4), e5 = EX(5);
      const uint32_t P2 = pack_bf16(e4, e5), P3 = pack_bf16(EX(6), EX(7));
      mmaA(o1[0], vf[2], P2, P3); mmaA(o1[1], vf[3], P2, P3); mma_h(z, ones0, ones1, P2, P3);
      const uint32_t Pm = pack_bf16(EX(8), EX(9));
      mma1688(o1[0], vm[0], vm[1], Pm); mma1688(o1[1], vm[2], vm[3], Pm); mma8_h(z, ones0, Pm);
      asm volatile("stmatrix.sync.aligned.m8n8.x4.shared.b16 [%0], {%1,%2,%3,%4};" :: "r"(wr16 + SM_OX),
        "r"(pack_bf16(o1[0][0], o1[0][1])), "r"(pack_bf16(o1[0][2], o1[0][3])), "r"(pack_bf16(o1[1][0], o1[1][1])), "r"(pack_bf16(o1[1][2], o1[1][3])) : "memory");
      if (j == 3) asm volatile("st.shared.v2.f32 [%0], {%1,%2};" :: "r"(l16 + SM_OX + 2048), "f"(z[0]), "f"(z[1]) : "memory");
    }
    bar_arrive<3, 384>();
    PRB(3)
    uint32_t tb[4];
    lds128(tb, mbar + MB_TAB + j * 64 + (s & 3) * 16);
    Tk = lds32(mbar + MB_TK);
    if (ct == 96) {
      mbar_expect(mbar + MB_QK, VR ? 1536 : 768); if (!VR) mbar_expect(mbar + MB_V, 2048);
      mbar_expect(mbar + MB_KV + par * 8, 8192);
    }
    __syncwarp();
    if (j == 2) v_load(s + 1);
    const char *g0 = comm + __shfl_sync(~0u, tb[0], 0), *g1 = comm + __shfl_sync(~0u, tb[1], 0), *g2 = comm + __shfl_sync(~0u, tb[2], 0);
    uint32_t T3 = Tk + p.period;
    if ((int)(T3 - gt32()) > 20000) T3 = gt32();
    mbar_wait(mbar + MB_X, s + 2 < NSEG ? par : 1);
    if (!VR) { PRB(4) }
    bar_sync<1, 384>();
    {
      const uint32_t dmy = lds32(mbar + MB_TK) & p.zero  , lim = gt32() + p.c3 + p.gap + dmy;
      while ((int)(lim - T3) > 0) T3 += p.slack;
    }
    load_k();
    bar_arrive<11, 384>();
#define NEXT_SLOT(T, TOL) { const uint32_t now = gt32(); while ((int)(now - T) > TOL) T += p.slack; }
    auto gather = [&]() {
      if (j == 3) {
        if (lane == 0) mbar_expect(mbar + MB_A, 10240);
        NEXT_SLOT(T3, (VR ? TOLV : TOLQ));
        wait_gt(T3);
        asm volatile("{.reg .pred p; elect.sync _|p, 0xffffffff;\n"
          "@p cp.async.bulk.shared::cluster.global.mbarrier::complete_tx::bytes [%0], [%2], 2048, [%1];\n"
          "@p cp.async.bulk.shared::cluster.global.mbarrier::complete_tx::bytes [%0+2048], [%3], 4096, [%1];\n"
          "@p cp.async.bulk.shared::cluster.global.mbarrier::complete_tx::bytes [%0+6144], [%4], 4096, [%1];}"
          :: "r"(sb + SM_MEMT), "r"(mbar + MB_A), "l"(g0), "l"(g1), "l"(g2) : "memory");
      }
    };
    if (is_red) {
      const uint32_t expect = ((s >> 1) & 1) ^ 1, o_wr = (ct & 15) * 8 + (ct & 16) / 4;
      const uint32_t* src = (const uint32_t*)(comm + (tb[0] + (ct & 31) * 8));
      uint32_t* wfar = (uint32_t*)(comm + (tb[1] + o_wr)); uint32_t* wnear = (uint32_t*)(comm + (tb[2] + o_wr)); uint32_t* wpoi = (uint32_t*)(comm + (tb[3] + o_wr));
      auto attempt = [&](bool first) {
        uint32_t x[32], ok;
#pragma unroll
        for (int i = 0; i < 16; i++) asm volatile("ld.relaxed.gpu.global.v2.u32 {%0,%1}, [%2];" : "=r"(x[2 * i]), "=r"(x[2 * i + 1]) : "l"(src + i * 64) : "memory");
        float ra[4][4];
        uint32_t bad[2];
#pragma unroll
        for (int i = 0; i < 8; i++) {
          const uint32_t u = lop3<0x7E>(x[4 * i], x[4 * i + 2], expect);
          bad[i & 1] = i < 2 ? u : (bad[i & 1] | u);
          if (i < 4) mma16816z(ra[i], x[4 * i], x[4 * i + 1], x[4 * i + 2], x[4 * i + 3], s0, s1);
          else mma16816(ra[i & 3], x[4 * i], x[4 * i + 1], x[4 * i + 2], x[4 * i + 3], s0, s1);
        }
        asm volatile("{.reg .pred p; setp.eq.u32 p, %1, 0; vote.sync.all.pred p, p, 0xffffffff; selp.u32 %0, 1, 0, p;}" : "=r"(ok) : "r"(lop3<0xA8>(bad[0], bad[1], fm)));
        const float a0 = (ra[0][0] + ra[1][0]) + (ra[2][0] + ra[3][0]), a1 = (ra[0][1] + ra[1][1]) + (ra[2][1] + ra[3][1]);
        const float a2 = (ra[0][2] + ra[1][2]) + (ra[2][2] + ra[3][2]), a3 = (ra[0][3] + ra[1][3]) + (ra[2][3] + ra[3][3]);
        const bool up = ct & 16;
        const float r0 = __shfl_xor_sync(~0u, up ? a0 : a2, 16), r1 = __shfl_xor_sync(~0u, up ? a1 : a3, 16);
        if (first) asm volatile("bar.arrive 12, %0;" :: "r"((h & 1) ? 320 : 352) : "memory");
        const uint32_t v = pack_bf16((up ? a2 : a0) + r0, (up ? a3 : a1) + r1);
        asm volatile("{.reg .pred p; setp.ne.u32 p, %3, 0; @p st.relaxed.gpu.global.u32 [%0], %2; @p st.relaxed.gpu.global.u32 [%1], %2; @p bar.arrive 15, %4;}"
          :: "l"(wfar), "l"(wnear), "r"(v), "r"(ok), "r"((h & 1) ? 96 : 128) : "memory");
        return ok;
      };
      uint32_t T2 = T3 - p.c3;
      wait_gt(T2);
      PRB(4)
      if (!attempt(true)) {
        uint32_t ok; int guard = 0;
        do { T2 += p.slack; NEXT_SLOT(T2, TOLQ); wait_gt(T2); ok = attempt(false); } while (!ok && ++guard < POLL_LIMIT);
        if (!ok) asm volatile("bar.arrive 15, %0;" :: "r"((h & 1) ? 96 : 128) : "memory");
      }
      PRB(5)
      st_relaxed(wpoi, 0xFFFFFFFFu); st_relaxed(wpoi + 1024, 0xFFFFFFFFu);
      if (s == 0 && blockIdx.x == 2 && ct == 0) st_relaxed(p.comm + CM_MISC * 1024 + 96, gt32() & ~31u);
    }
    if (VR && j == 3) asm volatile("bar.sync 15, %0;" :: "r"((h & 1) ? 96 : 128) : "memory");
    gather();
    PRB(6)
    load_v(s + 1);
    bar_sync<14, 384>();
    if (j == 3 && s + 3 < NSEG) { wait_gt(T3 + p.xlate); x_load(s + 3); }
    if (j == 2 && s + 2 < NSEG) t_store(s + 2);
    auto check = [&]() {
      uint32_t m = 0, ok;
#pragma unroll
      for (int i = 0; i < 5; i++) m = max(m, lds32(wr16 + SM_MEMT + (ct & 24) / 2 + i * 2048));
      asm volatile("{.reg .pred p; setp.ne.u32 p, %1, 0xffffffff; bar.red.and.pred p, 13, 128, p; selp.u32 %0, 1, 0, p;}" : "=r"(ok) : "r"(m) : "memory");
      return ok;
    };
    for (int guard = 0;; guard++) {
      mbar_wait(mbar + MB_A, att & 1); att++;
      if (check() || guard == POLL_LIMIT) break;
      bar_arrive<9, 384>();
      VERDICT(1);
      T3 += p.slack;
      gather();
    }
    PRB(7)
    publish(s + 1);
    if (j == 3) {
      if (s == 0) {
        int g2 = 0; do { T3 = ld_relaxed(p.comm + CM_MISC * 1024 + 96); } while (T3 == 0xFFFFFFFFu && ++g2 < POLL_LIMIT);
        T3 += p.c3;
      }
      sts32(mbar + MB_TK, T3);
    }
  }
  bar_arrive<9, 384>();
  VERDICT(0);
  bar_sync<10, 384>();
  publish(NSEG);
  if (ct == 0) TL_MAX(tlid, 2);
  CLUSTER_SYNC();
}

__global__ void __cluster_dims__(3, 1, 1) __launch_bounds__(384, 1) rec_kernel(const __grid_constant__ RecParams p TLP) {
  extern __shared__ __align__(1024) char smem_raw[];
  const uint32_t sb = (smem_u32(smem_raw) + 1023) & ~1023u;
  char* smem = smem_raw + (sb - smem_u32(smem_raw));
  const int tid = threadIdx.x, lane = tid & 31, w = tid >> 5;
  const int h = blockIdx.x / 3, r = blockIdx.x % 3;
  const uint32_t mbar = sb + SM_BAR;
  if (tid == 0) { TL_MIN(tlid, 0); TL_MAX(tlid, 4); }
  if (tid == 0) {
    for (int i = 0; i < 13; i++) mbar_init(mbar + i * 8, 1);
    asm volatile("fence.mbarrier_init.release.cluster;" ::: "memory");
    asm volatile("fence.proxy.async.shared::cta;" ::: "memory");
    mbar_expect(mbar + MB_QK, r == 2 ? 1536 : 768); if (r < 2) mbar_expect(mbar + MB_V, 2048);
    mbar_expect(mbar + MB_KV, 8192); mbar_expect(mbar + MB_KV + 8, 8192);
  }
  if (w >= 10 && lane == 0) {
    uint32_t best = ~0u; uint32_t* a = p.comm + (CM_MISC + (w & 1)) * 1024 + 128 + blockIdx.x * 8;
    for (int it = 0; it < 3; it++) {
      const uint32_t t0 = clk32();
      uint32_t v; asm volatile("atom.relaxed.gpu.global.exch.b32 %0, [%1], %2;" : "=r"(v) : "l"(a), "r"(t0) : "memory");
      st_relaxed_if(a, 0, v == t0 + 1);
      best = min(best, clk32() - t0);
    }
    ((uint32_t*)(smem + SM_BAR + MB_PRB))[w & 1] = best;
  }
  pdl_launch();
  __syncthreads();
  if (tid == 0) {
    mbar_expect(mbar + MB_IA, 163840); mbar_expect(mbar + MB_IC, r == 2 ? 32768 : 65536);
    for (int i = 0; i < 20; i++) tma2d(sb + i * 8192, &p.tmW[r == 2 ? 2 : i & 1], h * 128 + (r == 2 ? i & 1 : r) * 64, (i >> 1) * 64, mbar + MB_IA);
    for (int i = 0; i < (r == 2 ? 4 : 8); i++) tma2d(sb + SM_WST + i * 8192, &p.tmWo, r * 256 + (i >> 1) * 64, h * 128 + (i & 1) * 64, mbar + MB_IC);
  }
  if (tid == 288) pdl_wait();
  __syncthreads();
  if (w < 8) {
    if (r < 2) { asm volatile("setmaxnreg.inc.sync.aligned.u32 216;"); rec_gemm_warps<false>(p, sb, h, r TLA(tlid)); }
    else { asm volatile("setmaxnreg.inc.sync.aligned.u32 208;"); rec_gemm_warps<true>(p, sb, h, r TLA(tlid)); }
  } else {
    if (r < 2) { asm volatile("setmaxnreg.dec.sync.aligned.u32 72;"); rec_attn_warps<false>(p, sb, smem, h, r TLA(tlid)); }
    else { asm volatile("setmaxnreg.dec.sync.aligned.u32 88;"); rec_attn_warps<true>(p, sb, smem, h, r TLA(tlid)); }
  }
}

constexpr int PERIOD = 2144, C3 = 544, SLACK = 672, XLATE = 192, GAP = 32;
__device__ uint32_t g_ZT[640 * 1024];
__device__ uint32_t g_WT[321 * 2048];
__device__ bf16 g_x1[S_ * D_], g_x2[S_ * D_], g_hN[S_ * D_];
__device__ __align__(128) uint4 g_QKV[64 * 32 * 30720 / 16], g_O[ORING * 32 * 8192 / 16];
__device__ __align__(128) uint4 g_part[PRING * 32 * 8960 / 16];
__device__ uint32_t g_comm[(6 << 20) / 4];

typedef CUresult (*EncodeFn)(CUtensorMap*, CUtensorMapDataType, cuuint32_t, void*, const cuuint64_t*, const cuuint64_t*, const cuuint32_t*, const cuuint32_t*,
                             CUtensorMapInterleave, CUtensorMapSwizzle, CUtensorMapL2promotion, CUtensorMapFloatOOBfill);
static void make_map(EncodeFn fn, CUtensorMap* m, const void* base, uint64_t cols, uint64_t rows, uint32_t bc, uint32_t br) {
  cuuint64_t dims[2] = {cols, rows}, strides[1] = {cols * 2}; cuuint32_t box[2] = {bc, br}, es[2] = {1, 1};
  fn(m, CU_TENSOR_MAP_DATA_TYPE_BFLOAT16, 2, (void*)base, dims, strides, box, es, CU_TENSOR_MAP_INTERLEAVE_NONE, CU_TENSOR_MAP_SWIZZLE_128B, CU_TENSOR_MAP_L2_PROMOTION_L2_256B, CU_TENSOR_MAP_FLOAT_OOB_FILL_NONE);
}
template <typename T> static T* sym(T& s) { void* p; cudaGetSymbolAddress(&p, s); return (T*)p; }

template <typename... KA, typename... A> static void launch(void (*k)(KA...), int grid, int block, int smem, bool pdl, A... a) {
  cudaLaunchConfig_t cfg = {};
  cfg.gridDim = dim3(grid); cfg.blockDim = dim3(block); cfg.dynamicSmemBytes = smem; cfg.stream = cudaStreamPerThread;
  cudaLaunchAttribute at[1]; at[0].id = cudaLaunchAttributeProgrammaticStreamSerialization; at[0].val.programmaticStreamSerializationAllowed = 1;
  cfg.attrs = at; cfg.numAttrs = pdl ? 1 : 0;
  cudaLaunchKernelEx(&cfg, k, KA(a)...);
}

extern "C" void kernel_launch(void* const* d_in, const int* in_sizes, int n_in, void* d_out, int out_size) {
  const bf16 *x = (const bf16*)d_in[0], *wr = (const bf16*)d_in[1], *wi = (const bf16*)d_in[2], *mem0 = (const bf16*)d_in[4];
  const bf16 *Wq = (const bf16*)d_in[5], *Wk = (const bf16*)d_in[6], *Wv = (const bf16*)d_in[7], *Wo = (const bf16*)d_in[8];
  bf16* out = (bf16*)d_out;
  uint32_t *ZT = (uint32_t*)sym(g_ZT), *WT = (uint32_t*)sym(g_WT);
  bf16 *x1 = (bf16*)sym(g_x1), *x2 = (bf16*)sym(g_x2), *hN = (bf16*)sym(g_hN);
  char *QKV = (char*)sym(g_QKV), *part = (char*)sym(g_part);
  uint32_t* comm = (uint32_t*)(((uint64_t)sym(g_comm) + (2 << 20) - 1) & ~(uint64_t)((2 << 20) - 1));
  EncodeFn enc = nullptr; cudaDriverEntryPointQueryResult qr;
  cudaGetDriverEntryPoint("cuTensorMapEncodeTiled", (void**)&enc, cudaEnableDefault, &qr);
  CUtensorMap tmW[3], tmWo, tmX, tmP;
  { cuuint64_t dims[3] = {64, PRING * 32, 70}, strides[2] = {8960, 128}; cuuint32_t box[3] = {64, 32, 2}, es[3] = {1, 1, 1};
    enc(&tmP, CU_TENSOR_MAP_DATA_TYPE_BFLOAT16, 3, part, dims, strides, box, es, CU_TENSOR_MAP_INTERLEAVE_NONE, CU_TENSOR_MAP_SWIZZLE_128B, CU_TENSOR_MAP_L2_PROMOTION_NONE, CU_TENSOR_MAP_FLOAT_OOB_FILL_NONE); }
  { cuuint64_t dims[3] = {64, 2048, 10}, strides[2] = {1280, 128}; cuuint32_t box[3] = {64, 32, 10}, es[3] = {1, 1, 1};
    enc(&tmX, CU_TENSOR_MAP_DATA_TYPE_BFLOAT16, 3, hN, dims, strides, box, es, CU_TENSOR_MAP_INTERLEAVE_NONE, CU_TENSOR_MAP_SWIZZLE_128B, CU_TENSOR_MAP_L2_PROMOTION_L2_256B, CU_TENSOR_MAP_FLOAT_OOB_FILL_NONE); }
  make_map(enc, &tmW[0], Wq, 4096, 640, 64, 64); make_map(enc, &tmW[1], Wk, 4096, 640, 64, 64); make_map(enc, &tmW[2], Wv, 4096, 640, 64, 64);
  make_map(enc, &tmWo, Wo, 640, 4096, 64, 64);
  int dbgf = 0;
  constexpr int KA_PAD = 84 * 1024;
  cudaFuncSetAttribute(ka1_kernel, cudaFuncAttributeMaxDynamicSharedMemorySize, KA_PAD);
  cudaFuncSetAttribute(ka3_kernel, cudaFuncAttributeMaxDynamicSharedMemorySize, KA_PAD);
  cudaFuncSetAttribute(ka1_kernel, cudaFuncAttributePreferredSharedMemoryCarveout, 100);
  cudaFuncSetAttribute(kprep_kernel, cudaFuncAttributePreferredSharedMemoryCarveout, 100);
  cudaFuncSetAttribute(ka2_kernel, cudaFuncAttributePreferredSharedMemoryCarveout, 100);
  cudaFuncSetAttribute(ka3_kernel, cudaFuncAttributePreferredSharedMemoryCarveout, 100);
  cudaFuncSetAttribute(side_kernel, cudaFuncAttributeMaxDynamicSharedMemorySize, SD_SMEM);
  cudaFuncSetAttribute(rec_kernel, cudaFuncAttributeMaxDynamicSharedMemorySize, REC_SMEM);
  for (int L = 0; L < 2; L++) {
    const bf16* xin = L == 0 ? x : x2;
    uint32_t* cm = comm + L * ((2 << 20) / 4);
    launch(ka1_kernel, 128, 256, KA_PAD, L > 0, xin, ZT, Wk, Wv TLA(L * 10 + 0));
    if (L == 0) launch(kprep_kernel, 352, 256, 0, true, wr, wi, WT, comm TLA(1));
    launch(ka2_kernel, 321, 128, 0, true, ZT, WT TLA(L * 10 + 2));
    launch(ka3_kernel, 128, 256, KA_PAD, true, ZT, xin, x1, hN, Wq, Wo TLA(L * 10 + 3));
    RecParams rp = {{tmW[0], tmW[1], tmW[2]}, tmWo, tmX, mem0, QKV, cm, PERIOD, C3, SLACK, XLATE, GAP, 0, dbgf, nullptr, nullptr};
    SideParams sp = {tmWo, tmP, QKV, (char*)sym(g_O), part, x1, L == 0 ? x2 : out, cm, dbgf};
    launch(rec_kernel, 96, 384, REC_SMEM, true, rp TLA(L * 10 + 5));
    launch(side_kernel, 35, 512, SD_SMEM, !(dbgf & 16), sp TLA(L * 10 + 6));
  }
}
```

```cpp
#include <cuda_runtime.h>
#include <cuda_bf16.h>
#include <cuda.h>
#include <stdint.h>
typedef __nv_bfloat16 bf16;
constexpr int S_ = 2048, D_ = 640, H_ = 32, DH = 128, NSEG = 64;

__device__ __forceinline__ uint32_t smem_u32(const void* p) { return (uint32_t)__cvta_generic_to_shared(p); }
__device__ __forceinline__ uint32_t pack_bf16(float lo, float hi) { uint32_t r; asm("cvt.rn.bf16x2.f32 %0, %1, %2;" : "=r"(r) : "f"(hi), "f"(lo)); return r; }
__device__ __forceinline__ float bf_lo(uint32_t v) { return __uint_as_float(v << 16); }
__device__ __forceinline__ float bf_hi(uint32_t v) { return __uint_as_float(v & 0xFFFF0000u); }
__device__ __forceinline__ void ldsm4t(uint32_t& r0, uint32_t& r1, uint32_t& r2, uint32_t& r3, uint32_t a) {
  asm volatile("ldmatrix.sync.aligned.m8n8.x4.trans.shared.b16 {%0,%1,%2,%3}, [%4];" : "=r"(r0), "=r"(r1), "=r"(r2), "=r"(r3) : "r"(a) : "memory");
}
__device__ __forceinline__ void ldsm4(uint32_t& r0, uint32_t& r1, uint32_t& r2, uint32_t& r3, uint32_t a) {
  asm volatile("ldmatrix.sync.aligned.m8n8.x4.shared.b16 {%0,%1,%2,%3}, [%4];" : "=r"(r0), "=r"(r1), "=r"(r2), "=r"(r3) : "r"(a) : "memory");
}
__device__ __forceinline__ void mma16816(float* d, uint32_t a0, uint32_t a1, uint32_t a2, uint32_t a3, uint32_t b0, uint32_t b1) {
  asm volatile("mma.sync.aligned.m16n8k16.row.col.f32.bf16.bf16.f32 {%0,%1,%2,%3}, {%4,%5,%6,%7}, {%8,%9}, {%0,%1,%2,%3};"
    : "+f"(d[0]), "+f"(d[1]), "+f"(d[2]), "+f"(d[3]) : "r"(a0), "r"(a1), "r"(a2), "r"(a3), "r"(b0), "r"(b1));
}
__device__ __forceinline__ void mma16816z(float* d, uint32_t a0, uint32_t a1, uint32_t a2, uint32_t a3, uint32_t b0, uint32_t b1) {
  asm volatile("mma.sync.aligned.m16n8k16.row.col.f32.bf16.bf16.f32 {%0,%1,%2,%3}, {%4,%5,%6,%7}, {%8,%9}, {%10,%10,%10,%10};"
    : "=f"(d[0]), "=f"(d[1]), "=f"(d[2]), "=f"(d[3]) : "r"(a0), "r"(a1), "r"(a2), "r"(a3), "r"(b0), "r"(b1), "f"(0.f));
}
__device__ __forceinline__ void mma1688z(float* d, uint32_t a0, uint32_t a1, uint32_t b0) {
  asm volatile("mma.sync.aligned.m16n8k8.row.col.f32.bf16.bf16.f32 {%0,%1,%2,%3}, {%4,%5}, {%6}, {%7,%7,%7,%7};"
    : "=f"(d[0]), "=f"(d[1]), "=f"(d[2]), "=f"(d[3]) : "r"(a0), "r"(a1), "r"(b0), "f"(0.f));
}
__device__ __forceinline__ void mma1688(float* d, uint32_t a0, uint32_t a1, uint32_t b0) {
  asm volatile("mma.sync.aligned.m16n8k8.row.col.f32.bf16.bf16.f32 {%0,%1,%2,%3}, {%4,%5}, {%6}, {%0,%1,%2,%3};"
    : "+f"(d[0]), "+f"(d[1]), "+f"(d[2]), "+f"(d[3]) : "r"(a0), "r"(a1), "r"(b0));
}
__device__ __forceinline__ void mmaA(float* d, const uint32_t* a, uint32_t b0, uint32_t b1) { mma16816(d, a[0], a[1], a[2], a[3], b0, b1); }
__device__ __forceinline__ void mmaZ(float* d, const uint32_t* a, uint32_t b0, uint32_t b1) { mma16816z(d, a[0], a[1], a[2], a[3], b0, b1); }
__device__ __forceinline__ uint32_t movm(uint32_t a) { uint32_t d; asm volatile("movmatrix.sync.aligned.m8n8.trans.b16 %0, %1;" : "=r"(d) : "r"(a)); return d; }
__device__ __forceinline__ void cp_async16(uint32_t dst, const void* src) { asm volatile("cp.async.cg.shared.global [%0], [%1], 16;" :: "r"(dst), "l"(src) : "memory"); }
__device__ __forceinline__ void cp_commit() { asm volatile("cp.async.commit_group;" ::: "memory"); }
template <int N> __device__ __forceinline__ void cp_wait() { asm volatile("cp.async.wait_group %0;" :: "n"(N) : "memory"); }
__device__ __forceinline__ void lds128(uint32_t* r, uint32_t a) { asm volatile("ld.shared.v4.b32 {%0,%1,%2,%3}, [%4];" : "=r"(r[0]), "=r"(r[1]), "=r"(r[2]), "=r"(r[3]) : "r"(a) : "memory"); }
__device__ __forceinline__ void sts128(uint32_t a, uint32_t r0, uint32_t r1, uint32_t r2, uint32_t r3) { asm volatile("st.shared.v4.b32 [%0], {%1,%2,%3,%4};" :: "r"(a), "r"(r0), "r"(r1), "r"(r2), "r"(r3) : "memory"); }
__device__ __forceinline__ void stg128(void* p, uint32_t r0, uint32_t r1, uint32_t r2, uint32_t r3) { asm volatile("st.global.v4.b32 [%0], {%1,%2,%3,%4};" :: "l"(p), "r"(r0), "r"(r1), "r"(r2), "r"(r3) : "memory"); }
template <int ID, int N> __device__ __forceinline__ void bar_sync() { asm volatile("bar.sync %0, %1;" :: "n"(ID), "n"(N) : "memory"); }
template <int ID, int N> __device__ __forceinline__ void bar_arrive() { asm volatile("bar.arrive %0, %1;" :: "n"(ID), "n"(N) : "memory"); }
__device__ __forceinline__ void mbar_wait(uint32_t bar, uint32_t parity) {
  asm volatile("{\n.reg .pred p, pq;\n.reg .u32 n;\nmov.u32 n, 0;\nLW%=:\nmbarrier.try_wait.parity.shared::cta.b64 p, [%0], %1;\n@p bra.uni LD%=;\nadd.u32 n, n, 1;\nsetp.lt.u32 pq, n, 20000;\n@pq bra.uni LW%=;\nLD%=:\n}" :: "r"(bar), "r"(parity) : "memory");
}
#define mbar_wait_long mbar_wait
__device__ __forceinline__ void mbar_init(uint32_t bar, int n) { asm volatile("mbarrier.init.shared.b64 [%0], %1;" :: "r"(bar), "r"(n) : "memory"); }
__device__ __forceinline__ void mbar_expect(uint32_t bar, int bytes) { asm volatile("mbarrier.arrive.expect_tx.shared.b64 _, [%0], %1;" :: "r"(bar), "r"(bytes) : "memory"); }
__device__ __forceinline__ void mbar_arrive(uint32_t bar) { asm volatile("mbarrier.arrive.shared.b64 _, [%0];" :: "r"(bar) : "memory"); }
__device__ __forceinline__ void l2_prefetch(const void* p, int bytes) { asm volatile("cp.async.bulk.prefetch.L2.global [%0], %1;" :: "l"(p), "r"(bytes) : "memory"); }
__device__ __forceinline__ float ex2(float x) { float y; asm("ex2.approx.ftz.f32 %0, %1;" : "=f"(y) : "f"(x)); return y; }
__device__ __forceinline__ void pdl_wait() { asm volatile("griddepcontrol.wait;" ::: "memory"); }
__device__ __forceinline__ void pdl_launch() { asm volatile("griddepcontrol.launch_dependents;" ::: "memory"); }
__device__ __forceinline__ uint32_t hadd2(uint32_t a, uint32_t b) { uint32_t r; asm("add.rn.bf16x2 %0, %1, %2;" : "=r"(r) : "r"(a), "r"(b)); return r; }
__device__ __forceinline__ void sched_fence() { asm volatile("{\n.reg .pred p;\n.reg .u32 t;\nLF%=:\nmov.u32 t, %%clock;\nsetp.eq.u32 p, t, %0;\n@p bra.uni LF%=;\n}" :: "n"(12345) : "memory"); }
#define TL_MIN(id, k)
#define TL_MAX(id, k)
#define TLP
#define TLA(x)

constexpr int TB_F16 = 0, TB_640 = 64, TB_F40 = 384, TB_F32 = 784, TB_512 = 1040, TB_2048 = 1296;
__device__ __align__(128) const uint32_t g_tab[6208] = {
0x3f803f80,0xbf803f80,0x3f803f80,0xbf803f80,0x3f803f80,0xbf803f80,0x3f803f80,0xbf803f80,0x3f803f80,0xbf803f80,0x3f803f80,0xbf803f80,0x3f803f80,0xbf803f80,0x3f803f80,0xbf803f80,
0x3f6d3f80,0xbf6d3f80,0xbf6dbf80,0x3f6dbf80,0x3ec43f35,0xbec43f35,0xbec4bf35,0x3ec4bf35,0xbec40000,0x3ec40000,0x3ec40000,0xbec40000,0xbf6dbf35,0x3f6dbf35,0x3f6d3f35,0xbf6d3f35,
0x3f353f80,0xbf353f80,0x3f353f80,0xbf353f80,0xbf350000,0x3f350000,0xbf350000,0x3f350000,0xbf35bf80,0x3f35bf80,0xbf35bf80,0x3f35bf80,0x3f350000,0xbf350000,0x3f350000,0xbf350000,
0x3ec43f80,0xbec43f80,0xbec4bf80,0x3ec4bf80,0xbf6dbf35,0x3f6dbf35,0x3f6d3f35,0xbf6d3f35,0x3f6d0000,0xbf6d0000,0xbf6d0000,0x3f6d0000,0xbec43f35,0x3ec43f35,0x3ec4bf35,0xbec4bf35,
0x3f80,0x3f80,0x3f80,0x3f80,0xbf80,0xbf80,0xbf80,0xbf80,0x3f80,0x3f80,0x3f80,0x3f80,0xbf80,0xbf80,0xbf80,0xbf80,
0xbec43f80,0x3ec43f80,0x3ec4bf80,0xbec4bf80,0x3f6dbf35,0xbf6dbf35,0xbf6d3f35,0x3f6d3f35,0xbf6d0000,0x3f6d0000,0x3f6d0000,0xbf6d0000,0x3ec43f35,0xbec43f35,0xbec4bf35,0x3ec4bf35,
0xbf353f80,0x3f353f80,0xbf353f80,0x3f353f80,0x3f350000,0xbf350000,0x3f350000,0xbf350000,0x3f35bf80,0xbf35bf80,0x3f35bf80,0xbf35bf80,0xbf350000,0x3f350000,0xbf350000,0x3f350000,
0xbf6d3f80,0x3f6d3f80,0x3f6dbf80,0xbf6dbf80,0xbec43f35,0x3ec43f35,0x3ec4bf35,0xbec4bf35,0x3ec40000,0xbec40000,0xbec40000,0x3ec40000,0x3f6dbf35,0xbf6dbf35,0xbf6d3f35,0x3f6d3f35,
0x80008000,0x80008000,0x80008000,0x80008000,0x80008000,0x80008000,0x80008000,0x80008000,0x80008000,0x80008000,0x80008000,0x80008000,0x80008000,0x80008000,0x80008000,0x80008000,
0xbec48000,0x3ec48000,0x3ec48000,0xbec48000,0xbf6dbf35,0x3f6dbf35,0x3f6d3f35,0xbf6d3f35,0xbf6dbf80,0x3f6dbf80,0x3f6d3f80,0xbf6d3f80,0xbec4bf35,0x3ec4bf35,0x3ec43f35,0xbec43f35,
0xbf358000,0x3f358000,0xbf358000,0x3f358000,0xbf35bf80,0x3f35bf80,0xbf35bf80,0x3f35bf80,0x3f358000,0xbf358000,0x3f358000,0xbf358000,0x3f353f80,0xbf353f80,0x3f353f80,0xbf353f80,
0xbf6d8000,0x3f6d8000,0x3f6d8000,0xbf6d8000,0x3ec4bf35,0xbec4bf35,0xbec43f35,0x3ec43f35,0x3ec43f80,0xbec43f80,0xbec4bf80,0x3ec4bf80,0xbf6dbf35,0x3f6dbf35,0x3f6d3f35,0xbf6d3f35,
0xbf808000,0x3f808000,0xbf808000,0x3f808000,0x3f808000,0xbf808000,0x3f808000,0xbf808000,0xbf808000,0x3f808000,0xbf808000,0x3f808000,0x3f808000,0xbf808000,0x3f808000,0xbf808000,
0xbf6d8000,0x3f6d8000,0x3f6d8000,0xbf6d8000,0x3ec43f35,0xbec43f35,0xbec4bf35,0x3ec4bf35,0x3ec4bf80,0xbec4bf80,0xbec43f80,0x3ec43f80,0xbf6d3f35,0x3f6d3f35,0x3f6dbf35,0xbf6dbf35,
0xbf358000,0x3f358000,0xbf358000,0x3f358000,0xbf353f80,0x3f353f80,0xbf353f80,0x3f353f80,0x3f358000,0xbf358000,0x3f358000,0xbf358000,0x3f35bf80,0xbf35bf80,0x3f35bf80,0xbf35bf80,
0xbec48000,0x3ec48000,0x3ec48000,0xbec48000,0xbf6d3f35,0x3f6d3f35,0x3f6dbf35,0xbf6dbf35,0xbf6d3f80,0x3f6d3f80,0x3f6dbf80,0xbf6dbf80,0xbec43f35,0x3ec43f35,0x3ec4bf35,0xbec4bf35,
0x3f800000,0x3f800000,0x3f800000,0x3f7f35f9,0x3f800000,0x3f800000,0x3f7cd925,0x3f78ed3c,0x3f800000,0x3f800000,0x3f737871,0x3f6c835e,0x3f800000,0x3f800000,0x3f641901,0x3f5a46a0,
0x3f800000,0x3f7ffcd7,0x3f800000,0x3f7f0059,0x3f7ff35e,0x3f7fe394,0x3f7c0361,0x3f770f11,0x3f7fcd79,0x3f7fb10f,0x3f702d4f,0x3f676bd8,0x3f7f8e56,0x3f7f654e,0x3f5cdc29,0x3f50935b,
0x3f800000,0x3f7ff35e,0x3f800000,0x3f7ec46d,0x3f7fcd79,0x3f7f8e56,0x3f7b14be,0x3f74fa0b,0x3f7f35f9,0x3f7ec46d,0x3f6c835e,0x3f61c598,0x3f7e39bc,0x3f7d95f4,0x3f54db31,0x3f45e403,
0x3f800000,0x3f7fe394,0x3f800000,0x3f7e8238,0x3f7f8e56,0x3f7f0059,0x3f7a0d54,0x3f72ae9e,0x3f7e39bc,0x3f7d3aac,0x3f687c12,0x3f5b941a,0x3f7c0361,0x3f7a9421,0x3f4c1d35,0x3f3a4582,
0x3f800000,0x3f7fcd79,0x3f800000,0x3f7e39bc,0x3f7f35f9,0x3f7e39bc,0x3f78ed3c,0x3f702d4f,0x3f7cd925,0x3f7b14be,0x3f641901,0x3f54db31,0x3f78ed3c,0x3f766377,0x3f42a9f7,0x3f2dc5e3,
0x3f800000,0x3f7fb10f,0x3f800000,0x3f7deafa,0x3f7ec46d,0x3f7d3aac,0x3f77b493,0x3f6d76aa,0x3f7b14be,0x3f7853f8,0x3f5f5be6,0x3f4d9f02,0x3f74fa0b,0x3f710908,0x3f3889dc,0x3f207440,
0x3f800000,0x3f7f8e56,0x3f800000,0x3f7d95f4,0x3f7e39bc,0x3f7c0361,0x3f766377,0x3f6a8b4b,0x3f78ed3c,0x3f74fa0b,0x3f5a46a0,0x3f45e403,0x3f702d4f,0x3f6a8b4b,0x3f2dc5e3,0x3f1260b2,
0x3f800000,0x3f7f654e,0x3f800000,0x3f7d3aac,0x3f7d95f4,0x3f7a9421,0x3f74fa0b,0x3f676bd8,0x3f766377,0x3f710908,0x3f54db31,0x3f3daef9,0x3f6a8b4b,0x3f62f219,0x3f226799,0x3f039c3d,
0x3f800000,0x3f800000,0x3f4f1bbd,0x3f42a9f7,0x3f800000,0x3f800000,0x3f3504f3,0x3f26423a,0x3f800000,0x3f800000,0x3f167918,0x3f05c277,0x3f800000,0x3f800000,0x3ee87171,0x3ec3ef15,
0x3f7f35f9,0x3f7f0059,0x3f42a9f7,0x3f333bc6,0x3f7ec46d,0x3f7e8238,0x3f226799,0x3f104f0e,0x3f7e39bc,0x3f7deafa,0x3efa2c90,0x3ed1c759,0x3f7d95f4,0x3f7d3aac,0x3ea7bf25,0x3e78cfcc,
0x3f7cd925,0x3f7c0361,0x3f3504f3,0x3f226799,0x3f7b14be,0x3f7a0d54,0x3f0e39da,0x3ef15aea,0x3f78ed3c,0x3f77b493,0x3ec3ef15,0x3e94a031,0x3f766377,0x3f74fa0b,0x3e47c5c2,0x3dc8bd36,
0x3f78ed3c,0x3f770f11,0x3f26423a,0x3f104f0e,0x3f74fa0b,0x3f72ae9e,0x3ef15aea,0x3ebf47d7,0x3f702d4f,0x3f6d76aa,0x3e8afa3e,0x3e2a1c3f,0x3f6a8b4b,0x3f676bd8,0x3d712283,0xbd48fb30,
0x3f737871,0x3f702d4f,0x3f167918,0x3efa2c90,0x3f6c835e,0x3f687c12,0x3ec3ef15,0x3e8afa3e,0x3f641901,0x3f5f5be6,0x3e20305b,0x3d20cee7,0x3f5a46a0,0x3f54db31,0xbda0af2a,0xbe47c5c2,
0x3f6c835e,0x3f676bd8,0x3f05c277,0x3ed1c759,0x3f61c598,0x3f5b941a,0x3e94a031,0x3e2a1c3f,0x3f54db31,0x3f4d9f02,0x3d20cee7,0xbdb4b86a,0x3f45e403,0x3f3daef9,0xbe5b73dc,0xbeac7cd4,
0x3f641901,0x3f5cdc29,0x3ee87171,0x3ea7bf25,0x3f54db31,0x3f4c1d35,0x3e47c5c2,0x3d712283,0x3f42a9f7,0x3f3889dc,0xbda0af2a,0xbe5b73dc,0x3f2dc5e3,0x3f226799,0xbeb13641,0xbef15aea,
0x3f5a46a0,0x3f50935b,0x3ec3ef15,0x3e78cfcc,0x3f45e403,0x3f3a4582,0x3dc8bd36,0xbd48fb30,0x3f2dc5e3,0x3f207440,0xbe47c5c2,0xbeac7cd4,0x3f1260b2,0x3f039c3d,0xbef15aea,0xbf187fc0,
0x3f800000,0x3f800000,0x3e9e377a,0x3e6f0c4d,0x3f800000,0x3f800000,0x3e20305b,0x3da0af2a,0x3f800000,0x3f800000,0,0xbda0af2a,0x3f800000,0x3f800000,0xbe20305b,0xbe6f0c4d,
0x3f7cd925,0x3f7c7160,0x3e20305b,0x3d8ca1f2,0x3f7c0361,0x3f7b8f2a,0xbca0d6d6,0xbddcbd0d,0x3f7b14be,0x3f7a9421,0xbe47c5c2,0xbe8fcefe,0x3f7a0d54,0x3f79805c,0xbeba9be1,0xbee3f40d,
0x3f737871,0x3f71decf,0,0xbdc8bd36,0x3f702d4f,0x3f6e641a,0xbe47c5c2,0xbe94a031,0x3f6c835e,0x3f6a8b4b,0xbec3ef15,0xbef15aea,0x3f687c12,0x3f6655e7,0xbf0e39da,0xbf226799,
0x3f641901,0x3f609384,0xbe20305b,0xbe862210,0x3f5cdc29,0x3f58f3c4,0xbeba9be1,0xbeece91a,0x3f54db31,0x3f50935b,0xbf0e39da,0xbf2456f1,0x3f4c1d35,0x3f4779bc,0xbf3889dc,0xbf4a965e,
0x3f4f1bbd,0x3f490a88,0xbe9e377a,0xbed65a92,0x3f42a9f7,0x3f3bfc8f,0xbf05c277,0xbf1e7cf1,0x3f3504f3,0x3f2dc5e3,0xbf3504f3,0xbf490a88,0x3f26423a,0x3f1e7cf1,0xbf5a46a0,0xbf687c12,
0x3f3504f3,0x3f2beb4a,0xbee87171,0xbf104f0e,0x3f226799,0x3f187fc0,0xbf2a0c73,0xbf4105b8,0x3f0e39da,0x3f039c3d,0xbf54db31,0xbf653a48,0x3ef15aea,0x3edae880,0xbf71decf,0xbf7a9421,
0x3f167918,0x3f0a04f8,0xbf167918,0xbf316e2c,0x3efa2c90,0x3edf7108,0xbf490a88,0xbf5cdc29,0x3ec3ef15,0x3ea7bf25,0xbf6c835e,0xbf77b493,0x3e8afa3e,0x3e5b73dc,0xbf7e39bc,0xbf7ff35e,
0x3ee87171,0x3ec8917e,0xbf3504f3,0xbf4d9f02,0x3ea7bf25,0x3e862210,0xbf61c598,0xbf710908,0x3e47c5c2,0x3e0255f4,0xbf7b14be,0xbf7fb10f,0x3d712283,0xbc20d8d2,0xbf7ec46d,0xbf7853f8,
0x3f800000,0x3f800000,0xbe9e377a,0xbec3ef15,0x3f800000,0x3f800000,0xbee87171,0xbf05c277,0x3f800000,0x3f800000,0xbf167918,0xbf26423a,0x3f800000,0x3f800000,0xbf3504f3,0xbf42a9f7,
0x3f78ed3c,0x3f7853f8,0xbf05c277,0xbf187fc0,0x3f77b493,0x3f770f11,0xbf2a0c73,0xbf3a4582,0x3f766377,0x3f75b1c9,0xbf490a88,0xbf563e03,0x3f74fa0b,0x3f743c41,0xbf61c598,0xbf6b8a3d,
0x3f641901,0x3f61c598,0xbf3504f3,0xbf45e403,0x3f5f5be6,0x3f5cdc29,0xbf54db31,0xbf61c598,0x3f5a46a0,0x3f579b8c,0xbf6c835e,0xbf74fa0b,0x3f54db31,0x3f5205d4,0xbf7b14be,0xbf7ec46d,
0x3f42a9f7,0x3f3daef9,0xbf5a46a0,0xbf676bd8,0x3f3889dc,0x3f333bc6,0xbf71decf,0xbf79805c,0x3f2dc5e3,0x3f28296a,0xbf7e39bc,0xbf7ffcd7,0x3f226799,0x3f1c81b9,0xbf7ec46d,0xbf7a9421,
0x3f167918,0x3f0e39da,0xbf737871,0xbf7b14be,0x3f05c277,0x3efa2c90,0xbf7f35f9,0xbf7fcd79,0x3ee87171,0x3ed65a92,0xbf7cd925,0xbf766377,0x3ec3ef15,0x3eb13641,0xbf6c835e,0xbf5f5be6,
0x3ec3ef15,0x3eac7cd4,0xbf7f35f9,0xbf7fb10f,0x3e94a031,0x3e78cfcc,0xbf7c0361,0xbf743c41,0x3e47c5c2,0x3e164083,0xbf687c12,0xbf58f3c4,0x3dc8bd36,0x3d48fb30,0xbf45e403,0xbf2f9c32,
0x3e20305b,0x3dc8bd36,0xbf7cd925,0xbf74fa0b,0x3d20cee7,0xbca0d6d6,0xbf687c12,0xbf579b8c,0xbda0af2a,0xbe0c4cf7,0xbf42a9f7,0xbf2a0c73,0xbe47c5c2,0xbe814693,0xbf0e39da,0xbedf7108,
0xbda0af2a,0xbe164083,0xbf6c835e,0xbf5b941a,0xbe5b73dc,0xbe8fcefe,0xbf45e403,0xbf2beb4a,0xbeb13641,0xbed1c759,0xbf0e39da,0xbedae880,0xbef15aea,0xbf07e565,0xbe94a031,0xbe164083,
0x3f800000,0x3f800000,0xbf4f1bbd,0xbf5a46a0,0x3f800000,0x3f800000,0xbf641901,0xbf6c835e,0x3f800000,0x3f800000,0xbf737871,0xbf78ed3c,0x3f800000,0x3f800000,0xbf7cd925,0xbf7f35f9,
0x3f737871,0x3f72ae9e,0xbf737871,0xbf79805c,0x3f71decf,0x3f710908,0xbf7d95f4,0xbf7fb10f,0x3f702d4f,0x3f6f4ba8,0xbf7fcd79,0xbf7deafa,0x3f6e641a,0x3f6d76aa,0xbf7a0d54,0xbf743c41,
0x3f4f1bbd,0x3f4c1d35,0xbf800000,0xbf7ec46d,0x3f490a88,0x3f45e403,0xbf7b14be,0xbf74fa0b,0x3f42a9f7,0x3f3f5cb5,0xbf6c835e,0xbf61c598,0x3f3bfc8f,0x3f3889dc,0xbf54db31,0xbf45e403,
0x3f167918,0x3f104f0e,0xbf737871,0xbf698690,0x3f0a04f8,0x3f039c3d,0xbf5cdc29,0xbf4d9f02,0x3efa2c90,0x3eece91a,0xbf3bfc8f,0xbf28296a,0x3edf7108,0x3ed1c759,0xbf1260b2,0xbef5c6c5,
0x3e9e377a,0x3e8afa3e,0xbf4f1bbd,0xbf3bfc8f,0x3e6f0c4d,0x3e47c5c2,0xbf26423a,0xbf0e39da,0x3e20305b,0x3df0b772,0xbee87171,0xbeb13641,0x3da0af2a,0x3d20cee7,0xbe6f0c4d,0xbdf0b772,
0,0xbd48fb30,0xbf167918,0xbef5c6c5,0xbdc8bd36,0xbe164083,0xbeba9be1,0xbe78cfcc,0xbe47c5c2,0xbe78cfcc,0xbdf0b772,0x3c20d8d2,0xbe94a031,0xbeac7cd4,0x3e0c4cf7,0x3e862210,
0xbe9e377a,0xbeba9be1,0xbe9e377a,0xbe3403f1,0xbed65a92,0xbef15aea,0xbd20cee7,0x3dc8bd36,0xbf05c277,0xbf1260b2,0x3e6f0c4d,0x3eba9be1,0xbf1e7cf1,0xbf2a0c73,0x3efa2c90,0x3f1a82a4,
0xbf167918,0xbf2456f1,0,0x3e164083,0xbf316e2c,0xbf3daef9,0x3e94a031,0x3edae880,0xbf490a88,0xbf53731f,0x3f0e39da,0x3f2beb4a,0xbf5cdc29,0xbf653a48,0x3f45e403,0x3f5b941a,
0x80000000,0x80000000,0x80000000,0xbda0af2a,0x80000000,0x80000000,0xbe20305b,0xbe6f0c4d,0x80000000,0x80000000,0xbe9e377a,0xbec3ef15,0x80000000,0x80000000,0xbee87171,0xbf05c277,
0x80000000,0xbc20d8d2,0x80000000,0xbdb4b86a,0xbca0d6d6,0xbcf13d4c,0xbe3403f1,0xbe862210,0xbd20cee7,0xbd48fb30,0xbeb13641,0xbedae880,0xbd712283,0xbd8ca1f2,0xbf0172c3,0xbf146eba,
0x80000000,0xbca0d6d6,0x80000000,0xbdc8bd36,0xbd20cee7,0xbd712283,0xbe47c5c2,0xbe94a031,0xbda0af2a,0xbdc8bd36,0xbec3ef15,0xbef15aea,0xbdf0b772,0xbe0c4cf7,0xbf0e39da,0xbf226799,
0x80000000,0xbcf13d4c,0x80000000,0xbddcbd0d,0xbd712283,0xbdb4b86a,0xbe5b73dc,0xbea2fd52,0xbdf0b772,0xbe164083,0xbed65a92,0xbf039c3d,0xbe3403f1,0xbe519f65,0xbf1a82a4,0xbf2f9c32,
0x80000000,0xbd20cee7,0x80000000,0xbdf0b772,0xbda0af2a,0xbdf0b772,0xbe6f0c4d,0xbeb13641,0xbe20305b,0xbe47c5c2,0xbee87171,0xbf0e39da,0xbe6f0c4d,0xbe8afa3e,0xbf26423a,0xbf3bfc8f,
0x80000000,0xbd48fb30,0x80000000,0xbe0255f4,0xbdc8bd36,0xbe164083,0xbe814693,0xbebf47d7,0xbe47c5c2,0xbe78cfcc,0xbefa2c90,0xbf187fc0,0xbe94a031,0xbeac7cd4,0xbf316e2c,0xbf4779bc,
0x80000000,0xbd712283,0x80000000,0xbe0c4cf7,0xbdf0b772,0xbe3403f1,0xbe8afa3e,0xbecd2ef3,0xbe6f0c4d,0xbe94a031,0xbf05c277,0xbf226799,0xbeb13641,0xbecd2ef3,0xbf3bfc8f,0xbf5205d4,
0x80000000,0xbd8ca1f2,0x80000000,0xbe164083,0xbe0c4cf7,0xbe519f65,0xbe94a031,0xbedae880,0xbe8afa3e,0xbeac7cd4,0xbf0e39da,0xbf2beb4a,0xbecd2ef3,0xbeece91a,0xbf45e403,0xbf5b941a,
0x80000000,0x80000000,0xbf167918,0xbf26423a,0x80000000,0x80000000,0xbf3504f3,0xbf42a9f7,0x80000000,0x80000000,0xbf4f1bbd,0xbf5a46a0,0x80000000,0x80000000,0xbf641901,0xbf6c835e,
0xbda0af2a,0xbdb4b86a,0xbf26423a,0xbf36c9a9,0xbdc8bd36,0xbddcbd0d,0xbf45e403,0xbf53731f,0xbdf0b772,0xbe0255f4,0xbf5f5be6,0xbf698690,0xbe0c4cf7,0xbe164083,0xbf71decf,0xbf7853f8,
0xbe20305b,0xbe3403f1,0xbf3504f3,0xbf45e403,0xbe47c5c2,0xbe5b73dc,0xbf54db31,0xbf61c598,0xbe6f0c4d,0xbe814693,0xbf6c835e,0xbf74fa0b,0xbe8afa3e,0xbe94a031,0xbf7b14be,0xbf7ec46d,
0xbe6f0c4d,0xbe862210,0xbf42a9f7,0xbf53731f,0xbe94a031,0xbea2fd52,0xbf61c598,0xbf6d76aa,0xbeb13641,0xbebf47d7,0xbf766377,0xbf7c7160,0xbecd2ef3,0xbedae880,0xbf7f8e56,0xbf7fb10f,
0xbe9e377a,0xbeb13641,0xbf4f1bbd,0xbf5f5be6,0xbec3ef15,0xbed65a92,0xbf6c835e,0xbf766377,0xbee87171,0xbefa2c90,0xbf7cd925,0xbf7fcd79,0xbf05c277,0xbf0e39da,0xbf7f35f9,0xbf7b14be,
0xbec3ef15,0xbedae880,0xbf5a46a0,0xbf698690,0xbef15aea,0xbf039c3d,0xbf74fa0b,0xbf7c7160,0xbf0e39da,0xbf187fc0,0xbf7fcd79,0xbf7f0059,0xbf226799,0xbf2beb4a,0xbf7a0d54,0xbf710908,
0xbee87171,0xbf0172c3,0xbf641901,0xbf71decf,0xbf0e39da,0xbf1a82a4,0xbf7b14be,0xbf7f8e56,0xbf26423a,0xbf316e2c,0xbf7f35f9,0xbf7a0d54,0xbf3bfc8f,0xbf45e403,0xbf702d4f,0xbf61c598,
0xbf05c277,0xbf146eba,0xbf6c835e,0xbf7853f8,0xbf226799,0xbf2f9c32,0xbf7ec46d,0xbf7fb10f,0xbf3bfc8f,0xbf4779bc,0xbf7b14be,0xbf710908,0xbf5205d4,0xbf5b941a,0xbf61c598,0xbf4d9f02,
0x80000000,0x80000000,0xbf737871,0xbf78ed3c,0x80000000,0x80000000,0xbf7cd925,0xbf7f35f9,0x80000000,0x80000000,0xbf800000,0xbf7f35f9,0x80000000,0x80000000,0xbf7cd925,0xbf78ed3c,
0xbe20305b,0xbe2a1c3f,0xbf7cd925,0xbf7f654e,0xbe3403f1,0xbe3de731,0xbf7ff35e,0xbf7e8238,0xbe47c5c2,0xbe519f65,0xbf7b14be,0xbf75b1c9,0xbe5b73dc,0xbe6542e9,0xbf6e641a,0xbf653a48,
0xbe9e377a,0xbea7bf25,0xbf800000,0xbf7ec46d,0xbeb13641,0xbeba9be1,0xbf7b14be,0xbf74fa0b,0xbec3ef15,0xbecd2ef3,0xbf6c835e,0xbf61c598,0xbed65a92,0xbedf7108,0xbf54db31,0xbf45e403,
0xbee87171,0xbef5c6c5,0xbf7cd925,0xbf770f11,0xbf0172c3,0xbf07e565,0xbf6e641a,0xbf62f219,0xbf0e39da,0xbf146eba,0xbf54db31,0xbf444969,0xbf1a82a4,0xbf207440,0xbf316e2c,0xbf1c81b9,
0xbf167918,0xbf1e7cf1,0xbf737871,0xbf687c12,0xbf26423a,0xbf2dc5e3,0xbf5a46a0,0xbf490a88,0xbf3504f3,0xbf3bfc8f,0xbf3504f3,0xbf1e7cf1,0xbf42a9f7,0xbf490a88,0xbf05c277,0xbed65a92,
0xbf3504f3,0xbf3daef9,0xbf641901,0xbf53731f,0xbf45e403,0xbf4d9f02,0xbf3f5cb5,0xbf28296a,0xbf54db31,0xbf5b941a,0xbf0e39da,0xbee3f40d,0xbf61c598,0xbf676bd8,0xbea7bf25,0xbe519f65,
0xbf4f1bbd,0xbf579b8c,0xbf4f1bbd,0xbf3889dc,0xbf5f5be6,0xbf6655e7,0xbf1e7cf1,0xbf0172c3,0xbf6c835e,0xbf71decf,0xbec3ef15,0xbe814693,0xbf766377,0xbf7a0d54,0xbdf0b772,0x3ca0d6d6,
0xbf641901,0xbf6b8a3d,0xbf3504f3,0xbf187fc0,0xbf71decf,0xbf770f11,0xbef15aea,0xbeac7cd4,0xbf7b14be,0xbf7deafa,0xbe47c5c2,0xbd48fb30,0xbf7f8e56,0xbf7ffcd7,0x3dc8bd36,0x3e78cfcc,
0x80000000,0x80000000,0xbf737871,0xbf6c835e,0x80000000,0x80000000,0xbf641901,0xbf5a46a0,0x80000000,0x80000000,0xbf4f1bbd,0xbf42a9f7,0x80000000,0x80000000,0xbf3504f3,0xbf26423a,
0xbe6f0c4d,0xbe78cfcc,0xbf5a46a0,0xbf4d9f02,0xbe814693,0xbe862210,0xbf3f5cb5,0xbf2f9c32,0xbe8afa3e,0xbe8fcefe,0xbf1e7cf1,0xbf0c2124,0xbe94a031,0xbe996dba,0xbef15aea,0xbec8917e,
0xbee87171,0xbef15aea,0xbf3504f3,0xbf226799,0xbefa2c90,0xbf0172c3,0xbf0e39da,0xbef15aea,0xbf05c277,0xbf0a04f8,0xbec3ef15,0xbe94a031,0xbf0e39da,0xbf1260b2,0xbe47c5c2,0xbdc8bd36,
0xbf26423a,0xbf2beb4a,0xbf05c277,0xbedae880,0xbf316e2c,0xbf36c9a9,0xbea7bf25,0xbe6542e9,0xbf3bfc8f,0xbf4105b8,0xbdf0b772,0xbc20d8d2,0xbf45e403,0xbf4a965e,0x3dc8bd36,0x3e519f65,
0xbf4f1bbd,0xbf54db31,0xbe9e377a,0xbe47c5c2,0xbf5a46a0,0xbf5f5be6,0xbda0af2a,0x3d20cee7,0xbf641901,0xbf687c12,0x3e20305b,0x3e8afa3e,0xbf6c835e,0xbf702d4f,0x3ec3ef15,0x3efa2c90,
0xbf6c835e,0xbf710908,0xbda0af2a,0x3d48fb30,0xbf74fa0b,0xbf7853f8,0x3e3403f1,0x3e996dba,0xbf7b14be,0xbf7d3aac,0x3ed65a92,0x3f07e565,0xbf7ec46d,0xbf7fb10f,0x3f226799,0x3f3a4582,
0xbf7cd925,0xbf7ec46d,0x3e20305b,0x3e94a031,0xbf7fcd79,0xbf7ff35e,0x3ed65a92,0x3f0a04f8,0xbf7f35f9,0xbf7d95f4,0x3f26423a,0x3f3f5cb5,0xbf7b14be,0xbf77b493,0x3f54db31,0x3f6655e7,
0xbf7f35f9,0xbf7d3aac,0x3ec3ef15,0x3f039c3d,0xbf7a0d54,0xbf75b1c9,0x3f226799,0x3f3daef9,0xbf702d4f,0xbf698690,0x3f54db31,0x3f676bd8,0xbf61c598,0xbf58f3c4,0x3f74fa0b,0x3f7d3aac,
0x80000000,0x80000000,0xbf167918,0xbf05c277,0x80000000,0x80000000,0xbee87171,0xbec3ef15,0x80000000,0x80000000,0xbe9e377a,0xbe6f0c4d,0x80000000,0x80000000,0xbe20305b,0xbda0af2a,
0xbe9e377a,0xbea2fd52,0xbe9e377a,0xbe6542e9,0xbea7bf25,0xbeac7cd4,0xbe0c4cf7,0xbd48fb30,0xbeb13641,0xbeb5eb4f,0x3d20cee7,0x3e0255f4,0xbeba9be1,0xbebf47d7,0x3e5b73dc,0x3e996dba,
0xbf167918,0xbf1a82a4,0x80000000,0x3dc8bd36,0xbf1e7cf1,0xbf226799,0x3e47c5c2,0x3e94a031,0xbf26423a,0xbf2a0c73,0x3ec3ef15,0x3ef15aea,0xbf2dc5e3,0xbf316e2c,0x3f0e39da,0x3f226799,
0xbf4f1bbd,0xbf53731f,0x3e9e377a,0x3ed1c759,0xbf579b8c,0xbf5b941a,0x3f0172c3,0x3f187fc0,0xbf5f5be6,0xbf62f219,0x3f2dc5e3,0x3f4105b8,0xbf6655e7,0xbf698690,0x3f5205d4,0x3f609384,
0xbf737871,0xbf766377,0x3f167918,0x3f2dc5e3,0xbf78ed3c,0xbf7b14be,0x3f42a9f7,0x3f54db31,0xbf7cd925,0xbf7e39bc,0x3f641901,0x3f702d4f,0xbf7f35f9,0xbf7fcd79,0x3f78ed3c,0x3f7e39bc,
0xbf800000,0xbf7fb10f,0x3f4f1bbd,0x3f609384,0xbf7ec46d,0xbf7d3aac,0x3f6e641a,0x3f7853f8,0xbf7b14be,0xbf7853f8,0x3f7e39bc,0x3f7ffcd7,0xbf74fa0b,0xbf710908,0x3f7d95f4,0x3f770f11,
0xbf737871,0xbf6e641a,0x3f737871,0x3f7c0361,0xbf687c12,0xbf61c598,0x3f7fcd79,0x3f7ec46d,0xbf5a46a0,0xbf5205d4,0x3f78ed3c,0x3f6e641a,0xbf490a88,0xbf3f5cb5,0x3f5f5be6,0x3f4c1d35,
0xbf4f1bbd,0xbf444969,0x3f800000,0x3f7d3aac,0xbf3889dc,0xbf2beb4a,0x3f74fa0b,0x3f676bd8,0xbf1e7cf1,0xbf104f0e,0x3f54db31,0x3f3daef9,0xbf0172c3,0xbee3f40d,0x3f226799,0x3f039c3d,
0x3f803f80,0,0x3f803f80,0,0x3f803f80,0,0x3f803f80,0,0x3f7d3f80,0x3e200000,0x3f643f73,0x3ee83e9e,0x3f353f4f,0x3f353f16,0x3ee83f16,0x3f643f4f,
0x3f733f80,0x3e9e0000,0x3f163f4f,0x3f4f3f16,0x3e9e,0x3f803f73,0xbf16be9e,0x3f4f3f73,0x3f643f80,0x3ee80000,0x3e203f16,0x3f7d3f4f,0xbf35be9e,0x3f353f73,0xbf7dbf73,0xbe203e9e,
0x3f4f3f80,0x3f160000,0xbe9e3e9e,0x3f733f73,0xbf80bf4f,0x3f16,0xbe9ebf4f,0xbf73bf16,0x3f353f80,0x3f350000,0xbf350000,0x3f353f80,0xbf35bf80,0xbf350000,0x3f350000,0xbf35bf80,
0x3f163f80,0x3f4f0000,0xbf73be9e,0x3e9e3f73,0xbf4f,0xbf80bf16,0x3f733f4f,0x3e9ebf16,0x3ee83f80,0x3f640000,0xbf7dbf16,0xbe203f4f,0x3f35be9e,0xbf35bf73,0x3e203f73,0x3f7d3e9e,
0x3e9e3f80,0x3f730000,0xbf4fbf4f,0xbf163f16,0x3f803e9e,0xbf73,0xbf4f3e9e,0x3f163f73,0x3e203f80,0x3f7d0000,0xbee8bf73,0xbf643e9e,0x3f353f4f,0x3f35bf16,0xbf64bf16,0xbee83f4f,
0x3f80,0x3f800000,0xbf80,0xbf800000,0x3f80,0x3f800000,0xbf80,0xbf800000,0xbe203f80,0x3f7d0000,0x3ee8bf73,0xbf64be9e,0xbf353f4f,0x3f353f16,0x3f64bf16,0xbee8bf4f,
0xbe9e3f80,0x3f730000,0x3f4fbf4f,0xbf16bf16,0xbf803e9e,0x3f73,0x3f4f3e9e,0x3f16bf73,0xbee83f80,0x3f640000,0x3f7dbf16,0xbe20bf4f,0xbf35be9e,0xbf353f73,0xbe203f73,0x3f7dbe9e,
0xbf163f80,0x3f4f0000,0x3f73be9e,0x3e9ebf73,0xbf4f,0xbf803f16,0xbf733f4f,0x3e9e3f16,0xbf353f80,0x3f350000,0x3f350000,0x3f35bf80,0x3f35bf80,0xbf350000,0xbf350000,0xbf353f80,
0xbf4f3f80,0x3f160000,0x3e9e3e9e,0x3f73bf73,0x3f80bf4f,0xbf16,0x3e9ebf4f,0xbf733f16,0xbf643f80,0x3ee80000,0xbe203f16,0x3f7dbf4f,0x3f35be9e,0x3f35bf73,0x3f7dbf73,0xbe20be9e,
0xbf733f80,0x3e9e0000,0xbf163f4f,0x3f4fbf16,0x3e9e,0x3f80bf73,0x3f16be9e,0x3f4fbf73,0xbf7d3f80,0x3e200000,0xbf643f73,0x3ee8be9e,0xbf353f4f,0x3f35bf16,0xbee83f16,0x3f64bf4f,
0xbf803f80,0,0xbf803f80,0,0xbf803f80,0,0xbf803f80,0,0xbf7d3f80,0xbe200000,0xbf643f73,0xbee83e9e,0xbf353f4f,0xbf353f16,0xbee83f16,0xbf643f4f,
0xbf733f80,0xbe9e0000,0xbf163f4f,0xbf4f3f16,0x3e9e,0xbf803f73,0x3f16be9e,0xbf4f3f73,0xbf643f80,0xbee80000,0xbe203f16,0xbf7d3f4f,0x3f35be9e,0xbf353f73,0x3f7dbf73,0x3e203e9e,
0xbf4f3f80,0xbf160000,0x3e9e3e9e,0xbf733f73,0x3f80bf4f,0x3f16,0x3e9ebf4f,0x3f73bf16,0xbf353f80,0xbf350000,0x3f350000,0xbf353f80,0x3f35bf80,0x3f350000,0xbf350000,0x3f35bf80,
0xbf163f80,0xbf4f0000,0x3f73be9e,0xbe9e3f73,0xbf4f,0x3f80bf16,0xbf733f4f,0xbe9ebf16,0xbee83f80,0xbf640000,0x3f7dbf16,0x3e203f4f,0xbf35be9e,0x3f35bf73,0xbe203f73,0xbf7d3e9e,
0xbe9e3f80,0xbf730000,0x3f4fbf4f,0x3f163f16,0xbf803e9e,0xbf73,0x3f4f3e9e,0xbf163f73,0xbe203f80,0xbf7d0000,0x3ee8bf73,0x3f643e9e,0xbf353f4f,0xbf35bf16,0x3f64bf16,0x3ee83f4f,
0x3f80,0xbf800000,0xbf80,0x3f800000,0x3f80,0xbf800000,0xbf80,0x3f800000,0x3e203f80,0xbf7d0000,0xbee8bf73,0x3f64be9e,0x3f353f4f,0xbf353f16,0xbf64bf16,0x3ee8bf4f,
0x3e9e3f80,0xbf730000,0xbf4fbf4f,0x3f16bf16,0x3f803e9e,0x3f73,0xbf4f3e9e,0xbf16bf73,0x3ee83f80,0xbf640000,0xbf7dbf16,0x3e20bf4f,0x3f35be9e,0x3f353f73,0x3e203f73,0xbf7dbe9e,
0x3f163f80,0xbf4f0000,0xbf73be9e,0xbe9ebf73,0xbf4f,0x3f803f16,0x3f733f4f,0xbe9e3f16,0x3f353f80,0xbf350000,0xbf350000,0xbf35bf80,0xbf35bf80,0x3f350000,0x3f350000,0x3f353f80,
0x3f4f3f80,0xbf160000,0xbe9e3e9e,0xbf73bf73,0xbf80bf4f,0xbf16,0xbe9ebf4f,0x3f733f16,0x3f643f80,0xbee80000,0x3e203f16,0xbf7dbf4f,0xbf35be9e,0xbf35bf73,0xbf7dbf73,0x3e20be9e,
0x3f733f80,0xbe9e0000,0x3f163f4f,0xbf4fbf16,0x3e9e,0xbf80bf73,0xbf16be9e,0xbf4fbf73,0x3f7d3f80,0xbe200000,0x3f643f73,0xbee8be9e,0x3f353f4f,0xbf35bf16,0x3ee83f16,0xbf64bf4f,
0x3f803f80,0,0x3f803f80,0,0x3f803f80,0,0x3f803f80,0,0x3e203e9e,0x3f7d3f73,0xbe200000,0x3f7d3f80,0xbee8be9e,0x3f643f73,0xbf35bf16,0x3f353f4f,
0xbf73bf4f,0x3e9e3f16,0xbf73bf80,0xbe9e0000,0xbf16bf4f,0xbf4fbf16,0xbe9e,0xbf80bf73,0xbee8bf4f,0xbf64bf16,0x3ee80000,0xbf64bf80,0x3f7d3f4f,0xbe20bf16,0x3f353f73,0x3f353e9e,
0x3f4f3e9e,0xbf16bf73,0x3f4f3f80,0x3f160000,0xbe9e3e9e,0x3f733f73,0xbf80bf4f,0x3f16,0x3f353f80,0x3f350000,0xbf350000,0x3f353f80,0xbf35bf80,0xbf350000,0x3f350000,0xbf35bf80,
0xbf163e9e,0x3f4f3f73,0xbf16bf80,0xbf4f0000,0x3f733e9e,0xbe9ebf73,0x3f4f,0x3f803f16,0xbf64bf4f,0xbee83f16,0x3f640000,0xbee8bf80,0xbe203f4f,0x3f7d3f16,0xbf35bf73,0xbf353e9e,
0x3e9ebf4f,0xbf73bf16,0x3e9e3f80,0x3f730000,0xbf4fbf4f,0xbf163f16,0x3f803e9e,0xbf73,0x3f7d3e9e,0x3e20bf73,0xbf7d0000,0x3e203f80,0x3f64be9e,0xbee8bf73,0xbf353f16,0x3f353f4f,
0x3f80,0x3f800000,0xbf80,0xbf800000,0x3f80,0x3f800000,0xbf80,0xbf800000,0xbf7d3e9e,0x3e203f73,0x3f7d0000,0x3e20bf80,0xbf64be9e,0xbee83f73,0x3f353f16,0x3f35bf4f,
0xbe9ebf4f,0xbf733f16,0xbe9e3f80,0x3f730000,0x3f4fbf4f,0xbf16bf16,0xbf803e9e,0x3f73,0x3f64bf4f,0xbee8bf16,0xbf640000,0xbee83f80,0x3e203f4f,0x3f7dbf16,0x3f35bf73,0xbf35be9e,
0x3f163e9e,0x3f4fbf73,0x3f16bf80,0xbf4f0000,0xbf733e9e,0xbe9e3f73,0x3f4f,0x3f80bf16,0xbf353f80,0x3f350000,0x3f350000,0x3f35bf80,0x3f35bf80,0xbf350000,0xbf350000,0xbf353f80,
0xbf4f3e9e,0xbf163f73,0xbf4f3f80,0x3f160000,0x3e9e3e9e,0x3f73bf73,0x3f80bf4f,0xbf16,0x3ee8bf4f,0xbf643f16,0xbee80000,0xbf643f80,0xbf7d3f4f,0xbe203f16,0xbf353f73,0x3f35be9e,
0x3f73bf4f,0x3e9ebf16,0x3f73bf80,0xbe9e0000,0x3f16bf4f,0xbf4f3f16,0xbe9e,0xbf803f73,0xbe203e9e,0x3f7dbf73,0x3e200000,0x3f7dbf80,0x3ee8be9e,0x3f64bf73,0x3f35bf16,0x3f35bf4f,
0xbf803f80,0,0xbf803f80,0,0xbf803f80,0,0xbf803f80,0,0xbe203e9e,0xbf7d3f73,0x3e200000,0xbf7d3f80,0x3ee8be9e,0xbf643f73,0x3f35bf16,0xbf353f4f,
0x3f73bf4f,0xbe9e3f16,0x3f73bf80,0x3e9e0000,0x3f16bf4f,0x3f4fbf16,0xbe9e,0x3f80bf73,0x3ee8bf4f,0x3f64bf16,0xbee80000,0x3f64bf80,0xbf7d3f4f,0x3e20bf16,0xbf353f73,0xbf353e9e,
0xbf4f3e9e,0x3f16bf73,0xbf4f3f80,0xbf160000,0x3e9e3e9e,0xbf733f73,0x3f80bf4f,0x3f16,0xbf353f80,0xbf350000,0x3f350000,0xbf353f80,0x3f35bf80,0x3f350000,0xbf350000,0x3f35bf80,
0x3f163e9e,0xbf4f3f73,0x3f16bf80,0x3f4f0000,0xbf733e9e,0x3e9ebf73,0x3f4f,0xbf803f16,0x3f64bf4f,0x3ee83f16,0xbf640000,0x3ee8bf80,0x3e203f4f,0xbf7d3f16,0x3f35bf73,0x3f353e9e,
0xbe9ebf4f,0x3f73bf16,0xbe9e3f80,0xbf730000,0x3f4fbf4f,0x3f163f16,0xbf803e9e,0xbf73,0xbf7d3e9e,0xbe20bf73,0x3f7d0000,0xbe203f80,0xbf64be9e,0x3ee8bf73,0x3f353f16,0xbf353f4f,
0x3f80,0xbf800000,0xbf80,0x3f800000,0x3f80,0xbf800000,0xbf80,0x3f800000,0x3f7d3e9e,0xbe203f73,0xbf7d0000,0xbe20bf80,0x3f64be9e,0x3ee83f73,0xbf353f16,0xbf35bf4f,
0x3e9ebf4f,0x3f733f16,0x3e9e3f80,0xbf730000,0xbf4fbf4f,0x3f16bf16,0x3f803e9e,0x3f73,0xbf64bf4f,0x3ee8bf16,0x3f640000,0x3ee83f80,0xbe203f4f,0xbf7dbf16,0xbf35bf73,0x3f35be9e,
0xbf163e9e,0xbf4fbf73,0xbf16bf80,0x3f4f0000,0x3f733e9e,0x3e9e3f73,0x3f4f,0xbf80bf16,0x3f353f80,0xbf350000,0xbf350000,0xbf35bf80,0xbf35bf80,0x3f350000,0x3f350000,0x3f353f80,
0x3f4f3e9e,0x3f163f73,0x3f4f3f80,0xbf160000,0xbe9e3e9e,0xbf73bf73,0xbf80bf4f,0xbf16,0xbee8bf4f,0x3f643f16,0x3ee80000,0x3f643f80,0x3f7d3f4f,0x3e203f16,0x3f353f73,0xbf35be9e,
0xbf73bf4f,0xbe9ebf16,0xbf73bf80,0x3e9e0000,0xbf16bf4f,0x3f4f3f16,0xbe9e,0x3f803f73,0x3e203e9e,0xbf7dbf73,0xbe200000,0xbf7dbf80,0xbee8be9e,0xbf64bf73,0xbf35bf16,0xbf35bf4f,
0x3f803f80,0,0x3f803f80,0,0x3f803f80,0,0x3f803f80,0,0xbf64bf4f,0x3ee83f16,0xbf7dbf73,0x3e203e9e,0xbf7dbf80,0xbe200000,0xbf64bf73,0xbee8be9e,
0x3f163e9e,0xbf4fbf73,0x3f733f4f,0xbe9ebf16,0x3f733f80,0x3e9e0000,0x3f163f4f,0x3f4f3f16,0xbe203e9e,0x3f7d3f73,0xbf64bf16,0x3ee83f4f,0xbf64bf80,0xbee80000,0xbe20bf16,0xbf7dbf4f,
0xbe9ebf4f,0xbf73bf16,0x3f4f3e9e,0xbf16bf73,0x3f4f3f80,0x3f160000,0xbe9e3e9e,0x3f733f73,0x3f353f80,0x3f350000,0xbf350000,0x3f353f80,0xbf35bf80,0xbf350000,0x3f350000,0xbf35bf80,
0xbf73bf4f,0xbe9e3f16,0x3f16be9e,0xbf4fbf73,0x3f163f80,0x3f4f0000,0xbf73be9e,0x3e9e3f73,0x3f7d3e9e,0xbe20bf73,0xbee83f16,0x3f643f4f,0xbee8bf80,0xbf640000,0x3f7d3f16,0x3e20bf4f,
0xbf4f3e9e,0x3f163f73,0x3e9ebf4f,0xbf73bf16,0x3e9e3f80,0x3f730000,0xbf4fbf4f,0xbf163f16,0x3ee8bf4f,0xbf64bf16,0xbe203f73,0x3f7d3e9e,0xbe20bf80,0xbf7d0000,0x3ee83f73,0x3f64be9e,
0x3f80,0x3f800000,0xbf80,0xbf800000,0x3f80,0x3f800000,0xbf80,0xbf800000,0xbee8bf4f,0xbf643f16,0x3e203f73,0x3f7dbe9e,0x3e20bf80,0xbf7d0000,0xbee83f73,0x3f643e9e,
0x3f4f3e9e,0x3f16bf73,0xbe9ebf4f,0xbf733f16,0xbe9e3f80,0x3f730000,0x3f4fbf4f,0xbf16bf16,0xbf7d3e9e,0xbe203f73,0x3ee83f16,0x3f64bf4f,0x3ee8bf80,0xbf640000,0xbf7d3f16,0x3e203f4f,
0x3f73bf4f,0xbe9ebf16,0xbf16be9e,0xbf4f3f73,0xbf163f80,0x3f4f0000,0x3f73be9e,0x3e9ebf73,0xbf353f80,0x3f350000,0x3f350000,0x3f35bf80,0x3f35bf80,0xbf350000,0xbf350000,0xbf353f80,
0x3e9ebf4f,0xbf733f16,0xbf4f3e9e,0xbf163f73,0xbf4f3f80,0x3f160000,0x3e9e3e9e,0x3f73bf73,0x3e203e9e,0x3f7dbf73,0x3f64bf16,0x3ee8bf4f,0x3f64bf80,0xbee80000,0x3e20bf16,0xbf7d3f4f,
0xbf163e9e,0xbf4f3f73,0xbf733f4f,0xbe9e3f16,0xbf733f80,0x3e9e0000,0xbf163f4f,0x3f4fbf16,0x3f64bf4f,0x3ee8bf16,0x3f7dbf73,0x3e20be9e,0x3f7dbf80,0xbe200000,0x3f64bf73,0xbee83e9e,
0xbf803f80,0,0xbf803f80,0,0xbf803f80,0,0xbf803f80,0,0x3f64bf4f,0xbee83f16,0x3f7dbf73,0xbe203e9e,0x3f7dbf80,0x3e200000,0x3f64bf73,0x3ee8be9e,
0xbf163e9e,0x3f4fbf73,0xbf733f4f,0x3e9ebf16,0xbf733f80,0xbe9e0000,0xbf163f4f,0xbf4f3f16,0x3e203e9e,0xbf7d3f73,0x3f64bf16,0xbee83f4f,0x3f64bf80,0x3ee80000,0x3e20bf16,0x3f7dbf4f,
0x3e9ebf4f,0x3f73bf16,0xbf4f3e9e,0x3f16bf73,0xbf4f3f80,0xbf160000,0x3e9e3e9e,0xbf733f73,0xbf353f80,0xbf350000,0x3f350000,0xbf353f80,0x3f35bf80,0x3f350000,0xbf350000,0x3f35bf80,
0x3f73bf4f,0x3e9e3f16,0xbf16be9e,0x3f4fbf73,0xbf163f80,0xbf4f0000,0x3f73be9e,0xbe9e3f73,0xbf7d3e9e,0x3e20bf73,0x3ee83f16,0xbf643f4f,0x3ee8bf80,0x3f640000,0xbf7d3f16,0xbe20bf4f,
0x3f4f3e9e,0xbf163f73,0xbe9ebf4f,0x3f73bf16,0xbe9e3f80,0xbf730000,0x3f4fbf4f,0x3f163f16,0xbee8bf4f,0x3f64bf16,0x3e203f73,0xbf7d3e9e,0x3e20bf80,0x3f7d0000,0xbee83f73,0xbf64be9e,
0x3f80,0xbf800000,0xbf80,0x3f800000,0x3f80,0xbf800000,0xbf80,0x3f800000,0x3ee8bf4f,0x3f643f16,0xbe203f73,0xbf7dbe9e,0xbe20bf80,0x3f7d0000,0x3ee83f73,0xbf643e9e,
0xbf4f3e9e,0xbf16bf73,0x3e9ebf4f,0x3f733f16,0x3e9e3f80,0xbf730000,0xbf4fbf4f,0x3f16bf16,0x3f7d3e9e,0x3e203f73,0xbee83f16,0xbf64bf4f,0xbee8bf80,0x3f640000,0x3f7d3f16,0xbe203f4f,
0xbf73bf4f,0x3e9ebf16,0x3f16be9e,0x3f4f3f73,0x3f163f80,0xbf4f0000,0xbf73be9e,0xbe9ebf73,0x3f353f80,0xbf350000,0xbf350000,0xbf35bf80,0xbf35bf80,0x3f350000,0x3f350000,0x3f353f80,
0xbe9ebf4f,0x3f733f16,0x3f4f3e9e,0x3f163f73,0x3f4f3f80,0xbf160000,0xbe9e3e9e,0xbf73bf73,0xbe203e9e,0xbf7dbf73,0xbf64bf16,0xbee8bf4f,0xbf64bf80,0x3ee80000,0xbe20bf16,0x3f7d3f4f,
0x3f163e9e,0x3f4f3f73,0x3f733f4f,0x3e9e3f16,0x3f733f80,0xbe9e0000,0x3f163f4f,0xbf4fbf16,0xbf64bf4f,0xbee8bf16,0xbf7dbf73,0xbe20be9e,0xbf7dbf80,0x3e200000,0xbf64bf73,0x3ee83e9e,
0x3f803f80,0,0x3f803f80,0,0x3f803f80,0,0x3f803f80,0,0xbf35bf4f,0xbf35bf16,0xbee8bf16,0xbf64bf4f,0xbe20be9e,0xbf7dbf73,0x3e200000,0xbf7dbf80,
0x3e9e,0x3f803f73,0xbf16be9e,0x3f4f3f73,0xbf73bf4f,0x3e9e3f16,0xbf73bf80,0xbe9e0000,0x3f353e9e,0xbf35bf73,0x3f7d3f73,0x3e20be9e,0x3ee83f4f,0x3f643f16,0xbee80000,0x3f643f80,
0xbf80bf4f,0x3f16,0xbe9ebf4f,0xbf73bf16,0x3f4f3e9e,0xbf16bf73,0x3f4f3f80,0x3f160000,0x3f353f80,0x3f350000,0xbf350000,0x3f353f80,0xbf35bf80,0xbf350000,0x3f350000,0xbf35bf80,
0xbf4f,0xbf80bf16,0x3f733f4f,0x3e9ebf16,0xbf163e9e,0x3f4f3f73,0xbf16bf80,0xbf4f0000,0xbf353e9e,0x3f353f73,0xbe20bf73,0xbf7dbe9e,0x3f643f4f,0x3ee8bf16,0xbf640000,0x3ee83f80,
0x3f803e9e,0xbf73,0xbf4f3e9e,0x3f163f73,0x3e9ebf4f,0xbf73bf16,0x3e9e3f80,0x3f730000,0xbf35bf4f,0xbf353f16,0x3f643f16,0x3ee8bf4f,0xbf7dbe9e,0xbe203f73,0x3f7d0000,0xbe20bf80,
0x3f80,0x3f800000,0xbf80,0xbf800000,0x3f80,0x3f800000,0xbf80,0xbf800000,0x3f35bf4f,0xbf35bf16,0xbf643f16,0x3ee83f4f,0x3f7dbe9e,0xbe20bf73,0xbf7d0000,0xbe203f80,
0xbf803e9e,0x3f73,0x3f4f3e9e,0x3f16bf73,0xbe9ebf4f,0xbf733f16,0xbe9e3f80,0x3f730000,0x3f353e9e,0x3f35bf73,0x3e20bf73,0xbf7d3e9e,0xbf643f4f,0x3ee83f16,0x3f640000,0x3ee8bf80,
0xbf4f,0xbf803f16,0xbf733f4f,0x3e9e3f16,0x3f163e9e,0x3f4fbf73,0x3f16bf80,0xbf4f0000,0xbf353f80,0x3f350000,0x3f350000,0x3f35bf80,0x3f35bf80,0xbf350000,0xbf350000,0xbf353f80,
0x3f80bf4f,0xbf16,0x3e9ebf4f,0xbf733f16,0xbf4f3e9e,0xbf163f73,0xbf4f3f80,0x3f160000,0xbf353e9e,0xbf353f73,0xbf7d3f73,0x3e203e9e,0xbee83f4f,0x3f64bf16,0x3ee80000,0x3f64bf80,
0x3e9e,0x3f80bf73,0x3f16be9e,0x3f4fbf73,0x3f73bf4f,0x3e9ebf16,0x3f73bf80,0xbe9e0000,0x3f35bf4f,0xbf353f16,0x3ee8bf16,0xbf643f4f,0x3e20be9e,0xbf7d3f73,0xbe200000,0xbf7d3f80,
0xbf803f80,0,0xbf803f80,0,0xbf803f80,0,0xbf803f80,0,0x3f35bf4f,0x3f35bf16,0x3ee8bf16,0x3f64bf4f,0x3e20be9e,0x3f7dbf73,0xbe200000,0x3f7dbf80,
0x3e9e,0xbf803f73,0x3f16be9e,0xbf4f3f73,0x3f73bf4f,0xbe9e3f16,0x3f73bf80,0x3e9e0000,0xbf353e9e,0x3f35bf73,0xbf7d3f73,0xbe20be9e,0xbee83f4f,0xbf643f16,0x3ee80000,0xbf643f80,
0x3f80bf4f,0x3f16,0x3e9ebf4f,0x3f73bf16,0xbf4f3e9e,0x3f16bf73,0xbf4f3f80,0xbf160000,0xbf353f80,0xbf350000,0x3f350000,0xbf353f80,0x3f35bf80,0x3f350000,0xbf350000,0x3f35bf80,
0xbf4f,0x3f80bf16,0xbf733f4f,0xbe9ebf16,0x3f163e9e,0xbf4f3f73,0x3f16bf80,0x3f4f0000,0x3f353e9e,0xbf353f73,0x3e20bf73,0x3f7dbe9e,0xbf643f4f,0xbee8bf16,0x3f640000,0xbee83f80,
0xbf803e9e,0xbf73,0x3f4f3e9e,0xbf163f73,0xbe9ebf4f,0x3f73bf16,0xbe9e3f80,0xbf730000,0x3f35bf4f,0x3f353f16,0xbf643f16,0xbee8bf4f,0x3f7dbe9e,0x3e203f73,0xbf7d0000,0x3e20bf80,
0x3f80,0xbf800000,0xbf80,0x3f800000,0x3f80,0xbf800000,0xbf80,0x3f800000,0xbf35bf4f,0x3f35bf16,0x3f643f16,0xbee83f4f,0xbf7dbe9e,0x3e20bf73,0x3f7d0000,0x3e203f80,
0x3f803e9e,0x3f73,0xbf4f3e9e,0xbf16bf73,0x3e9ebf4f,0x3f733f16,0x3e9e3f80,0xbf730000,0xbf353e9e,0xbf35bf73,0xbe20bf73,0x3f7d3e9e,0x3f643f4f,0xbee83f16,0xbf640000,0xbee8bf80,
0xbf4f,0x3f803f16,0x3f733f4f,0xbe9e3f16,0xbf163e9e,0xbf4fbf73,0xbf16bf80,0x3f4f0000,0x3f353f80,0xbf350000,0xbf350000,0xbf35bf80,0xbf35bf80,0x3f350000,0x3f350000,0x3f353f80,
0xbf80bf4f,0xbf16,0xbe9ebf4f,0x3f733f16,0x3f4f3e9e,0x3f163f73,0x3f4f3f80,0xbf160000,0x3f353e9e,0x3f353f73,0x3f7d3f73,0xbe203e9e,0x3ee83f4f,0xbf64bf16,0xbee80000,0xbf64bf80,
0x3e9e,0xbf80bf73,0xbf16be9e,0xbf4fbf73,0xbf73bf4f,0xbe9ebf16,0xbf73bf80,0x3e9e0000,0xbf35bf4f,0x3f353f16,0xbee8bf16,0x3f643f4f,0xbe20be9e,0x3f7d3f73,0x3e200000,0x3f7d3f80,
0x3f803f80,0,0x3f803f80,0,0x3f803f80,0,0x3f803f80,0,0x3ee83e9e,0xbf64bf73,0x3f353f16,0xbf35bf4f,0x3f643f4f,0xbee8bf16,0x3f7d3f73,0xbe20be9e,
0xbf16bf4f,0xbf4fbf16,0xbe9e,0xbf80bf73,0x3f163e9e,0xbf4fbf73,0x3f733f4f,0xbe9ebf16,0xbf7dbf4f,0x3e203f16,0xbf35bf73,0xbf35be9e,0x3e20be9e,0xbf7dbf73,0x3f643f16,0xbee8bf4f,
0xbe9e3e9e,0x3f733f73,0xbf80bf4f,0x3f16,0xbe9ebf4f,0xbf73bf16,0x3f4f3e9e,0xbf16bf73,0x3f353f80,0x3f350000,0xbf350000,0x3f353f80,0xbf35bf80,0xbf350000,0x3f350000,0xbf35bf80,
0x3f733e9e,0xbe9ebf73,0x3f4f,0x3f803f16,0xbf73bf4f,0xbe9e3f16,0x3f16be9e,0xbf4fbf73,0x3e20bf4f,0xbf7dbf16,0x3f353f73,0x3f35be9e,0xbf7dbe9e,0x3e203f73,0x3ee8bf16,0xbf64bf4f,
0xbf4fbf4f,0xbf163f16,0x3f803e9e,0xbf73,0xbf4f3e9e,0x3f163f73,0x3e9ebf4f,0xbf73bf16,0xbf643e9e,0x3ee83f73,0x3f35bf16,0xbf35bf4f,0xbee83f4f,0x3f643f16,0x3e20bf73,0xbf7dbe9e,
0x3f80,0x3f800000,0xbf80,0xbf800000,0x3f80,0x3f800000,0xbf80,0xbf800000,0x3f643e9e,0x3ee8bf73,0xbf35bf16,0xbf353f4f,0x3ee83f4f,0x3f64bf16,0xbe20bf73,0xbf7d3e9e,
0x3f4fbf4f,0xbf16bf16,0xbf803e9e,0x3f73,0x3f4f3e9e,0x3f16bf73,0xbe9ebf4f,0xbf733f16,0xbe20bf4f,0xbf7d3f16,0xbf353f73,0x3f353e9e,0x3f7dbe9e,0x3e20bf73,0xbee8bf16,0xbf643f4f,
0xbf733e9e,0xbe9e3f73,0x3f4f,0x3f80bf16,0x3f73bf4f,0xbe9ebf16,0xbf16be9e,0xbf4f3f73,0xbf353f80,0x3f350000,0x3f350000,0x3f35bf80,0x3f35bf80,0xbf350000,0xbf350000,0xbf353f80,
0x3e9e3e9e,0x3f73bf73,0x3f80bf4f,0xbf16,0x3e9ebf4f,0xbf733f16,0xbf4f3e9e,0xbf163f73,0x3f7dbf4f,0x3e20bf16,0x3f35bf73,0xbf353e9e,0xbe20be9e,0xbf7d3f73,0xbf643f16,0xbee83f4f,
0x3f16bf4f,0xbf4f3f16,0xbe9e,0xbf803f73,0xbf163e9e,0xbf4f3f73,0xbf733f4f,0xbe9e3f16,0xbee83e9e,0xbf643f73,0xbf353f16,0xbf353f4f,0xbf643f4f,0xbee83f16,0xbf7d3f73,0xbe203e9e,
0xbf803f80,0,0xbf803f80,0,0xbf803f80,0,0xbf803f80,0,0xbee83e9e,0x3f64bf73,0xbf353f16,0x3f35bf4f,0xbf643f4f,0x3ee8bf16,0xbf7d3f73,0x3e20be9e,
0x3f16bf4f,0x3f4fbf16,0xbe9e,0x3f80bf73,0xbf163e9e,0x3f4fbf73,0xbf733f4f,0x3e9ebf16,0x3f7dbf4f,0xbe203f16,0x3f35bf73,0x3f35be9e,0xbe20be9e,0x3f7dbf73,0xbf643f16,0x3ee8bf4f,
0x3e9e3e9e,0xbf733f73,0x3f80bf4f,0x3f16,0x3e9ebf4f,0x3f73bf16,0xbf4f3e9e,0x3f16bf73,0xbf353f80,0xbf350000,0x3f350000,0xbf353f80,0x3f35bf80,0x3f350000,0xbf350000,0x3f35bf80,
0xbf733e9e,0x3e9ebf73,0x3f4f,0xbf803f16,0x3f73bf4f,0x3e9e3f16,0xbf16be9e,0x3f4fbf73,0xbe20bf4f,0x3f7dbf16,0xbf353f73,0xbf35be9e,0x3f7dbe9e,0xbe203f73,0xbee8bf16,0x3f64bf4f,
0x3f4fbf4f,0x3f163f16,0xbf803e9e,0xbf73,0x3f4f3e9e,0xbf163f73,0xbe9ebf4f,0x3f73bf16,0x3f643e9e,0xbee83f73,0xbf35bf16,0x3f35bf4f,0x3ee83f4f,0xbf643f16,0xbe20bf73,0x3f7dbe9e,
0x3f80,0xbf800000,0xbf80,0x3f800000,0x3f80,0xbf800000,0xbf80,0x3f800000,0xbf643e9e,0xbee8bf73,0x3f35bf16,0x3f353f4f,0xbee83f4f,0xbf64bf16,0x3e20bf73,0x3f7d3e9e,
0xbf4fbf4f,0x3f16bf16,0x3f803e9e,0x3f73,0xbf4f3e9e,0xbf16bf73,0x3e9ebf4f,0x3f733f16,0x3e20bf4f,0x3f7d3f16,0x3f353f73,0xbf353e9e,0xbf7dbe9e,0xbe20bf73,0x3ee8bf16,0x3f643f4f,
0x3f733e9e,0x3e9e3f73,0x3f4f,0xbf80bf16,0xbf73bf4f,0x3e9ebf16,0x3f16be9e,0x3f4f3f73,0x3f353f80,0xbf350000,0xbf350000,0xbf35bf80,0xbf35bf80,0x3f350000,0x3f350000,0x3f353f80,
0xbe9e3e9e,0xbf73bf73,0xbf80bf4f,0xbf16,0xbe9ebf4f,0x3f733f16,0x3f4f3e9e,0x3f163f73,0xbf7dbf4f,0xbe20bf16,0xbf35bf73,0x3f353e9e,0x3e20be9e,0x3f7d3f73,0x3f643f16,0x3ee83f4f,
0xbf16bf4f,0x3f4f3f16,0xbe9e,0x3f803f73,0x3f163e9e,0x3f4f3f73,0x3f733f4f,0x3e9e3f16,0x3ee83e9e,0x3f643f73,0x3f353f16,0x3f353f4f,0x3f643f4f,0x3ee83f16,0x3f7d3f73,0x3e203e9e,
0x3f803f80,0x3f80,0xbf803f80,0x3f80,0x3f803f80,0xbf80,0xbf803f80,0xbf80,0x3f803f80,0x3f80,0xbf803f80,0x3f80,0x3f803f80,0xbf80,0xbf803f80,0xbf80,
0x3f7b3f80,0xbe483f80,0xbf7b3f80,0x3e483f80,0x3f553f6d,0x3f0ebf6d,0xbf553f6d,0xbf0ebf6d,0x3f0e3f35,0xbf553f35,0xbf0e3f35,0x3f553f35,0x3e483ec4,0x3f7bbec4,0xbe483ec4,0xbf7bbec4,
0x3f6d3f80,0xbec43f80,0xbf6d3f80,0x3ec43f80,0x3ec43f35,0x3f6dbf35,0xbec43f35,0xbf6dbf35,0xbec40000,0xbf6d0000,0x3ec40000,0x3f6d0000,0xbf6dbf35,0x3ec43f35,0x3f6dbf35,0xbec43f35,
0x3f553f80,0xbf0e3f80,0xbf553f80,0x3f0e3f80,0xbe483ec4,0x3f7bbec4,0x3e483ec4,0xbf7bbec4,0xbf7bbf35,0xbe48bf35,0x3f7bbf35,0x3e48bf35,0xbf0ebf6d,0xbf553f6d,0x3f0ebf6d,0x3f553f6d,
0x3f353f80,0xbf353f80,0xbf353f80,0x3f353f80,0xbf350000,0x3f350000,0x3f350000,0xbf350000,0xbf35bf80,0x3f35bf80,0x3f35bf80,0xbf35bf80,0x3f350000,0xbf350000,0xbf350000,0x3f350000,
0x3f0e3f80,0xbf553f80,0xbf0e3f80,0x3f553f80,0xbf7bbec4,0x3e483ec4,0x3f7bbec4,0xbe483ec4,0x3e48bf35,0x3f7bbf35,0xbe48bf35,0xbf7bbf35,0x3f553f6d,0x3f0ebf6d,0xbf553f6d,0xbf0ebf6d,
0x3ec43f80,0xbf6d3f80,0xbec43f80,0x3f6d3f80,0xbf6dbf35,0xbec43f35,0x3f6dbf35,0x3ec43f35,0x3f6d0000,0x3ec40000,0xbf6d0000,0xbec40000,0xbec43f35,0x3f6dbf35,0x3ec43f35,0xbf6dbf35,
0x3e483f80,0xbf7b3f80,0xbe483f80,0x3f7b3f80,0xbf0ebf6d,0xbf553f6d,0x3f0ebf6d,0x3f553f6d,0x3f553f35,0xbf0e3f35,0xbf553f35,0x3f0e3f35,0xbf7bbec4,0xbe483ec4,0x3f7bbec4,0x3e483ec4,
0x3f803f80,0x3f80,0xbf803f80,0x3f80,0x3f803f80,0xbf80,0xbf803f80,0xbf80,0x3f803f80,0x3f80,0xbf803f80,0x3f80,0x3f803f80,0xbf80,0xbf803f80,0xbf80,
0xbe480000,0xbf7b0000,0x3e480000,0x3f7b0000,0xbf0ebec4,0x3f553ec4,0x3f0ebec4,0xbf553ec4,0xbf55bf35,0xbf0ebf35,0x3f55bf35,0x3f0ebf35,0xbf7bbf6d,0x3e483f6d,0x3f7bbf6d,0xbe483f6d,
0xbf6dbf80,0x3ec4bf80,0x3f6dbf80,0xbec4bf80,0xbec4bf35,0xbf6d3f35,0x3ec4bf35,0x3f6d3f35,0x3ec40000,0x3f6d0000,0xbec40000,0xbf6d0000,0x3f6d3f35,0xbec4bf35,0xbf6d3f35,0x3ec4bf35,
0x3f0e0000,0x3f550000,0xbf0e0000,0xbf550000,0x3f7b3f6d,0x3e48bf6d,0xbf7b3f6d,0xbe48bf6d,0x3e483f35,0xbf7b3f35,0xbe483f35,0x3f7b3f35,0xbf55bec4,0x3f0e3ec4,0x3f55bec4,0xbf0e3ec4,
0x3f353f80,0xbf353f80,0xbf353f80,0x3f353f80,0xbf350000,0x3f350000,0x3f350000,0xbf350000,0xbf35bf80,0x3f35bf80,0x3f35bf80,0xbf35bf80,0x3f350000,0xbf350000,0xbf350000,0x3f350000,
0xbf550000,0xbf0e0000,0x3f550000,0x3f0e0000,0xbe48bf6d,0xbf7b3f6d,0x3e48bf6d,0x3f7b3f6d,0x3f7b3f35,0xbe483f35,0xbf7b3f35,0x3e483f35,0xbf0e3ec4,0x3f55bec4,0x3f0e3ec4,0xbf55bec4,
0xbec4bf80,0x3f6dbf80,0x3ec4bf80,0xbf6dbf80,0x3f6d3f35,0x3ec4bf35,0xbf6d3f35,0xbec4bf35,0xbf6d0000,0xbec40000,0x3f6d0000,0x3ec40000,0x3ec4bf35,0xbf6d3f35,0xbec4bf35,0x3f6d3f35,
0x3f7b0000,0x3e480000,0xbf7b0000,0xbe480000,0xbf553ec4,0x3f0ebec4,0x3f553ec4,0xbf0ebec4,0x3f0ebf35,0x3f55bf35,0xbf0ebf35,0xbf55bf35,0xbe483f6d,0x3f7bbf6d,0x3e483f6d,0xbf7bbf6d,
0x3f803f80,0x3f80,0xbf803f80,0x3f80,0x3f803f80,0xbf80,0xbf803f80,0xbf80,0x3f803f80,0x3f80,0xbf803f80,0x3f80,0x3f803f80,0xbf80,0xbf803f80,0xbf80,
0xbf7bbf80,0x3e48bf80,0x3f7bbf80,0xbe48bf80,0xbf55bf6d,0xbf0e3f6d,0x3f55bf6d,0x3f0e3f6d,0xbf0ebf35,0x3f55bf35,0x3f0ebf35,0xbf55bf35,0xbe48bec4,0xbf7b3ec4,0x3e48bec4,0x3f7b3ec4,
0x3f6d3f80,0xbec43f80,0xbf6d3f80,0x3ec43f80,0x3ec43f35,0x3f6dbf35,0xbec43f35,0xbf6dbf35,0xbec40000,0xbf6d0000,0x3ec40000,0x3f6d0000,0xbf6dbf35,0x3ec43f35,0x3f6dbf35,0xbec43f35,
0xbf55bf80,0x3f0ebf80,0x3f55bf80,0xbf0ebf80,0x3e48bec4,0xbf7b3ec4,0xbe48bec4,0x3f7b3ec4,0x3f7b3f35,0x3e483f35,0xbf7b3f35,0xbe483f35,0x3f0e3f6d,0x3f55bf6d,0xbf0e3f6d,0xbf55bf6d,
0x3f353f80,0xbf353f80,0xbf353f80,0x3f353f80,0xbf350000,0x3f350000,0x3f350000,0xbf350000,0xbf35bf80,0x3f35bf80,0x3f35bf80,0xbf35bf80,0x3f350000,0xbf350000,0xbf350000,0x3f350000,
0xbf0ebf80,0x3f55bf80,0x3f0ebf80,0xbf55bf80,0x3f7b3ec4,0xbe48bec4,0xbf7b3ec4,0x3e48bec4,0xbe483f35,0xbf7b3f35,0x3e483f35,0x3f7b3f35,0xbf55bf6d,0xbf0e3f6d,0x3f55bf6d,0x3f0e3f6d,
0x3ec43f80,0xbf6d3f80,0xbec43f80,0x3f6d3f80,0xbf6dbf35,0xbec43f35,0x3f6dbf35,0x3ec43f35,0x3f6d0000,0x3ec40000,0xbf6d0000,0xbec40000,0xbec43f35,0x3f6dbf35,0x3ec43f35,0xbf6dbf35,
0xbe48bf80,0x3f7bbf80,0x3e48bf80,0xbf7bbf80,0x3f0e3f6d,0x3f55bf6d,0xbf0e3f6d,0xbf55bf6d,0xbf55bf35,0x3f0ebf35,0x3f55bf35,0xbf0ebf35,0x3f7b3ec4,0x3e48bec4,0xbf7b3ec4,0xbe48bec4,
0x3f803f80,0x3f80,0xbf803f80,0x3f80,0x3f803f80,0xbf80,0xbf803f80,0xbf80,0x3f803f80,0x3f80,0xbf803f80,0x3f80,0x3f803f80,0xbf80,0xbf803f80,0xbf80,
0x3e480000,0x3f7b0000,0xbe480000,0xbf7b0000,0x3f0e3ec4,0xbf55bec4,0xbf0e3ec4,0x3f55bec4,0x3f553f35,0x3f0e3f35,0xbf553f35,0xbf0e3f35,0x3f7b3f6d,0xbe48bf6d,0xbf7b3f6d,0x3e48bf6d,
0xbf6dbf80,0x3ec4bf80,0x3f6dbf80,0xbec4bf80,0xbec4bf35,0xbf6d3f35,0x3ec4bf35,0x3f6d3f35,0x3ec40000,0x3f6d0000,0xbec40000,0xbf6d0000,0x3f6d3f35,0xbec4bf35,0xbf6d3f35,0x3ec4bf35,
0xbf0e0000,0xbf550000,0x3f0e0000,0x3f550000,0xbf7bbf6d,0xbe483f6d,0x3f7bbf6d,0x3e483f6d,0xbe48bf35,0x3f7bbf35,0x3e48bf35,0xbf7bbf35,0x3f553ec4,0xbf0ebec4,0xbf553ec4,0x3f0ebec4,
0x3f353f80,0xbf353f80,0xbf353f80,0x3f353f80,0xbf350000,0x3f350000,0x3f350000,0xbf350000,0xbf35bf80,0x3f35bf80,0x3f35bf80,0xbf35bf80,0x3f350000,0xbf350000,0xbf350000,0x3f350000,
0x3f550000,0x3f0e0000,0xbf550000,0xbf0e0000,0x3e483f6d,0x3f7bbf6d,0xbe483f6d,0xbf7bbf6d,0xbf7bbf35,0x3e48bf35,0x3f7bbf35,0xbe48bf35,0x3f0ebec4,0xbf553ec4,0xbf0ebec4,0x3f553ec4,
0xbec4bf80,0x3f6dbf80,0x3ec4bf80,0xbf6dbf80,0x3f6d3f35,0x3ec4bf35,0xbf6d3f35,0xbec4bf35,0xbf6d0000,0xbec40000,0x3f6d0000,0x3ec40000,0x3ec4bf35,0xbf6d3f35,0xbec4bf35,0x3f6d3f35,
0xbf7b0000,0xbe480000,0x3f7b0000,0x3e480000,0x3f55bec4,0xbf0e3ec4,0xbf55bec4,0x3f0e3ec4,0xbf0e3f35,0xbf553f35,0x3f0e3f35,0x3f553f35,0x3e48bf6d,0xbf7b3f6d,0xbe48bf6d,0x3f7b3f6d,
0,0x3f800000,0,0xbf800000,0,0xbf800000,0,0x3f800000,0,0x3f800000,0,0xbf800000,0,0xbf800000,0,0x3f800000,
0x3e480000,0x3f7b0000,0xbe480000,0xbf7b0000,0x3f0e3ec4,0xbf55bec4,0xbf0e3ec4,0x3f55bec4,0x3f553f35,0x3f0e3f35,0xbf553f35,0xbf0e3f35,0x3f7b3f6d,0xbe48bf6d,0xbf7b3f6d,0x3e48bf6d,
0x3ec40000,0x3f6d0000,0xbec40000,0xbf6d0000,0x3f6d3f35,0xbec4bf35,0xbf6d3f35,0x3ec4bf35,0x3f6d3f80,0xbec43f80,0xbf6d3f80,0x3ec43f80,0x3ec43f35,0x3f6dbf35,0xbec43f35,0xbf6dbf35,
0x3f0e0000,0x3f550000,0xbf0e0000,0xbf550000,0x3f7b3f6d,0x3e48bf6d,0xbf7b3f6d,0xbe48bf6d,0x3e483f35,0xbf7b3f35,0xbe483f35,0x3f7b3f35,0xbf55bec4,0x3f0e3ec4,0x3f55bec4,0xbf0e3ec4,
0x3f350000,0x3f350000,0xbf350000,0xbf350000,0x3f353f80,0x3f35bf80,0xbf353f80,0xbf35bf80,0xbf350000,0xbf350000,0x3f350000,0x3f350000,0xbf35bf80,0xbf353f80,0x3f35bf80,0x3f353f80,
0x3f550000,0x3f0e0000,0xbf550000,0xbf0e0000,0x3e483f6d,0x3f7bbf6d,0xbe483f6d,0xbf7bbf6d,0xbf7bbf35,0x3e48bf35,0x3f7bbf35,0xbe48bf35,0x3f0ebec4,0xbf553ec4,0xbf0ebec4,0x3f553ec4,
0x3f6d0000,0x3ec40000,0xbf6d0000,0xbec40000,0xbec43f35,0x3f6dbf35,0x3ec43f35,0xbf6dbf35,0xbec4bf80,0x3f6dbf80,0x3ec4bf80,0xbf6dbf80,0x3f6d3f35,0x3ec4bf35,0xbf6d3f35,0xbec4bf35,
0x3f7b0000,0x3e480000,0xbf7b0000,0xbe480000,0xbf553ec4,0x3f0ebec4,0x3f553ec4,0xbf0ebec4,0x3f0ebf35,0x3f55bf35,0xbf0ebf35,0xbf55bf35,0xbe483f6d,0x3f7bbf6d,0x3e483f6d,0xbf7bbf6d,
0,0x3f800000,0,0xbf800000,0,0xbf800000,0,0x3f800000,0,0x3f800000,0,0xbf800000,0,0xbf800000,0,0x3f800000,
0x3f7b3f80,0xbe483f80,0xbf7b3f80,0x3e483f80,0x3f553f6d,0x3f0ebf6d,0xbf553f6d,0xbf0ebf6d,0x3f0e3f35,0xbf553f35,0xbf0e3f35,0x3f553f35,0x3e483ec4,0x3f7bbec4,0xbe483ec4,0xbf7bbec4,
0xbec40000,0xbf6d0000,0x3ec40000,0x3f6d0000,0xbf6dbf35,0x3ec43f35,0x3f6dbf35,0xbec43f35,0xbf6dbf80,0x3ec4bf80,0x3f6dbf80,0xbec4bf80,0xbec4bf35,0xbf6d3f35,0x3ec4bf35,0x3f6d3f35,
0xbf55bf80,0x3f0ebf80,0x3f55bf80,0xbf0ebf80,0x3e48bec4,0xbf7b3ec4,0xbe48bec4,0x3f7b3ec4,0x3f7b3f35,0x3e483f35,0xbf7b3f35,0xbe483f35,0x3f0e3f6d,0x3f55bf6d,0xbf0e3f6d,0xbf55bf6d,
0x3f350000,0x3f350000,0xbf350000,0xbf350000,0x3f353f80,0x3f35bf80,0xbf353f80,0xbf35bf80,0xbf350000,0xbf350000,0x3f350000,0x3f350000,0xbf35bf80,0xbf353f80,0x3f35bf80,0x3f353f80,
0x3f0e3f80,0xbf553f80,0xbf0e3f80,0x3f553f80,0xbf7bbec4,0x3e483ec4,0x3f7bbec4,0xbe483ec4,0x3e48bf35,0x3f7bbf35,0xbe48bf35,0xbf7bbf35,0x3f553f6d,0x3f0ebf6d,0xbf553f6d,0xbf0ebf6d,
0xbf6d0000,0xbec40000,0x3f6d0000,0x3ec40000,0x3ec4bf35,0xbf6d3f35,0xbec4bf35,0x3f6d3f35,0x3ec43f80,0xbf6d3f80,0xbec43f80,0x3f6d3f80,0xbf6dbf35,0xbec43f35,0x3f6dbf35,0x3ec43f35,
0xbe48bf80,0x3f7bbf80,0x3e48bf80,0xbf7bbf80,0x3f0e3f6d,0x3f55bf6d,0xbf0e3f6d,0xbf55bf6d,0xbf55bf35,0x3f0ebf35,0x3f55bf35,0xbf0ebf35,0x3f7b3ec4,0x3e48bec4,0xbf7b3ec4,0xbe48bec4,
0,0x3f800000,0,0xbf800000,0,0xbf800000,0,0x3f800000,0,0x3f800000,0,0xbf800000,0,0xbf800000,0,0x3f800000,
0xbe480000,0xbf7b0000,0x3e480000,0x3f7b0000,0xbf0ebec4,0x3f553ec4,0x3f0ebec4,0xbf553ec4,0xbf55bf35,0xbf0ebf35,0x3f55bf35,0x3f0ebf35,0xbf7bbf6d,0x3e483f6d,0x3f7bbf6d,0xbe483f6d,
0x3ec40000,0x3f6d0000,0xbec40000,0xbf6d0000,0x3f6d3f35,0xbec4bf35,0xbf6d3f35,0x3ec4bf35,0x3f6d3f80,0xbec43f80,0xbf6d3f80,0x3ec43f80,0x3ec43f35,0x3f6dbf35,0xbec43f35,0xbf6dbf35,
0xbf0e0000,0xbf550000,0x3f0e0000,0x3f550000,0xbf7bbf6d,0xbe483f6d,0x3f7bbf6d,0x3e483f6d,0xbe48bf35,0x3f7bbf35,0x3e48bf35,0xbf7bbf35,0x3f553ec4,0xbf0ebec4,0xbf553ec4,0x3f0ebec4,
0x3f350000,0x3f350000,0xbf350000,0xbf350000,0x3f353f80,0x3f35bf80,0xbf353f80,0xbf35bf80,0xbf350000,0xbf350000,0x3f350000,0x3f350000,0xbf35bf80,0xbf353f80,0x3f35bf80,0x3f353f80,
0xbf550000,0xbf0e0000,0x3f550000,0x3f0e0000,0xbe48bf6d,0xbf7b3f6d,0x3e48bf6d,0x3f7b3f6d,0x3f7b3f35,0xbe483f35,0xbf7b3f35,0x3e483f35,0xbf0e3ec4,0x3f55bec4,0x3f0e3ec4,0xbf55bec4,
0x3f6d0000,0x3ec40000,0xbf6d0000,0xbec40000,0xbec43f35,0x3f6dbf35,0x3ec43f35,0xbf6dbf35,0xbec4bf80,0x3f6dbf80,0x3ec4bf80,0xbf6dbf80,0x3f6d3f35,0x3ec4bf35,0xbf6d3f35,0xbec4bf35,
0xbf7b0000,0xbe480000,0x3f7b0000,0x3e480000,0x3f55bec4,0xbf0e3ec4,0xbf55bec4,0x3f0e3ec4,0xbf0e3f35,0xbf553f35,0x3f0e3f35,0x3f553f35,0x3e48bf6d,0xbf7b3f6d,0xbe48bf6d,0x3f7b3f6d,
0,0x3f800000,0,0xbf800000,0,0xbf800000,0,0x3f800000,0,0x3f800000,0,0xbf800000,0,0xbf800000,0,0x3f800000,
0xbf7bbf80,0x3e48bf80,0x3f7bbf80,0xbe48bf80,0xbf55bf6d,0xbf0e3f6d,0x3f55bf6d,0x3f0e3f6d,0xbf0ebf35,0x3f55bf35,0x3f0ebf35,0xbf55bf35,0xbe48bec4,0xbf7b3ec4,0x3e48bec4,0x3f7b3ec4,
0xbec40000,0xbf6d0000,0x3ec40000,0x3f6d0000,0xbf6dbf35,0x3ec43f35,0x3f6dbf35,0xbec43f35,0xbf6dbf80,0x3ec4bf80,0x3f6dbf80,0xbec4bf80,0xbec4bf35,0xbf6d3f35,0x3ec4bf35,0x3f6d3f35,
0x3f553f80,0xbf0e3f80,0xbf553f80,0x3f0e3f80,0xbe483ec4,0x3f7bbec4,0x3e483ec4,0xbf7bbec4,0xbf7bbf35,0xbe48bf35,0x3f7bbf35,0x3e48bf35,0xbf0ebf6d,0xbf553f6d,0x3f0ebf6d,0x3f553f6d,
0x3f350000,0x3f350000,0xbf350000,0xbf350000,0x3f353f80,0x3f35bf80,0xbf353f80,0xbf35bf80,0xbf350000,0xbf350000,0x3f350000,0x3f350000,0xbf35bf80,0xbf353f80,0x3f35bf80,0x3f353f80,
0xbf0ebf80,0x3f55bf80,0x3f0ebf80,0xbf55bf80,0x3f7b3ec4,0xbe48bec4,0xbf7b3ec4,0x3e48bec4,0xbe483f35,0xbf7b3f35,0x3e483f35,0x3f7b3f35,0xbf55bf6d,0xbf0e3f6d,0x3f55bf6d,0x3f0e3f6d,
0xbf6d0000,0xbec40000,0x3f6d0000,0x3ec40000,0x3ec4bf35,0xbf6d3f35,0xbec4bf35,0x3f6d3f35,0x3ec43f80,0xbf6d3f80,0xbec43f80,0x3f6d3f80,0xbf6dbf35,0xbec43f35,0x3f6dbf35,0x3ec43f35,
0x3e483f80,0xbf7b3f80,0xbe483f80,0x3f7b3f80,0xbf0ebf6d,0xbf553f6d,0x3f0ebf6d,0x3f553f6d,0x3f553f35,0xbf0e3f35,0xbf553f35,0x3f0e3f35,0xbf7bbec4,0xbe483ec4,0x3f7bbec4,0x3e483ec4,
0x3f800000,0x3f800000,0x3f800000,0x3f7ec46d,0x3f800000,0x3f800000,0x3f7b14be,0x3f74fa0b,0x3f800000,0x3f800000,0x3f6c835e,0x3f61c598,0x3f800000,0x3f800000,0x3f54db31,0x3f45e403,
0x3f800000,0x3f7ffb11,0x3f800000,0x3f7e70b0,0x3f7fec43,0x3f7fd397,0x3f79c79d,0x3f721352,0x3f7fb10f,0x3f7f84ab,0x3f676bd8,0x3f59f26a,0x3f7f4e6d,0x3f7f0e58,0x3f49d112,0x3f373a23,
0x3f800000,0x3f7fec43,0x3f800000,0x3f7e1324,0x3f7fb10f,0x3f7f4e6d,0x3f7853f8,0x3f6ed89e,0x3f7ec46d,0x3f7e1324,0x3f61c598,0x3f514d3d,0x3f7d3aac,0x3f7c3b28,0x3f3daef9,0x3f273656,
0x3f800000,0x3f7fd397,0x3f800000,0x3f7dabcc,0x3f7f4e6d,0x3f7e70b0,0x3f76ba07,0x3f6b4b0c,0x3f7d3aac,0x3f7baccd,0x3f5b941a,0x3f47de65,0x3f79c79d,0x3f778bc5,0x3f3085bb,0x3f15f6d9,
0x3f800000,0x3f7fb10f,0x3f800000,0x3f7d3aac,0x3f7ec46d,0x3f7d3aac,0x3f74fa0b,0x3f676bd8,0x3f7b14be,0x3f7853f8,0x3f54db31,0x3f3daef9,0x3f74fa0b,0x3f710908,0x3f226799,0x3f039c3d,
0x3f800000,0x3f7f84ab,0x3f800000,0x3f7cbfc9,0x3f7e1324,0x3f7baccd,0x3f731447,0x3f633c5a,0x3f7853f8,0x3f740bdd,0x3f4d9f02,0x3f32c8c9,0x3f6ed89e,0x3f68bf3c,0x3f13682a,0x3ee0924f,
0x3f800000,0x3f7f4e6d,0x3f800000,0x3f7c3b28,0x3f7d3aac,0x3f79c79d,0x3f710908,0x3f5ebe05,0x3f74fa0b,0x3f6ed89e,0x3f45e403,0x3f273656,0x3f676bd8,0x3f5ebe05,0x3f039c3d,0x3eb8442a,
0x3f800000,0x3f7f0e58,0x3f800000,0x3f7baccd,0x3f7c3b28,0x3f778bc5,0x3f6ed89e,0x3f59f26a,0x3f710908,0x3f68bf3c,0x3f3daef9,0x3f1b02c6,0x3f5ebe05,0x3f531849,0x3ee63375,0x3e8e9a22,
0x3f800000,0x3f800000,0x3f3504f3,0x3f226799,0x3f800000,0x3f800000,0x3f0e39da,0x3ef15aea,0x3f800000,0x3f800000,0x3ec3ef15,0x3e94a031,0x3f800000,0x3f800000,0x3e47c5c2,0x3dc8bd36,
0x3f7ec46d,0x3f7e70b0,0x3f226799,0x3f0b9a6b,0x3f7e1324,0x3f7dabcc,0x3ee63375,0x3eb263ef,0x3f7d3aac,0x3f7cbfc9,0x3e78cfcc,0x3e09cf86,0x3f7c3b28,0x3f7baccd,0x3cc90ab0,0xbdafb680,
0x3f7b14be,0x3f79c79d,0x3f0e39da,0x3ee63375,0x3f7853f8,0x3f76ba07,0x3eac7cd4,0x3e605c13,0x3f74fa0b,0x3f731447,0x3dc8bd36,0xbcc90ab0,0x3f710908,0x3f6ed89e,0xbe164083,0xbe888e93,
0x3f74fa0b,0x3f721352,0x3ef15aea,0x3eb263ef,0x3f6ed89e,0x3f6b4b0c,0x3e605c13,0x3dafb680,0x3f676bd8,0x3f633c5a,0xbd48fb30,0xbe3b6ecf,0x3f5ebe05,0x3f59f26a,0xbea09ae5,0xbee0924f,
0x3f6c835e,0x3f676bd8,0x3ec3ef15,0x3e78cfcc,0x3f61c598,0x3f5b941a,0x3dc8bd36,0xbd48fb30,0x3f54db31,0x3f4d9f02,0xbe47c5c2,0xbeac7cd4,0x3f45e403,0x3f3daef9,0xbef15aea,0xbf187fc0,
0x3f61c598,0x3f59f26a,0x3e94a031,0x3e09cf86,0x3f514d3d,0x3f47de65,0xbcc90ab0,0xbe3b6ecf,0x3f3daef9,0x3f32c8c9,0xbeac7cd4,0xbef6e0cb,0x3f273656,0x3f1b02c6,0xbf1d7fd1,0xbf3b8f3b,
0x3f54db31,0x3f49d112,0x3e47c5c2,0x3cc90ab0,0x3f3daef9,0x3f3085bb,0xbe164083,0xbea09ae5,0x3f226799,0x3f13682a,0xbef15aea,0xbf1d7fd1,0x3f039c3d,0x3ee63375,0xbf3daef9,0xbf584853,
0x3f45e403,0x3f373a23,0x3dc8bd36,0xbdafb680,0x3f273656,0x3f15f6d9,0xbe888e93,0xbee0924f,0x3f039c3d,0x3ee0924f,0xbf187fc0,0xbf3b8f3b,0x3eb8442a,0x3e8e9a22,0xbf584853,0xbf6db293,
0x3f800000,0x3f800000,0,0xbdc8bd36,0x3f800000,0x3f800000,0xbe47c5c2,0xbe94a031,0x3f800000,0x3f800000,0xbec3ef15,0xbef15aea,0x3f800000,0x3f800000,0xbf0e39da,0xbf226799,
0x3f7b14be,0x3f7a7302,0xbe47c5c2,0xbe9aa086,0x3f79c79d,0x3f791298,0xbecf7bca,0xbf00e7e4,0x3f7853f8,0x3f778bc5,0xbf187fc0,0xbf2e3bde,0x3f76ba07,0x3f75dec6,0xbf41d870,0xbf531849,
0x3f6c835e,0x3f6a09a7,0xbec3ef15,0xbefc5d27,0x3f676bd8,0x3f64aa59,0xbf187fc0,0xbf3085bb,0x3f61c598,0x3f5ebe05,0xbf45e403,0xbf584853,0x3f5b941a,0x3f584853,0xbf676bd8,0xbf731447,
0x3f54db31,0x3f4f7a1f,0xbf0e39da,0xbf299415,0x3f49d112,0x3f43e200,0xbf41d870,0xbf5695e5,0x3f3daef9,0x3f373a23,0xbf676bd8,0xbf740bdd,0x3f3085bb,0x3f299415,0xbf7c3b28,0xbf7fd397,
0x3f3504f3,0x3f2beb4a,0xbf3504f3,0xbf4d9f02,0x3f226799,0x3f187fc0,0xbf61c598,0xbf710908,0x3f0e39da,0x3f039c3d,0xbf7b14be,0xbf7fb10f,0x3ef15aea,0x3edae880,0xbf7ec46d,0xbf7853f8,
0x3f0e39da,0x3f00e7e4,0xbf54db31,0xbf68bf3c,0x3ee63375,0x3ec9b953,0xbf76ba07,0xbf7e70b0,0x3eac7cd4,0x3e8e9a22,0xbf7fb10f,0xbf7a7302,0x3e605c13,0x3e22abb6,0xbf6ed89e,0xbf5d2d53,
0x3ec3ef15,0x3ea09ae5,0xbf6c835e,0xbf79c79d,0x3e78cfcc,0x3e2f10a2,0xbf7fb10f,0xbf7e1324,0x3dc8bd36,0x3cc90ab0,0xbf74fa0b,0xbf64aa59,0xbd48fb30,0xbdfab273,0xbf4d9f02,0xbf3085bb,
0x3e47c5c2,0x3de1bc2e,0xbf7b14be,0xbf7ffb11,0x3cc90ab0,0xbd7b2b74,0xbf7c3b28,0xbf6ff573,0xbe164083,0xbe6c9a7f,0xbf5b941a,0xbf3fc767,0xbea09ae5,0xbec9b953,0xbf1d7fd1,0xbeebcbbb,
0x3f800000,0x3f800000,0xbf3504f3,0xbf45e403,0x3f800000,0x3f800000,0xbf54db31,0xbf61c598,0x3f800000,0x3f800000,0xbf6c835e,0xbf74fa0b,0x3f800000,0x3f800000,0xbf7b14be,0xbf7ec46d,
0x3f74fa0b,0x3f740bdd,0xbf61c598,0xbf6db293,0x3f731447,0x3f721352,0xbf76ba07,0xbf7cbfc9,0x3f710908,0x3f6ff573,0xbf7fb10f,0xbf7f84ab,0x3f6ed89e,0x3f6db293,0xbf7c3b28,0xbf75dec6,
0x3f54db31,0x3f514d3d,0xbf7b14be,0xbf7f4e6d,0x3f4d9f02,0x3f49d112,0xbf7fb10f,0xbf7c3b28,0x3f45e403,0x3f41d870,0xbf74fa0b,0xbf6a09a7,0x3f3daef9,0x3f396842,0xbf5b941a,0xbf49d112,
0x3f226799,0x3f1b02c6,0xbf7ec46d,0xbf791298,0x3f13682a,0x3f0b9a6b,0xbf6ed89e,0xbf604621,0x3f039c3d,0x3ef6e0cb,0xbf4d9f02,0xbf373a23,0x3ee63375,0x3ed53641,0xbf1d7fd1,0xbf00e7e4,
0x3ec3ef15,0x3eac7cd4,0xbf6c835e,0xbf5b941a,0x3e94a031,0x3e78cfcc,0xbf45e403,0xbf2beb4a,0x3e47c5c2,0x3e164083,0xbf0e39da,0xbedae880,0x3dc8bd36,0x3d48fb30,0xbe94a031,0xbe164083,
0x3dc8bd36,0x3d16c32c,0xbf45e403,0xbf299415,0xbcc90ab0,0xbdafb680,0xbf08f59b,0xbec9b953,0xbe164083,0xbe541501,0xbe78cfcc,0xbdafb680,0xbe888e93,0xbea68f12,0x3d96a905,0x3e6c9a7f,
0xbe47c5c2,0xbe888e93,0xbf0e39da,0xbecf7bca,0xbeac7cd4,0xbecf7bca,0xbe78cfcc,0xbd96a905,0xbef15aea,0xbf08f59b,0x3dc8bd36,0x3e888e93,0xbf187fc0,0xbf273656,0x3edae880,0x3f13682a,
0xbef15aea,0xbf0b9a6b,0xbe94a031,0xbde1bc2e,0xbf1d7fd1,0xbf2e3bde,0x3d96a905,0x3e827dc0,0xbf3daef9,0xbf4bbbf8,0x3edae880,0x3f15f6d9,0xbf584853,0xbf633c5a,0x3f396842,0x3f5695e5,
0,0,0,0x3dc8bd36,0,0,0x3e47c5c2,0x3e94a031,0,0,0x3ec3ef15,0x3ef15aea,0,0,0x3f0e39da,0x3f226799,
0,0x3c490e90,0,0x3de1bc2e,0x3cc90ab0,0x3d16c32c,0x3e605c13,0x3ea68f12,0x3d48fb30,0x3d7b2b74,0x3edae880,0x3f064b82,0x3d96a905,0x3dafb680,0x3f1d7fd1,0x3f32c8c9,
0,0x3cc90ab0,0,0x3dfab273,0x3d48fb30,0x3d96a905,0x3e78cfcc,0x3eb8442a,0x3dc8bd36,0x3dfab273,0x3ef15aea,0x3f13682a,0x3e164083,0x3e2f10a2,0x3f2beb4a,0x3f41d870,
0,0x3d16c32c,0,0x3e09cf86,0x3d96a905,0x3de1bc2e,0x3e888e93,0x3ec9b953,0x3e164083,0x3e3b6ecf,0x3f039c3d,0x3f1ff6cb,0x3e605c13,0x3e827dc0,0x3f396842,0x3f4f7a1f,
0,0x3d48fb30,0,0x3e164083,0x3dc8bd36,0x3e164083,0x3e94a031,0x3edae880,0x3e47c5c2,0x3e78cfcc,0x3f0e39da,0x3f2beb4a,0x3e94a031,0x3eac7cd4,0x3f45e403,0x3f5b941a,
0,0x3d7b2b74,0,0x3e22abb6,0x3dfab273,0x3e3b6ecf,0x3ea09ae5,0x3eebcbbb,0x3e78cfcc,0x3e9aa086,0x3f187fc0,0x3f373a23,0x3eb8442a,0x3ed53641,0x3f514d3d,0x3f660f88,
0,0x3d96a905,0,0x3e2f10a2,0x3e164083,0x3e605c13,0x3eac7cd4,0x3efc5d27,0x3e94a031,0x3eb8442a,0x3f226799,0x3f41d870,0x3edae880,0x3efc5d27,0x3f5b941a,0x3f6ed89e,
0,0x3dafb680,0,0x3e3b6ecf,0x3e2f10a2,0x3e827dc0,0x3eb8442a,0x3f064b82,0x3eac7cd4,0x3ed53641,0x3f2beb4a,0x3f4bbbf8,0x3efc5d27,0x3f10d3cd,0x3f64aa59,0x3f75dec6,
0,0,0x3f3504f3,0x3f45e403,0,0,0x3f54db31,0x3f61c598,0,0,0x3f6c835e,0x3f74fa0b,0,0,0x3f7b14be,0x3f7ec46d,
0x3dc8bd36,0x3de1bc2e,0x3f45e403,0x3f5695e5,0x3dfab273,0x3e09cf86,0x3f64aa59,0x3f6ff573,0x3e164083,0x3e22abb6,0x3f7853f8,0x3f7dabcc,0x3e2f10a2,0x3e3b6ecf,0x3f7fec43,0x3f7f0e58,
0x3e47c5c2,0x3e605c13,0x3f54db31,0x3f64aa59,0x3e78cfcc,0x3e888e93,0x3f710908,0x3f79c79d,0x3e94a031,0x3ea09ae5,0x3f7ec46d,0x3f7fec43,0x3eac7cd4,0x3eb8442a,0x3f7d3aac,0x3f76ba07,
0x3e94a031,0x3ea68f12,0x3f61c598,0x3f6ff573,0x3eb8442a,0x3ec9b953,0x3f79c79d,0x3f7f0e58,0x3edae880,0x3eebcbbb,0x3f7fb10f,0x3f7baccd,0x3efc5d27,0x3f064b82,0x3f731447,0x3f660f88,
0x3ec3ef15,0x3edae880,0x3f6c835e,0x3f7853f8,0x3ef15aea,0x3f039c3d,0x3f7ec46d,0x3f7fb10f,0x3f0e39da,0x3f187fc0,0x3f7b14be,0x3f710908,0x3f226799,0x3f2beb4a,0x3f61c598,0x3f4d9f02,
0x3ef15aea,0x3f064b82,0x3f74fa0b,0x3f7dabcc,0x3f13682a,0x3f1ff6cb,0x3f7fec43,0x3f7baccd,0x3f2beb4a,0x3f373a23,0x3f710908,0x3f604621,0x3f41d870,0x3f4bbbf8,0x3f49d112,0x3f2e3bde,
0x3f0e39da,0x3f1d7fd1,0x3f7b14be,0x3f7fec43,0x3f2beb4a,0x3f396842,0x3f7d3aac,0x3f731447,0x3f45e403,0x3f514d3d,0x3f61c598,0x3f49d112,0x3f5b941a,0x3f64aa59,0x3f2beb4a,0x3f08f59b,
0x3f226799,0x3f32c8c9,0x3f7ec46d,0x3f7f0e58,0x3f41d870,0x3f4f7a1f,0x3f76ba07,0x3f660f88,0x3f5b941a,0x3f660f88,0x3f4d9f02,0x3f2e3bde,0x3f6ed89e,0x3f75dec6,0x3f08f59b,0x3ebe1d4a,
0,0,0x3f800000,0x3f7ec46d,0,0,0x3f7b14be,0x3f74fa0b,0,0,0x3f6c835e,0x3f61c598,0,0,0x3f54db31,0x3f45e403,
0x3e47c5c2,0x3e541501,0x3f7b14be,0x3f740bdd,0x3e605c13,0x3e6c9a7f,0x3f6a09a7,0x3f5d2d53,0x3e78cfcc,0x3e827dc0,0x3f4d9f02,0x3f3b8f3b,0x3e888e93,0x3e8e9a22,0x3f273656,0x3f10d3cd,
0x3ec3ef15,0x3ecf7bca,0x3f6c835e,0x3f5ebe05,0x3edae880,0x3ee63375,0x3f4d9f02,0x3f396842,0x3ef15aea,0x3efc5d27,0x3f226799,0x3f08f59b,0x3f039c3d,0x3f08f59b,0x3edae880,0x3ea09ae5,
0x3f0e39da,0x3f15f6d9,0x3f54db31,0x3f3fc767,0x3f1d7fd1,0x3f24d225,0x3f273656,0x3f0b9a6b,0x3f2beb4a,0x3f32c8c9,0x3edae880,0x3e9aa086,0x3f396842,0x3f3fc767,0x3e2f10a2,0x3d16c32c,
0x3f3504f3,0x3f3daef9,0x3f3504f3,0x3f187fc0,0x3f45e403,0x3f4d9f02,0x3ef15aea,0x3eac7cd4,0x3f54db31,0x3f5b941a,0x3e47c5c2,0x3d48fb30,0x3f61c598,0x3f676bd8,0xbdc8bd36,0xbe78cfcc,
0x3f54db31,0x3f5d2d53,0x3f0e39da,0x3ed53641,0x3f64aa59,0x3f6b4b0c,0x3e888e93,0x3de1bc2e,0x3f710908,0x3f75dec6,0xbd48fb30,0xbe541501,0x3f79c79d,0x3f7cbfc9,0xbeb8442a,0xbf00e7e4,
0x3f6c835e,0x3f731447,0x3ec3ef15,0x3e605c13,0x3f7853f8,0x3f7c3b28,0x3d48fb30,0xbdfab273,0x3f7ec46d,0x3f7fec43,0xbe94a031,0xbee63375,0x3f7fb10f,0x3f7e1324,0xbf187fc0,0xbf396842,
0x3f7b14be,0x3f7e70b0,0x3e47c5c2,0x3c490e90,0x3f7fec43,0x3f7f84ab,0xbe2f10a2,0xbeb263ef,0x3f7d3aac,0x3f791298,0xbf039c3d,0xbf299415,0x3f731447,0x3f6b4b0c,0xbf49d112,0xbf633c5a,
0,0,0x3f3504f3,0x3f226799,0,0,0x3f0e39da,0x3ef15aea,0,0,0x3ec3ef15,0x3e94a031,0,0,0x3e47c5c2,0x3dc8bd36,
0x3e94a031,0x3e9aa086,0x3ef15aea,0x3ebe1d4a,0x3ea09ae5,0x3ea68f12,0x3e888e93,0x3e22abb6,0x3eac7cd4,0x3eb263ef,0x3d48fb30,0xbd7b2b74,0x3eb8442a,0x3ebe1d4a,0xbe2f10a2,0xbe8e9a22,
0x3f0e39da,0x3f13682a,0x3e47c5c2,0x3d96a905,0x3f187fc0,0x3f1d7fd1,0xbd48fb30,0xbe2f10a2,0x3f226799,0x3f273656,0xbe94a031,0xbecf7bca,0x3f2beb4a,0x3f3085bb,0xbf039c3d,0xbf1d7fd1,
0x3f45e403,0x3f4bbbf8,0xbdc8bd36,0xbe6c9a7f,0x3f514d3d,0x3f5695e5,0xbeb8442a,0xbef6e0cb,0x3f5b941a,0x3f604621,0xbf187fc0,0xbf32c8c9,0x3f64aa59,0x3f68bf3c,0xbf49d112,0xbf5d2d53,
0x3f6c835e,0x3f710908,0xbec3ef15,0xbf039c3d,0x3f74fa0b,0x3f7853f8,0xbf226799,0xbf3daef9,0x3f7b14be,0x3f7d3aac,0xbf54db31,0xbf676bd8,0x3f7ec46d,0x3f7fb10f,0xbf74fa0b,0xbf7d3aac,
0x3f7ec46d,0x3f7fd397,0xbf226799,0xbf3fc767,0x3f7fec43,0x3f7f0e58,0xbf584853,0xbf6b4b0c,0x3f7d3aac,0x3f7a7302,0xbf7853f8,0xbf7f0e58,0x3f76ba07,0x3f721352,0xbf7f4e6d,0xbf791298,
0x3f7b14be,0x3f76ba07,0xbf54db31,0xbf6a09a7,0x3f710908,0x3f6a09a7,0xbf7853f8,0xbf7f4e6d,0x3f61c598,0x3f584853,0xbf7ec46d,0xbf76ba07,0x3f4d9f02,0x3f41d870,0xbf676bd8,0xbf514d3d,
0x3f61c598,0x3f5695e5,0xbf74fa0b,0xbf7e70b0,0x3f49d112,0x3f3b8f3b,0xbf7f4e6d,0xbf778bc5,0x3f2beb4a,0x3f1b02c6,0xbf676bd8,0xbf4f7a1f,0x3f08f59b,0x3eebcbbb,0xbf3085bb,0xbf0b9a6b,
0x3f800000,0x3f7fffb1,0x3f7ffec4,0x3f7ffd39,0x3f7ffb11,0x3f7ff84a,0x3f7ff4e6,0x3f7ff0e3,0x3f7fec43,0x3f7fe705,0x3f7fe129,0x3f7fdaaf,0x3f7fd397,0x3f7fcbe2,0x3f7fc38f,0x3f7fba9e,
0x3f7fb10f,0x3f7fa6e3,0x3f7f9c18,0x3f7f90b1,0x3f7f84ab,0x3f7f7808,0x3f7f6ac7,0x3f7f5ce9,0x3f7f4e6d,0x3f7f3f54,0x3f7f2f9d,0x3f7f1f49,0x3f7f0e58,0x3f7efcc9,0x3f7eea9d,0x3f7ed7d4,
0x3f7ec46d,0x3f7eb069,0x3f7e9bc9,0x3f7e868b,0x3f7e70b0,0x3f7e5a38,0x3f7e4323,0x3f7e2b72,0x3f7e1324,0x3f7dfa38,0x3f7de0b1,0x3f7dc68c,0x3f7dabcc,0x3f7d906e,0x3f7d7474,0x3f7d57de,
0x3f7d3aac,0x3f7d1cdd,0x3f7cfe73,0x3f7cdf6c,0x3f7cbfc9,0x3f7c9f8a,0x3f7c7eb0,0x3f7c5d3a,0x3f7c3b28,0x3f7c187a,0x3f7bf531,0x3f7bd14d,0x3f7baccd,0x3f7b87b2,0x3f7b61fc,0x3f7b3bab,
0x3f7b14be,0x3f7aed37,0x3f7ac516,0x3f7a9c59,0x3f7a7302,0x3f7a4910,0x3f7a1e84,0x3f79f35e,0x3f79c79d,0x3f799b43,0x3f796e4e,0x3f7940c0,0x3f791298,0x3f78e3d6,0x3f78b47b,0x3f788486,
0x3f7853f8,0x3f7822d1,0x3f77f110,0x3f77beb7,0x3f778bc5,0x3f77583a,0x3f772417,0x3f76ef5b,0x3f76ba07,0x3f76841b,0x3f764d97,0x3f76167a,0x3f75dec6,0x3f75a67b,0x3f756d97,0x3f75341d,
0x3f74fa0b,0x3f74bf62,0x3f748422,0x3f74484b,0x3f740bdd,0x3f73ced9,0x3f73913f,0x3f73530e,0x3f731447,0x3f72d4eb,0x3f7294f8,0x3f725470,0x3f721352,0x3f71d19f,0x3f718f57,0x3f714c7a,
0x3f710908,0x3f70c501,0x3f708066,0x3f703b37,0x3f6ff573,0x3f6faf1b,0x3f6f6830,0x3f6f20b0,0x3f6ed89e,0x3f6e8ff8,0x3f6e46be,0x3f6dfcf2,0x3f6db293,0x3f6d67a1,0x3f6d1c1d,0x3f6cd007,
0x3f6c835e,0x3f6c3624,0x3f6be858,0x3f6b99fb,0x3f6b4b0c,0x3f6afb8c,0x3f6aab7b,0x3f6a5ad9,0x3f6a09a7,0x3f69b7e4,0x3f696591,0x3f6912ae,0x3f68bf3c,0x3f686b39,0x3f6816a8,0x3f67c187,
0x3f676bd8,0x3f671599,0x3f66becc,0x3f666771,0x3f660f88,0x3f65b710,0x3f655e0b,0x3f650479,0x3f64aa59,0x3f644fac,0x3f63f473,0x3f6398ac,0x3f633c5a,0x3f62df7b,0x3f628210,0x3f62241a,
0x3f61c598,0x3f61668a,0x3f6106f2,0x3f60a6cf,0x3f604621,0x3f5fe4e9,0x3f5f8327,0x3f5f20db,0x3f5ebe05,0x3f5e5aa6,0x3f5df6be,0x3f5d924d,0x3f5d2d53,0x3f5cc7d1,0x3f5c61c7,0x3f5bfb34,
0x3f5b941a,0x3f5b2c79,0x3f5ac450,0x3f5a5ba0,0x3f59f26a,0x3f5988ad,0x3f591e6a,0x3f58b3a1,0x3f584853,0x3f57dc7f,0x3f577026,0x3f570348,0x3f5695e5,0x3f5627fe,0x3f55b993,0x3f554aa4,
0x3f54db31,0x3f546b3b,0x3f53fac3,0x3f5389c7,0x3f531849,0x3f52a649,0x3f5233c6,0x3f51c0c2,0x3f514d3d,0x3f50d937,0x3f5064af,0x3f4fefa8,0x3f4f7a1f,0x3f4f0417,0x3f4e8d90,0x3f4e1689,
0x3f4d9f02,0x3f4d26fd,0x3f4cae79,0x3f4c3578,0x3f4bbbf8,0x3f4b41fa,0x3f4ac77f,0x3f4a4c87,0x3f49d112,0x3f495521,0x3f48d8b3,0x3f485bca,0x3f47de65,0x3f476085,0x3f46e22a,0x3f466354,
0x3f45e403,0x3f456439,0x3f44e3f5,0x3f446337,0x3f43e200,0x3f436051,0x3f42de29,0x3f425b89,0x3f41d870,0x3f4154e1,0x3f40d0da,0x3f404c5c,0x3f3fc767,0x3f3f41fc,0x3f3ebc1b,0x3f3e35c5,
0x3f3daef9,0x3f3d27b8,0x3f3ca003,0x3f3c17d9,0x3f3b8f3b,0x3f3b0629,0x3f3a7ca4,0x3f39f2ac,0x3f396842,0x3f38dd65,0x3f385216,0x3f37c655,0x3f373a23,0x3f36ad7f,0x3f36206c,0x3f3592e7,
0x3f3504f3,0x3f34768f,0x3f33e7bc,0x3f33587a,0x3f32c8c9,0x3f3238aa,0x3f31a81d,0x3f311722,0x3f3085bb,0x3f2ff3e6,0x3f2f61a5,0x3f2ecef7,0x3f2e3bde,0x3f2da859,0x3f2d1469,0x3f2c800f,
0x3f2beb4a,0x3f2b561b,0x3f2ac082,0x3f2a2a80,0x3f299415,0x3f28fd41,0x3f286605,0x3f27ce61,0x3f273656,0x3f269de3,0x3f26050a,0x3f256bcb,0x3f24d225,0x3f24381a,0x3f239da9,0x3f2302d3,
0x3f226799,0x3f21cbfb,0x3f212ff9,0x3f209393,0x3f1ff6cb,0x3f1f599f,0x3f1ebc12,0x3f1e1e22,0x3f1d7fd1,0x3f1ce11f,0x3f1c420c,0x3f1ba299,0x3f1b02c6,0x3f1a6293,0x3f19c200,0x3f19210f,
0x3f187fc0,0x3f17de12,0x3f173c07,0x3f16999f,0x3f15f6d9,0x3f1553b7,0x3f14b039,0x3f140c5f,0x3f13682a,0x3f12c39a,0x3f121eb0,0x3f11796b,0x3f10d3cd,0x3f102dd5,0x3f0f8784,0x3f0ee0db,
0x3f0e39da,0x3f0d9281,0x3f0cead0,0x3f0c42c9,0x3f0b9a6b,0x3f0af1b7,0x3f0a48ad,0x3f099f4e,0x3f08f59b,0x3f084b92,0x3f07a136,0x3f06f686,0x3f064b82,0x3f05a02c,0x3f04f484,0x3f044889,
0x3f039c3d,0x3f02ef9f,0x3f0242b1,0x3f019573,0x3f00e7e4,0x3f003a06,0x3eff17b2,0x3efdbabb,0x3efc5d27,0x3efafef7,0x3ef9a02d,0x3ef840c8,0x3ef6e0cb,0x3ef58035,0x3ef41f07,0x3ef2bd43,
0x3ef15aea,0x3eeff7fb,0x3eee9479,0x3eed3063,0x3eebcbbb,0x3eea6681,0x3ee900b7,0x3ee79a5d,0x3ee63375,0x3ee4cbfe,0x3ee363fa,0x3ee1fb6a,0x3ee0924f,0x3edf28a9,0x3eddbe79,0x3edc53c1,
0x3edae880,0x3ed97cb9,0x3ed8106b,0x3ed6a399,0x3ed53641,0x3ed3c867,0x3ed25a09,0x3ed0eb2a,0x3ecf7bca,0x3ece0bea,0x3ecc9b8b,0x3ecb2aae,0x3ec9b953,0x3ec8477c,0x3ec6d529,0x3ec5625c,
0x3ec3ef15,0x3ec27b55,0x3ec1071e,0x3ebf926f,0x3ebe1d4a,0x3ebca7af,0x3ebb31a0,0x3eb9bb1e,0x3eb8442a,0x3eb6ccc3,0x3eb554ec,0x3eb3dca5,0x3eb263ef,0x3eb0eacb,0x3eaf713a,0x3eadf73c,
0x3eac7cd4,0x3eab0201,0x3ea986c4,0x3ea80b1f,0x3ea68f12,0x3ea5129f,0x3ea395c5,0x3ea21887,0x3ea09ae5,0x3e9f1cdf,0x3e9d9e78,0x3e9c1faf,0x3e9aa086,0x3e9920fe,0x3e97a117,0x3e9620d2,
0x3e94a031,0x3e931f35,0x3e919ddd,0x3e901c2c,0x3e8e9a22,0x3e8d17c0,0x3e8b9507,0x3e8a11f7,0x3e888e93,0x3e870ada,0x3e8586ce,0x3e840270,0x3e827dc0,0x3e80f8c0,0x3e7ee6e1,0x3e7bdba4,
0x3e78cfcc,0x3e75c35a,0x3e72b651,0x3e6fa8b2,0x3e6c9a7f,0x3e698bba,0x3e667c66,0x3e636c83,0x3e605c13,0x3e5d4b1a,0x3e5a3997,0x3e57278f,0x3e541501,0x3e5101f1,0x3e4dee60,0x3e4ada4f,
0x3e47c5c2,0x3e44b0b9,0x3e419b37,0x3e3e853e,0x3e3b6ecf,0x3e3857ec,0x3e354098,0x3e3228d4,0x3e2f10a2,0x3e2bf804,0x3e28defc,0x3e25c58c,0x3e22abb6,0x3e1f917b,0x3e1c76de,0x3e195be0,
0x3e164083,0x3e1324ca,0x3e1008b7,0x3e0cec4a,0x3e09cf86,0x3e06b26e,0x3e039502,0x3e007745,0x3dfab273,0x3df475c0,0x3dee3876,0x3de7fa9a,0x3de1bc2e,0x3ddb7d37,0x3dd53db9,0x3dcefdb7,
0x3dc8bd36,0x3dc27c39,0x3dbc3ac3,0x3db5f8da,0x3dafb680,0x3da973ba,0x3da3308c,0x3d9cecf9,0x3d96a905,0x3d9064b4,0x3d8a200a,0x3d83db0a,0x3d7b2b74,0x3d6ea038,0x3d621469,0x3d55880e,
0x3d48fb30,0x3d3c6dd5,0x3d2fe007,0x3d2351cb,0x3d16c32c,0x3d0a342f,0x3cfb49ba,0x3ce22a7a,0x3cc90ab0,0x3cafea69,0x3c96c9b6,0x3c7b514b,0x3c490e90,0x3c16cb58,0x3bc90f88,0x3b490fc6,
0,0x3b490fc6,0x3bc90f88,0x3c16cb58,0x3c490e90,0x3c7b514b,0x3c96c9b6,0x3cafea69,0x3cc90ab0,0x3ce22a7a,0x3cfb49ba,0x3d0a342f,0x3d16c32c,0x3d2351cb,0x3d2fe007,0x3d3c6dd5,
0x3d48fb30,0x3d55880e,0x3d621469,0x3d6ea038,0x3d7b2b74,0x3d83db0a,0x3d8a200a,0x3d9064b4,0x3d96a905,0x3d9cecf9,0x3da3308c,0x3da973ba,0x3dafb680,0x3db5f8da,0x3dbc3ac3,0x3dc27c39,
0x3dc8bd36,0x3dcefdb7,0x3dd53db9,0x3ddb7d37,0x3de1bc2e,0x3de7fa9a,0x3dee3876,0x3df475c0,0x3dfab273,0x3e007745,0x3e039502,0x3e06b26e,0x3e09cf86,0x3e0cec4a,0x3e1008b7,0x3e1324ca,
0x3e164083,0x3e195be0,0x3e1c76de,0x3e1f917b,0x3e22abb6,0x3e25c58c,0x3e28defc,0x3e2bf804,0x3e2f10a2,0x3e3228d4,0x3e354098,0x3e3857ec,0x3e3b6ecf,0x3e3e853e,0x3e419b37,0x3e44b0b9,
0x3e47c5c2,0x3e4ada4f,0x3e4dee60,0x3e5101f1,0x3e541501,0x3e57278f,0x3e5a3997,0x3e5d4b1a,0x3e605c13,0x3e636c83,0x3e667c66,0x3e698bba,0x3e6c9a7f,0x3e6fa8b2,0x3e72b651,0x3e75c35a,
0x3e78cfcc,0x3e7bdba4,0x3e7ee6e1,0x3e80f8c0,0x3e827dc0,0x3e840270,0x3e8586ce,0x3e870ada,0x3e888e93,0x3e8a11f7,0x3e8b9507,0x3e8d17c0,0x3e8e9a22,0x3e901c2c,0x3e919ddd,0x3e931f35,
0x3e94a031,0x3e9620d2,0x3e97a117,0x3e9920fe,0x3e9aa086,0x3e9c1faf,0x3e9d9e78,0x3e9f1cdf,0x3ea09ae5,0x3ea21887,0x3ea395c5,0x3ea5129f,0x3ea68f12,0x3ea80b1f,0x3ea986c4,0x3eab0201,
0x3eac7cd4,0x3eadf73c,0x3eaf713a,0x3eb0eacb,0x3eb263ef,0x3eb3dca5,0x3eb554ec,0x3eb6ccc3,0x3eb8442a,0x3eb9bb1e,0x3ebb31a0,0x3ebca7af,0x3ebe1d4a,0x3ebf926f,0x3ec1071e,0x3ec27b55,
0x3ec3ef15,0x3ec5625c,0x3ec6d529,0x3ec8477c,0x3ec9b953,0x3ecb2aae,0x3ecc9b8b,0x3ece0bea,0x3ecf7bca,0x3ed0eb2a,0x3ed25a09,0x3ed3c867,0x3ed53641,0x3ed6a399,0x3ed8106b,0x3ed97cb9,
0x3edae880,0x3edc53c1,0x3eddbe79,0x3edf28a9,0x3ee0924f,0x3ee1fb6a,0x3ee363fa,0x3ee4cbfe,0x3ee63375,0x3ee79a5d,0x3ee900b7,0x3eea6681,0x3eebcbbb,0x3eed3063,0x3eee9479,0x3eeff7fb,
0x3ef15aea,0x3ef2bd43,0x3ef41f07,0x3ef58035,0x3ef6e0cb,0x3ef840c8,0x3ef9a02d,0x3efafef7,0x3efc5d27,0x3efdbabb,0x3eff17b2,0x3f003a06,0x3f00e7e4,0x3f019573,0x3f0242b1,0x3f02ef9f,
0x3f039c3d,0x3f044889,0x3f04f484,0x3f05a02c,0x3f064b82,0x3f06f686,0x3f07a136,0x3f084b92,0x3f08f59b,0x3f099f4e,0x3f0a48ad,0x3f0af1b7,0x3f0b9a6b,0x3f0c42c9,0x3f0cead0,0x3f0d9281,
0x3f0e39da,0x3f0ee0db,0x3f0f8784,0x3f102dd5,0x3f10d3cd,0x3f11796b,0x3f121eb0,0x3f12c39a,0x3f13682a,0x3f140c5f,0x3f14b039,0x3f1553b7,0x3f15f6d9,0x3f16999f,0x3f173c07,0x3f17de12,
0x3f187fc0,0x3f19210f,0x3f19c200,0x3f1a6293,0x3f1b02c6,0x3f1ba299,0x3f1c420c,0x3f1ce11f,0x3f1d7fd1,0x3f1e1e22,0x3f1ebc12,0x3f1f599f,0x3f1ff6cb,0x3f209393,0x3f212ff9,0x3f21cbfb,
0x3f226799,0x3f2302d3,0x3f239da9,0x3f24381a,0x3f24d225,0x3f256bcb,0x3f26050a,0x3f269de3,0x3f273656,0x3f27ce61,0x3f286605,0x3f28fd41,0x3f299415,0x3f2a2a80,0x3f2ac082,0x3f2b561b,
0x3f2beb4a,0x3f2c800f,0x3f2d1469,0x3f2da859,0x3f2e3bde,0x3f2ecef7,0x3f2f61a5,0x3f2ff3e6,0x3f3085bb,0x3f311722,0x3f31a81d,0x3f3238aa,0x3f32c8c9,0x3f33587a,0x3f33e7bc,0x3f34768f,
0x3f3504f3,0x3f3592e7,0x3f36206c,0x3f36ad7f,0x3f373a23,0x3f37c655,0x3f385216,0x3f38dd65,0x3f396842,0x3f39f2ac,0x3f3a7ca4,0x3f3b0629,0x3f3b8f3b,0x3f3c17d9,0x3f3ca003,0x3f3d27b8,
0x3f3daef9,0x3f3e35c5,0x3f3ebc1b,0x3f3f41fc,0x3f3fc767,0x3f404c5c,0x3f40d0da,0x3f4154e1,0x3f41d870,0x3f425b89,0x3f42de29,0x3f436051,0x3f43e200,0x3f446337,0x3f44e3f5,0x3f456439,
0x3f45e403,0x3f466354,0x3f46e22a,0x3f476085,0x3f47de65,0x3f485bca,0x3f48d8b3,0x3f495521,0x3f49d112,0x3f4a4c87,0x3f4ac77f,0x3f4b41fa,0x3f4bbbf8,0x3f4c3578,0x3f4cae79,0x3f4d26fd,
0x3f4d9f02,0x3f4e1689,0x3f4e8d90,0x3f4f0417,0x3f4f7a1f,0x3f4fefa8,0x3f5064af,0x3f50d937,0x3f514d3d,0x3f51c0c2,0x3f5233c6,0x3f52a649,0x3f531849,0x3f5389c7,0x3f53fac3,0x3f546b3b,
0x3f54db31,0x3f554aa4,0x3f55b993,0x3f5627fe,0x3f5695e5,0x3f570348,0x3f577026,0x3f57dc7f,0x3f584853,0x3f58b3a1,0x3f591e6a,0x3f5988ad,0x3f59f26a,0x3f5a5ba0,0x3f5ac450,0x3f5b2c79,
0x3f5b941a,0x3f5bfb34,0x3f5c61c7,0x3f5cc7d1,0x3f5d2d53,0x3f5d924d,0x3f5df6be,0x3f5e5aa6,0x3f5ebe05,0x3f5f20db,0x3f5f8327,0x3f5fe4e9,0x3f604621,0x3f60a6cf,0x3f6106f2,0x3f61668a,
0x3f61c598,0x3f62241a,0x3f628210,0x3f62df7b,0x3f633c5a,0x3f6398ac,0x3f63f473,0x3f644fac,0x3f64aa59,0x3f650479,0x3f655e0b,0x3f65b710,0x3f660f88,0x3f666771,0x3f66becc,0x3f671599,
0x3f676bd8,0x3f67c187,0x3f6816a8,0x3f686b39,0x3f68bf3c,0x3f6912ae,0x3f696591,0x3f69b7e4,0x3f6a09a7,0x3f6a5ad9,0x3f6aab7b,0x3f6afb8c,0x3f6b4b0c,0x3f6b99fb,0x3f6be858,0x3f6c3624,
0x3f6c835e,0x3f6cd007,0x3f6d1c1d,0x3f6d67a1,0x3f6db293,0x3f6dfcf2,0x3f6e46be,0x3f6e8ff8,0x3f6ed89e,0x3f6f20b0,0x3f6f6830,0x3f6faf1b,0x3f6ff573,0x3f703b37,0x3f708066,0x3f70c501,
0x3f710908,0x3f714c7a,0x3f718f57,0x3f71d19f,0x3f721352,0x3f725470,0x3f7294f8,0x3f72d4eb,0x3f731447,0x3f73530e,0x3f73913f,0x3f73ced9,0x3f740bdd,0x3f74484b,0x3f748422,0x3f74bf62,
0x3f74fa0b,0x3f75341d,0x3f756d97,0x3f75a67b,0x3f75dec6,0x3f76167a,0x3f764d97,0x3f76841b,0x3f76ba07,0x3f76ef5b,0x3f772417,0x3f77583a,0x3f778bc5,0x3f77beb7,0x3f77f110,0x3f7822d1,
0x3f7853f8,0x3f788486,0x3f78b47b,0x3f78e3d6,0x3f791298,0x3f7940c0,0x3f796e4e,0x3f799b43,0x3f79c79d,0x3f79f35e,0x3f7a1e84,0x3f7a4910,0x3f7a7302,0x3f7a9c59,0x3f7ac516,0x3f7aed37,
0x3f7b14be,0x3f7b3bab,0x3f7b61fc,0x3f7b87b2,0x3f7baccd,0x3f7bd14d,0x3f7bf531,0x3f7c187a,0x3f7c3b28,0x3f7c5d3a,0x3f7c7eb0,0x3f7c9f8a,0x3f7cbfc9,0x3f7cdf6c,0x3f7cfe73,0x3f7d1cdd,
0x3f7d3aac,0x3f7d57de,0x3f7d7474,0x3f7d906e,0x3f7dabcc,0x3f7dc68c,0x3f7de0b1,0x3f7dfa38,0x3f7e1324,0x3f7e2b72,0x3f7e4323,0x3f7e5a38,0x3f7e70b0,0x3f7e868b,0x3f7e9bc9,0x3f7eb069,
0x3f7ec46d,0x3f7ed7d4,0x3f7eea9d,0x3f7efcc9,0x3f7f0e58,0x3f7f1f49,0x3f7f2f9d,0x3f7f3f54,0x3f7f4e6d,0x3f7f5ce9,0x3f7f6ac7,0x3f7f7808,0x3f7f84ab,0x3f7f90b1,0x3f7f9c18,0x3f7fa6e3,
0x3f7fb10f,0x3f7fba9e,0x3f7fc38f,0x3f7fcbe2,0x3f7fd397,0x3f7fdaaf,0x3f7fe129,0x3f7fe705,0x3f7fec43,0x3f7ff0e3,0x3f7ff4e6,0x3f7ff84a,0x3f7ffb11,0x3f7ffd39,0x3f7ffec4,0x3f7fffb1,
};

__device__ __forceinline__ int tid_here() { return __shfl_xor_sync(~0u, (int)threadIdx.x, 0); }
__device__ __forceinline__ void ld_tab(uint32_t* d, int chunk) { asm volatile("ld.global.v4.u32 {%0,%1,%2,%3}, [%4];" : "=r"(d[0]), "=r"(d[1]), "=r"(d[2]), "=r"(d[3]) : "l"((const uint4*)g_tab + chunk) : "memory"); }
__device__ __forceinline__ void ld_tab(float* d, int chunk) { asm volatile("ld.global.v4.f32 {%0,%1,%2,%3}, [%4];" : "=f"(d[0]), "=f"(d[1]), "=f"(d[2]), "=f"(d[3]) : "l"((const uint4*)g_tab + chunk) : "memory"); }
__device__ __forceinline__ void fft640(uint32_t plane, uint32_t tab, int lane, const uint32_t* fr, const uint32_t* fi, const float (*tc)[4], const float (*ts)[4], float (*xr)[4], float (*xi)[4], int zero) {
  uint32_t A1[5][4], nfi[4];
#pragma unroll
  for (int i = 0; i < 4; i++) nfi[i] = fi[i] ^ 0x80008000u;
  const uint32_t la = plane + (lane >> 4) * 1280 + (lane & 15) * 80;
#pragma unroll
  for (int j = 0; j < 5; j++) {
    uint32_t r0, r1, i0, i1; ldsm4t(r0, r1, i0, i1, la + j * 16);
    float yr[4], yi[4];
    mmaZ(yr, fr, r0, r1); mmaZ(yi, fi, r0, r1); mmaA(yr, nfi, i0, i1); mmaA(yi, fr, i0, i1);
    float zr[4], zi[4];
#pragma unroll
    for (int e = 0; e < 4; e++) { zr[e] = yr[e] * tc[j][e] - yi[e] * ts[j][e]; zi[e] = yr[e] * ts[j][e] + yi[e] * tc[j][e]; }
    A1[j][0] = pack_bf16(zr[0], zr[1]); A1[j][1] = pack_bf16(zr[2], zr[3]); A1[j][2] = pack_bf16(zi[0], zi[1]); A1[j][3] = pack_bf16(zi[2], zi[3]);
  }
#pragma unroll
  for (int t = 0; t < 5; t++) {
    uint32_t A2[4] = {A1[t][2], A1[t][3], A1[t][0] ^ 0x80008000u, A1[t][1] ^ 0x80008000u};
#pragma unroll
    for (int u = 0; u < 5; u++) {
      uint32_t b0, b1; asm volatile("ld.shared.v2.b32 {%0,%1}, [%2];" : "=r"(b0), "=r"(b1) : "r"(tab + (t * 5 + u) * 256 + lane * 8));
      if (t == 0) { mmaZ(xr[u], A1[t], b0, b1); mmaZ(xi[u], A2, b0, b1); } else { mmaA(xr[u], A1[t], b0, b1); mmaA(xi[u], A2, b0, b1); }
    }
  }
}
__device__ __forceinline__ void ln_row(float* v) {
  float s = 0.f;
#pragma unroll
  for (int i = 0; i < 20; i++) s += v[i];
#pragma unroll
  for (int o = 16; o; o >>= 1) s += __shfl_xor_sync(~0u, s, o);
  const float mean = s * (1.f / D_);
  float qv = 0.f;
#pragma unroll
  for (int i = 0; i < 20; i++) { v[i] -= mean; qv += v[i] * v[i]; }
#pragma unroll
  for (int o = 16; o; o >>= 1) qv += __shfl_xor_sync(~0u, qv, o);
  const float rs = rsqrtf(qv * (1.f / D_) + 1e-5f);
#pragma unroll
  for (int i = 0; i < 20; i++) v[i] *= rs;
}

struct AParams { const bf16* x; uint32_t* ZT; const uint32_t* WT; bf16 *x1, *hN; uint32_t* sync; const uint32_t* rowdone; int n1, zero; };
constexpr int SY_1 = 0, SY_2 = 32, SY_3 = 64;
__device__ __forceinline__ void red_release(uint32_t* p) { asm volatile("red.release.gpu.global.add.u32 [%0], 1;" :: "l"(p) : "memory"); }
__device__ __forceinline__ void spin_count(const uint32_t* p, uint32_t n) {
  uint32_t v; int guard = 0;
  do { asm volatile("ld.relaxed.gpu.global.u32 %0, [%1];" : "=r"(v) : "l"(p) : "memory"); } while (v < n && ++guard < 400000);
}

constexpr int WP_RUN = 2592 + 32;
__device__ __forceinline__ void filter_prep(const bf16* wr, const bf16* wi, uint32_t* WT, uint32_t sm, uint32_t bar, int kg) {
  const int tid = threadIdx.x, lane = tid & 31, w = tid >> 5;
  auto row = [&](int j) { return 4 * ((kg >> 2) + 8 * ((j >> 1) & 1) + 16 * (8 * (j >> 2) + 2 * (kg & 3) + (j & 1))); };
  if (lane < 4 && w < 8) {
    const int j = 2 * w + (lane >> 1), o = row(j) * 642, o0 = o & ~15, n = ((o + 2568 + 15) & ~15) - o0;
    mbar_expect(bar, n);
    asm volatile("cp.async.bulk.shared::cluster.global.mbarrier::complete_tx::bytes [%0], [%1], %2, [%3];" :: "r"(sm + ((lane & 1) * 16 + (j & 3) * 4 + (j >> 2)) * WP_RUN), "l"((const char*)((lane & 1) ? wi : wr) + o0), "r"(n), "r"(bar) : "memory");
  }
  __syncwarp();
  const int u = lane & 3, r = w & 3;
  uint32_t src[4];
#pragma unroll
  for (int e = 0; e < 4; e++) src[e] = sm + (e * 4 + u) * WP_RUN + ((row(4 * u + e) * 642) & 15) + r * 642;
  mbar_wait(bar, 0);
#pragma unroll 2
  for (int f = (w >> 2) * 8 + (lane >> 2); f < 321; f += 24) {
    uint32_t v[4];
#pragma unroll
    for (int e = 0; e < 4; e++) {
      unsigned short lo, hi;
      asm volatile("ld.shared.u16 %0, [%1];" : "=h"(lo) : "r"(src[e] + f * 2)); asm volatile("ld.shared.u16 %0, [%1];" : "=h"(hi) : "r"(src[e] + f * 2 + 16 * WP_RUN));
      v[e] = lo | ((uint32_t)hi << 16);
    }
    stg128(WT + (size_t)f * 2048 + r * 512 + kg * 16 + u * 4, v[0], v[1], v[2], v[3]);
  }
}

__device__ __forceinline__ void a_phase2(const AParams& a, float* buf, int f TLP) {
  const int t0 = tid_here(), tid = t0 & 127, lane = tid & 31, w = tid >> 5, g = lane >> 2, q = lane & 3, barid = 5 + (t0 >> 7);
  const int f2 = (640 - f) % 640;
  uint32_t* ZT = a.ZT;
#define WGBAR() asm volatile("bar.sync %0, 128;" :: "r"(barid) : "memory")
  uint32_t fr[4], fi[4], nfi[4], br[4][4], bi[4][4];
  float tc[4][4], ts[4][4], wc[4], ws[4];
  ld_tab(wc, TB_2048 + tid); ld_tab(ws, TB_2048 + 128 + tid); ld_tab(fr, TB_F16 + lane); ld_tab(fi, TB_F16 + 32 + lane);
#pragma unroll
  for (int j = 0; j < 4; j++) { ld_tab(tc[j], TB_512 + j * 32 + lane); ld_tab(ts[j], TB_512 + 128 + j * 32 + lane); }
  asm volatile("prefetch.global.L1 [%0];" :: "l"((const uint4*)g_tab + TB_F32 + lane * 8));
  if (tid == 0) { spin_count(a.sync + SY_1, a.n1); TL_MIN(tlid - 3, 1); TL_MAX(tlid - 3, 3); }
  WGBAR();
  uint4 wt[4];
#pragma unroll
  for (int u = 0; u < 4; u++) wt[u] = __ldcg((const uint4*)(a.WT + (size_t)f * 2048 + w * 512 + lane * 16 + u * 4));
  const uint32_t sbuf = smem_u32(buf);
  {
    uint2 P[4], Q[4];
#pragma unroll
    for (int j = 0; j < 4; j++) { P[j] = __ldcg((const uint2*)(ZT + (size_t)f * 1024 + j * 256 + 2 * tid)); Q[j] = __ldcg((const uint2*)(ZT + (size_t)f2 * 1024 + j * 256 + 2 * tid)); }
    float ur[4][4], ui[4][4];
#pragma unroll
    for (int i = 0; i < 4; i++) {
      float ar[4], ai[4];
#pragma unroll
      for (int j = 0; j < 4; j++) {
        const uint32_t p = (i >> 1) ? P[j].y : P[j].x, z = (i >> 1) ? Q[j].y : Q[j].x;
        if (!(i & 1)) { ar[j] = bf_lo(p) + bf_lo(z); ai[j] = bf_hi(p) - bf_hi(z); }
        else { ar[j] = bf_hi(p) + bf_hi(z); ai[j] = bf_lo(z) - bf_lo(p); }
      }
      const float s0r = ar[0] + ar[2], s0i = ai[0] + ai[2], d0r = ar[0] - ar[2], d0i = ai[0] - ai[2];
      const float s1r = ar[1] + ar[3], s1i = ai[1] + ai[3], d1r = ar[1] - ar[3], d1i = ai[1] - ai[3];
      ur[0][i] = s0r + s1r; ui[0][i] = s0i + s1i;
      const float vr[3] = {d0r + d1i, s0r - s1r, d0r - d1i}, vi[3] = {d0i - d1r, s0i - s1i, d0i + d1r};
      const float c2 = wc[i] * wc[i] - ws[i] * ws[i], s2 = 2.f * wc[i] * ws[i];
      const float twc[4] = {1.f, wc[i], c2, c2 * wc[i] - s2 * ws[i]}, tws[4] = {0.f, ws[i], s2, s2 * wc[i] + c2 * ws[i]};
#pragma unroll
      for (int r = 1; r < 4; r++) { const float c = twc[r], s = tws[r]; ur[r][i] = vr[r - 1] * c + vi[r - 1] * s; ui[r][i] = vi[r - 1] * c - vr[r - 1] * s; }
    }
    const uint32_t o = sbuf + (tid >> 3) * 80 + (tid & 7) * 8;
#pragma unroll
    for (int r = 0; r < 4; r++) {
      asm volatile("st.shared.v2.b32 [%0], {%1,%2};" :: "r"(o + r * 5120), "r"(pack_bf16(ur[r][0], ur[r][1])), "r"(pack_bf16(ur[r][2], ur[r][3])) : "memory");
      asm volatile("st.shared.v2.b32 [%0], {%1,%2};" :: "r"(o + r * 5120 + 1280), "r"(pack_bf16(ui[r][0], ui[r][1])), "r"(pack_bf16(ui[r][2], ui[r][3])) : "memory");
    }
  }
#pragma unroll
  for (int j = 0; j < 4; j++) { ld_tab(br[j], TB_F32 + j * 32 + lane); ld_tab(bi[j], TB_F32 + 128 + j * 32 + lane); }
  WGBAR();
  if (tid == 0) TL_MAX(tlid - 3, 5);
  {
    uint32_t A1[4][4], A2[4][4];
#pragma unroll
    for (int i = 0; i < 4; i++) nfi[i] = fi[i] ^ 0x80008000u;
    const uint32_t la = sbuf + w * 5120 + (lane >> 4) * 1280 + (lane & 15) * 80;
#pragma unroll
    for (int j = 0; j < 4; j++) {
      uint32_t r0, r1, i0, i1; ldsm4t(r0, r1, i0, i1, la + j * 16);
      float yr[4], yi[4];
      mmaZ(yr, fr, r0, r1); mmaZ(yi, fi, r0, r1); mmaA(yr, nfi, i0, i1); mmaA(yi, fr, i0, i1);
      float zr[4], zi[4];
#pragma unroll
      for (int e = 0; e < 4; e++) { zr[e] = yr[e] * tc[j][e] + yi[e] * ts[j][e]; zi[e] = yi[e] * tc[j][e] - yr[e] * ts[j][e]; }
      A1[j][0] = pack_bf16(zr[0], zr[1]); A1[j][1] = pack_bf16(zr[2], zr[3]); A1[j][2] = pack_bf16(zi[0], zi[1]); A1[j][3] = pack_bf16(zi[2], zi[3]);
      A2[j][0] = A1[j][2]; A2[j][1] = A1[j][3]; A2[j][2] = A1[j][0] ^ 0x80008000u; A2[j][3] = A1[j][1] ^ 0x80008000u;
    }
    float xr[4][4], xi[4][4];
#pragma unroll
    for (int t = 0; t < 4; t++)
#pragma unroll
      for (int u = 0; u < 4; u++) {
        if (t == 0) { mmaZ(xr[u], A1[t], br[t][u], bi[t][u]); mmaZ(xi[u], A2[t], br[t][u], bi[t][u]); } else { mmaA(xr[u], A1[t], br[t][u], bi[t][u]); mmaA(xi[u], A2[t], br[t][u], bi[t][u]); }
      }
#pragma unroll
    for (int u = 0; u < 4; u++) {
      const uint32_t wv[4] = {wt[u].x, wt[u].y, wt[u].z, wt[u].w};
      float zr[4], zi[4];
#pragma unroll
      for (int e = 0; e < 4; e++) { const float c = bf_lo(wv[e]), b = bf_hi(wv[e]); zr[e] = xr[u][e] * c - xi[u][e] * b; zi[e] = xr[u][e] * b + xi[u][e] * c; }
      A2[u][2] = pack_bf16(zr[0], zr[1]); A2[u][3] = pack_bf16(zr[2], zr[3]); A2[u][0] = pack_bf16(zi[0], zi[1]); A2[u][1] = pack_bf16(zi[2], zi[3]);
      A1[u][0] = A2[u][2]; A1[u][1] = A2[u][3]; A1[u][2] = A2[u][0] ^ 0x80008000u; A1[u][3] = A2[u][1] ^ 0x80008000u;
    }
#pragma unroll
    for (int t = 0; t < 4; t++)
#pragma unroll
      for (int u = 0; u < 4; u++) {
        if (t == 0) { mmaZ(xr[u], A1[t], br[t][u], bi[t][u]); mmaZ(xi[u], A2[t], br[t][u], bi[t][u]); } else { mmaA(xr[u], A1[t], br[t][u], bi[t][u]); mmaA(xi[u], A2[t], br[t][u], bi[t][u]); }
      }
    __syncwarp();
    float* pl = buf + w * 1280;
    const float nrm = 0.5f / (2048.f * 640.f);
#pragma unroll
    for (int j = 0; j < 4; j++) {
      float zr[4], zi[4];
#pragma unroll
      for (int e = 0; e < 4; e++) { zr[e] = xr[j][e] * tc[j][e] - xi[j][e] * ts[j][e]; zi[e] = xi[j][e] * tc[j][e] + xr[j][e] * ts[j][e]; }
      const uint32_t r0 = movm(pack_bf16(zr[0], zr[1])), r1 = movm(pack_bf16(zr[2], zr[3])), i0 = movm(pack_bf16(zi[0], zi[1])), i1 = movm(pack_bf16(zi[2], zi[3]));
      float yr[4], yi[4];
      mmaZ(yr, fr, r0, r1); mmaZ(yi, nfi, r0, r1); mmaA(yr, fi, i0, i1); mmaA(yi, fr, i0, i1);
      *(float2*)(pl + g * 40 + 8 * j + 2 * q) = make_float2(yr[0] * nrm, yr[1] * nrm); *(float2*)(pl + (g + 8) * 40 + 8 * j + 2 * q) = make_float2(yr[2] * nrm, yr[3] * nrm);
      *(float2*)(pl + 640 + g * 40 + 8 * j + 2 * q) = make_float2(yi[0] * nrm, yi[1] * nrm); *(float2*)(pl + 640 + (g + 8) * 40 + 8 * j + 2 * q) = make_float2(yi[2] * nrm, yi[3] * nrm);
    }
  }
  ld_tab(wc, TB_2048 + tid); ld_tab(ws, TB_2048 + 128 + tid);
  WGBAR();
  if (tid == 0) TL_MAX(tlid - 3, 6);
  {
    float4 Ur[4], Ui[4];
#pragma unroll
    for (int r = 0; r < 4; r++) { Ur[r] = *(const float4*)(buf + r * 1280 + (tid >> 3) * 40 + (tid & 7) * 4); Ui[r] = *(const float4*)(buf + r * 1280 + 640 + (tid >> 3) * 40 + (tid & 7) * 4); }
    float yr[4][4], yi[4][4];
#pragma unroll
    for (int i = 0; i < 4; i++) {
      float ar[4], ai[4];
      const float c2 = wc[i] * wc[i] - ws[i] * ws[i], s2 = 2.f * wc[i] * ws[i];
      const float twc[4] = {1.f, wc[i], c2, c2 * wc[i] - s2 * ws[i]}, tws[4] = {0.f, ws[i], s2, s2 * wc[i] + c2 * ws[i]};
#pragma unroll
      for (int r = 0; r < 4; r++) {
        const float a = i == 0 ? Ur[r].x : i == 1 ? Ur[r].y : i == 2 ? Ur[r].z : Ur[r].w, b = i == 0 ? Ui[r].x : i == 1 ? Ui[r].y : i == 2 ? Ui[r].z : Ui[r].w;
        if (r == 0) { ar[r] = a; ai[r] = b; } else { const float c = twc[r], s = tws[r]; ar[r] = a * c - b * s; ai[r] = b * c + a * s; }
      }
      const float s0r = ar[0] + ar[2], s0i = ai[0] + ai[2], d0r = ar[0] - ar[2], d0i = ai[0] - ai[2];
      const float s1r = ar[1] + ar[3], s1i = ai[1] + ai[3], d1r = ar[1] - ar[3], d1i = ai[1] - ai[3];
      yr[0][i] = s0r + s1r; yi[0][i] = s0i + s1i; yr[2][i] = s0r - s1r; yi[2][i] = s0i - s1i;
      yr[1][i] = d0r - d1i; yi[1][i] = d0i + d1r; yr[3][i] = d0r + d1i; yi[3][i] = d0i - d1r;
    }
    const float im = (f == f2) ? 0.f : 1.f;
#pragma unroll
    for (int j = 0; j < 4; j++) {
      *(uint2*)(ZT + (size_t)f * 1024 + j * 256 + 2 * tid) = make_uint2(pack_bf16(yr[j][0] - im * yi[j][1], yr[j][1] + im * yi[j][0]), pack_bf16(yr[j][2] - im * yi[j][3], yr[j][3] + im * yi[j][2]));
      if (f != f2) *(uint2*)(ZT + (size_t)f2 * 1024 + j * 256 + 2 * tid) = make_uint2(pack_bf16(yr[j][0] + yi[j][1], yr[j][1] - yi[j][0]), pack_bf16(yr[j][2] + yi[j][3], yr[j][3] - yi[j][2]));
    }
  }
  if (tid == 0) TL_MAX(tlid - 3, 2);
}

constexpr int KA_TR_STRIDE = 804;
template <typename F0, typename F1> __device__ __forceinline__ void a_layer(const AParams& a, char* scratch, int v, F0 after_load, F1 after_phase2 TLP) {
  const int tid = threadIdx.x, lane = tid & 31, w = tid >> 5;
  uint32_t raw[2][10], fr[4], fi[4];
  float tc[5][4], ts[5][4];
  bool act = v < 86;
  int m = min(v * 12 + w, 1023);
  uint32_t* buf = (uint32_t*)(scratch + 6400) + (w & 3) * KA_TR_STRIDE + (w >> 2) * 3244;
  auto load_rows = [&]() {
    const int lane = tid_here() & 31;
#pragma unroll
    for (int i = 0; i < 10; i++) asm volatile("ld.global.cg.v2.u32 {%0,%1}, [%2];" : "=r"(raw[i / 5][2 * (i % 5)]), "=r"(raw[i / 5][2 * (i % 5) + 1]) : "l"(a.x + (size_t)(2 * m) * D_ + i * 128 + lane * 4) : "memory");
  };
  auto load_tabs = [&]() {
    uint32_t t[2][4];
    const int tid = tid_here(), lane = tid & 31;
    ld_tab(t[0], TB_F40 + (tid & 255)); ld_tab(t[1], TB_F40 + 144 + (tid & 255));
    ld_tab(fr, TB_F16 + lane); ld_tab(fi, TB_F16 + 32 + lane);
#pragma unroll
    for (int j = 0; j < 5; j++) { ld_tab(tc[j], TB_640 + j * 32 + lane); ld_tab(ts[j], TB_640 + 160 + j * 32 + lane); }
    sts128(smem_u32(scratch) + (tid & 255) * 16, t[0][0], t[0][1], t[0][2], t[0][3]); sts128(smem_u32(scratch) + 2304 + (tid & 255) * 16, t[1][0], t[1][1], t[1][2], t[1][3]);
  };
  if (act) {
    if (!a.rowdone) load_rows();
    load_tabs();
    if (a.rowdone) { spin_count(a.rowdone + (m >> 4) * 16, 32); load_rows(); }
  }
  __syncthreads();
  if (tid == 0) TL_MAX(tlid - 5, 3);
#pragma unroll 1
  for (int it = 0;; it++) {
    if (act) {
#pragma unroll
      for (int r = 0; r < 2; r++) {
        float x[20];
#pragma unroll
        for (int i = 0; i < 10; i++) { x[2 * i] = bf_lo(raw[r][i]); x[2 * i + 1] = bf_hi(raw[r][i]); }
        ln_row(x);
#pragma unroll
        for (int i = 0; i < 10; i++) raw[r][i] = pack_bf16(x[2 * i], x[2 * i + 1]);
      }
    }
    if (it) break;
    if (!a.rowdone) after_load();
    if (act) {
#pragma unroll
      for (int i = 0; i < 10; i++) *(uint2*)(buf + i * 64 + lane * 2) = make_uint2(raw[i / 5][2 * (i % 5)], raw[i / 5][2 * (i % 5) + 1]);
      __syncwarp();
    }
    if (tid == 0) TL_MAX(tlid - 5, 5);
#pragma unroll 1
    for (int ph = 0;; ph++) {
      if (act) {
        float xr[5][4], xi[5][4];
        const int lane = tid_here() & 31, g = lane >> 2, q = lane & 3;
        fft640(smem_u32(buf), smem_u32(scratch), lane, fr, fi, tc, ts, xr, xi, a.zero);
        __syncwarp();
#pragma unroll
        for (int u = 0; u < 5; u++)
#pragma unroll
          for (int e = 0; e < 4; e++) { const int f = g + 8 * (e >> 1) + 16 * (8 * u + 2 * q + (e & 1)); buf[f + 8 * (f >> 5)] = pack_bf16(xr[u][e], xi[u][e]); }
        __syncwarp();
      }
      if (ph) break;
      __syncthreads();
      if (tid == 0) TL_MAX(tlid - 5, 6);
      const int t1 = tid_here(), f0 = t1 / 3, part = t1 % 3;
      if (v * 12 + part * 4 < 1024) {
        const uint32_t* src = (const uint32_t*)(scratch + 6400) + part * 3244 + f0 + 8 * (f0 >> 5);
        uint32_t ov[5][4];
#pragma unroll
        for (int i = 0; i < 5; i++)
#pragma unroll
          for (int k = 0; k < 4; k++) ov[i][k] = src[k * KA_TR_STRIDE + i * 160];
#pragma unroll
        for (int i = 0; i < 5; i++) stg128(a.ZT + (size_t)(i * 128 + f0) * 1024 + v * 12 + part * 4, ov[i][0], ov[i][1], ov[i][2], ov[i][3]);
      }
      if (tid == 0) TL_MAX(tlid - 5, 7);
      __syncthreads();
      if (tid == 32 && v < a.n1) { red_release(a.sync + SY_1); TL_MAX(tlid - 5, 2); }
      if (a.rowdone) { if (w < 2) spin_count(a.rowdone + 63 * 16, 32); after_load(); }
      const int f = (w >> 2) * 131 + 130 - v;
      if (f < 321) a_phase2(a, (float*)(scratch + (w >> 2) * 20480), f TLA(tlid));
      asm volatile("fence.proxy.async.shared::cta;" ::: "memory");
      __syncthreads();
      if (tid == 32) red_release(a.sync + SY_2);
      after_phase2();
      if (w >= 8 || v >= 128) return;
      act = true; m = v * 8 + w;
      scratch += 32768; buf = (uint32_t*)(scratch + 6400);
      {
        load_rows(); load_tabs();
        if (tid == 0) { spin_count(a.sync + SY_2, 131); TL_MIN(tlid - 2, 1); TL_MAX(tlid - 2, 3); }
        bar_sync<5, 256>();
        uint4 za[3], zb[3];
        const int tid = tid_here();
#pragma unroll
        for (int i = 0; i < 3; i++) if (i < 2 || tid < 128) {
          const uint32_t* s = a.ZT + (size_t)(i * 256 + (tid & ~1)) * 1024 + v * 8 + (tid & 1) * 4;
          za[i] = __ldcg((const uint4*)s); zb[i] = __ldcg((const uint4*)(s + 1024));
        }
        sched_fence();
#pragma unroll
        for (int i = 0; i < 3; i++) if (i < 2 || tid < 128) {
          const uint4 c = za[i], b = zb[i];
          uint32_t* d = buf + (tid & 1) * 4 * KA_TR_STRIDE + i * 128 + (tid >> 1);
          d[320] = __byte_perm(c.x, b.x, 0x5410); d[0] = __byte_perm(c.x, b.x, 0x7632); d += KA_TR_STRIDE;
          d[320] = __byte_perm(c.y, b.y, 0x5410); d[0] = __byte_perm(c.y, b.y, 0x7632); d += KA_TR_STRIDE;
          d[320] = __byte_perm(c.z, b.z, 0x5410); d[0] = __byte_perm(c.z, b.z, 0x7632); d += KA_TR_STRIDE;
          d[320] = __byte_perm(c.w, b.w, 0x5410); d[0] = __byte_perm(c.w, b.w, 0x7632);
        }
        bar_sync<5, 256>();
        if (tid == 0) TL_MAX(tlid - 2, 5);
      }
      buf += w * KA_TR_STRIDE;
    }
    {
      if (tid == 0) TL_MAX(tlid - 2, 6);
      const int lane = tid_here() & 31;
#pragma unroll
      for (int i = 0; i < 5; i++) {
        const uint4 y = *(const uint4*)(buf + i * 160 + lane * 4 + 8 * (lane >> 3));
        raw[0][2 * i] = hadd2(raw[0][2 * i], __byte_perm(y.x, y.y, 0x7632)); raw[0][2 * i + 1] = hadd2(raw[0][2 * i + 1], __byte_perm(y.z, y.w, 0x7632));
        raw[1][2 * i] = hadd2(raw[1][2 * i], __byte_perm(y.x, y.y, 0x5410)); raw[1][2 * i + 1] = hadd2(raw[1][2 * i + 1], __byte_perm(y.z, y.w, 0x5410));
      }
#pragma unroll
      for (int i = 0; i < 10; i++) *(uint2*)(a.x1 + (size_t)(2 * m) * D_ + i * 128 + lane * 4) = make_uint2(raw[i / 5][2 * (i % 5)], raw[i / 5][2 * (i % 5) + 1]);
    }
  }
  {
#pragma unroll
    for (int i = 0; i < 10; i++) *(uint2*)(a.hN + (size_t)(2 * m) * D_ + i * 128 + lane * 4) = make_uint2(raw[i / 5][2 * (i % 5)], raw[i / 5][2 * (i % 5) + 1]);
    if (tid == 0) TL_MAX(tlid - 2, 7);
    bar_sync<5, 256>();
    if (tid == 0) { red_release(a.sync + SY_3); TL_MAX(tlid - 2, 2); }
  }
}

__device__ __forceinline__ void tma2d(uint32_t dst, const CUtensorMap* tm, int c0, int c1, uint32_t bar) {
  asm volatile("cp.async.bulk.tensor.2d.shared::cluster.global.mbarrier::complete_tx::bytes [%0], [%1, {%3, %4}], [%2];" :: "r"(dst), "l"(tm), "r"(bar), "r"(c0), "r"(c1) : "memory");
}
__device__ __forceinline__ void bulk_g2s(uint32_t dst, const void* src, int bytes, uint32_t bar) {
  asm volatile("cp.async.bulk.shared::cluster.global.mbarrier::complete_tx::bytes [%0], [%1], %2, [%3];" :: "r"(dst), "l"(src), "r"(bytes), "r"(bar) : "memory");
}
__device__ __forceinline__ uint64_t desc128(uint32_t a) { return (uint64_t)((a & 0x3FFFF) >> 4) | (1ull << 16) | (64ull << 32) | (1ull << 62); }
#define WG_FENCE() asm volatile("wgmma.fence.sync.aligned;" ::: "memory")
#define WG_COMMIT() asm volatile("wgmma.commit_group.sync.aligned;" ::: "memory")
#define WG_WAIT(n) asm volatile("wgmma.wait_group.sync.aligned " #n ";" ::: "memory")
__device__ __forceinline__ void wg_rs_n64(float* d, const uint32_t* a, uint64_t db, int acc) {
  asm volatile("{.reg .pred p; setp.ne.b32 p, %37, 0;\n"
    "wgmma.mma_async.sync.aligned.m64n64k16.f32.bf16.bf16 {%0,%1,%2,%3,%4,%5,%6,%7,%8,%9,%10,%11,%12,%13,%14,%15,%16,%17,%18,%19,%20,%21,%22,%23,%24,%25,%26,%27,%28,%29,%30,%31}, {%32,%33,%34,%35}, %36, p, 1, 1, 0;}"
    : "+f"(d[0]), "+f"(d[1]), "+f"(d[2]), "+f"(d[3]), "+f"(d[4]), "+f"(d[5]), "+f"(d[6]), "+f"(d[7]), "+f"(d[8]), "+f"(d[9]), "+f"(d[10]), "+f"(d[11]), "+f"(d[12]), "+f"(d[13]), "+f"(d[14]), "+f"(d[15]),
      "+f"(d[16]), "+f"(d[17]), "+f"(d[18]), "+f"(d[19]), "+f"(d[20]), "+f"(d[21]), "+f"(d[22]), "+f"(d[23]), "+f"(d[24]), "+f"(d[25]), "+f"(d[26]), "+f"(d[27]), "+f"(d[28]), "+f"(d[29]), "+f"(d[30]), "+f"(d[31])
    : "r"(a[0]), "r"(a[1]), "r"(a[2]), "r"(a[3]), "l"(db), "r"(acc));
}
__device__ __forceinline__ void wg_rs_n32(float* d, const uint32_t* a, uint64_t db, int acc) {
  asm volatile("{.reg .pred p; setp.ne.b32 p, %21, 0;\n"
    "wgmma.mma_async.sync.aligned.m64n32k16.f32.bf16.bf16 {%0,%1,%2,%3,%4,%5,%6,%7,%8,%9,%10,%11,%12,%13,%14,%15}, {%16,%17,%18,%19}, %20, p, 1, 1, 0;}"
    : "+f"(d[0]), "+f"(d[1]), "+f"(d[2]), "+f"(d[3]), "+f"(d[4]), "+f"(d[5]), "+f"(d[6]), "+f"(d[7]), "+f"(d[8]), "+f"(d[9]), "+f"(d[10]), "+f"(d[11]), "+f"(d[12]), "+f"(d[13]), "+f"(d[14]), "+f"(d[15])
    : "r"(a[0]), "r"(a[1]), "r"(a[2]), "r"(a[3]), "l"(db), "r"(acc));
}
__device__ __forceinline__ void wg_ss_n40_tt(float* d, uint64_t da, uint64_t db, int acc) {
  asm volatile("{.reg .pred p; setp.ne.b32 p, %22, 0;\n"
    "wgmma.mma_async.sync.aligned.m64n40k16.f32.bf16.bf16 {%0,%1,%2,%3,%4,%5,%6,%7,%8,%9,%10,%11,%12,%13,%14,%15,%16,%17,%18,%19}, %20, %21, p, 1, 1, 1, 1;}"
    : "+f"(d[0]), "+f"(d[1]), "+f"(d[2]), "+f"(d[3]), "+f"(d[4]), "+f"(d[5]), "+f"(d[6]), "+f"(d[7]), "+f"(d[8]), "+f"(d[9]), "+f"(d[10]), "+f"(d[11]), "+f"(d[12]), "+f"(d[13]), "+f"(d[14]), "+f"(d[15]),
      "+f"(d[16]), "+f"(d[17]), "+f"(d[18]), "+f"(d[19])
    : "l"(da), "l"(db), "r"(acc));
}
__device__ __forceinline__ void wg_ss_n32_ta(float* d, uint64_t da, uint64_t db, int acc) {
  asm volatile("{.reg .pred p; setp.ne.b32 p, %18, 0;\n"
    "wgmma.mma_async.sync.aligned.m64n32k16.f32.bf16.bf16 {%0,%1,%2,%3,%4,%5,%6,%7,%8,%9,%10,%11,%12,%13,%14,%15}, %16, %17, p, 1, 1, 1, 0;}"
    : "+f"(d[0]), "+f"(d[1]), "+f"(d[2]), "+f"(d[3]), "+f"(d[4]), "+f"(d[5]), "+f"(d[6]), "+f"(d[7]), "+f"(d[8]), "+f"(d[9]), "+f"(d[10]), "+f"(d[11]), "+f"(d[12]), "+f"(d[13]), "+f"(d[14]), "+f"(d[15])
    : "l"(da), "l"(db), "r"(acc));
}
__device__ __forceinline__ uint64_t desc_ns(uint32_t a, uint32_t lbo, uint32_t sbo) { return (uint64_t)((a & 0x3FFFF) >> 4) | ((uint64_t)(lbo >> 4) << 16) | ((uint64_t)(sbo >> 4) << 32); }
__device__ __forceinline__ void wait_count(const uint32_t* p, uint32_t n) {
  uint32_t v; int guard = 0;
  while (true) { asm volatile("ld.relaxed.gpu.global.u32 %0, [%1];" : "=r"(v) : "l"(p) : "memory"); if (v >= n || ++guard > 200000) break; __nanosleep(40); }
}

constexpr int SD_WS = 0, SD_REC = 16384, SD_O = SD_REC + 2 * 30720, SD_OI = SD_O + 2 * 8192, SD_OUT = SD_OI + 2 * 40960, SD_FIN = SD_OUT + 8192, SD_BAR = SD_FIN + 10240;
constexpr int SD_SMEM = SD_BAR + 256 + 1024;
#define QRING 4
constexpr int ORING = 4, PRING = 2 * ORING;
constexpr int FL_MEM = 162 * 1024, FL_RDY = 163 * 1024;
struct SideParams { CUtensorMap tmWo, tmP; const char* QKV; char *O, *part; const bf16* x1; bf16* out; uint32_t *comm, *sync; int first, dbgf; };
#define DBGF(m) false
#define ELECT "{.reg .pred p; elect.sync _|p, 0xffffffff;\n"
#define ATS(i)
__global__ void __launch_bounds__(512, 1) side_kernel(const __grid_constant__ SideParams p TLP) {
  extern __shared__ __align__(1024) char smem_raw[];
  const uint32_t sb = (smem_u32(smem_raw) + 1023) & ~1023u, wfull = sb + SD_BAR, rland = wfull + 8, ofull = wfull + 16, ofree = wfull + 32,
    ifull = wfull + 48, ifree = wfull + 64, rfull = wfull + 80, rfree = wfull + 96, fdone = wfull + 112, ffull = wfull + 128;
  const int tid = threadIdx.x, lane = tid & 31, w = tid >> 5, h = blockIdx.x;
  const int cb = h % 5, ks = h / 5, h0 = ks < 4 ? 5 * ks : 4 + 4 * ks, nh = ks < 4 ? 5 : 4;
  const int nseg = DBGF(16) ? 0 : NSEG;
  if (tid == 0) { TL_MIN(tlid, 0); TL_MAX(tlid, 4); }
  if (!DBGF(16)) pdl_launch();
  if (tid == 0) {
    mbar_init(wfull, 1); mbar_init(rland, 1); mbar_init(ffull, 1);
    for (int i = 0; i < 2; i++) { mbar_init(ofull + i * 8, 2); mbar_init(ofree + i * 8, 1); mbar_init(ifull + i * 8, 1); mbar_init(ifree + i * 8, 8); mbar_init(rfull + i * 8, 1); mbar_init(rfree + i * 8, 4); }
    sts128(fdone, 0, 0, 0, 0);
    asm volatile("fence.proxy.async.shared::cta;" ::: "memory");
    mbar_expect(wfull, nh * 32768);
#pragma unroll 1
    for (int b = 0; b < 4 * nh; b++) tma2d(sb + ((b + 2) % 20) * 8192, &p.tmWo, cb * 128 + (b & 1) * 64, h0 * 128 + (b >> 1) * 64, wfull);
    spin_count(p.sync + SY_2, 131);
  }
  __syncthreads();
  if (w < 8) {
    asm volatile("setmaxnreg.inc.sync.aligned.u32 192;");
    const int c = __shfl_sync(~0u, w >> 2, 0), mg = w & 3;
    const uint32_t boxoff = (((lane >> 4) << 3) + (lane & 7)) * 128 + (((2 * mg + ((lane >> 3) & 1)) ^ (lane & 7)) << 4);
    uint32_t A[36][4];
    mbar_wait(wfull, 0);
#pragma unroll
    for (int f = 0; f < 36; f++) ldsm4t(A[f][0], A[f][1], A[f][2], A[f][3], sb + 16384 + c * 8192 + boxoff + (f >> 2) * 16384 + (f & 3) * 2048);
    asm volatile("fence.proxy.async.shared::cta;" ::: "memory");
    bar_sync<1, 320>();
    if (tid == 0) TL_MAX(tlid, 3);
    const uint32_t oa = sb + SD_OUT + c * 4096 + boxoff;
#pragma unroll 1
    for (int s = 0; s < nseg; s++) {
      const int b = s & 1;
      const uint64_t db = desc128(sb + SD_OI + b * 40960), da = desc128(sb + SD_WS + c * 8192);
      float acc[16];
      mbar_wait_long(ifull + b * 8, (s >> 1) & 1);
      ATS(0)
      WG_FENCE();
#pragma unroll
      for (int k = 0; k < 32; k++) wg_rs_n32(acc, A[k], db + (k >> 2) * 256 + (k & 3) * 2, k);
      if (nh == 5) {
#pragma unroll
        for (int k = 32; k < 36; k++) wg_rs_n32(acc, A[k], db + 2048 + (k & 3) * 2, 1);
#pragma unroll
        for (int k = 0; k < 4; k++) wg_ss_n32_ta(acc, da + k * 128, db + 2304 + k * 2, 1);
      }
      WG_COMMIT();
      bar_sync<2, 256>();
      WG_WAIT(0);
      ATS(1)
      if (lane == 0) mbar_arrive(ifree + b * 8);
#pragma unroll
      for (int u = 0; u < 2; u++)
        asm volatile("stmatrix.sync.aligned.m8n8.x4.trans.shared.b16 [%0], {%1,%2,%3,%4};" :: "r"(oa + u * 2048),
          "r"(pack_bf16(acc[8 * u], acc[8 * u + 1])), "r"(pack_bf16(acc[8 * u + 2], acc[8 * u + 3])), "r"(pack_bf16(acc[8 * u + 4], acc[8 * u + 5])), "r"(pack_bf16(acc[8 * u + 6], acc[8 * u + 7])) : "memory");
      asm volatile("fence.proxy.async.shared::cta;" ::: "memory");
      if (w > 0) bar_arrive<4, 256>();
      else {
        bar_sync<4, 256>();
        asm volatile(ELECT "@p cp.async.bulk.tensor.3d.global.shared::cta.bulk_group [%0, {%2, %3, %4}], [%1];\n"
          "cp.async.bulk.commit_group;\ncp.async.bulk.wait_group 0;\n@p fence.proxy.async.global;\n@p red.release.gpu.global.add.u32 [%5], 1;}"
          :: "l"(&p.tmP), "r"(sb + SD_OUT), "r"(0), "r"((s % PRING) * 32), "r"(ks * 10 + cb * 2), "l"(p.comm + FL_RDY + s * 16 + 8) : "memory");
        ATS(2)
      }
    }
    if (tid == 0) TL_MAX(tlid, 6);
  } else if (w < 12) {
    asm volatile("setmaxnreg.dec.sync.aligned.u32 72;");
    const int a = __shfl_sync(~0u, w - 8, 0), g = lane >> 2, q = lane & 3;
    const float sc2 = 0.08838834764831845f * 1.4426950408889634f;
#pragma unroll 1
    for (int s = 0; s < (h < 32 ? nseg : 0); s++) {
      const int b = s & 1;
      const uint32_t rec = sb + SD_REC + b * 30720;
      mbar_wait_long(rfull + b * 8, (s >> 1) & 1);
      ATS(1)
      if (s == 0 && tid == 256) TL_MIN(tlid, 1);
      uint32_t P[3][4]; float inv[2];
      {
        float sc[20];
        const uint64_t dq = desc_ns(rec + 1024, 128, 1024), dk = desc_ns(rec + 5120, 128, 1024);
        WG_FENCE();
#pragma unroll
        for (int k = 0; k < 8; k++) wg_ss_n40_tt(sc, dq + (k >> 2) * 640 + (k & 3) * 16, dk + (k >> 2) * 640 + (k & 3) * 16, k);
        WG_COMMIT(); WG_WAIT(0);
        ATS(2)
#pragma unroll
        for (int rh = 0; rh < 2; rh++) {
          const int row = 16 * a + 8 * rh + g;
          float v[5][2], mx = -3.0e38f;
#pragma unroll
          for (int n = 0; n < 5; n++)
#pragma unroll
            for (int e = 0; e < 2; e++) {
              const bool ok = n == 0 || (8 * (n - 1) + 2 * q + e) <= row;
              v[n][e] = ok ? sc[4 * n + 2 * rh + e] * sc2 : -1.0e9f * 1.4426950408889634f; mx = fmaxf(mx, v[n][e]);
            }
          mx = fmaxf(mx, __shfl_xor_sync(~0u, mx, 1)); mx = fmaxf(mx, __shfl_xor_sync(~0u, mx, 2));
          float sum = 0.f;
#pragma unroll
          for (int n = 0; n < 5; n++) { const float e0 = ex2(v[n][0] - mx), e1 = ex2(v[n][1] - mx); sum += e0 + e1; P[n >> 1][(n & 1) * 2 + rh] = pack_bf16(e0, e1); }
          P[2][2 + rh] = 0u;
          sum += __shfl_xor_sync(~0u, sum, 1); sum += __shfl_xor_sync(~0u, sum, 2);
          asm("rcp.approx.ftz.f32 %0, %1;" : "=f"(inv[rh]) : "f"(sum));
        }
      }
      ATS(3)
      mbar_wait_long(ofree + b * 8, ((s >> 1) & 1) ^ 1);
      ATS(4)
      const uint32_t od = sb + SD_O + b * 8192 + (16 * a + (lane & 15)) * 128;
#pragma unroll
      for (int hf = 0; hf < 2; hf++) {
        float o[32];
        const uint64_t dv = desc_ns(rec + 20480 + hf * 5120, 1024, 128);
        WG_FENCE();
        wg_rs_n64(o, P[0], dv, 0); wg_rs_n64(o, P[1], dv + 128, 1); wg_rs_n64(o, P[2], desc_ns(rec + 20480 + hf * 5120 + 4096, 0, 128), 1);
        WG_COMMIT(); WG_WAIT(0);
        if (a < 2) {
#pragma unroll
          for (int n = 0; n < 8; n += 2) {
            const float* x = o + 4 * n;
            asm volatile("stmatrix.sync.aligned.m8n8.x4.shared.b16 [%0], {%1,%2,%3,%4};" :: "r"(od + hf * 4096 + (((n + (lane >> 4)) ^ (lane & 7)) << 4)),
              "r"(pack_bf16(x[0] * inv[0], x[1] * inv[0])), "r"(pack_bf16(x[2] * inv[1], x[3] * inv[1])), "r"(pack_bf16(x[4] * inv[0], x[5] * inv[0])), "r"(pack_bf16(x[6] * inv[1], x[7] * inv[1])) : "memory");
          }
        }
      }
      if (a < 2) {
        asm volatile("fence.proxy.async.shared::cta;" ::: "memory");
        __syncwarp();
        if (lane == 0) mbar_arrive(ofull + b * 8);
      }
      if (lane == 0) mbar_arrive(rfree + b * 8);
      ATS(5)
    }
    if (tid == 256) TL_MAX(tlid, 5);
  } else {
    asm volatile("setmaxnreg.dec.sync.aligned.u32 56;");
    if (w == 13) {
      bar_sync<1, 320>();
#pragma unroll 1
      for (int s = 0; s < nseg; s++) {
        mbar_wait_long(ifree + (s & 1) * 8, ((s >> 1) & 1) ^ 1);
        wait_count(p.comm + FL_RDY + s * 16 + ks, nh);
        ATS(0)
        asm volatile(ELECT "@p mbarrier.arrive.expect_tx.shared.b64 _, [%2], %3;\n@p cp.async.bulk.shared::cluster.global.mbarrier::complete_tx::bytes [%0], [%1], %3, [%2];}"
          :: "r"(sb + SD_OI + (s & 1) * 40960), "l"(p.O + (size_t)((s % ORING) * 32 + h0) * 8192), "r"(ifull + (s & 1) * 8), "r"(nh * 8192) : "memory");
      }
    } else if (h >= 32) {
      if (w == 15) bar_sync<1, 320>();
    } else if (w == 12) {
#pragma unroll 1
      for (int s = 0; s < nseg; s++) {
        mbar_wait_long(ofull + (s & 1) * 8, (s >> 1) & 1);
        int fin, guard = 0;
        do { asm volatile("ld.volatile.shared.b32 %0, [%1];" : "=r"(fin) : "r"(fdone) : "memory"); } while (fin + ORING <= s && ++guard < 1000000);
        ATS(0)
        asm volatile(ELECT "@p cp.async.bulk.global.shared::cta.bulk_group [%0], [%1], 8192;\n"
          "cp.async.bulk.commit_group;\ncp.async.bulk.wait_group 0;\n@p mbarrier.arrive.shared.b64 _, [%3];\n@p fence.proxy.async.global;\n@p red.release.gpu.global.add.u32 [%2], 1;}"
          :: "l"(p.O + (size_t)((s % ORING) * 32 + h) * 8192), "r"(sb + SD_O + (s & 1) * 8192), "l"(p.comm + FL_RDY + s * 16 + (h < 20 ? h / 5 : (h - 4) >> 2)), "r"(ofree + (s & 1) * 8) : "memory");
        ATS(1)
      }
      if (lane == 0) TL_MAX(tlid, 7);
    } else if (w == 14) {
      if (DBGF(16)) pdl_wait(); else
      mbar_wait_long(ofull, 0);
#pragma unroll 1
      for (int s = 0; s < nseg; s++) {
        asm volatile("fence.proxy.async.shared::cta;" ::: "memory");
        __syncwarp();
        asm volatile(ELECT "@p mbarrier.arrive.expect_tx.shared.b64 _, [%2], 10240;\n@p cp.async.bulk.shared::cluster.global.mbarrier::complete_tx::bytes [%0], [%1], 1280, [%2];}"
          :: "r"(sb + SD_FIN + 8960), "l"(p.x1 + (size_t)(s * 32 + h) * D_), "r"(ffull) : "memory");
        wait_count(p.comm + FL_RDY + s * 16 + 8, 35);
        ATS(0)
        asm volatile(ELECT "@p cp.async.bulk.shared::cluster.global.mbarrier::complete_tx::bytes [%0], [%1], 8960, [%2];}"
          :: "r"(sb + SD_FIN), "l"(p.part + (size_t)((s % PRING) * 32 + h) * 8960), "r"(ffull) : "memory");
        mbar_wait_long(ffull, s & 1);
        ATS(1)
        asm volatile("st.volatile.shared.b32 [%0], %1;" :: "r"(fdone), "r"(s + 1) : "memory");
#pragma unroll
        for (int i = 0; i < 5; i++) {
          uint32_t v[8][2];
#pragma unroll
          for (int u = 0; u < 8; u++) asm volatile("ld.shared.v2.b32 {%0,%1}, [%2];" : "=r"(v[u][0]), "=r"(v[u][1]) : "r"(sb + SD_FIN + u * 1280 + i * 256 + lane * 8) : "memory");
          uint32_t y[2];
#pragma unroll
          for (int k = 0; k < 2; k++) {
            y[k] = pack_bf16(((bf_lo(v[0][k]) + bf_lo(v[1][k])) + (bf_lo(v[2][k]) + bf_lo(v[3][k]))) + ((bf_lo(v[4][k]) + bf_lo(v[5][k])) + bf_lo(v[6][k])),
                             ((bf_hi(v[0][k]) + bf_hi(v[1][k])) + (bf_hi(v[2][k]) + bf_hi(v[3][k]))) + ((bf_hi(v[4][k]) + bf_hi(v[5][k])) + bf_hi(v[6][k])));
            asm("add.rn.bf16x2 %0, %0, %1;" : "+r"(y[k]) : "r"(v[7][k]));
          }
          *(uint2*)(p.out + (size_t)(s * 32 + h) * D_ + i * 128 + lane * 4) = make_uint2(y[0], y[1]);
        }
        __syncwarp();
        if (lane == 0 && p.first) red_release(p.comm + FL_RDY + s * 16 + 12);
        ATS(2)
      }
    } else {
      uint32_t lp = 0, known = 0;
      bar_sync<1, 320>();
#pragma unroll 1
      for (int s = 0; s < nseg; s++) {
        const int b = s & 1;
        const uint32_t rec = sb + SD_REC + b * 30720;
        mbar_wait_long(rfree + b * 8, ((s >> 1) & 1) ^ 1);
        for (int tries = 0; tries < 2000; tries++) {
          int guard = 0;
          while (known <= (uint32_t)s && ++guard < 100000) {
            uint32_t f = ~0u;
            if (lane < 3) asm volatile("ld.relaxed.gpu.global.u32 %0, [%1];" : "=r"(f) : "l"(p.comm + FL_MEM + h * 32 + lane * 8) : "memory");
            known = __reduce_min_sync(~0u, f);
          }
          ATS(0)
          if (lane == 0) {
            asm volatile("fence.proxy.async.shared::cta;" ::: "memory");
            mbar_expect(rland, 30720);
            bulk_g2s(rec, p.QKV + (size_t)((s % QRING) * 32 + h) * 30720, 30720, rland);
          }
          __syncwarp();
          mbar_wait_long(rland, lp); lp ^= 1;
          uint32_t mx = 0;
#pragma unroll
          for (int k = 0; k < 4; k++) { uint32_t v; asm volatile("ld.shared.b32 %0, [%1];" : "=r"(v) : "r"(rec + (k == 0 ? 5120 : 10240 + k * 5120) + lane * 32 + (lane >> 2) * 4) : "memory"); mx = max(mx, v); }
          if (__all_sync(~0u, mx != ~0u)) break;
        }
        if (lane == 0) { mbar_arrive(rfull + b * 8); asm volatile("st.relaxed.gpu.global.u32 [%0], %1;" :: "l"(p.comm + FL_MEM + h * 32 + 24), "r"(s + 1) : "memory"); }
      }
    }
    if (lane == 0) TL_MAX(tlid, 2);
    if (!p.first && tid == 448 && h == 0) { for (int i = 0; i < 6; i++) p.sync[i * 32 - 96] = 0; }
  }
}

__device__ __forceinline__ uint32_t ld_relaxed(const void* p) { uint32_t v; asm volatile("ld.relaxed.gpu.global.u32 %0, [%1];" : "=r"(v) : "l"(p) : "memory"); return v; }
__device__ __forceinline__ void st_relaxed(void* p, uint32_t v) { asm volatile("st.relaxed.gpu.global.u32 [%0], %1;" :: "l"(p), "r"(v) : "memory"); }
__device__ __forceinline__ void st_relaxed_if(void* p, uint32_t v, uint32_t c) { asm volatile("{.reg .pred p; setp.ne.u32 p, %2, 0; @p st.relaxed.gpu.global.u32 [%0], %1;}" :: "l"(p), "r"(v), "r"(c) : "memory"); }
__device__ __forceinline__ uint32_t clk32() { uint32_t c; asm volatile("mov.u32 %0, %%clock;" : "=r"(c) :: "memory"); return c; }
__device__ __forceinline__ uint32_t gt32() { uint64_t c; asm volatile("mov.u64 %0, %%globaltimer;" : "=l"(c) :: "memory"); return (uint32_t)c; }
__device__ __forceinline__ void wait_gt(uint32_t T) {
  asm volatile("{\n.reg .pred p;\n.reg .u64 t;\n.reg .u32 lo, hi;\nLG%=:\nmov.u64 t, %%globaltimer;\nmov.b64 {lo, hi}, t;\nsub.u32 lo, lo, %0;\nsetp.lt.s32 p, lo, 0;\n@p bra.uni LG%=;\n}" :: "r"(T) : "memory");
}
template <int LUT> __device__ __forceinline__ uint32_t lop3(uint32_t a, uint32_t b, uint32_t c) { uint32_t r; asm("lop3.b32 %0, %1, %2, %3, %4;" : "=r"(r) : "r"(a), "r"(b), "r"(c), "n"(LUT)); return r; }
__device__ __forceinline__ void mma_h(float* d, uint32_t a0, uint32_t a2, uint32_t b0, uint32_t b1) {
  asm volatile("{.reg .b32 u0, u1; mma.sync.aligned.m16n8k16.row.col.f32.bf16.bf16.f32 {%0,%1,%2,%3}, {%4,u0,%5,u1}, {%6,%7}, {%0,%1,%2,%3};}"
    : "+f"(d[0]), "+f"(d[1]), "+f"(d[2]), "+f"(d[3]) : "r"(a0), "r"(a2), "r"(b0), "r"(b1));
}
__device__ __forceinline__ void mma_hz(float* d, uint32_t a0, uint32_t a2, uint32_t b0, uint32_t b1) {
  asm volatile("{.reg .b32 u0, u1; mma.sync.aligned.m16n8k16.row.col.f32.bf16.bf16.f32 {%0,%1,%2,%3}, {%4,u0,%5,u1}, {%6,%7}, {%8,%8,%8,%8};}"
    : "=f"(d[0]), "=f"(d[1]), "=f"(d[2]), "=f"(d[3]) : "r"(a0), "r"(a2), "r"(b0), "r"(b1), "f"(0.f));
}
__device__ __forceinline__ void mma8_h(float* d, uint32_t a0, uint32_t b0) {
  asm volatile("{.reg .b32 u0; mma.sync.aligned.m16n8k8.row.col.f32.bf16.bf16.f32 {%0,%1,%2,%3}, {%4,u0}, {%5}, {%0,%1,%2,%3};}"
    : "+f"(d[0]), "+f"(d[1]), "+f"(d[2]), "+f"(d[3]) : "r"(a0), "r"(b0));
}
__device__ __forceinline__ uint32_t ldsm1t(uint32_t a) { uint32_t r; asm volatile("ldmatrix.sync.aligned.m8n8.x1.trans.shared.b16 {%0}, [%1];" : "=r"(r) : "r"(a) : "memory"); return r; }
__device__ __forceinline__ uint32_t hmax2(uint32_t a, uint32_t b) { uint32_t r; asm("max.bf16x2 %0, %1, %2;" : "=r"(r) : "r"(a), "r"(b)); return r; }
__device__ __forceinline__ uint32_t lds32(uint32_t a) { uint32_t v; asm volatile("ld.shared.b32 %0, [%1];" : "=r"(v) : "r"(a) : "memory"); return v; }
__device__ __forceinline__ void sts32(uint32_t a, uint32_t v) { asm volatile("st.shared.b32 [%0], %1;" :: "r"(a), "r"(v) : "memory"); }
__device__ __forceinline__ uint32_t mapa(uint32_t a, int rank) { uint32_t r; asm("mapa.shared::cluster.u32 %0, %1, %2;" : "=r"(r) : "r"(a), "r"(rank)); return r; }
template <int OFF> __device__ __forceinline__ void stas32(uint32_t a, uint32_t v, uint32_t bar) {
  asm volatile("st.async.weak.shared::cluster.mbarrier::complete_tx::bytes.b32 [%0+%3], %1, [%2];" :: "r"(a), "r"(v), "r"(bar), "n"(OFF) : "memory");
}
#define OPAQUE(x) x = __shfl_sync(~0u, x, lane)
#define CLUSTER_SYNC() asm volatile("barrier.cluster.arrive.release.aligned; barrier.cluster.wait.acquire.aligned;" ::: "memory")

constexpr int SM_BAR = 0;
constexpr int SM_WO = 2048;
constexpr int SM_VR = 43008;
constexpr int SM_RED = 59392;
constexpr int SM_AT = 67584;
constexpr int SM_MEMT = 108544;
constexpr int SM_QK = 118784;
constexpr int SM_SC = 122880;
constexpr int SM_OX = 124928;
constexpr int SM_VM = 127488;
constexpr int SM_ST = 139264;
constexpr int SM_X = 149504;
constexpr int SM_WST = 2048;
constexpr int SM_WS = 67584;
constexpr int REC_SMEM = 231424 + 1024;
constexpr int MB_A = 0, MB_QK = 24, MB_V = 56, MB_KV = 64, MB_X = 80, MB_IA = 96, MB_IC = 104, MB_TK = 112, MB_PRB = 120, MB_DP = 128, MB_TAB = 256, MB_T2 = 512;
#define NTQ 10
#define NTV 5
#define NB0 4
#define PINK 14
#define NB1 8
#define PINT 5
#define GATEK 6
#define TOLQ 96
#define TOLV 160
constexpr int POLL_LIMIT = 20000;
constexpr int CM_X3 = 160, CM_MISC = 172;
__device__ __forceinline__ uint32_t x3_slot(int slot) { return (CM_X3 + (slot & 1) * 64 + (slot & 2) * 128) * 4096; }
__device__ __forceinline__ int near_page(int pg, int side) { return pg + ((__popc(pg & 0xB3) ^ side) & 1); }
__device__ __forceinline__ int mem_line(int jb) { const int ks = jb >> 1, c = ks >= 20, kk = ks - 20 * c; return (kk >> 2) * 16 + c * 8 + (kk & 3) * 2 + (jb & 1); }

struct RecParams {
  CUtensorMap tmW[3], tmWo, tmX;
  AParams a;
  const bf16 *mem0, *Wo, *wr, *wi;
  char* QKV;
  uint32_t* comm;
  int period, c3, slack, xlate, gap, zero, helper, dbgf;
  uint32_t *dbg, *log;
};
#define PRB(k)
#define LDW(d, a) ldsm4t(d[0], d[1], d[2], d[3], a)

#define PRBASE (mbar + w * 16)
#define PRIMM 1024
#define PROFF 0
template <bool VR>
__device__ __forceinline__ void rec_gemm_warps(const RecParams& p, const uint32_t sb, const int h, const int r TLP) {
  const int tid = threadIdx.x, lane = tid & 31, w = __shfl_sync(~0u, tid >> 5, 0);
  const int mg = w & 3, c = w >> 2;
  constexpr int NT = VR ? NTV : NTQ, NW = VR ? 8 : 16;
  uint32_t R[20][4], P[20][4], Wr[NW - NT][4];
  const uint32_t mbar = sb + SM_BAR;
  uint32_t l16 = lane * 16, lm = (lane >> 4) * 1024 + (lane & 15) * 16;
  OPAQUE(l16); OPAQUE(lm);
#define wl16 (l16 + (sb + w * 512))
  {
    const uint32_t boxoff = (((lane >> 4) << 3) + (lane & 7)) * 128 + (((2 * mg + ((lane >> 3) & 1)) ^ (lane & 7)) << 4);
    mbar_wait(mbar + MB_IA, 0);
    if (tid == 0) TL_MAX(tlid, 5);
    const uint32_t wa = sb + SM_WS + c * 40960 + boxoff;
#pragma unroll
    for (int k = 0; k < 20; k++) LDW(R[k], wa + 81920 + k * 2048);
    bar_arrive<4, 288>();
#pragma unroll
    for (int k = 0; k < 20; k++) LDW(P[k], wa + k * 2048);
    bar_sync<2, 256>();
#pragma unroll
    for (int i = 0; i < NT; i++) sts128(wl16 + SM_AT + i * 4096, P[i][0], P[i][1], P[i][2], P[i][3]);
    mbar_wait(mbar + MB_IC, 0);
    if (tid == 0) TL_MAX(tlid, 6);
    const uint32_t woa = sb + SM_WST + c * 16384 + boxoff;
#pragma unroll
    for (int i = 0; i < NW; i++) {
      const uint32_t a = woa + (VR ? i * 2048 : (i & 1) * 32768 + (i >> 1) * 2048);
      if (i >= 4 && i < 4 + NW - NT) LDW(Wr[i - 4], a); else LDW(P[i < 4 ? i : i - (NW - NT)], a);
    }
    asm volatile("fence.proxy.async.shared::cta;" ::: "memory");
    bar_sync<1, 384>();
#pragma unroll
    for (int i = 0; i < NT; i++) sts128(wl16 + SM_WO + i * 4096, P[i][0], P[i][1], P[i][2], P[i][3]);
    asm volatile("barrier.cluster.arrive.relaxed.aligned; barrier.cluster.wait.aligned;" ::: "memory");
  }
#define LDT(i) lds128(P[i], wl16 + SM_AT + (i) * 4096)
  auto stream = [&](int n) {
    float ta[16], tb[16];
    const uint32_t dR = (((sb + SM_X + c * 20480) >> 4) | 0x10000) + (n & 1) * 2560, dP = dR + (~n & p.zero);
#define WGX(acc, A, ks, sc) wg_rs_n32(acc, A[ks], (uint64_t)(d##A + ((ks) >> 2) * 256 + ((ks) & 3) * 2) | (0x40000040ull << 32), sc)
    WG_FENCE();
    constexpr int NE = NT - 4;
#pragma unroll
    for (int k = 0; k < 20; k++) { WGX(ta, R, k, k); if ((k & 1) && k / 2 < NE) LDT(k / 2); }
    WG_COMMIT();
    constexpr int K2 = VR ? NT + 2 : 16;
#pragma unroll
    for (int k = K2; k < 20; k++) {
      if (VR && k == K2 + GATEK) asm volatile("bar.sync 12, %0;" :: "r"((h & 1) ? 320 : 352) : "memory");
      WGX(tb, P, k, k - K2);
    }
    WG_COMMIT();
    WG_WAIT(1);
#pragma unroll
    for (int i = 0; i < 2; i++)
      sts128(l16 + (sb + (w ^ 4) * 512) + SM_RED + i * 4096, pack_bf16(ta[8 * i], ta[8 * i + 1]), pack_bf16(ta[8 * i + 2], ta[8 * i + 3]), pack_bf16(ta[8 * i + 4], ta[8 * i + 5]), pack_bf16(ta[8 * i + 6], ta[8 * i + 7]));
#pragma unroll
    for (int i = NE; i < NT; i++) LDT(i);
#pragma unroll
    for (int k = NT; k < K2; k++) WGX(tb, P, k, 1);
    WG_FENCE();
#pragma unroll
    for (int k = 0; k < NE; k++) WGX(tb, P, k, 1);
    bar_sync<11, 384>();
    uint32_t o[2][4];
    lds128(o[0], wl16 + SM_RED); lds128(o[1], wl16 + SM_RED + 4096);
    WG_FENCE();
#pragma unroll
    for (int k = NE; k < NT; k++) WGX(tb, P, k, 1);
    WG_COMMIT();
    WG_WAIT(0);
#pragma unroll
    for (int i = 0; i < 2; i++)
      asm volatile("stmatrix.sync.aligned.m8n8.x4.shared.b16 [%0], {%1,%2,%3,%4};" :: "r"(lm + (sb + (c ^ 1) * 5120 + mg * 256) + SM_ST + 1024 + i * 2048),
        "r"(hadd2(pack_bf16(tb[8 * i], tb[8 * i + 1]), o[i][0])), "r"(hadd2(pack_bf16(tb[8 * i + 2], tb[8 * i + 3]), o[i][1])),
        "r"(hadd2(pack_bf16(tb[8 * i + 4], tb[8 * i + 5]), o[i][2])), "r"(hadd2(pack_bf16(tb[8 * i + 6], tb[8 * i + 7]), o[i][3])) : "memory");
    bar_arrive<14, 320>();
  };
  int s = -2, att = 0;
#pragma unroll 1
  while (true) {
    if (s >= 0) {
    uint32_t B[10][4], Wf[NT][4], dp[4];
    float ap[2][4], ar[2][4];
#define LDO(i, base) lds128(Wf[i], (base) + SM_WO + (i) * 4096)
#define LDB(k2) ldsm4t(B[k2][0], B[k2][1], B[k2][2], B[k2][3], l16 + (sb + c * 1024) + SM_MEMT + ((k2) >> 1) * 2048 + ((k2) & 1) * 512)
#define BK(k) B[(k) >> 1][((k) & 1) * 2], B[(k) >> 1][((k) & 1) * 2 + 1]
    mbar_wait(mbar + MB_A, att & 1);
    PRB(0)
    LDB(0); LDB(1);
#pragma unroll
    for (int k = 0; k < 20; k++) {
      if (!(k & 1) && k < 16) LDB(k / 2 + 2);
      if (k == PINK) {
        const uint32_t wb = lop3<0xF8>(l16, __float_as_uint(ap[0][0]), p.zero) + (sb + w * 512);
#pragma unroll
        for (int u = 0; u < NB0 && u < NT; u++) LDO(u, wb);
      }
      if (k < 2) { mmaZ(ap[k], P[k], BK(k)); mmaZ(ar[k], R[k], BK(k)); } else { mmaA(ap[k & 1], P[k], BK(k)); mmaA(ar[k & 1], R[k], BK(k)); }
    }
    asm volatile("stmatrix.sync.aligned.m8n8.x4.shared.b16 [%0], {%1,%2,%3,%4};" :: "r"(lm + (sb + c * 2048 + mg * 256) + SM_QK),
      "r"(pack_bf16(ar[0][0] + ar[1][0], ar[0][1] + ar[1][1])), "r"(pack_bf16(ar[0][2] + ar[1][2], ar[0][3] + ar[1][3])),
      "r"(pack_bf16(ap[0][0] + ap[1][0], ap[0][1] + ap[1][1])), "r"(pack_bf16(ap[0][2] + ap[1][2], ap[0][3] + ap[1][3])) : "memory");
    bar_arrive<9, 384>();
    PRB(1)
    att++;
    uint32_t bad;
    asm volatile("{.reg .pred p; setp.ne.u32 p, 0, 0; bar.red.or.pred p, 8, 384, p; selp.u32 %0, 1, 0, p;}" : "=r"(bad) :: "memory");
    if (bad) {
#pragma unroll
      for (int i = 0; i < NT; i++) LDT(i);
      continue;
    }
    if (s == NSEG - 1) break;
    lds128(dp, mbar + MB_DP + w * 16);
#pragma unroll
    for (int i = NB0; i < NT && (VR || i < NB1); i++) LDO(i, wl16);
    uint32_t fmask = (~(l16 | dp[0]) >> 4) & 1, bit = ((s >> 1) & 1) ? 0u : fmask;
    char* cb = (char*)p.comm + ((s & 1) * (256 * 4096) + (l16 >> 2));
    char *d0 = cb + dp[0], *d1 = cb + dp[1], *d2 = cb + dp[2], *d3 = cb + dp[3];
    if (VR) asm volatile("" : "+l"(d0), "+l"(d1), "+r"(bit), "+r"(fmask)); else asm volatile("" : "+l"(d0), "+l"(d1), "+l"(d2), "+l"(d3), "+r"(bit), "+r"(fmask));
    sched_fence();
    if (!VR) {
      bar_sync<2, 384>();
#pragma unroll
      for (int i = NB1; i < NT; i++) LDO(i, wl16);
    }
    bar_sync<3, 384>();
    PRB(2)
    uint32_t ob[4][4];
    float z0, z1;
#pragma unroll
    for (int i = 0; i < 4; i++) LDW(ob[i], l16 + sb + SM_OX + i * 512);
    asm volatile("ld.shared.v2.f32 {%0,%1}, [%2];" : "=f"(z0), "=f"(z1) : "r"(l16 + sb + SM_OX + 2048) : "memory");
#define WO(i) ((i) >= 4 && (i) < 4 + NW - NT ? Wr[(i) >= 4 && (i) < 4 + NW - NT ? (i) - 4 : 0] : Wf[(i) < 4 ? (i) : (i) < 4 + NW - NT ? 0 : (i) - (NW - NT)])
    float ga[4][4];
#pragma unroll
    for (int i = 0; i < NW; i++) {
      const int ks = VR ? i : i >> 1;
      if (i < 4) mmaZ(ga[i], WO(i), ob[ks >> 1][(ks & 1) * 2], ob[ks >> 1][(ks & 1) * 2 + 1]); else mmaA(ga[i & 3], WO(i), ob[ks >> 1][(ks & 1) * 2], ob[ks >> 1][(ks & 1) * 2 + 1]);
    }
    asm("rcp.approx.ftz.f32 %0, %0;" : "+f"(z0)); asm("rcp.approx.ftz.f32 %0, %0;" : "+f"(z1));
#pragma unroll
    for (int i = 0; i < 4; i++) { ga[0][i] += ga[2][i]; ga[1][i] += ga[3][i]; if (VR) ga[0][i] += ga[1][i]; }
#pragma unroll
    for (int t = 0; t < NW / 8; t++) {
      st_relaxed(t ? d2 : d0, lop3<0xF4>(bit, pack_bf16(ga[t][0] * z0, ga[t][1] * z1), fmask));
      st_relaxed(t ? d3 : d1, lop3<0xF4>(bit, pack_bf16(ga[t][2] * z0, ga[t][3] * z1), fmask));
    }
    PRB(3)
    } else mbar_wait(mbar + MB_X + (s & 1) * 8, 0);
    bar_sync<10, 256>();
    stream(s);
    PRB(4)
    s++;
  }
  CLUSTER_SYNC();
#undef wl16
}

#undef PRBASE
#undef PRIMM
#undef PROFF
#define PRBASE (mbar + j * 16)
#define PRIMM (1024 + 4)
#define PROFF 8
__device__ __forceinline__ void x_load(const RecParams& p, const uint32_t sb, int n) {
  if (DBGF(32)) { if ((threadIdx.x & 31) == 0) mbar_arrive(sb + SM_BAR + MB_X + (n & 1) * 8); return; }
  asm volatile(ELECT "@p mbarrier.arrive.expect_tx.shared.b64 _, [%2], 40960;\n"
    "@p cp.async.bulk.tensor.3d.shared::cluster.global.mbarrier::complete_tx::bytes [%0], [%1, {%3, %4, %3}], [%2];}"
      :: "r"(sb + SM_X + (n & 1) * 40960), "l"(&p.tmX), "r"(sb + SM_BAR + MB_X + (n & 1) * 8), "r"(0), "r"(n * 32) : "memory");
}
__device__ __forceinline__ int rec_attn_setup(const RecParams& p, const uint32_t sb, const int h, const int r TLP) {
  const int lane = threadIdx.x & 31, ct = threadIdx.x - 256, j = __shfl_sync(~0u, ct >> 5, 0);
  const uint32_t mbar = sb + SM_BAR;
  uint32_t* misc = p.comm + CM_MISC * 1024;
  if (j >= 2 && lane == 0) {
    uint32_t best = ~0u; uint32_t* a = misc + (j & 1) * 1024 + 128 + blockIdx.x * 8;
#pragma unroll 1
    for (int it = 0; it < 5; it++) {
      const uint32_t t0 = clk32();
      uint32_t v; asm volatile("atom.relaxed.gpu.global.exch.b32 %0, [%1], %2;" : "=r"(v) : "l"(a), "r"(t0) : "memory");
      st_relaxed_if(a, 0, v == t0 + 1);
      best = min(best, clk32() - t0);
    }
    sts32(mbar + MB_PRB + (j & 1) * 4, best);
  }
  if (blockIdx.x == 0 && ct == 0) st_relaxed(misc + 96, gt32() & ~31u);
  bar_sync<15, 128>();
  const uint32_t b0 = lds32(mbar + MB_PRB), b1 = lds32(mbar + MB_PRB + 4);
  const int side = __shfl_sync(~0u, ((b1 < b0) ^ __popc(CM_MISC & 0xB3)) & 1, 0);
  if (r == 2 && lane == 0 && j + (h & 1) < 3) st_relaxed(misc + (j < 2 ? 2 * h + j : 64 + (h >> 1)), side);
  if (j < 2) {
    const int job = 2 * (16 * r + (lane >> 2) + ((lane & 2) && r < 2 ? 8 : 0)) + (lane & 1);
    uint32_t v; int guard = 0;
    do { v = ld_relaxed(misc + (j ? 96 : job)); } while (v == 0xFFFFFFFFu && ++guard < 1000000);
    sts32(mbar + (j ? MB_TK : MB_DP + lane * 4), j ? v : near_page(2 * job, v) * 4096 + h * 128);
    __syncwarp();
  }
  uint32_t m0[5][4];
#pragma unroll
  for (int i = 0; i < 20; i++) m0[i >> 2][i & 3] = *(const uint32_t*)(p.mem0 + (lane >> 2) * D_ + (j * 20 + i) * 8 + (lane & 3) * 2);
  if (j == 3) {
    spin_count(p.a.sync + SY_3, 128);
    bar_sync<4, 288>();
    asm volatile("fence.proxy.async;" ::: "memory");
    x_load(p, sb, 0); x_load(p, sb, 1);
    if (lane == 0) TL_MIN(tlid, 1);
  }
  bar_sync<1, 384>();
  asm volatile("barrier.cluster.arrive.relaxed.aligned;" ::: "memory");
#pragma unroll
  for (int i = 0; i < 5; i++)
    asm volatile("stmatrix.sync.aligned.m8n8.x4.trans.shared.b16 [%0], {%1,%2,%3,%4};" :: "r"(sb + SM_MEMT + mem_line(j * 20 + i * 4) * 128 + lane * 16), "r"(m0[i][0]), "r"(m0[i][1]), "r"(m0[i][2]), "r"(m0[i][3]) : "memory");
  sts128(sb + SM_ST + (ct >> 6) * 5120 + (ct & 63) * 16, ~0u, ~0u, ~0u, ~0u);
  asm volatile("barrier.cluster.wait.aligned;" ::: "memory");
  return side;
}
template <bool VR>
__device__ __forceinline__ void rec_attn_warps(const RecParams& p, const uint32_t sb, char* smem, const int h, const int r, const int side TLP) {
  const int lane = threadIdx.x & 31, g = lane >> 2, q = lane & 3;
  const int j = __shfl_sync(~0u, (int)(threadIdx.x >> 5) - 8, 0);
  const uint32_t mbar = sb + SM_BAR;
#define is_red (VR && j + (h & 1) < 3)
  const int mi = lane >> 3;
  uint32_t l16 = sb + lane * 16;
#define wr16 (l16 + j * 512)
#define L0 ((l16 & 511) == 0)
  uint32_t ka = j < 2 ? sb + SM_ST + 6144 + (2 * j + (mi & 1)) * 1024 + ((mi >> 1) * 8 + (lane & 7)) * 16 : sb + SM_QK + j * 512 + ((mi & 1) * 16 + (mi >> 1) * 8 + (lane & 7)) * 16;
  uint32_t va = sb + SM_VR + (j >> 1) * 4096 + (mi >> 1) * 1024 + ((j & 1) * 32 + (mi & 1) * 8 + (lane & 7)) * 16;
  uint32_t own = sb + SM_SC + (r & 1) * 1024 + (j < 2 ? j * 256 : 256 + j * 128) + lane * 4, ps[2], pb[2];
#pragma unroll
  for (int i = 0; i < 2; i++) {
    const int peer = VR ? i : i == 0 ? r ^ 1 : 2;
    ps[i] = mapa(VR ? wr16 + SM_VM : own, peer); pb[i] = mapa(mbar + (VR ? MB_V : MB_QK), peer);
    if (VR) ps[i] = mapa(sb, peer) - sb + SM_VM + j * 512; else { OPAQUE(ps[i]); OPAQUE(pb[i]); }
  }
  if (!VR) { OPAQUE(ka); OPAQUE(own); }
  OPAQUE(va); OPAQUE(l16);
  const char* comm = (const char*)p.comm;
  uint32_t s0 = (g >> 1) != q ? 0u : (g & 1) ? 0x3F800000u : 0x00003F80u, s1 = s0 | (p.zero & 0x40000000);
  uint32_t ones0 = 0x3F803F80u | (p.zero & 0x40000000), ones1 = 0x3F803F80u | (p.zero & 0x40);
  if (VR) { OPAQUE(s0); OPAQUE(s1); }
  OPAQUE(ones0); OPAQUE(ones1);
  const float sc2 = 0.08838834764831845f * 1.4426950408889634f;
  uint32_t kf[4][4], vf[4][4];
#pragma unroll
  for (int i = 0; i < 16; i++) kf[i >> 2][i & 3] = vf[i >> 2][i & 3] = p.zero;
  auto load_v = [&](int n) {
    if (n >= 0) mbar_wait(mbar + MB_KV + (n & 1) * 8, (n >> 1) & 1);
#pragma unroll
    for (int i = 0; i < 4; i++) ldsm4(vf[i][0], vf[i][1], vf[i][2], vf[i][3], va + (n & 1) * 8192 + (i >> 1) * 2048 + (i & 1) * 256);
  };
  auto v_load = [&](int n) {
    asm volatile("cp.async.bulk.wait_group 0;" ::: "memory");
    if (VR) asm volatile(ELECT
      "@p cp.async.bulk.shared::cluster.global.mbarrier::complete_tx::bytes.multicast::cluster [%0], [%1], 4096, [%2], %3;\n"
      "@p cp.async.bulk.shared::cluster.global.mbarrier::complete_tx::bytes.multicast::cluster [%0+4096], [%1+5120], 4096, [%2], %3;}"
        :: "r"(sb + SM_VR + (n & 1) * 8192), "l"(p.QKV + ((size_t)((n & (QRING - 1)) * 32 + h) * 3 + 2) * 10240 + 1024), "r"(mbar + MB_KV + (n & 1) * 8), "h"((unsigned short)7) : "memory");
  };
  auto t_store = [&](int n) {
    if (DBGF(64)) return;
    asm volatile("fence.proxy.async.shared::cta;" ::: "memory");
    asm volatile(ELECT "@p cp.async.bulk.global.shared::cta.bulk_group [%0], [%1], 10240;}" :: "l"(p.QKV + ((size_t)((n & (QRING - 1)) * 32 + h) * 3 + r) * 10240), "r"(sb + SM_ST) : "memory");
    asm volatile("cp.async.bulk.commit_group;" ::: "memory");
  };
  auto m_store = [&](int n) {
    if (VR || j < 2) {
      const int jj = VR ? j : j + 2;
      uint32_t a[4], b[4]; lds128(a, l16 + jj * 512 + SM_QK); lds128(b, l16 + (jj ^ 2) * 512 + SM_QK + 2048);
      asm volatile("st.relaxed.gpu.global.v4.u32 [%0], {%1,%2,%3,%4};" :: "l"(p.QKV + (uint32_t)(l16 + ((((n & (QRING - 1)) * 32 + h) * 3 + r) * 10240 + (jj >> 1) * 5120 + (j & 1) * 512 - sb))),
        "r"(hadd2(a[0], b[0])), "r"(hadd2(a[1], b[1])), "r"(hadd2(a[2], b[2])), "r"(hadd2(a[3], b[3])) : "memory");
    }
  };
  auto publish = [&](int n) {
    if (j == 1) st_relaxed(p.comm + FL_MEM + h * 32 + r * 8, n);
  };
  int att = 1;
  uint32_t T3 = lds32(mbar + MB_TK);
  const int jb = j < 2 ? 2 * h + j : 64 + (h >> 1), ln = mem_line(jb) + 16;
  const uint32_t inbox = near_page(2 * jb, side) * 4096, bline = (ln >> 5) * 16384 + (ln & 31) * 128;
#define VERDICT(bad) asm volatile("{.reg .pred p; setp.ne.u32 p, %0, 0; bar.red.or.pred p, 8, 384, p;}" :: "n"(bad) : "memory")
#pragma unroll 1
  for (int s = -2; s < NSEG - 1; s++) {
    const uint32_t par = s & 1;
    if (s >= 0) {
    uint32_t su[6], sw[6], vm[4];
#define LDSM2T(d, a) asm volatile("ldmatrix.sync.aligned.m8n8.x2.trans.shared.b16 {%0,%1}, [%2];" : "=r"(d[4]), "=r"(d[5]) : "r"(a) : "memory")
#define HADD4(a, b) { a[0] = hadd2(a[0], b[0]); a[1] = hadd2(a[1], b[1]); a[2] = hadd2(a[2], b[2]); a[3] = hadd2(a[3], b[3]); }
    bar_sync<9, 384>();
    PRB(0)
    if (!VR) {
      uint32_t qf[2][4], qg[2][4];
      float sa[4][4];
      if (j < 2) {
        LDW(qf[0], l16 + SM_QK); LDW(qg[0], l16 + SM_QK + 3072); LDW(qf[1], l16 + SM_QK + 512); LDW(qg[1], l16 + SM_QK + 3584);
        HADD4(qf[0], qg[0]); HADD4(qf[1], qg[1]);
#pragma unroll
        for (int i = 0; i < 4; i++) mmaZ(sa[i], kf[i], qf[i >> 1][(i & 1) * 2], qf[i >> 1][(i & 1) * 2 + 1]);
        const uint32_t t0 = pack_bf16((sa[0][0] + sa[1][0]) + (sa[2][0] + sa[3][0]), (sa[0][1] + sa[1][1]) + (sa[2][1] + sa[3][1]));
        const uint32_t t1 = pack_bf16((sa[0][2] + sa[1][2]) + (sa[2][2] + sa[3][2]), (sa[0][3] + sa[1][3]) + (sa[2][3] + sa[3][3]));
        stas32<0>(ps[0], t0, pb[0]); stas32<0>(ps[1], t0, pb[1]); stas32<128>(ps[0], t1, pb[0]); stas32<128>(ps[1], t1, pb[1]);
        sts32(own, t0); sts32(own + 128, t1);
      } else {
        LDW(qf[0], wr16 + SM_QK - 1024); LDW(qg[0], wr16 + SM_QK + 2048); LDW(qf[1], ka); LDW(qg[1], ka + 1024);
        HADD4(qf[0], qg[0]); HADD4(qf[1], qg[1]);
        mmaZ(sa[0], qf[1], qf[0][0], qf[0][1]); mmaZ(sa[1], qf[1], qf[0][2], qf[0][3]);
        const uint32_t t0 = pack_bf16(sa[0][0] + sa[1][2], sa[0][1] + sa[1][3]);
        stas32<0>(ps[0], t0, pb[0]); stas32<0>(ps[1], t0, pb[1]);
        sts32(own, t0);
      }
      PRB(1)
      VERDICT(0);
      LDW(su, l16 + SM_SC + r * 1024); LDSM2T(su, l16 + SM_SC + 512 + r * 1024);
      su[4] = hadd2(su[4], su[5]);
      mbar_wait(mbar + MB_QK, par);
      PRB(2)
      LDW(sw, l16 + SM_SC + 1024 - r * 1024); LDSM2T(sw, l16 + SM_SC + 1536 - r * 1024);
    } else {
      ldsm4(vm[0], vm[1], vm[2], vm[3], wr16 + SM_QK); ldsm4(su[0], su[1], su[2], su[3], l16 + (j ^ 2) * 512 + SM_QK + 2048);
      HADD4(vm, su);
#pragma unroll
      for (int i = 0; i < 2; i++)
        asm volatile("st.async.weak.shared::cluster.mbarrier::complete_tx::bytes.v4.b32 [%0], {%1,%2,%3,%4}, [%5];" :: "r"(ps[i] + l16), "r"(vm[0]), "r"(vm[1]), "r"(vm[2]), "r"(vm[3]), "r"(pb[i]) : "memory");
      PRB(1)
      VERDICT(0);
      char* mv = p.QKV + (uint32_t)((l16 >> 2) + ((((s & (QRING - 1)) * 32 + h) * 3 + 2) * 10240 + (j >> 1) * 5120 + (j & 1) * 512 - (sb >> 2)));
#pragma unroll
      for (int i = 0; i < 4; i++) st_relaxed(mv + i * 128, vm[i]);
      T3 = lds32(mbar + MB_TK);
      mbar_wait(mbar + MB_QK, par);
      PRB(2)
      LDW(su, l16 + SM_SC); LDW(sw, l16 + SM_SC + 1024); LDSM2T(su, l16 + SM_SC + 512); LDSM2T(sw, l16 + SM_SC + 1536);
      su[4] = hadd2(su[4], su[5]);
    }
    {
      HADD4(su, sw); su[4] = hadd2(su[4], hadd2(sw[4], sw[5]));
      uint32_t m = hmax2(hmax2(hmax2(su[0], su[1]), hmax2(su[2], su[3])), su[4]);
      const uint32_t m1 = __shfl_xor_sync(~0u, m, 1), m2 = __shfl_xor_sync(~0u, m, 2), m3 = __shfl_xor_sync(~0u, m, 3);
      float t[10];
#pragma unroll
      for (int i = 0; i < 5; i++) { t[2 * i] = bf_lo(su[i]) * sc2; t[2 * i + 1] = bf_hi(su[i]) * sc2; }
      if (!VR) {
        asm volatile("" : "+f"(t[0]), "+f"(t[1]), "+f"(t[2]), "+f"(t[3]), "+f"(t[4]), "+f"(t[5]), "+f"(t[6]), "+f"(t[7]), "+f"(t[8]), "+f"(t[9]));
        mbar_wait(mbar + MB_V, par); bar_arrive<2, 384>(); lds128(vm, wr16 + SM_VM);
      }
      if (!VR) t[PINT] = __uint_as_float(lop3<0xF8>(__float_as_uint(t[PINT]), vm[0], p.zero));
      m = hmax2(hmax2(m, m1), hmax2(m2, m3));
      const float mx = fmaxf(bf_lo(m), bf_hi(m));
#define EX(i) ex2(fmaf(mx, -sc2, t[i]))
      float o1[2][4], z[4];
      const uint32_t P0 = pack_bf16(EX(0), EX(1)), P1 = pack_bf16(EX(2), EX(3));
      mmaZ(o1[0], vf[0], P0, P1); mmaZ(o1[1], vf[1], P0, P1); mma_hz(z, ones0, ones1, P0, P1);
      const float e4 = EX(4), e5 = EX(5);
      const uint32_t P2 = pack_bf16(e4, e5), P3 = pack_bf16(EX(6), EX(7));
      mmaA(o1[0], vf[2], P2, P3); mmaA(o1[1], vf[3], P2, P3); mma_h(z, ones0, ones1, P2, P3);
      const uint32_t Pm = pack_bf16(EX(8), EX(9));
      mma1688(o1[0], vm[0], vm[1], Pm); mma1688(o1[1], vm[2], vm[3], Pm); mma8_h(z, ones0, Pm);
      asm volatile("stmatrix.sync.aligned.m8n8.x4.shared.b16 [%0], {%1,%2,%3,%4};" :: "r"(wr16 + SM_OX),
        "r"(pack_bf16(o1[0][0], o1[0][1])), "r"(pack_bf16(o1[0][2], o1[0][3])), "r"(pack_bf16(o1[1][0], o1[1][1])), "r"(pack_bf16(o1[1][2], o1[1][3])) : "memory");
      if (j == 3) asm volatile("st.shared.v2.f32 [%0], {%1,%2};" :: "r"(l16 + SM_OX + 2048), "f"(z[0]), "f"(z[1]) : "memory");
    }
    bar_arrive<3, 384>();
    PRB(3)
    {
      const uint32_t now = gt32(), lim = now + p.c3 + p.gap;
      T3 += p.period;
      if ((int)(T3 - now) > 20000) T3 = now;
      while ((int)(lim - T3) > 0) T3 += p.slack;
    }
    if (j == 3) {
      asm volatile(ELECT "@p mbarrier.arrive.expect_tx.shared.b64 _, [%0], %2;\n@p mbarrier.arrive.expect_tx.shared.b64 _, [%1], 8192;\n@p mbarrier.arrive.expect_tx.shared.b64 _, [%3], 10240;}"
        :: "r"(mbar + MB_QK), "r"(mbar + MB_KV + par * 8), "n"(VR ? 1536 : 768), "r"(mbar + MB_A) : "memory");
      if (!VR) asm volatile(ELECT "@p mbarrier.arrive.expect_tx.shared.b64 _, [%0], 2048;}" :: "r"(mbar + MB_V) : "memory");
    }
    if (!VR) m_store(s);
    }
    if (!VR) {
      if (j < 2) {
#pragma unroll
        for (int i = 0; i < 4; i++) LDW(kf[i], ka + i * 256);
      } else {
#pragma unroll
        for (int i = 0; i < 16; i++) kf[i >> 2][i & 3] = p.zero;
      }
    }
    int used = 0;
    if (j == 2 && s >= -1) { v_load(s + 1); used = ld_relaxed(p.comm + FL_MEM + h * 32 + 24); }
    bar_arrive<11, 384>();
    if (!VR) { PRB(4) }
#define NEXT_SLOT(T, TOL) { const uint32_t now = gt32(); while ((int)(now - T) > TOL) T += p.slack; }
    auto gather = [&]() {
      if (j == 3) {
        NEXT_SLOT(T3, (VR ? TOLV : TOLQ));
        wait_gt(T3);
        asm volatile("{.reg .pred p; elect.sync _|p, 0xffffffff;\n"
          "@p cp.async.bulk.shared::cluster.global.mbarrier::complete_tx::bytes [%0], [%2+2048], 2048, [%1];\n"
          "@p cp.async.bulk.shared::cluster.global.mbarrier::complete_tx::bytes [%0+2048], [%2+16384], 4096, [%1];\n"
          "@p cp.async.bulk.shared::cluster.global.mbarrier::complete_tx::bytes [%0+6144], [%2+32768], 4096, [%1];}"
          :: "r"(sb + SM_MEMT), "r"(mbar + MB_A), "l"(comm + (x3_slot(s + 1) + side * 4096)) : "memory");
      }
    };
    if (s < 0) { if (is_red) asm volatile("bar.arrive 12, %0;" :: "r"((h & 1) ? 320 : 352) : "memory"); }
    else {
    if (is_red) {
      const uint32_t expect = ((s >> 1) & 1) ^ 1, o_wr = (l16 & 255) / 2 + (l16 & 256) / 64;
      const uint32_t* src = (const uint32_t*)(comm + (inbox + par * (256 * 4096) + (l16 & 511) / 2));
      uint32_t* wfar = (uint32_t*)(comm + (x3_slot(s + 1) + bline + (side ^ 1) * 4096 + o_wr)); uint32_t* wnear = (uint32_t*)(comm + (x3_slot(s + 1) + bline + side * 4096 + o_wr));
      asm volatile("" : "+l"(src), "+l"(wfar), "+l"(wnear));
      auto attempt = [&](int nth) {
        uint32_t x[32], ok;
#pragma unroll
        for (int i = 0; i < 16; i++) asm volatile("ld.relaxed.gpu.global.v2.u32 {%0,%1}, [%2];" : "=r"(x[2 * i]), "=r"(x[2 * i + 1]) : "l"(src + i * 64) : "memory");
        float ra[4][4];
        uint32_t bad[2];
#pragma unroll
        for (int i = 0; i < 8; i++) {
          const uint32_t u = lop3<0x7E>(x[4 * i], x[4 * i + 2], expect);
          bad[i & 1] = i < 2 ? u : (bad[i & 1] | u);
          if (i < 4) mma16816z(ra[i], x[4 * i], x[4 * i + 1], x[4 * i + 2], x[4 * i + 3], s0, s1);
          else mma16816(ra[i & 3], x[4 * i], x[4 * i + 1], x[4 * i + 2], x[4 * i + 3], s0, s1);
        }
        asm volatile("{.reg .pred p; setp.eq.u32 p, %1, 0; vote.sync.all.pred p, p, 0xffffffff; selp.u32 %0, 1, 0, p;}" : "=r"(ok) : "r"((bad[0] | bad[1]) & 1));
        const float a0 = (ra[0][0] + ra[1][0]) + (ra[2][0] + ra[3][0]), a1 = (ra[0][1] + ra[1][1]) + (ra[2][1] + ra[3][1]);
        const float a2 = (ra[0][2] + ra[1][2]) + (ra[2][2] + ra[3][2]), a3 = (ra[0][3] + ra[1][3]) + (ra[2][3] + ra[3][3]);
        const bool up = l16 & 256;
        const float r0 = __shfl_xor_sync(~0u, up ? a0 : a2, 16), r1 = __shfl_xor_sync(~0u, up ? a1 : a3, 16);
        asm volatile("{.reg .pred p; setp.eq.u32 p, %1, 0; @p bar.arrive 12, %0;}" :: "r"((h & 1) ? 320 : 352), "r"(nth) : "memory");
        const uint32_t v = pack_bf16((up ? a2 : a0) + r0, (up ? a3 : a1) + r1);
        asm volatile("{.reg .pred p; setp.ne.u32 p, %3, 0; @p st.relaxed.gpu.global.u32 [%0], %2; @p st.relaxed.gpu.global.u32 [%1], %2; @p bar.arrive 15, %4;}"
          :: "l"(wfar), "l"(wnear), "r"(v), "r"(ok), "r"((h & 1) ? 96 : 128) : "memory");
        return ok;
      };
      uint32_t T2 = T3 - p.c3;
#pragma unroll 1
      for (int nth = 0;; nth++) {
        wait_gt(T2);
        PRB(4)
        if (attempt(nth)) break;
        if (nth == POLL_LIMIT) { asm volatile("bar.arrive 15, %0;" :: "r"((h & 1) ? 96 : 128) : "memory"); break; }
        T2 += p.slack; NEXT_SLOT(T2, TOLQ);
      }
      PRB(5)
      uint32_t* wpoi = (uint32_t*)(comm + (x3_slot(s + 3) + bline + (l16 & 511) / 4));
      st_relaxed(wpoi, 0xFFFFFFFFu); st_relaxed(wpoi + 1024, 0xFFFFFFFFu);
    }
    if (VR && j == 3) { asm volatile("bar.sync 15, %0;" :: "r"((h & 1) ? 96 : 128) : "memory"); sts32(mbar + MB_PRB, 0); }
    gather();
    PRB(6)
    }
    load_v(s + 1);
    if (j < 2) {
      if (s + 3 < NSEG) mbar_wait(mbar + MB_X + (par ^ 1) * 8, ((s + 3) >> 1) & 1);
    } else {
      bar_sync<14, 320>();
      if (j == 2) {
        for (int guard = 0; used + QRING < s + 3 && guard < POLL_LIMIT && !DBGF(16); guard++) used = ld_relaxed(p.comm + FL_MEM + h * 32 + 24);
        if (s + 2 < NSEG) t_store(s + 2);
      } else if (s + 4 < NSEG) { if (s >= 0) wait_gt(T3 + p.xlate); x_load(p, sb, s + 4); }
    }
    for (int guard = 0;; guard++) {
      uint32_t m = 0, ok;
      if (j < 2 && s >= 0) {
        mbar_wait(mbar + MB_A, att & 1);
#pragma unroll
        for (int i = 0; i < 5; i++) m = max(m, lds32(l16 + (l16 & 511) + (l16 & 448) / 16 + (j * 1024 + SM_MEMT + i * 2048)));
      }
      att++;
      asm volatile("{.reg .pred p; setp.ne.u32 p, %1, 0xffffffff; bar.red.and.pred p, 13, 128, p; selp.u32 %0, 1, 0, p;}" : "=r"(ok) : "r"(m) : "memory");
      if (ok || guard == POLL_LIMIT) break;
      bar_arrive<9, 384>();
      VERDICT(1);
      if (j == 3) asm volatile(ELECT "@p mbarrier.arrive.expect_tx.shared.b64 _, [%0], 10240;}" :: "r"(mbar + MB_A) : "memory");
      T3 += p.slack;
      gather();
    }
    PRB(7)
    if (VR && j == 3) sts32(mbar + MB_TK, T3);
    if (s >= 0) publish(s + 1);
    else if (j == 0 && L0) { if (s == -2) mbar_arrive(mbar + MB_A); else TL_MAX(tlid, 3); }
  }
  bar_sync<9, 384>();
  m_store(NSEG - 1);
  VERDICT(0);
  publish(NSEG);
  if (j == 0 && L0) TL_MAX(tlid, 2);
  CLUSTER_SYNC();
}

__global__ void __launch_bounds__(384, 1) rec_kernel(const __grid_constant__ RecParams p TLP) {
  extern __shared__ __align__(1024) char smem_raw[];
  const uint32_t sb = (smem_u32(smem_raw) + 1023) & ~1023u;
  char* smem = smem_raw + (sb - smem_u32(smem_raw));
  const int tid = threadIdx.x, w = tid >> 5;
  const int h = blockIdx.x / 3, r = blockIdx.x % 3;
  const uint32_t mbar = sb + SM_BAR;
  if (tid == 0) { TL_MIN(tlid - p.helper, 0); TL_MAX(tlid - p.helper, 4); }
  if (tid == 0) {
#pragma unroll 1
    for (int i = 0; i < 14; i++) mbar_init(mbar + i * 8, i == 1 ? 32 : 1);
    asm volatile("fence.mbarrier_init.release.cluster;" ::: "memory");
    asm volatile("fence.proxy.async.shared::cta;" ::: "memory");
    mbar_expect(mbar + MB_QK, r == 2 ? 1536 : 768); if (r < 2) mbar_expect(mbar + MB_V, 2048);
    mbar_expect(mbar + MB_KV, 8192); mbar_expect(mbar + MB_KV + 8, 8192);
  }
  pdl_launch();
  if (!p.helper) {
    if (p.wr && tid >= 32 && tid < 46) { const int i = blockIdx.x * 7 + (tid - 32 >> 1); if (i < 642) l2_prefetch(((tid & 1) ? p.wi : p.wr) + i * 1024, 2048); }
    if (tid == 64 && blockIdx.x < 12) l2_prefetch(g_tab + TB_F32 * 4 + blockIdx.x * 256, 1024);
#pragma unroll 1
    for (int o = blockIdx.x * 384 + tid; o < 384 * 256; o += 96 * 384) {
      const int i = o >> 8, u = i % 192, pg = (i / 192) * 256 + (u < 176 ? u : u + 48);
      const uint32_t v = (u >= 160 && (pg >> 1) != 81) ? ~0u : 0u;
      stg128((uint4*)p.comm + pg * 256 + (o & 255), v, v, v, v);
    }
  } else if (p.wr && blockIdx.x < 32) {
    __syncthreads();
    filter_prep(p.wr, p.wi, (uint32_t*)p.a.WT, sb + SM_WS, mbar + 8, blockIdx.x);
  }
  auto wo_load = [&](int i0) {
#pragma unroll 1
    for (int i = i0; i < i0 + 4; i++) tma2d(sb + SM_WST + i * 8192, &p.tmWo, r * 256 + (i >> 1) * 64, h * 128 + (i & 1) * 64, mbar + MB_IC);
  };
  a_layer(p.a, smem + SM_WST, blockIdx.x + p.helper * 96, [&]() {
      if (!p.helper) {
        if (tid == 0) {
          mbar_expect(mbar + MB_IA, 163840); mbar_expect(mbar + MB_IC, r == 2 ? 32768 : 65536);
#pragma unroll 1
          for (int i = 0; i < 4; i++)
            asm volatile("cp.async.bulk.tensor.3d.shared::cluster.global.mbarrier::complete_tx::bytes [%0], [%1, {%3, %4, %5}], [%2];"
              :: "r"(sb + SM_WS + ((i >> 1) + ((i ^ (i >> 1) ^ 1) & 1) * 2) * 40960), "l"(&p.tmW[r == 2 ? 2 : i & 1]), "r"(mbar + MB_IA), "r"(h * 128 + (r == 2 ? i & 1 : r) * 64), "r"(0), "r"((i >> 1) * 5) : "memory");
        }
        if (tid >= 32 && tid < 46 && blockIdx.x * 14 + tid - 32 < 1280) l2_prefetch(p.Wo + (blockIdx.x * 14 + tid - 32) * 2048, 4096);
        __syncwarp();
      }
    }, [&]() { if (tid == 256 && !p.helper) wo_load(0); __syncwarp(); } TLA(tlid));
  if (p.helper) return;
  if (tid == 64 && r < 2) { asm volatile("fence.proxy.async.shared::cta;" ::: "memory"); wo_load(4); }
  __syncwarp();
  if (w < 8) {
    if (r < 2) { asm volatile("setmaxnreg.inc.sync.aligned.u32 216;"); rec_gemm_warps<false>(p, sb, h, r TLA(tlid)); }
    else { asm volatile("setmaxnreg.inc.sync.aligned.u32 208;"); rec_gemm_warps<true>(p, sb, h, r TLA(tlid)); }
  } else {
    asm volatile("setmaxnreg.dec.sync.aligned.u32 72;");
    const int side = rec_attn_setup(p, sb, h, r TLA(tlid));
    if (r < 2) rec_attn_warps<false>(p, sb, smem, h, r, side TLA(tlid));
    else { asm volatile("setmaxnreg.inc.sync.aligned.u32 88;"); rec_attn_warps<true>(p, sb, smem, h, r, side TLA(tlid)); }
  }
}

constexpr int PERIOD = 2144, C3 = 544, SLACK = 672, XLATE = 192, GAP = 32;
__device__ uint32_t g_ZT[640 * 1024];
__device__ uint32_t g_WT[321 * 2048];
__device__ bf16 g_x1[S_ * D_], g_x2[S_ * D_], g_hN[S_ * D_];
__device__ __align__(128) uint4 g_QKV[QRING * 32 * 30720 / 16], g_O[ORING * 32 * 8192 / 16];
__device__ __align__(128) uint4 g_part[PRING * 32 * 8960 / 16];
__device__ __align__(128) uint32_t g_sync[192];
__device__ uint32_t g_comm[(6 << 20) / 4];

typedef CUresult (*EncodeFn)(CUtensorMap*, CUtensorMapDataType, cuuint32_t, void*, const cuuint64_t*, const cuuint64_t*, const cuuint32_t*, const cuuint32_t*,
                             CUtensorMapInterleave, CUtensorMapSwizzle, CUtensorMapL2promotion, CUtensorMapFloatOOBfill);
static void make_map(EncodeFn fn, CUtensorMap* m, const void* base, uint64_t cols, uint64_t rows, uint32_t bc, uint32_t br) {
  cuuint64_t dims[2] = {cols, rows}, strides[1] = {cols * 2}; cuuint32_t box[2] = {bc, br}, es[2] = {1, 1};
  fn(m, CU_TENSOR_MAP_DATA_TYPE_BFLOAT16, 2, (void*)base, dims, strides, box, es, CU_TENSOR_MAP_INTERLEAVE_NONE, CU_TENSOR_MAP_SWIZZLE_128B, CU_TENSOR_MAP_L2_PROMOTION_L2_256B, CU_TENSOR_MAP_FLOAT_OOB_FILL_NONE);
}
template <typename T> static T* sym(T& s) { void* p; cudaGetSymbolAddress(&p, s); return (T*)p; }

template <typename... KA, typename... A> static void launch(void (*k)(KA...), int grid, int block, int smem, bool pdl, int cluster, A... a) {
  cudaLaunchConfig_t cfg = {};
  cfg.gridDim = dim3(grid); cfg.blockDim = dim3(block); cfg.dynamicSmemBytes = smem; cfg.stream = cudaStreamPerThread;
  cudaLaunchAttribute at[2]; int n = 0;
  if (pdl) { at[n].id = cudaLaunchAttributeProgrammaticStreamSerialization; at[n].val.programmaticStreamSerializationAllowed = 1; n++; }
  if (cluster > 1) { at[n].id = cudaLaunchAttributeClusterDimension; at[n].val.clusterDim.x = cluster; at[n].val.clusterDim.y = 1; at[n].val.clusterDim.z = 1; n++; }
  cfg.attrs = at; cfg.numAttrs = n;
  cudaLaunchKernelEx(&cfg, k, KA(a)...);
}

extern "C" void kernel_launch(void* const* d_in, const int* in_sizes, int n_in, void* d_out, int out_size) {
  const bf16 *x = (const bf16*)d_in[0], *wr = (const bf16*)d_in[1], *wi = (const bf16*)d_in[2], *mem0 = (const bf16*)d_in[4];
  const bf16 *Wq = (const bf16*)d_in[5], *Wk = (const bf16*)d_in[6], *Wv = (const bf16*)d_in[7], *Wo = (const bf16*)d_in[8];
  bf16* out = (bf16*)d_out;
  uint32_t *ZT = (uint32_t*)sym(g_ZT), *WT = (uint32_t*)sym(g_WT);
  bf16 *x1 = (bf16*)sym(g_x1), *x2 = (bf16*)sym(g_x2), *hN = (bf16*)sym(g_hN);
  char *QKV = (char*)sym(g_QKV), *part = (char*)sym(g_part);
  uint32_t* comm = (uint32_t*)(((uint64_t)sym(g_comm) + (2 << 20) - 1) & ~(uint64_t)((2 << 20) - 1));
  EncodeFn enc = nullptr; cudaDriverEntryPointQueryResult qr;
  cudaGetDriverEntryPoint("cuTensorMapEncodeTiled", (void**)&enc, cudaEnableDefault, &qr);
  CUtensorMap tmW[3], tmWo, tmX, tmP;
  { cuuint64_t dims[3] = {64, PRING * 32, 70}, strides[2] = {8960, 128}; cuuint32_t box[3] = {64, 32, 2}, es[3] = {1, 1, 1};
    enc(&tmP, CU_TENSOR_MAP_DATA_TYPE_BFLOAT16, 3, part, dims, strides, box, es, CU_TENSOR_MAP_INTERLEAVE_NONE, CU_TENSOR_MAP_SWIZZLE_128B, CU_TENSOR_MAP_L2_PROMOTION_NONE, CU_TENSOR_MAP_FLOAT_OOB_FILL_NONE); }
  { cuuint64_t dims[3] = {64, 2048, 10}, strides[2] = {1280, 128}; cuuint32_t box[3] = {64, 32, 10}, es[3] = {1, 1, 1};
    enc(&tmX, CU_TENSOR_MAP_DATA_TYPE_BFLOAT16, 3, hN, dims, strides, box, es, CU_TENSOR_MAP_INTERLEAVE_NONE, CU_TENSOR_MAP_SWIZZLE_128B, CU_TENSOR_MAP_L2_PROMOTION_L2_256B, CU_TENSOR_MAP_FLOAT_OOB_FILL_NONE); }
  for (int i = 0; i < 3; i++) {
    cuuint64_t dims[3] = {4096, 64, 10}, strides[2] = {8192, 64 * 8192}; cuuint32_t box[3] = {64, 64, 5}, es[3] = {1, 1, 1};
    enc(&tmW[i], CU_TENSOR_MAP_DATA_TYPE_BFLOAT16, 3, (void*)(i == 0 ? Wq : i == 1 ? Wk : Wv), dims, strides, box, es, CU_TENSOR_MAP_INTERLEAVE_NONE, CU_TENSOR_MAP_SWIZZLE_128B, CU_TENSOR_MAP_L2_PROMOTION_L2_256B, CU_TENSOR_MAP_FLOAT_OOB_FILL_NONE);
  }
  make_map(enc, &tmWo, Wo, 640, 4096, 64, 64);
  int dbgf = 0;
  cudaFuncSetAttribute(side_kernel, cudaFuncAttributeMaxDynamicSharedMemorySize, SD_SMEM);
  cudaFuncSetAttribute(rec_kernel, cudaFuncAttributeMaxDynamicSharedMemorySize, REC_SMEM);
  for (int L = 0; L < 2; L++) {
    const bf16* xin = L == 0 ? x : x2;
    uint32_t* cm = comm + L * ((2 << 20) / 4);
    AParams ap = {xin, ZT, WT, x1, hN, (uint32_t*)sym(g_sync) + L * 96, L && !(dbgf & 16) ? comm + FL_RDY + 12 : nullptr, L ? 96 : 128, 0};
    RecParams rp = {{tmW[0], tmW[1], tmW[2]}, tmWo, tmX, ap, mem0, Wo, L ? nullptr : wr, wi, QKV, cm, PERIOD, C3, SLACK, XLATE, GAP, 0, 0, dbgf, nullptr, nullptr};
    SideParams sp = {tmWo, tmP, QKV, (char*)sym(g_O), part, x1, L == 0 ? x2 : out, cm, ap.sync, L == 0, dbgf};
    launch(rec_kernel, 96, 384, REC_SMEM, L > 0, 3, rp TLA(L * 10 + 5));
    rp.helper = 1;
    launch(rec_kernel, 35, 384, REC_SMEM, true, 1, rp TLA(L * 10 + 5));
    launch(side_kernel, 35, 512, SD_SMEM, true, 1, sp TLA(L * 10 + 6));
  }
}
```

```cpp
#include <cuda_runtime.h>
#include <cuda_bf16.h>
#include <cuda.h>
#include <stdint.h>
typedef __nv_bfloat16 bf16;
constexpr int S_ = 2048, D_ = 640, H_ = 32, DH = 128, NSEG = 64;

__device__ __forceinline__ uint32_t smem_u32(const void* p) { return (uint32_t)__cvta_generic_to_shared(p); }
__device__ __forceinline__ uint32_t pack_bf16(float lo, float hi) { uint32_t r; asm("cvt.rn.bf16x2.f32 %0, %1, %2;" : "=r"(r) : "f"(hi), "f"(lo)); return r; }
__device__ __forceinline__ float bf_lo(uint32_t v) { return __uint_as_float(v << 16); }
__device__ __forceinline__ float bf_hi(uint32_t v) { return __uint_as_float(v & 0xFFFF0000u); }
__device__ __forceinline__ void ldsm4t(uint32_t& r0, uint32_t& r1, uint32_t& r2, uint32_t& r3, uint32_t a) {
  asm volatile("ldmatrix.sync.aligned.m8n8.x4.trans.shared.b16 {%0,%1,%2,%3}, [%4];" : "=r"(r0), "=r"(r1), "=r"(r2), "=r"(r3) : "r"(a) : "memory");
}
__device__ __forceinline__ void ldsm4(uint32_t& r0, uint32_t& r1, uint32_t& r2, uint32_t& r3, uint32_t a) {
  asm volatile("ldmatrix.sync.aligned.m8n8.x4.shared.b16 {%0,%1,%2,%3}, [%4];" : "=r"(r0), "=r"(r1), "=r"(r2), "=r"(r3) : "r"(a) : "memory");
}
__device__ __forceinline__ void mma16816(float* d, uint32_t a0, uint32_t a1, uint32_t a2, uint32_t a3, uint32_t b0, uint32_t b1) {
  asm volatile("mma.sync.aligned.m16n8k16.row.col.f32.bf16.bf16.f32 {%0,%1,%2,%3}, {%4,%5,%6,%7}, {%8,%9}, {%0,%1,%2,%3};"
    : "+f"(d[0]), "+f"(d[1]), "+f"(d[2]), "+f"(d[3]) : "r"(a0), "r"(a1), "r"(a2), "r"(a3), "r"(b0), "r"(b1));
}
__device__ __forceinline__ void mma16816z(float* d, uint32_t a0, uint32_t a1, uint32_t a2, uint32_t a3, uint32_t b0, uint32_t b1) {
  asm volatile("mma.sync.aligned.m16n8k16.row.col.f32.bf16.bf16.f32 {%0,%1,%2,%3}, {%4,%5,%6,%7}, {%8,%9}, {%10,%10,%10,%10};"
    : "=f"(d[0]), "=f"(d[1]), "=f"(d[2]), "=f"(d[3]) : "r"(a0), "r"(a1), "r"(a2), "r"(a3), "r"(b0), "r"(b1), "f"(0.f));
}
__device__ __forceinline__ void mma1688z(float* d, uint32_t a0, uint32_t a1, uint32_t b0) {
  asm volatile("mma.sync.aligned.m16n8k8.row.col.f32.bf16.bf16.f32 {%0,%1,%2,%3}, {%4,%5}, {%6}, {%7,%7,%7,%7};"
    : "=f"(d[0]), "=f"(d[1]), "=f"(d[2]), "=f"(d[3]) : "r"(a0), "r"(a1), "r"(b0), "f"(0.f));
}
__device__ __forceinline__ void mma1688(float* d, uint32_t a0, uint32_t a1, uint32_t b0) {
  asm volatile("mma.sync.aligned.m16n8k8.row.col.f32.bf16.bf16.f32 {%0,%1,%2,%3}, {%4,%5}, {%6}, {%0,%1,%2,%3};"
    : "+f"(d[0]), "+f"(d[1]), "+f"(d[2]), "+f"(d[3]) : "r"(a0), "r"(a1), "r"(b0));
}
__device__ __forceinline__ void mmaA(float* d, const uint32_t* a, uint32_t b0, uint32_t b1) { mma16816(d, a[0], a[1], a[2], a[3], b0, b1); }
__device__ __forceinline__ void mmaZ(float* d, const uint32_t* a, uint32_t b0, uint32_t b1) { mma16816z(d, a[0], a[1], a[2], a[3], b0, b1); }
__device__ __forceinline__ uint32_t movm(uint32_t a) { uint32_t d; asm volatile("movmatrix.sync.aligned.m8n8.trans.b16 %0, %1;" : "=r"(d) : "r"(a)); return d; }
__device__ __forceinline__ void cp_async16(uint32_t dst, const void* src) { asm volatile("cp.async.cg.shared.global [%0], [%1], 16;" :: "r"(dst), "l"(src) : "memory"); }
__device__ __forceinline__ void cp_commit() { asm volatile("cp.async.commit_group;" ::: "memory"); }
template <int N> __device__ __forceinline__ void cp_wait() { asm volatile("cp.async.wait_group %0;" :: "n"(N) : "memory"); }
__device__ __forceinline__ void lds128(uint32_t* r, uint32_t a) { asm volatile("ld.shared.v4.b32 {%0,%1,%2,%3}, [%4];" : "=r"(r[0]), "=r"(r[1]), "=r"(r[2]), "=r"(r[3]) : "r"(a) : "memory"); }
__device__ __forceinline__ void sts128(uint32_t a, uint32_t r0, uint32_t r1, uint32_t r2, uint32_t r3) { asm volatile("st.shared.v4.b32 [%0], {%1,%2,%3,%4};" :: "r"(a), "r"(r0), "r"(r1), "r"(r2), "r"(r3) : "memory"); }
__device__ __forceinline__ void stg128(void* p, uint32_t r0, uint32_t r1, uint32_t r2, uint32_t r3) { asm volatile("st.global.v4.b32 [%0], {%1,%2,%3,%4};" :: "l"(p), "r"(r0), "r"(r1), "r"(r2), "r"(r3) : "memory"); }
template <int ID, int N> __device__ __forceinline__ void bar_sync() { asm volatile("bar.sync %0, %1;" :: "n"(ID), "n"(N) : "memory"); }
template <int ID, int N> __device__ __forceinline__ void bar_arrive() { asm volatile("bar.arrive %0, %1;" :: "n"(ID), "n"(N) : "memory"); }
__device__ __forceinline__ void mbar_wait(uint32_t bar, uint32_t parity) {
  asm volatile("{\n.reg .pred p, pq;\n.reg .u32 n;\nmov.u32 n, 0;\nLW%=:\nmbarrier.try_wait.parity.shared::cta.b64 p, [%0], %1;\n@p bra.uni LD%=;\nadd.u32 n, n, 1;\nsetp.lt.u32 pq, n, 20000;\n@pq bra.uni LW%=;\nLD%=:\n}" :: "r"(bar), "r"(parity) : "memory");
}
#define mbar_wait_long mbar_wait
__device__ __forceinline__ void mbar_init(uint32_t bar, int n) { asm volatile("mbarrier.init.shared.b64 [%0], %1;" :: "r"(bar), "r"(n) : "memory"); }
__device__ __forceinline__ void mbar_expect(uint32_t bar, int bytes) { asm volatile("mbarrier.arrive.expect_tx.shared.b64 _, [%0], %1;" :: "r"(bar), "r"(bytes) : "memory"); }
__device__ __forceinline__ void mbar_arrive(uint32_t bar) { asm volatile("mbarrier.arrive.shared.b64 _, [%0];" :: "r"(bar) : "memory"); }
__device__ __forceinline__ void l2_prefetch(const void* p, int bytes) { asm volatile("cp.async.bulk.prefetch.L2.global [%0], %1;" :: "l"(p), "r"(bytes) : "memory"); }
__device__ __forceinline__ float ex2(float x) { float y; asm("ex2.approx.ftz.f32 %0, %1;" : "=f"(y) : "f"(x)); return y; }
__device__ __forceinline__ void pdl_wait() { asm volatile("griddepcontrol.wait;" ::: "memory"); }
__device__ __forceinline__ void pdl_launch() { asm volatile("griddepcontrol.launch_dependents;" ::: "memory"); }
__device__ __forceinline__ uint32_t hadd2(uint32_t a, uint32_t b) { uint32_t r; asm("add.rn.bf16x2 %0, %1, %2;" : "=r"(r) : "r"(a), "r"(b)); return r; }
__device__ __forceinline__ void sched_fence() { asm volatile("{\n.reg .pred p;\n.reg .u32 t;\nLF%=:\nmov.u32 t, %%clock;\nsetp.eq.u32 p, t, %0;\n@p bra.uni LF%=;\n}" :: "n"(12345) : "memory"); }
#define TL_MIN(id, k)
#define TL_MAX(id, k)
#define TLP
#define TLA(x)

constexpr int TB_F16 = 0, TB_640 = 64, TB_F40 = 384, TB_F32 = 784, TB_512 = 1040, TB_2048 = 1296;
__device__ __align__(128) const uint32_t g_tab[6208] = {
0x3f803f80,0xbf803f80,0x3f803f80,0xbf803f80,0x3f803f80,0xbf803f80,0x3f803f80,0xbf803f80,0x3f803f80,0xbf803f80,0x3f803f80,0xbf803f80,0x3f803f80,0xbf803f80,0x3f803f80,0xbf803f80,
0x3f6d3f80,0xbf6d3f80,0xbf6dbf80,0x3f6dbf80,0x3ec43f35,0xbec43f35,0xbec4bf35,0x3ec4bf35,0xbec40000,0x3ec40000,0x3ec40000,0xbec40000,0xbf6dbf35,0x3f6dbf35,0x3f6d3f35,0xbf6d3f35,
0x3f353f80,0xbf353f80,0x3f353f80,0xbf353f80,0xbf350000,0x3f350000,0xbf350000,0x3f350000,0xbf35bf80,0x3f35bf80,0xbf35bf80,0x3f35bf80,0x3f350000,0xbf350000,0x3f350000,0xbf350000,
0x3ec43f80,0xbec43f80,0xbec4bf80,0x3ec4bf80,0xbf6dbf35,0x3f6dbf35,0x3f6d3f35,0xbf6d3f35,0x3f6d0000,0xbf6d0000,0xbf6d0000,0x3f6d0000,0xbec43f35,0x3ec43f35,0x3ec4bf35,0xbec4bf35,
0x3f80,0x3f80,0x3f80,0x3f80,0xbf80,0xbf80,0xbf80,0xbf80,0x3f80,0x3f80,0x3f80,0x3f80,0xbf80,0xbf80,0xbf80,0xbf80,
0xbec43f80,0x3ec43f80,0x3ec4bf80,0xbec4bf80,0x3f6dbf35,0xbf6dbf35,0xbf6d3f35,0x3f6d3f35,0xbf6d0000,0x3f6d0000,0x3f6d0000,0xbf6d0000,0x3ec43f35,0xbec43f35,0xbec4bf35,0x3ec4bf35,
0xbf353f80,0x3f353f80,0xbf353f80,0x3f353f80,0x3f350000,0xbf350000,0x3f350000,0xbf350000,0x3f35bf80,0xbf35bf80,0x3f35bf80,0xbf35bf80,0xbf350000,0x3f350000,0xbf350000,0x3f350000,
0xbf6d3f80,0x3f6d3f80,0x3f6dbf80,0xbf6dbf80,0xbec43f35,0x3ec43f35,0x3ec4bf35,0xbec4bf35,0x3ec40000,0xbec40000,0xbec40000,0x3ec40000,0x3f6dbf35,0xbf6dbf35,0xbf6d3f35,0x3f6d3f35,
0x80008000,0x80008000,0x80008000,0x80008000,0x80008000,0x80008000,0x80008000,0x80008000,0x80008000,0x80008000,0x80008000,0x80008000,0x80008000,0x80008000,0x80008000,0x80008000,
0xbec48000,0x3ec48000,0x3ec48000,0xbec48000,0xbf6dbf35,0x3f6dbf35,0x3f6d3f35,0xbf6d3f35,0xbf6dbf80,0x3f6dbf80,0x3f6d3f80,0xbf6d3f80,0xbec4bf35,0x3ec4bf35,0x3ec43f35,0xbec43f35,
0xbf358000,0x3f358000,0xbf358000,0x3f358000,0xbf35bf80,0x3f35bf80,0xbf35bf80,0x3f35bf80,0x3f358000,0xbf358000,0x3f358000,0xbf358000,0x3f353f80,0xbf353f80,0x3f353f80,0xbf353f80,
0xbf6d8000,0x3f6d8000,0x3f6d8000,0xbf6d8000,0x3ec4bf35,0xbec4bf35,0xbec43f35,0x3ec43f35,0x3ec43f80,0xbec43f80,0xbec4bf80,0x3ec4bf80,0xbf6dbf35,0x3f6dbf35,0x3f6d3f35,0xbf6d3f35,
0xbf808000,0x3f808000,0xbf808000,0x3f808000,0x3f808000,0xbf808000,0x3f808000,0xbf808000,0xbf808000,0x3f808000,0xbf808000,0x3f808000,0x3f808000,0xbf808000,0x3f808000,0xbf808000,
0xbf6d8000,0x3f6d8000,0x3f6d8000,0xbf6d8000,0x3ec43f35,0xbec43f35,0xbec4bf35,0x3ec4bf35,0x3ec4bf80,0xbec4bf80,0xbec43f80,0x3ec43f80,0xbf6d3f35,0x3f6d3f35,0x3f6dbf35,0xbf6dbf35,
0xbf358000,0x3f358000,0xbf358000,0x3f358000,0xbf353f80,0x3f353f80,0xbf353f80,0x3f353f80,0x3f358000,0xbf358000,0x3f358000,0xbf358000,0x3f35bf80,0xbf35bf80,0x3f35bf80,0xbf35bf80,
0xbec48000,0x3ec48000,0x3ec48000,0xbec48000,0xbf6d3f35,0x3f6d3f35,0x3f6dbf35,0xbf6dbf35,0xbf6d3f80,0x3f6d3f80,0x3f6dbf80,0xbf6dbf80,0xbec43f35,0x3ec43f35,0x3ec4bf35,0xbec4bf35,
0x3f800000,0x3f800000,0x3f800000,0x3f7f35f9,0x3f800000,0x3f800000,0x3f7cd925,0x3f78ed3c,0x3f800000,0x3f800000,0x3f737871,0x3f6c835e,0x3f800000,0x3f800000,0x3f641901,0x3f5a46a0,
0x3f800000,0x3f7ffcd7,0x3f800000,0x3f7f0059,0x3f7ff35e,0x3f7fe394,0x3f7c0361,0x3f770f11,0x3f7fcd79,0x3f7fb10f,0x3f702d4f,0x3f676bd8,0x3f7f8e56,0x3f7f654e,0x3f5cdc29,0x3f50935b,
0x3f800000,0x3f7ff35e,0x3f800000,0x3f7ec46d,0x3f7fcd79,0x3f7f8e56,0x3f7b14be,0x3f74fa0b,0x3f7f35f9,0x3f7ec46d,0x3f6c835e,0x3f61c598,0x3f7e39bc,0x3f7d95f4,0x3f54db31,0x3f45e403,
0x3f800000,0x3f7fe394,0x3f800000,0x3f7e8238,0x3f7f8e56,0x3f7f0059,0x3f7a0d54,0x3f72ae9e,0x3f7e39bc,0x3f7d3aac,0x3f687c12,0x3f5b941a,0x3f7c0361,0x3f7a9421,0x3f4c1d35,0x3f3a4582,
0x3f800000,0x3f7fcd79,0x3f800000,0x3f7e39bc,0x3f7f35f9,0x3f7e39bc,0x3f78ed3c,0x3f702d4f,0x3f7cd925,0x3f7b14be,0x3f641901,0x3f54db31,0x3f78ed3c,0x3f766377,0x3f42a9f7,0x3f2dc5e3,
0x3f800000,0x3f7fb10f,0x3f800000,0x3f7deafa,0x3f7ec46d,0x3f7d3aac,0x3f77b493,0x3f6d76aa,0x3f7b14be,0x3f7853f8,0x3f5f5be6,0x3f4d9f02,0x3f74fa0b,0x3f710908,0x3f3889dc,0x3f207440,
0x3f800000,0x3f7f8e56,0x3f800000,0x3f7d95f4,0x3f7e39bc,0x3f7c0361,0x3f766377,0x3f6a8b4b,0x3f78ed3c,0x3f74fa0b,0x3f5a46a0,0x3f45e403,0x3f702d4f,0x3f6a8b4b,0x3f2dc5e3,0x3f1260b2,
0x3f800000,0x3f7f654e,0x3f800000,0x3f7d3aac,0x3f7d95f4,0x3f7a9421,0x3f74fa0b,0x3f676bd8,0x3f766377,0x3f710908,0x3f54db31,0x3f3daef9,0x3f6a8b4b,0x3f62f219,0x3f226799,0x3f039c3d,
0x3f800000,0x3f800000,0x3f4f1bbd,0x3f42a9f7,0x3f800000,0x3f800000,0x3f3504f3,0x3f26423a,0x3f800000,0x3f800000,0x3f167918,0x3f05c277,0x3f800000,0x3f800000,0x3ee87171,0x3ec3ef15,
0x3f7f35f9,0x3f7f0059,0x3f42a9f7,0x3f333bc6,0x3f7ec46d,0x3f7e8238,0x3f226799,0x3f104f0e,0x3f7e39bc,0x3f7deafa,0x3efa2c90,0x3ed1c759,0x3f7d95f4,0x3f7d3aac,0x3ea7bf25,0x3e78cfcc,
0x3f7cd925,0x3f7c0361,0x3f3504f3,0x3f226799,0x3f7b14be,0x3f7a0d54,0x3f0e39da,0x3ef15aea,0x3f78ed3c,0x3f77b493,0x3ec3ef15,0x3e94a031,0x3f766377,0x3f74fa0b,0x3e47c5c2,0x3dc8bd36,
0x3f78ed3c,0x3f770f11,0x3f26423a,0x3f104f0e,0x3f74fa0b,0x3f72ae9e,0x3ef15aea,0x3ebf47d7,0x3f702d4f,0x3f6d76aa,0x3e8afa3e,0x3e2a1c3f,0x3f6a8b4b,0x3f676bd8,0x3d712283,0xbd48fb30,
0x3f737871,0x3f702d4f,0x3f167918,0x3efa2c90,0x3f6c835e,0x3f687c12,0x3ec3ef15,0x3e8afa3e,0x3f641901,0x3f5f5be6,0x3e20305b,0x3d20cee7,0x3f5a46a0,0x3f54db31,0xbda0af2a,0xbe47c5c2,
0x3f6c835e,0x3f676bd8,0x3f05c277,0x3ed1c759,0x3f61c598,0x3f5b941a,0x3e94a031,0x3e2a1c3f,0x3f54db31,0x3f4d9f02,0x3d20cee7,0xbdb4b86a,0x3f45e403,0x3f3daef9,0xbe5b73dc,0xbeac7cd4,
0x3f641901,0x3f5cdc29,0x3ee87171,0x3ea7bf25,0x3f54db31,0x3f4c1d35,0x3e47c5c2,0x3d712283,0x3f42a9f7,0x3f3889dc,0xbda0af2a,0xbe5b73dc,0x3f2dc5e3,0x3f226799,0xbeb13641,0xbef15aea,
0x3f5a46a0,0x3f50935b,0x3ec3ef15,0x3e78cfcc,0x3f45e403,0x3f3a4582,0x3dc8bd36,0xbd48fb30,0x3f2dc5e3,0x3f207440,0xbe47c5c2,0xbeac7cd4,0x3f1260b2,0x3f039c3d,0xbef15aea,0xbf187fc0,
0x3f800000,0x3f800000,0x3e9e377a,0x3e6f0c4d,0x3f800000,0x3f800000,0x3e20305b,0x3da0af2a,0x3f800000,0x3f800000,0,0xbda0af2a,0x3f800000,0x3f800000,0xbe20305b,0xbe6f0c4d,
0x3f7cd925,0x3f7c7160,0x3e20305b,0x3d8ca1f2,0x3f7c0361,0x3f7b8f2a,0xbca0d6d6,0xbddcbd0d,0x3f7b14be,0x3f7a9421,0xbe47c5c2,0xbe8fcefe,0x3f7a0d54,0x3f79805c,0xbeba9be1,0xbee3f40d,
0x3f737871,0x3f71decf,0,0xbdc8bd36,0x3f702d4f,0x3f6e641a,0xbe47c5c2,0xbe94a031,0x3f6c835e,0x3f6a8b4b,0xbec3ef15,0xbef15aea,0x3f687c12,0x3f6655e7,0xbf0e39da,0xbf226799,
0x3f641901,0x3f609384,0xbe20305b,0xbe862210,0x3f5cdc29,0x3f58f3c4,0xbeba9be1,0xbeece91a,0x3f54db31,0x3f50935b,0xbf0e39da,0xbf2456f1,0x3f4c1d35,0x3f4779bc,0xbf3889dc,0xbf4a965e,
0x3f4f1bbd,0x3f490a88,0xbe9e377a,0xbed65a92,0x3f42a9f7,0x3f3bfc8f,0xbf05c277,0xbf1e7cf1,0x3f3504f3,0x3f2dc5e3,0xbf3504f3,0xbf490a88,0x3f26423a,0x3f1e7cf1,0xbf5a46a0,0xbf687c12,
0x3f3504f3,0x3f2beb4a,0xbee87171,0xbf104f0e,0x3f226799,0x3f187fc0,0xbf2a0c73,0xbf4105b8,0x3f0e39da,0x3f039c3d,0xbf54db31,0xbf653a48,0x3ef15aea,0x3edae880,0xbf71decf,0xbf7a9421,
0x3f167918,0x3f0a04f8,0xbf167918,0xbf316e2c,0x3efa2c90,0x3edf7108,0xbf490a88,0xbf5cdc29,0x3ec3ef15,0x3ea7bf25,0xbf6c835e,0xbf77b493,0x3e8afa3e,0x3e5b73dc,0xbf7e39bc,0xbf7ff35e,
0x3ee87171,0x3ec8917e,0xbf3504f3,0xbf4d9f02,0x3ea7bf25,0x3e862210,0xbf61c598,0xbf710908,0x3e47c5c2,0x3e0255f4,0xbf7b14be,0xbf7fb10f,0x3d712283,0xbc20d8d2,0xbf7ec46d,0xbf7853f8,
0x3f800000,0x3f800000,0xbe9e377a,0xbec3ef15,0x3f800000,0x3f800000,0xbee87171,0xbf05c277,0x3f800000,0x3f800000,0xbf167918,0xbf26423a,0x3f800000,0x3f800000,0xbf3504f3,0xbf42a9f7,
0x3f78ed3c,0x3f7853f8,0xbf05c277,0xbf187fc0,0x3f77b493,0x3f770f11,0xbf2a0c73,0xbf3a4582,0x3f766377,0x3f75b1c9,0xbf490a88,0xbf563e03,0x3f74fa0b,0x3f743c41,0xbf61c598,0xbf6b8a3d,
0x3f641901,0x3f61c598,0xbf3504f3,0xbf45e403,0x3f5f5be6,0x3f5cdc29,0xbf54db31,0xbf61c598,0x3f5a46a0,0x3f579b8c,0xbf6c835e,0xbf74fa0b,0x3f54db31,0x3f5205d4,0xbf7b14be,0xbf7ec46d,
0x3f42a9f7,0x3f3daef9,0xbf5a46a0,0xbf676bd8,0x3f3889dc,0x3f333bc6,0xbf71decf,0xbf79805c,0x3f2dc5e3,0x3f28296a,0xbf7e39bc,0xbf7ffcd7,0x3f226799,0x3f1c81b9,0xbf7ec46d,0xbf7a9421,
0x3f167918,0x3f0e39da,0xbf737871,0xbf7b14be,0x3f05c277,0x3efa2c90,0xbf7f35f9,0xbf7fcd79,0x3ee87171,0x3ed65a92,0xbf7cd925,0xbf766377,0x3ec3ef15,0x3eb13641,0xbf6c835e,0xbf5f5be6,
0x3ec3ef15,0x3eac7cd4,0xbf7f35f9,0xbf7fb10f,0x3e94a031,0x3e78cfcc,0xbf7c0361,0xbf743c41,0x3e47c5c2,0x3e164083,0xbf687c12,0xbf58f3c4,0x3dc8bd36,0x3d48fb30,0xbf45e403,0xbf2f9c32,
0x3e20305b,0x3dc8bd36,0xbf7cd925,0xbf74fa0b,0x3d20cee7,0xbca0d6d6,0xbf687c12,0xbf579b8c,0xbda0af2a,0xbe0c4cf7,0xbf42a9f7,0xbf2a0c73,0xbe47c5c2,0xbe814693,0xbf0e39da,0xbedf7108,
0xbda0af2a,0xbe164083,0xbf6c835e,0xbf5b941a,0xbe5b73dc,0xbe8fcefe,0xbf45e403,0xbf2beb4a,0xbeb13641,0xbed1c759,0xbf0e39da,0xbedae880,0xbef15aea,0xbf07e565,0xbe94a031,0xbe164083,
0x3f800000,0x3f800000,0xbf4f1bbd,0xbf5a46a0,0x3f800000,0x3f800000,0xbf641901,0xbf6c835e,0x3f800000,0x3f800000,0xbf737871,0xbf78ed3c,0x3f800000,0x3f800000,0xbf7cd925,0xbf7f35f9,
0x3f737871,0x3f72ae9e,0xbf737871,0xbf79805c,0x3f71decf,0x3f710908,0xbf7d95f4,0xbf7fb10f,0x3f702d4f,0x3f6f4ba8,0xbf7fcd79,0xbf7deafa,0x3f6e641a,0x3f6d76aa,0xbf7a0d54,0xbf743c41,
0x3f4f1bbd,0x3f4c1d35,0xbf800000,0xbf7ec46d,0x3f490a88,0x3f45e403,0xbf7b14be,0xbf74fa0b,0x3f42a9f7,0x3f3f5cb5,0xbf6c835e,0xbf61c598,0x3f3bfc8f,0x3f3889dc,0xbf54db31,0xbf45e403,
0x3f167918,0x3f104f0e,0xbf737871,0xbf698690,0x3f0a04f8,0x3f039c3d,0xbf5cdc29,0xbf4d9f02,0x3efa2c90,0x3eece91a,0xbf3bfc8f,0xbf28296a,0x3edf7108,0x3ed1c759,0xbf1260b2,0xbef5c6c5,
0x3e9e377a,0x3e8afa3e,0xbf4f1bbd,0xbf3bfc8f,0x3e6f0c4d,0x3e47c5c2,0xbf26423a,0xbf0e39da,0x3e20305b,0x3df0b772,0xbee87171,0xbeb13641,0x3da0af2a,0x3d20cee7,0xbe6f0c4d,0xbdf0b772,
0,0xbd48fb30,0xbf167918,0xbef5c6c5,0xbdc8bd36,0xbe164083,0xbeba9be1,0xbe78cfcc,0xbe47c5c2,0xbe78cfcc,0xbdf0b772,0x3c20d8d2,0xbe94a031,0xbeac7cd4,0x3e0c4cf7,0x3e862210,
0xbe9e377a,0xbeba9be1,0xbe9e377a,0xbe3403f1,0xbed65a92,0xbef15aea,0xbd20cee7,0x3dc8bd36,0xbf05c277,0xbf1260b2,0x3e6f0c4d,0x3eba9be1,0xbf1e7cf1,0xbf2a0c73,0x3efa2c90,0x3f1a82a4,
0xbf167918,0xbf2456f1,0,0x3e164083,0xbf316e2c,0xbf3daef9,0x3e94a031,0x3edae880,0xbf490a88,0xbf53731f,0x3f0e39da,0x3f2beb4a,0xbf5cdc29,0xbf653a48,0x3f45e403,0x3f5b941a,
0x80000000,0x80000000,0x80000000,0xbda0af2a,0x80000000,0x80000000,0xbe20305b,0xbe6f0c4d,0x80000000,0x80000000,0xbe9e377a,0xbec3ef15,0x80000000,0x80000000,0xbee87171,0xbf05c277,
0x80000000,0xbc20d8d2,0x80000000,0xbdb4b86a,0xbca0d6d6,0xbcf13d4c,0xbe3403f1,0xbe862210,0xbd20cee7,0xbd48fb30,0xbeb13641,0xbedae880,0xbd712283,0xbd8ca1f2,0xbf0172c3,0xbf146eba,
0x80000000,0xbca0d6d6,0x80000000,0xbdc8bd36,0xbd20cee7,0xbd712283,0xbe47c5c2,0xbe94a031,0xbda0af2a,0xbdc8bd36,0xbec3ef15,0xbef15aea,0xbdf0b772,0xbe0c4cf7,0xbf0e39da,0xbf226799,
0x80000000,0xbcf13d4c,0x80000000,0xbddcbd0d,0xbd712283,0xbdb4b86a,0xbe5b73dc,0xbea2fd52,0xbdf0b772,0xbe164083,0xbed65a92,0xbf039c3d,0xbe3403f1,0xbe519f65,0xbf1a82a4,0xbf2f9c32,
0x80000000,0xbd20cee7,0x80000000,0xbdf0b772,0xbda0af2a,0xbdf0b772,0xbe6f0c4d,0xbeb13641,0xbe20305b,0xbe47c5c2,0xbee87171,0xbf0e39da,0xbe6f0c4d,0xbe8afa3e,0xbf26423a,0xbf3bfc8f,
0x80000000,0xbd48fb30,0x80000000,0xbe0255f4,0xbdc8bd36,0xbe164083,0xbe814693,0xbebf47d7,0xbe47c5c2,0xbe78cfcc,0xbefa2c90,0xbf187fc0,0xbe94a031,0xbeac7cd4,0xbf316e2c,0xbf4779bc,
0x80000000,0xbd712283,0x80000000,0xbe0c4cf7,0xbdf0b772,0xbe3403f1,0xbe8afa3e,0xbecd2ef3,0xbe6f0c4d,0xbe94a031,0xbf05c277,0xbf226799,0xbeb13641,0xbecd2ef3,0xbf3bfc8f,0xbf5205d4,
0x80000000,0xbd8ca1f2,0x80000000,0xbe164083,0xbe0c4cf7,0xbe519f65,0xbe94a031,0xbedae880,0xbe8afa3e,0xbeac7cd4,0xbf0e39da,0xbf2beb4a,0xbecd2ef3,0xbeece91a,0xbf45e403,0xbf5b941a,
0x80000000,0x80000000,0xbf167918,0xbf26423a,0x80000000,0x80000000,0xbf3504f3,0xbf42a9f7,0x80000000,0x80000000,0xbf4f1bbd,0xbf5a46a0,0x80000000,0x80000000,0xbf641901,0xbf6c835e,
0xbda0af2a,0xbdb4b86a,0xbf26423a,0xbf36c9a9,0xbdc8bd36,0xbddcbd0d,0xbf45e403,0xbf53731f,0xbdf0b772,0xbe0255f4,0xbf5f5be6,0xbf698690,0xbe0c4cf7,0xbe164083,0xbf71decf,0xbf7853f8,
0xbe20305b,0xbe3403f1,0xbf3504f3,0xbf45e403,0xbe47c5c2,0xbe5b73dc,0xbf54db31,0xbf61c598,0xbe6f0c4d,0xbe814693,0xbf6c835e,0xbf74fa0b,0xbe8afa3e,0xbe94a031,0xbf7b14be,0xbf7ec46d,
0xbe6f0c4d,0xbe862210,0xbf42a9f7,0xbf53731f,0xbe94a031,0xbea2fd52,0xbf61c598,0xbf6d76aa,0xbeb13641,0xbebf47d7,0xbf766377,0xbf7c7160,0xbecd2ef3,0xbedae880,0xbf7f8e56,0xbf7fb10f,
0xbe9e377a,0xbeb13641,0xbf4f1bbd,0xbf5f5be6,0xbec3ef15,0xbed65a92,0xbf6c835e,0xbf766377,0xbee87171,0xbefa2c90,0xbf7cd925,0xbf7fcd79,0xbf05c277,0xbf0e39da,0xbf7f35f9,0xbf7b14be,
0xbec3ef15,0xbedae880,0xbf5a46a0,0xbf698690,0xbef15aea,0xbf039c3d,0xbf74fa0b,0xbf7c7160,0xbf0e39da,0xbf187fc0,0xbf7fcd79,0xbf7f0059,0xbf226799,0xbf2beb4a,0xbf7a0d54,0xbf710908,
0xbee87171,0xbf0172c3,0xbf641901,0xbf71decf,0xbf0e39da,0xbf1a82a4,0xbf7b14be,0xbf7f8e56,0xbf26423a,0xbf316e2c,0xbf7f35f9,0xbf7a0d54,0xbf3bfc8f,0xbf45e403,0xbf702d4f,0xbf61c598,
0xbf05c277,0xbf146eba,0xbf6c835e,0xbf7853f8,0xbf226799,0xbf2f9c32,0xbf7ec46d,0xbf7fb10f,0xbf3bfc8f,0xbf4779bc,0xbf7b14be,0xbf710908,0xbf5205d4,0xbf5b941a,0xbf61c598,0xbf4d9f02,
0x80000000,0x80000000,0xbf737871,0xbf78ed3c,0x80000000,0x80000000,0xbf7cd925,0xbf7f35f9,0x80000000,0x80000000,0xbf800000,0xbf7f35f9,0x80000000,0x80000000,0xbf7cd925,0xbf78ed3c,
0xbe20305b,0xbe2a1c3f,0xbf7cd925,0xbf7f654e,0xbe3403f1,0xbe3de731,0xbf7ff35e,0xbf7e8238,0xbe47c5c2,0xbe519f65,0xbf7b14be,0xbf75b1c9,0xbe5b73dc,0xbe6542e9,0xbf6e641a,0xbf653a48,
0xbe9e377a,0xbea7bf25,0xbf800000,0xbf7ec46d,0xbeb13641,0xbeba9be1,0xbf7b14be,0xbf74fa0b,0xbec3ef15,0xbecd2ef3,0xbf6c835e,0xbf61c598,0xbed65a92,0xbedf7108,0xbf54db31,0xbf45e403,
0xbee87171,0xbef5c6c5,0xbf7cd925,0xbf770f11,0xbf0172c3,0xbf07e565,0xbf6e641a,0xbf62f219,0xbf0e39da,0xbf146eba,0xbf54db31,0xbf444969,0xbf1a82a4,0xbf207440,0xbf316e2c,0xbf1c81b9,
0xbf167918,0xbf1e7cf1,0xbf737871,0xbf687c12,0xbf26423a,0xbf2dc5e3,0xbf5a46a0,0xbf490a88,0xbf3504f3,0xbf3bfc8f,0xbf3504f3,0xbf1e7cf1,0xbf42a9f7,0xbf490a88,0xbf05c277,0xbed65a92,
0xbf3504f3,0xbf3daef9,0xbf641901,0xbf53731f,0xbf45e403,0xbf4d9f02,0xbf3f5cb5,0xbf28296a,0xbf54db31,0xbf5b941a,0xbf0e39da,0xbee3f40d,0xbf61c598,0xbf676bd8,0xbea7bf25,0xbe519f65,
0xbf4f1bbd,0xbf579b8c,0xbf4f1bbd,0xbf3889dc,0xbf5f5be6,0xbf6655e7,0xbf1e7cf1,0xbf0172c3,0xbf6c835e,0xbf71decf,0xbec3ef15,0xbe814693,0xbf766377,0xbf7a0d54,0xbdf0b772,0x3ca0d6d6,
0xbf641901,0xbf6b8a3d,0xbf3504f3,0xbf187fc0,0xbf71decf,0xbf770f11,0xbef15aea,0xbeac7cd4,0xbf7b14be,0xbf7deafa,0xbe47c5c2,0xbd48fb30,0xbf7f8e56,0xbf7ffcd7,0x3dc8bd36,0x3e78cfcc,
0x80000000,0x80000000,0xbf737871,0xbf6c835e,0x80000000,0x80000000,0xbf641901,0xbf5a46a0,0x80000000,0x80000000,0xbf4f1bbd,0xbf42a9f7,0x80000000,0x80000000,0xbf3504f3,0xbf26423a,
0xbe6f0c4d,0xbe78cfcc,0xbf5a46a0,0xbf4d9f02,0xbe814693,0xbe862210,0xbf3f5cb5,0xbf2f9c32,0xbe8afa3e,0xbe8fcefe,0xbf1e7cf1,0xbf0c2124,0xbe94a031,0xbe996dba,0xbef15aea,0xbec8917e,
0xbee87171,0xbef15aea,0xbf3504f3,0xbf226799,0xbefa2c90,0xbf0172c3,0xbf0e39da,0xbef15aea,0xbf05c277,0xbf0a04f8,0xbec3ef15,0xbe94a031,0xbf0e39da,0xbf1260b2,0xbe47c5c2,0xbdc8bd36,
0xbf26423a,0xbf2beb4a,0xbf05c277,0xbedae880,0xbf316e2c,0xbf36c9a9,0xbea7bf25,0xbe6542e9,0xbf3bfc8f,0xbf4105b8,0xbdf0b772,0xbc20d8d2,0xbf45e403,0xbf4a965e,0x3dc8bd36,0x3e519f65,
0xbf4f1bbd,0xbf54db31,0xbe9e377a,0xbe47c5c2,0xbf5a46a0,0xbf5f5be6,0xbda0af2a,0x3d20cee7,0xbf641901,0xbf687c12,0x3e20305b,0x3e8afa3e,0xbf6c835e,0xbf702d4f,0x3ec3ef15,0x3efa2c90,
0xbf6c835e,0xbf710908,0xbda0af2a,0x3d48fb30,0xbf74fa0b,0xbf7853f8,0x3e3403f1,0x3e996dba,0xbf7b14be,0xbf7d3aac,0x3ed65a92,0x3f07e565,0xbf7ec46d,0xbf7fb10f,0x3f226799,0x3f3a4582,
0xbf7cd925,0xbf7ec46d,0x3e20305b,0x3e94a031,0xbf7fcd79,0xbf7ff35e,0x3ed65a92,0x3f0a04f8,0xbf7f35f9,0xbf7d95f4,0x3f26423a,0x3f3f5cb5,0xbf7b14be,0xbf77b493,0x3f54db31,0x3f6655e7,
0xbf7f35f9,0xbf7d3aac,0x3ec3ef15,0x3f039c3d,0xbf7a0d54,0xbf75b1c9,0x3f226799,0x3f3daef9,0xbf702d4f,0xbf698690,0x3f54db31,0x3f676bd8,0xbf61c598,0xbf58f3c4,0x3f74fa0b,0x3f7d3aac,
0x80000000,0x80000000,0xbf167918,0xbf05c277,0x80000000,0x80000000,0xbee87171,0xbec3ef15,0x80000000,0x80000000,0xbe9e377a,0xbe6f0c4d,0x80000000,0x80000000,0xbe20305b,0xbda0af2a,
0xbe9e377a,0xbea2fd52,0xbe9e377a,0xbe6542e9,0xbea7bf25,0xbeac7cd4,0xbe0c4cf7,0xbd48fb30,0xbeb13641,0xbeb5eb4f,0x3d20cee7,0x3e0255f4,0xbeba9be1,0xbebf47d7,0x3e5b73dc,0x3e996dba,
0xbf167918,0xbf1a82a4,0x80000000,0x3dc8bd36,0xbf1e7cf1,0xbf226799,0x3e47c5c2,0x3e94a031,0xbf26423a,0xbf2a0c73,0x3ec3ef15,0x3ef15aea,0xbf2dc5e3,0xbf316e2c,0x3f0e39da,0x3f226799,
0xbf4f1bbd,0xbf53731f,0x3e9e377a,0x3ed1c759,0xbf579b8c,0xbf5b941a,0x3f0172c3,0x3f187fc0,0xbf5f5be6,0xbf62f219,0x3f2dc5e3,0x3f4105b8,0xbf6655e7,0xbf698690,0x3f5205d4,0x3f609384,
0xbf737871,0xbf766377,0x3f167918,0x3f2dc5e3,0xbf78ed3c,0xbf7b14be,0x3f42a9f7,0x3f54db31,0xbf7cd925,0xbf7e39bc,0x3f641901,0x3f702d4f,0xbf7f35f9,0xbf7fcd79,0x3f78ed3c,0x3f7e39bc,
0xbf800000,0xbf7fb10f,0x3f4f1bbd,0x3f609384,0xbf7ec46d,0xbf7d3aac,0x3f6e641a,0x3f7853f8,0xbf7b14be,0xbf7853f8,0x3f7e39bc,0x3f7ffcd7,0xbf74fa0b,0xbf710908,0x3f7d95f4,0x3f770f11,
0xbf737871,0xbf6e641a,0x3f737871,0x3f7c0361,0xbf687c12,0xbf61c598,0x3f7fcd79,0x3f7ec46d,0xbf5a46a0,0xbf5205d4,0x3f78ed3c,0x3f6e641a,0xbf490a88,0xbf3f5cb5,0x3f5f5be6,0x3f4c1d35,
0xbf4f1bbd,0xbf444969,0x3f800000,0x3f7d3aac,0xbf3889dc,0xbf2beb4a,0x3f74fa0b,0x3f676bd8,0xbf1e7cf1,0xbf104f0e,0x3f54db31,0x3f3daef9,0xbf0172c3,0xbee3f40d,0x3f226799,0x3f039c3d,
0x3f803f80,0,0x3f803f80,0,0x3f803f80,0,0x3f803f80,0,0x3f7d3f80,0x3e200000,0x3f643f73,0x3ee83e9e,0x3f353f4f,0x3f353f16,0x3ee83f16,0x3f643f4f,
0x3f733f80,0x3e9e0000,0x3f163f4f,0x3f4f3f16,0x3e9e,0x3f803f73,0xbf16be9e,0x3f4f3f73,0x3f643f80,0x3ee80000,0x3e203f16,0x3f7d3f4f,0xbf35be9e,0x3f353f73,0xbf7dbf73,0xbe203e9e,
0x3f4f3f80,0x3f160000,0xbe9e3e9e,0x3f733f73,0xbf80bf4f,0x3f16,0xbe9ebf4f,0xbf73bf16,0x3f353f80,0x3f350000,0xbf350000,0x3f353f80,0xbf35bf80,0xbf350000,0x3f350000,0xbf35bf80,
0x3f163f80,0x3f4f0000,0xbf73be9e,0x3e9e3f73,0xbf4f,0xbf80bf16,0x3f733f4f,0x3e9ebf16,0x3ee83f80,0x3f640000,0xbf7dbf16,0xbe203f4f,0x3f35be9e,0xbf35bf73,0x3e203f73,0x3f7d3e9e,
0x3e9e3f80,0x3f730000,0xbf4fbf4f,0xbf163f16,0x3f803e9e,0xbf73,0xbf4f3e9e,0x3f163f73,0x3e203f80,0x3f7d0000,0xbee8bf73,0xbf643e9e,0x3f353f4f,0x3f35bf16,0xbf64bf16,0xbee83f4f,
0x3f80,0x3f800000,0xbf80,0xbf800000,0x3f80,0x3f800000,0xbf80,0xbf800000,0xbe203f80,0x3f7d0000,0x3ee8bf73,0xbf64be9e,0xbf353f4f,0x3f353f16,0x3f64bf16,0xbee8bf4f,
0xbe9e3f80,0x3f730000,0x3f4fbf4f,0xbf16bf16,0xbf803e9e,0x3f73,0x3f4f3e9e,0x3f16bf73,0xbee83f80,0x3f640000,0x3f7dbf16,0xbe20bf4f,0xbf35be9e,0xbf353f73,0xbe203f73,0x3f7dbe9e,
0xbf163f80,0x3f4f0000,0x3f73be9e,0x3e9ebf73,0xbf4f,0xbf803f16,0xbf733f4f,0x3e9e3f16,0xbf353f80,0x3f350000,0x3f350000,0x3f35bf80,0x3f35bf80,0xbf350000,0xbf350000,0xbf353f80,
0xbf4f3f80,0x3f160000,0x3e9e3e9e,0x3f73bf73,0x3f80bf4f,0xbf16,0x3e9ebf4f,0xbf733f16,0xbf643f80,0x3ee80000,0xbe203f16,0x3f7dbf4f,0x3f35be9e,0x3f35bf73,0x3f7dbf73,0xbe20be9e,
0xbf733f80,0x3e9e0000,0xbf163f4f,0x3f4fbf16,0x3e9e,0x3f80bf73,0x3f16be9e,0x3f4fbf73,0xbf7d3f80,0x3e200000,0xbf643f73,0x3ee8be9e,0xbf353f4f,0x3f35bf16,0xbee83f16,0x3f64bf4f,
0xbf803f80,0,0xbf803f80,0,0xbf803f80,0,0xbf803f80,0,0xbf7d3f80,0xbe200000,0xbf643f73,0xbee83e9e,0xbf353f4f,0xbf353f16,0xbee83f16,0xbf643f4f,
0xbf733f80,0xbe9e0000,0xbf163f4f,0xbf4f3f16,0x3e9e,0xbf803f73,0x3f16be9e,0xbf4f3f73,0xbf643f80,0xbee80000,0xbe203f16,0xbf7d3f4f,0x3f35be9e,0xbf353f73,0x3f7dbf73,0x3e203e9e,
0xbf4f3f80,0xbf160000,0x3e9e3e9e,0xbf733f73,0x3f80bf4f,0x3f16,0x3e9ebf4f,0x3f73bf16,0xbf353f80,0xbf350000,0x3f350000,0xbf353f80,0x3f35bf80,0x3f350000,0xbf350000,0x3f35bf80,
0xbf163f80,0xbf4f0000,0x3f73be9e,0xbe9e3f73,0xbf4f,0x3f80bf16,0xbf733f4f,0xbe9ebf16,0xbee83f80,0xbf640000,0x3f7dbf16,0x3e203f4f,0xbf35be9e,0x3f35bf73,0xbe203f73,0xbf7d3e9e,
0xbe9e3f80,0xbf730000,0x3f4fbf4f,0x3f163f16,0xbf803e9e,0xbf73,0x3f4f3e9e,0xbf163f73,0xbe203f80,0xbf7d0000,0x3ee8bf73,0x3f643e9e,0xbf353f4f,0xbf35bf16,0x3f64bf16,0x3ee83f4f,
0x3f80,0xbf800000,0xbf80,0x3f800000,0x3f80,0xbf800000,0xbf80,0x3f800000,0x3e203f80,0xbf7d0000,0xbee8bf73,0x3f64be9e,0x3f353f4f,0xbf353f16,0xbf64bf16,0x3ee8bf4f,
0x3e9e3f80,0xbf730000,0xbf4fbf4f,0x3f16bf16,0x3f803e9e,0x3f73,0xbf4f3e9e,0xbf16bf73,0x3ee83f80,0xbf640000,0xbf7dbf16,0x3e20bf4f,0x3f35be9e,0x3f353f73,0x3e203f73,0xbf7dbe9e,
0x3f163f80,0xbf4f0000,0xbf73be9e,0xbe9ebf73,0xbf4f,0x3f803f16,0x3f733f4f,0xbe9e3f16,0x3f353f80,0xbf350000,0xbf350000,0xbf35bf80,0xbf35bf80,0x3f350000,0x3f350000,0x3f353f80,
0x3f4f3f80,0xbf160000,0xbe9e3e9e,0xbf73bf73,0xbf80bf4f,0xbf16,0xbe9ebf4f,0x3f733f16,0x3f643f80,0xbee80000,0x3e203f16,0xbf7dbf4f,0xbf35be9e,0xbf35bf73,0xbf7dbf73,0x3e20be9e,
0x3f733f80,0xbe9e0000,0x3f163f4f,0xbf4fbf16,0x3e9e,0xbf80bf73,0xbf16be9e,0xbf4fbf73,0x3f7d3f80,0xbe200000,0x3f643f73,0xbee8be9e,0x3f353f4f,0xbf35bf16,0x3ee83f16,0xbf64bf4f,
0x3f803f80,0,0x3f803f80,0,0x3f803f80,0,0x3f803f80,0,0x3e203e9e,0x3f7d3f73,0xbe200000,0x3f7d3f80,0xbee8be9e,0x3f643f73,0xbf35bf16,0x3f353f4f,
0xbf73bf4f,0x3e9e3f16,0xbf73bf80,0xbe9e0000,0xbf16bf4f,0xbf4fbf16,0xbe9e,0xbf80bf73,0xbee8bf4f,0xbf64bf16,0x3ee80000,0xbf64bf80,0x3f7d3f4f,0xbe20bf16,0x3f353f73,0x3f353e9e,
0x3f4f3e9e,0xbf16bf73,0x3f4f3f80,0x3f160000,0xbe9e3e9e,0x3f733f73,0xbf80bf4f,0x3f16,0x3f353f80,0x3f350000,0xbf350000,0x3f353f80,0xbf35bf80,0xbf350000,0x3f350000,0xbf35bf80,
0xbf163e9e,0x3f4f3f73,0xbf16bf80,0xbf4f0000,0x3f733e9e,0xbe9ebf73,0x3f4f,0x3f803f16,0xbf64bf4f,0xbee83f16,0x3f640000,0xbee8bf80,0xbe203f4f,0x3f7d3f16,0xbf35bf73,0xbf353e9e,
0x3e9ebf4f,0xbf73bf16,0x3e9e3f80,0x3f730000,0xbf4fbf4f,0xbf163f16,0x3f803e9e,0xbf73,0x3f7d3e9e,0x3e20bf73,0xbf7d0000,0x3e203f80,0x3f64be9e,0xbee8bf73,0xbf353f16,0x3f353f4f,
0x3f80,0x3f800000,0xbf80,0xbf800000,0x3f80,0x3f800000,0xbf80,0xbf800000,0xbf7d3e9e,0x3e203f73,0x3f7d0000,0x3e20bf80,0xbf64be9e,0xbee83f73,0x3f353f16,0x3f35bf4f,
0xbe9ebf4f,0xbf733f16,0xbe9e3f80,0x3f730000,0x3f4fbf4f,0xbf16bf16,0xbf803e9e,0x3f73,0x3f64bf4f,0xbee8bf16,0xbf640000,0xbee83f80,0x3e203f4f,0x3f7dbf16,0x3f35bf73,0xbf35be9e,
0x3f163e9e,0x3f4fbf73,0x3f16bf80,0xbf4f0000,0xbf733e9e,0xbe9e3f73,0x3f4f,0x3f80bf16,0xbf353f80,0x3f350000,0x3f350000,0x3f35bf80,0x3f35bf80,0xbf350000,0xbf350000,0xbf353f80,
0xbf4f3e9e,0xbf163f73,0xbf4f3f80,0x3f160000,0x3e9e3e9e,0x3f73bf73,0x3f80bf4f,0xbf16,0x3ee8bf4f,0xbf643f16,0xbee80000,0xbf643f80,0xbf7d3f4f,0xbe203f16,0xbf353f73,0x3f35be9e,
0x3f73bf4f,0x3e9ebf16,0x3f73bf80,0xbe9e0000,0x3f16bf4f,0xbf4f3f16,0xbe9e,0xbf803f73,0xbe203e9e,0x3f7dbf73,0x3e200000,0x3f7dbf80,0x3ee8be9e,0x3f64bf73,0x3f35bf16,0x3f35bf4f,
0xbf803f80,0,0xbf803f80,0,0xbf803f80,0,0xbf803f80,0,0xbe203e9e,0xbf7d3f73,0x3e200000,0xbf7d3f80,0x3ee8be9e,0xbf643f73,0x3f35bf16,0xbf353f4f,
0x3f73bf4f,0xbe9e3f16,0x3f73bf80,0x3e9e0000,0x3f16bf4f,0x3f4fbf16,0xbe9e,0x3f80bf73,0x3ee8bf4f,0x3f64bf16,0xbee80000,0x3f64bf80,0xbf7d3f4f,0x3e20bf16,0xbf353f73,0xbf353e9e,
0xbf4f3e9e,0x3f16bf73,0xbf4f3f80,0xbf160000,0x3e9e3e9e,0xbf733f73,0x3f80bf4f,0x3f16,0xbf353f80,0xbf350000,0x3f350000,0xbf353f80,0x3f35bf80,0x3f350000,0xbf350000,0x3f35bf80,
0x3f163e9e,0xbf4f3f73,0x3f16bf80,0x3f4f0000,0xbf733e9e,0x3e9ebf73,0x3f4f,0xbf803f16,0x3f64bf4f,0x3ee83f16,0xbf640000,0x3ee8bf80,0x3e203f4f,0xbf7d3f16,0x3f35bf73,0x3f353e9e,
0xbe9ebf4f,0x3f73bf16,0xbe9e3f80,0xbf730000,0x3f4fbf4f,0x3f163f16,0xbf803e9e,0xbf73,0xbf7d3e9e,0xbe20bf73,0x3f7d0000,0xbe203f80,0xbf64be9e,0x3ee8bf73,0x3f353f16,0xbf353f4f,
0x3f80,0xbf800000,0xbf80,0x3f800000,0x3f80,0xbf800000,0xbf80,0x3f800000,0x3f7d3e9e,0xbe203f73,0xbf7d0000,0xbe20bf80,0x3f64be9e,0x3ee83f73,0xbf353f16,0xbf35bf4f,
0x3e9ebf4f,0x3f733f16,0x3e9e3f80,0xbf730000,0xbf4fbf4f,0x3f16bf16,0x3f803e9e,0x3f73,0xbf64bf4f,0x3ee8bf16,0x3f640000,0x3ee83f80,0xbe203f4f,0xbf7dbf16,0xbf35bf73,0x3f35be9e,
0xbf163e9e,0xbf4fbf73,0xbf16bf80,0x3f4f0000,0x3f733e9e,0x3e9e3f73,0x3f4f,0xbf80bf16,0x3f353f80,0xbf350000,0xbf350000,0xbf35bf80,0xbf35bf80,0x3f350000,0x3f350000,0x3f353f80,
0x3f4f3e9e,0x3f163f73,0x3f4f3f80,0xbf160000,0xbe9e3e9e,0xbf73bf73,0xbf80bf4f,0xbf16,0xbee8bf4f,0x3f643f16,0x3ee80000,0x3f643f80,0x3f7d3f4f,0x3e203f16,0x3f353f73,0xbf35be9e,
0xbf73bf4f,0xbe9ebf16,0xbf73bf80,0x3e9e0000,0xbf16bf4f,0x3f4f3f16,0xbe9e,0x3f803f73,0x3e203e9e,0xbf7dbf73,0xbe200000,0xbf7dbf80,0xbee8be9e,0xbf64bf73,0xbf35bf16,0xbf35bf4f,
0x3f803f80,0,0x3f803f80,0,0x3f803f80,0,0x3f803f80,0,0xbf64bf4f,0x3ee83f16,0xbf7dbf73,0x3e203e9e,0xbf7dbf80,0xbe200000,0xbf64bf73,0xbee8be9e,
0x3f163e9e,0xbf4fbf73,0x3f733f4f,0xbe9ebf16,0x3f733f80,0x3e9e0000,0x3f163f4f,0x3f4f3f16,0xbe203e9e,0x3f7d3f73,0xbf64bf16,0x3ee83f4f,0xbf64bf80,0xbee80000,0xbe20bf16,0xbf7dbf4f,
0xbe9ebf4f,0xbf73bf16,0x3f4f3e9e,0xbf16bf73,0x3f4f3f80,0x3f160000,0xbe9e3e9e,0x3f733f73,0x3f353f80,0x3f350000,0xbf350000,0x3f353f80,0xbf35bf80,0xbf350000,0x3f350000,0xbf35bf80,
0xbf73bf4f,0xbe9e3f16,0x3f16be9e,0xbf4fbf73,0x3f163f80,0x3f4f0000,0xbf73be9e,0x3e9e3f73,0x3f7d3e9e,0xbe20bf73,0xbee83f16,0x3f643f4f,0xbee8bf80,0xbf640000,0x3f7d3f16,0x3e20bf4f,
0xbf4f3e9e,0x3f163f73,0x3e9ebf4f,0xbf73bf16,0x3e9e3f80,0x3f730000,0xbf4fbf4f,0xbf163f16,0x3ee8bf4f,0xbf64bf16,0xbe203f73,0x3f7d3e9e,0xbe20bf80,0xbf7d0000,0x3ee83f73,0x3f64be9e,
0x3f80,0x3f800000,0xbf80,0xbf800000,0x3f80,0x3f800000,0xbf80,0xbf800000,0xbee8bf4f,0xbf643f16,0x3e203f73,0x3f7dbe9e,0x3e20bf80,0xbf7d0000,0xbee83f73,0x3f643e9e,
0x3f4f3e9e,0x3f16bf73,0xbe9ebf4f,0xbf733f16,0xbe9e3f80,0x3f730000,0x3f4fbf4f,0xbf16bf16,0xbf7d3e9e,0xbe203f73,0x3ee83f16,0x3f64bf4f,0x3ee8bf80,0xbf640000,0xbf7d3f16,0x3e203f4f,
0x3f73bf4f,0xbe9ebf16,0xbf16be9e,0xbf4f3f73,0xbf163f80,0x3f4f0000,0x3f73be9e,0x3e9ebf73,0xbf353f80,0x3f350000,0x3f350000,0x3f35bf80,0x3f35bf80,0xbf350000,0xbf350000,0xbf353f80,
0x3e9ebf4f,0xbf733f16,0xbf4f3e9e,0xbf163f73,0xbf4f3f80,0x3f160000,0x3e9e3e9e,0x3f73bf73,0x3e203e9e,0x3f7dbf73,0x3f64bf16,0x3ee8bf4f,0x3f64bf80,0xbee80000,0x3e20bf16,0xbf7d3f4f,
0xbf163e9e,0xbf4f3f73,0xbf733f4f,0xbe9e3f16,0xbf733f80,0x3e9e0000,0xbf163f4f,0x3f4fbf16,0x3f64bf4f,0x3ee8bf16,0x3f7dbf73,0x3e20be9e,0x3f7dbf80,0xbe200000,0x3f64bf73,0xbee83e9e,
0xbf803f80,0,0xbf803f80,0,0xbf803f80,0,0xbf803f80,0,0x3f64bf4f,0xbee83f16,0x3f7dbf73,0xbe203e9e,0x3f7dbf80,0x3e200000,0x3f64bf73,0x3ee8be9e,
0xbf163e9e,0x3f4fbf73,0xbf733f4f,0x3e9ebf16,0xbf733f80,0xbe9e0000,0xbf163f4f,0xbf4f3f16,0x3e203e9e,0xbf7d3f73,0x3f64bf16,0xbee83f4f,0x3f64bf80,0x3ee80000,0x3e20bf16,0x3f7dbf4f,
0x3e9ebf4f,0x3f73bf16,0xbf4f3e9e,0x3f16bf73,0xbf4f3f80,0xbf160000,0x3e9e3e9e,0xbf733f73,0xbf353f80,0xbf350000,0x3f350000,0xbf353f80,0x3f35bf80,0x3f350000,0xbf350000,0x3f35bf80,
0x3f73bf4f,0x3e9e3f16,0xbf16be9e,0x3f4fbf73,0xbf163f80,0xbf4f0000,0x3f73be9e,0xbe9e3f73,0xbf7d3e9e,0x3e20bf73,0x3ee83f16,0xbf643f4f,0x3ee8bf80,0x3f640000,0xbf7d3f16,0xbe20bf4f,
0x3f4f3e9e,0xbf163f73,0xbe9ebf4f,0x3f73bf16,0xbe9e3f80,0xbf730000,0x3f4fbf4f,0x3f163f16,0xbee8bf4f,0x3f64bf16,0x3e203f73,0xbf7d3e9e,0x3e20bf80,0x3f7d0000,0xbee83f73,0xbf64be9e,
0x3f80,0xbf800000,0xbf80,0x3f800000,0x3f80,0xbf800000,0xbf80,0x3f800000,0x3ee8bf4f,0x3f643f16,0xbe203f73,0xbf7dbe9e,0xbe20bf80,0x3f7d0000,0x3ee83f73,0xbf643e9e,
0xbf4f3e9e,0xbf16bf73,0x3e9ebf4f,0x3f733f16,0x3e9e3f80,0xbf730000,0xbf4fbf4f,0x3f16bf16,0x3f7d3e9e,0x3e203f73,0xbee83f16,0xbf64bf4f,0xbee8bf80,0x3f640000,0x3f7d3f16,0xbe203f4f,
0xbf73bf4f,0x3e9ebf16,0x3f16be9e,0x3f4f3f73,0x3f163f80,0xbf4f0000,0xbf73be9e,0xbe9ebf73,0x3f353f80,0xbf350000,0xbf350000,0xbf35bf80,0xbf35bf80,0x3f350000,0x3f350000,0x3f353f80,
0xbe9ebf4f,0x3f733f16,0x3f4f3e9e,0x3f163f73,0x3f4f3f80,0xbf160000,0xbe9e3e9e,0xbf73bf73,0xbe203e9e,0xbf7dbf73,0xbf64bf16,0xbee8bf4f,0xbf64bf80,0x3ee80000,0xbe20bf16,0x3f7d3f4f,
0x3f163e9e,0x3f4f3f73,0x3f733f4f,0x3e9e3f16,0x3f733f80,0xbe9e0000,0x3f163f4f,0xbf4fbf16,0xbf64bf4f,0xbee8bf16,0xbf7dbf73,0xbe20be9e,0xbf7dbf80,0x3e200000,0xbf64bf73,0x3ee83e9e,
0x3f803f80,0,0x3f803f80,0,0x3f803f80,0,0x3f803f80,0,0xbf35bf4f,0xbf35bf16,0xbee8bf16,0xbf64bf4f,0xbe20be9e,0xbf7dbf73,0x3e200000,0xbf7dbf80,
0x3e9e,0x3f803f73,0xbf16be9e,0x3f4f3f73,0xbf73bf4f,0x3e9e3f16,0xbf73bf80,0xbe9e0000,0x3f353e9e,0xbf35bf73,0x3f7d3f73,0x3e20be9e,0x3ee83f4f,0x3f643f16,0xbee80000,0x3f643f80,
0xbf80bf4f,0x3f16,0xbe9ebf4f,0xbf73bf16,0x3f4f3e9e,0xbf16bf73,0x3f4f3f80,0x3f160000,0x3f353f80,0x3f350000,0xbf350000,0x3f353f80,0xbf35bf80,0xbf350000,0x3f350000,0xbf35bf80,
0xbf4f,0xbf80bf16,0x3f733f4f,0x3e9ebf16,0xbf163e9e,0x3f4f3f73,0xbf16bf80,0xbf4f0000,0xbf353e9e,0x3f353f73,0xbe20bf73,0xbf7dbe9e,0x3f643f4f,0x3ee8bf16,0xbf640000,0x3ee83f80,
0x3f803e9e,0xbf73,0xbf4f3e9e,0x3f163f73,0x3e9ebf4f,0xbf73bf16,0x3e9e3f80,0x3f730000,0xbf35bf4f,0xbf353f16,0x3f643f16,0x3ee8bf4f,0xbf7dbe9e,0xbe203f73,0x3f7d0000,0xbe20bf80,
0x3f80,0x3f800000,0xbf80,0xbf800000,0x3f80,0x3f800000,0xbf80,0xbf800000,0x3f35bf4f,0xbf35bf16,0xbf643f16,0x3ee83f4f,0x3f7dbe9e,0xbe20bf73,0xbf7d0000,0xbe203f80,
0xbf803e9e,0x3f73,0x3f4f3e9e,0x3f16bf73,0xbe9ebf4f,0xbf733f16,0xbe9e3f80,0x3f730000,0x3f353e9e,0x3f35bf73,0x3e20bf73,0xbf7d3e9e,0xbf643f4f,0x3ee83f16,0x3f640000,0x3ee8bf80,
0xbf4f,0xbf803f16,0xbf733f4f,0x3e9e3f16,0x3f163e9e,0x3f4fbf73,0x3f16bf80,0xbf4f0000,0xbf353f80,0x3f350000,0x3f350000,0x3f35bf80,0x3f35bf80,0xbf350000,0xbf350000,0xbf353f80,
0x3f80bf4f,0xbf16,0x3e9ebf4f,0xbf733f16,0xbf4f3e9e,0xbf163f73,0xbf4f3f80,0x3f160000,0xbf353e9e,0xbf353f73,0xbf7d3f73,0x3e203e9e,0xbee83f4f,0x3f64bf16,0x3ee80000,0x3f64bf80,
0x3e9e,0x3f80bf73,0x3f16be9e,0x3f4fbf73,0x3f73bf4f,0x3e9ebf16,0x3f73bf80,0xbe9e0000,0x3f35bf4f,0xbf353f16,0x3ee8bf16,0xbf643f4f,0x3e20be9e,0xbf7d3f73,0xbe200000,0xbf7d3f80,
0xbf803f80,0,0xbf803f80,0,0xbf803f80,0,0xbf803f80,0,0x3f35bf4f,0x3f35bf16,0x3ee8bf16,0x3f64bf4f,0x3e20be9e,0x3f7dbf73,0xbe200000,0x3f7dbf80,
0x3e9e,0xbf803f73,0x3f16be9e,0xbf4f3f73,0x3f73bf4f,0xbe9e3f16,0x3f73bf80,0x3e9e0000,0xbf353e9e,0x3f35bf73,0xbf7d3f73,0xbe20be9e,0xbee83f4f,0xbf643f16,0x3ee80000,0xbf643f80,
0x3f80bf4f,0x3f16,0x3e9ebf4f,0x3f73bf16,0xbf4f3e9e,0x3f16bf73,0xbf4f3f80,0xbf160000,0xbf353f80,0xbf350000,0x3f350000,0xbf353f80,0x3f35bf80,0x3f350000,0xbf350000,0x3f35bf80,
0xbf4f,0x3f80bf16,0xbf733f4f,0xbe9ebf16,0x3f163e9e,0xbf4f3f73,0x3f16bf80,0x3f4f0000,0x3f353e9e,0xbf353f73,0x3e20bf73,0x3f7dbe9e,0xbf643f4f,0xbee8bf16,0x3f640000,0xbee83f80,
0xbf803e9e,0xbf73,0x3f4f3e9e,0xbf163f73,0xbe9ebf4f,0x3f73bf16,0xbe9e3f80,0xbf730000,0x3f35bf4f,0x3f353f16,0xbf643f16,0xbee8bf4f,0x3f7dbe9e,0x3e203f73,0xbf7d0000,0x3e20bf80,
0x3f80,0xbf800000,0xbf80,0x3f800000,0x3f80,0xbf800000,0xbf80,0x3f800000,0xbf35bf4f,0x3f35bf16,0x3f643f16,0xbee83f4f,0xbf7dbe9e,0x3e20bf73,0x3f7d0000,0x3e203f80,
0x3f803e9e,0x3f73,0xbf4f3e9e,0xbf16bf73,0x3e9ebf4f,0x3f733f16,0x3e9e3f80,0xbf730000,0xbf353e9e,0xbf35bf73,0xbe20bf73,0x3f7d3e9e,0x3f643f4f,0xbee83f16,0xbf640000,0xbee8bf80,
0xbf4f,0x3f803f16,0x3f733f4f,0xbe9e3f16,0xbf163e9e,0xbf4fbf73,0xbf16bf80,0x3f4f0000,0x3f353f80,0xbf350000,0xbf350000,0xbf35bf80,0xbf35bf80,0x3f350000,0x3f350000,0x3f353f80,
0xbf80bf4f,0xbf16,0xbe9ebf4f,0x3f733f16,0x3f4f3e9e,0x3f163f73,0x3f4f3f80,0xbf160000,0x3f353e9e,0x3f353f73,0x3f7d3f73,0xbe203e9e,0x3ee83f4f,0xbf64bf16,0xbee80000,0xbf64bf80,
0x3e9e,0xbf80bf73,0xbf16be9e,0xbf4fbf73,0xbf73bf4f,0xbe9ebf16,0xbf73bf80,0x3e9e0000,0xbf35bf4f,0x3f353f16,0xbee8bf16,0x3f643f4f,0xbe20be9e,0x3f7d3f73,0x3e200000,0x3f7d3f80,
0x3f803f80,0,0x3f803f80,0,0x3f803f80,0,0x3f803f80,0,0x3ee83e9e,0xbf64bf73,0x3f353f16,0xbf35bf4f,0x3f643f4f,0xbee8bf16,0x3f7d3f73,0xbe20be9e,
0xbf16bf4f,0xbf4fbf16,0xbe9e,0xbf80bf73,0x3f163e9e,0xbf4fbf73,0x3f733f4f,0xbe9ebf16,0xbf7dbf4f,0x3e203f16,0xbf35bf73,0xbf35be9e,0x3e20be9e,0xbf7dbf73,0x3f643f16,0xbee8bf4f,
0xbe9e3e9e,0x3f733f73,0xbf80bf4f,0x3f16,0xbe9ebf4f,0xbf73bf16,0x3f4f3e9e,0xbf16bf73,0x3f353f80,0x3f350000,0xbf350000,0x3f353f80,0xbf35bf80,0xbf350000,0x3f350000,0xbf35bf80,
0x3f733e9e,0xbe9ebf73,0x3f4f,0x3f803f16,0xbf73bf4f,0xbe9e3f16,0x3f16be9e,0xbf4fbf73,0x3e20bf4f,0xbf7dbf16,0x3f353f73,0x3f35be9e,0xbf7dbe9e,0x3e203f73,0x3ee8bf16,0xbf64bf4f,
0xbf4fbf4f,0xbf163f16,0x3f803e9e,0xbf73,0xbf4f3e9e,0x3f163f73,0x3e9ebf4f,0xbf73bf16,0xbf643e9e,0x3ee83f73,0x3f35bf16,0xbf35bf4f,0xbee83f4f,0x3f643f16,0x3e20bf73,0xbf7dbe9e,
0x3f80,0x3f800000,0xbf80,0xbf800000,0x3f80,0x3f800000,0xbf80,0xbf800000,0x3f643e9e,0x3ee8bf73,0xbf35bf16,0xbf353f4f,0x3ee83f4f,0x3f64bf16,0xbe20bf73,0xbf7d3e9e,
0x3f4fbf4f,0xbf16bf16,0xbf803e9e,0x3f73,0x3f4f3e9e,0x3f16bf73,0xbe9ebf4f,0xbf733f16,0xbe20bf4f,0xbf7d3f16,0xbf353f73,0x3f353e9e,0x3f7dbe9e,0x3e20bf73,0xbee8bf16,0xbf643f4f,
0xbf733e9e,0xbe9e3f73,0x3f4f,0x3f80bf16,0x3f73bf4f,0xbe9ebf16,0xbf16be9e,0xbf4f3f73,0xbf353f80,0x3f350000,0x3f350000,0x3f35bf80,0x3f35bf80,0xbf350000,0xbf350000,0xbf353f80,
0x3e9e3e9e,0x3f73bf73,0x3f80bf4f,0xbf16,0x3e9ebf4f,0xbf733f16,0xbf4f3e9e,0xbf163f73,0x3f7dbf4f,0x3e20bf16,0x3f35bf73,0xbf353e9e,0xbe20be9e,0xbf7d3f73,0xbf643f16,0xbee83f4f,
0x3f16bf4f,0xbf4f3f16,0xbe9e,0xbf803f73,0xbf163e9e,0xbf4f3f73,0xbf733f4f,0xbe9e3f16,0xbee83e9e,0xbf643f73,0xbf353f16,0xbf353f4f,0xbf643f4f,0xbee83f16,0xbf7d3f73,0xbe203e9e,
0xbf803f80,0,0xbf803f80,0,0xbf803f80,0,0xbf803f80,0,0xbee83e9e,0x3f64bf73,0xbf353f16,0x3f35bf4f,0xbf643f4f,0x3ee8bf16,0xbf7d3f73,0x3e20be9e,
0x3f16bf4f,0x3f4fbf16,0xbe9e,0x3f80bf73,0xbf163e9e,0x3f4fbf73,0xbf733f4f,0x3e9ebf16,0x3f7dbf4f,0xbe203f16,0x3f35bf73,0x3f35be9e,0xbe20be9e,0x3f7dbf73,0xbf643f16,0x3ee8bf4f,
0x3e9e3e9e,0xbf733f73,0x3f80bf4f,0x3f16,0x3e9ebf4f,0x3f73bf16,0xbf4f3e9e,0x3f16bf73,0xbf353f80,0xbf350000,0x3f350000,0xbf353f80,0x3f35bf80,0x3f350000,0xbf350000,0x3f35bf80,
0xbf733e9e,0x3e9ebf73,0x3f4f,0xbf803f16,0x3f73bf4f,0x3e9e3f16,0xbf16be9e,0x3f4fbf73,0xbe20bf4f,0x3f7dbf16,0xbf353f73,0xbf35be9e,0x3f7dbe9e,0xbe203f73,0xbee8bf16,0x3f64bf4f,
0x3f4fbf4f,0x3f163f16,0xbf803e9e,0xbf73,0x3f4f3e9e,0xbf163f73,0xbe9ebf4f,0x3f73bf16,0x3f643e9e,0xbee83f73,0xbf35bf16,0x3f35bf4f,0x3ee83f4f,0xbf643f16,0xbe20bf73,0x3f7dbe9e,
0x3f80,0xbf800000,0xbf80,0x3f800000,0x3f80,0xbf800000,0xbf80,0x3f800000,0xbf643e9e,0xbee8bf73,0x3f35bf16,0x3f353f4f,0xbee83f4f,0xbf64bf16,0x3e20bf73,0x3f7d3e9e,
0xbf4fbf4f,0x3f16bf16,0x3f803e9e,0x3f73,0xbf4f3e9e,0xbf16bf73,0x3e9ebf4f,0x3f733f16,0x3e20bf4f,0x3f7d3f16,0x3f353f73,0xbf353e9e,0xbf7dbe9e,0xbe20bf73,0x3ee8bf16,0x3f643f4f,
0x3f733e9e,0x3e9e3f73,0x3f4f,0xbf80bf16,0xbf73bf4f,0x3e9ebf16,0x3f16be9e,0x3f4f3f73,0x3f353f80,0xbf350000,0xbf350000,0xbf35bf80,0xbf35bf80,0x3f350000,0x3f350000,0x3f353f80,
0xbe9e3e9e,0xbf73bf73,0xbf80bf4f,0xbf16,0xbe9ebf4f,0x3f733f16,0x3f4f3e9e,0x3f163f73,0xbf7dbf4f,0xbe20bf16,0xbf35bf73,0x3f353e9e,0x3e20be9e,0x3f7d3f73,0x3f643f16,0x3ee83f4f,
0xbf16bf4f,0x3f4f3f16,0xbe9e,0x3f803f73,0x3f163e9e,0x3f4f3f73,0x3f733f4f,0x3e9e3f16,0x3ee83e9e,0x3f643f73,0x3f353f16,0x3f353f4f,0x3f643f4f,0x3ee83f16,0x3f7d3f73,0x3e203e9e,
0x3f803f80,0x3f80,0xbf803f80,0x3f80,0x3f803f80,0xbf80,0xbf803f80,0xbf80,0x3f803f80,0x3f80,0xbf803f80,0x3f80,0x3f803f80,0xbf80,0xbf803f80,0xbf80,
0x3f7b3f80,0xbe483f80,0xbf7b3f80,0x3e483f80,0x3f553f6d,0x3f0ebf6d,0xbf553f6d,0xbf0ebf6d,0x3f0e3f35,0xbf553f35,0xbf0e3f35,0x3f553f35,0x3e483ec4,0x3f7bbec4,0xbe483ec4,0xbf7bbec4,
0x3f6d3f80,0xbec43f80,0xbf6d3f80,0x3ec43f80,0x3ec43f35,0x3f6dbf35,0xbec43f35,0xbf6dbf35,0xbec40000,0xbf6d0000,0x3ec40000,0x3f6d0000,0xbf6dbf35,0x3ec43f35,0x3f6dbf35,0xbec43f35,
0x3f553f80,0xbf0e3f80,0xbf553f80,0x3f0e3f80,0xbe483ec4,0x3f7bbec4,0x3e483ec4,0xbf7bbec4,0xbf7bbf35,0xbe48bf35,0x3f7bbf35,0x3e48bf35,0xbf0ebf6d,0xbf553f6d,0x3f0ebf6d,0x3f553f6d,
0x3f353f80,0xbf353f80,0xbf353f80,0x3f353f80,0xbf350000,0x3f350000,0x3f350000,0xbf350000,0xbf35bf80,0x3f35bf80,0x3f35bf80,0xbf35bf80,0x3f350000,0xbf350000,0xbf350000,0x3f350000,
0x3f0e3f80,0xbf553f80,0xbf0e3f80,0x3f553f80,0xbf7bbec4,0x3e483ec4,0x3f7bbec4,0xbe483ec4,0x3e48bf35,0x3f7bbf35,0xbe48bf35,0xbf7bbf35,0x3f553f6d,0x3f0ebf6d,0xbf553f6d,0xbf0ebf6d,
0x3ec43f80,0xbf6d3f80,0xbec43f80,0x3f6d3f80,0xbf6dbf35,0xbec43f35,0x3f6dbf35,0x3ec43f35,0x3f6d0000,0x3ec40000,0xbf6d0000,0xbec40000,0xbec43f35,0x3f6dbf35,0x3ec43f35,0xbf6dbf35,
0x3e483f80,0xbf7b3f80,0xbe483f80,0x3f7b3f80,0xbf0ebf6d,0xbf553f6d,0x3f0ebf6d,0x3f553f6d,0x3f553f35,0xbf0e3f35,0xbf553f35,0x3f0e3f35,0xbf7bbec4,0xbe483ec4,0x3f7bbec4,0x3e483ec4,
0x3f803f80,0x3f80,0xbf803f80,0x3f80,0x3f803f80,0xbf80,0xbf803f80,0xbf80,0x3f803f80,0x3f80,0xbf803f80,0x3f80,0x3f803f80,0xbf80,0xbf803f80,0xbf80,
0xbe480000,0xbf7b0000,0x3e480000,0x3f7b0000,0xbf0ebec4,0x3f553ec4,0x3f0ebec4,0xbf553ec4,0xbf55bf35,0xbf0ebf35,0x3f55bf35,0x3f0ebf35,0xbf7bbf6d,0x3e483f6d,0x3f7bbf6d,0xbe483f6d,
0xbf6dbf80,0x3ec4bf80,0x3f6dbf80,0xbec4bf80,0xbec4bf35,0xbf6d3f35,0x3ec4bf35,0x3f6d3f35,0x3ec40000,0x3f6d0000,0xbec40000,0xbf6d0000,0x3f6d3f35,0xbec4bf35,0xbf6d3f35,0x3ec4bf35,
0x3f0e0000,0x3f550000,0xbf0e0000,0xbf550000,0x3f7b3f6d,0x3e48bf6d,0xbf7b3f6d,0xbe48bf6d,0x3e483f35,0xbf7b3f35,0xbe483f35,0x3f7b3f35,0xbf55bec4,0x3f0e3ec4,0x3f55bec4,0xbf0e3ec4,
0x3f353f80,0xbf353f80,0xbf353f80,0x3f353f80,0xbf350000,0x3f350000,0x3f350000,0xbf350000,0xbf35bf80,0x3f35bf80,0x3f35bf80,0xbf35bf80,0x3f350000,0xbf350000,0xbf350000,0x3f350000,
0xbf550000,0xbf0e0000,0x3f550000,0x3f0e0000,0xbe48bf6d,0xbf7b3f6d,0x3e48bf6d,0x3f7b3f6d,0x3f7b3f35,0xbe483f35,0xbf7b3f35,0x3e483f35,0xbf0e3ec4,0x3f55bec4,0x3f0e3ec4,0xbf55bec4,
0xbec4bf80,0x3f6dbf80,0x3ec4bf80,0xbf6dbf80,0x3f6d3f35,0x3ec4bf35,0xbf6d3f35,0xbec4bf35,0xbf6d0000,0xbec40000,0x3f6d0000,0x3ec40000,0x3ec4bf35,0xbf6d3f35,0xbec4bf35,0x3f6d3f35,
0x3f7b0000,0x3e480000,0xbf7b0000,0xbe480000,0xbf553ec4,0x3f0ebec4,0x3f553ec4,0xbf0ebec4,0x3f0ebf35,0x3f55bf35,0xbf0ebf35,0xbf55bf35,0xbe483f6d,0x3f7bbf6d,0x3e483f6d,0xbf7bbf6d,
0x3f803f80,0x3f80,0xbf803f80,0x3f80,0x3f803f80,0xbf80,0xbf803f80,0xbf80,0x3f803f80,0x3f80,0xbf803f80,0x3f80,0x3f803f80,0xbf80,0xbf803f80,0xbf80,
0xbf7bbf80,0x3e48bf80,0x3f7bbf80,0xbe48bf80,0xbf55bf6d,0xbf0e3f6d,0x3f55bf6d,0x3f0e3f6d,0xbf0ebf35,0x3f55bf35,0x3f0ebf35,0xbf55bf35,0xbe48bec4,0xbf7b3ec4,0x3e48bec4,0x3f7b3ec4,
0x3f6d3f80,0xbec43f80,0xbf6d3f80,0x3ec43f80,0x3ec43f35,0x3f6dbf35,0xbec43f35,0xbf6dbf35,0xbec40000,0xbf6d0000,0x3ec40000,0x3f6d0000,0xbf6dbf35,0x3ec43f35,0x3f6dbf35,0xbec43f35,
0xbf55bf80,0x3f0ebf80,0x3f55bf80,0xbf0ebf80,0x3e48bec4,0xbf7b3ec4,0xbe48bec4,0x3f7b3ec4,0x3f7b3f35,0x3e483f35,0xbf7b3f35,0xbe483f35,0x3f0e3f6d,0x3f55bf6d,0xbf0e3f6d,0xbf55bf6d,
0x3f353f80,0xbf353f80,0xbf353f80,0x3f353f80,0xbf350000,0x3f350000,0x3f350000,0xbf350000,0xbf35bf80,0x3f35bf80,0x3f35bf80,0xbf35bf80,0x3f350000,0xbf350000,0xbf350000,0x3f350000,
0xbf0ebf80,0x3f55bf80,0x3f0ebf80,0xbf55bf80,0x3f7b3ec4,0xbe48bec4,0xbf7b3ec4,0x3e48bec4,0xbe483f35,0xbf7b3f35,0x3e483f35,0x3f7b3f35,0xbf55bf6d,0xbf0e3f6d,0x3f55bf6d,0x3f0e3f6d,
0x3ec43f80,0xbf6d3f80,0xbec43f80,0x3f6d3f80,0xbf6dbf35,0xbec43f35,0x3f6dbf35,0x3ec43f35,0x3f6d0000,0x3ec40000,0xbf6d0000,0xbec40000,0xbec43f35,0x3f6dbf35,0x3ec43f35,0xbf6dbf35,
0xbe48bf80,0x3f7bbf80,0x3e48bf80,0xbf7bbf80,0x3f0e3f6d,0x3f55bf6d,0xbf0e3f6d,0xbf55bf6d,0xbf55bf35,0x3f0ebf35,0x3f55bf35,0xbf0ebf35,0x3f7b3ec4,0x3e48bec4,0xbf7b3ec4,0xbe48bec4,
0x3f803f80,0x3f80,0xbf803f80,0x3f80,0x3f803f80,0xbf80,0xbf803f80,0xbf80,0x3f803f80,0x3f80,0xbf803f80,0x3f80,0x3f803f80,0xbf80,0xbf803f80,0xbf80,
0x3e480000,0x3f7b0000,0xbe480000,0xbf7b0000,0x3f0e3ec4,0xbf55bec4,0xbf0e3ec4,0x3f55bec4,0x3f553f35,0x3f0e3f35,0xbf553f35,0xbf0e3f35,0x3f7b3f6d,0xbe48bf6d,0xbf7b3f6d,0x3e48bf6d,
0xbf6dbf80,0x3ec4bf80,0x3f6dbf80,0xbec4bf80,0xbec4bf35,0xbf6d3f35,0x3ec4bf35,0x3f6d3f35,0x3ec40000,0x3f6d0000,0xbec40000,0xbf6d0000,0x3f6d3f35,0xbec4bf35,0xbf6d3f35,0x3ec4bf35,
0xbf0e0000,0xbf550000,0x3f0e0000,0x3f550000,0xbf7bbf6d,0xbe483f6d,0x3f7bbf6d,0x3e483f6d,0xbe48bf35,0x3f7bbf35,0x3e48bf35,0xbf7bbf35,0x3f553ec4,0xbf0ebec4,0xbf553ec4,0x3f0ebec4,
0x3f353f80,0xbf353f80,0xbf353f80,0x3f353f80,0xbf350000,0x3f350000,0x3f350000,0xbf350000,0xbf35bf80,0x3f35bf80,0x3f35bf80,0xbf35bf80,0x3f350000,0xbf350000,0xbf350000,0x3f350000,
0x3f550000,0x3f0e0000,0xbf550000,0xbf0e0000,0x3e483f6d,0x3f7bbf6d,0xbe483f6d,0xbf7bbf6d,0xbf7bbf35,0x3e48bf35,0x3f7bbf35,0xbe48bf35,0x3f0ebec4,0xbf553ec4,0xbf0ebec4,0x3f553ec4,
0xbec4bf80,0x3f6dbf80,0x3ec4bf80,0xbf6dbf80,0x3f6d3f35,0x3ec4bf35,0xbf6d3f35,0xbec4bf35,0xbf6d0000,0xbec40000,0x3f6d0000,0x3ec40000,0x3ec4bf35,0xbf6d3f35,0xbec4bf35,0x3f6d3f35,
0xbf7b0000,0xbe480000,0x3f7b0000,0x3e480000,0x3f55bec4,0xbf0e3ec4,0xbf55bec4,0x3f0e3ec4,0xbf0e3f35,0xbf553f35,0x3f0e3f35,0x3f553f35,0x3e48bf6d,0xbf7b3f6d,0xbe48bf6d,0x3f7b3f6d,
0,0x3f800000,0,0xbf800000,0,0xbf800000,0,0x3f800000,0,0x3f800000,0,0xbf800000,0,0xbf800000,0,0x3f800000,
0x3e480000,0x3f7b0000,0xbe480000,0xbf7b0000,0x3f0e3ec4,0xbf55bec4,0xbf0e3ec4,0x3f55bec4,0x3f553f35,0x3f0e3f35,0xbf553f35,0xbf0e3f35,0x3f7b3f6d,0xbe48bf6d,0xbf7b3f6d,0x3e48bf6d,
0x3ec40000,0x3f6d0000,0xbec40000,0xbf6d0000,0x3f6d3f35,0xbec4bf35,0xbf6d3f35,0x3ec4bf35,0x3f6d3f80,0xbec43f80,0xbf6d3f80,0x3ec43f80,0x3ec43f35,0x3f6dbf35,0xbec43f35,0xbf6dbf35,
0x3f0e0000,0x3f550000,0xbf0e0000,0xbf550000,0x3f7b3f6d,0x3e48bf6d,0xbf7b3f6d,0xbe48bf6d,0x3e483f35,0xbf7b3f35,0xbe483f35,0x3f7b3f35,0xbf55bec4,0x3f0e3ec4,0x3f55bec4,0xbf0e3ec4,
0x3f350000,0x3f350000,0xbf350000,0xbf350000,0x3f353f80,0x3f35bf80,0xbf353f80,0xbf35bf80,0xbf350000,0xbf350000,0x3f350000,0x3f350000,0xbf35bf80,0xbf353f80,0x3f35bf80,0x3f353f80,
0x3f550000,0x3f0e0000,0xbf550000,0xbf0e0000,0x3e483f6d,0x3f7bbf6d,0xbe483f6d,0xbf7bbf6d,0xbf7bbf35,0x3e48bf35,0x3f7bbf35,0xbe48bf35,0x3f0ebec4,0xbf553ec4,0xbf0ebec4,0x3f553ec4,
0x3f6d0000,0x3ec40000,0xbf6d0000,0xbec40000,0xbec43f35,0x3f6dbf35,0x3ec43f35,0xbf6dbf35,0xbec4bf80,0x3f6dbf80,0x3ec4bf80,0xbf6dbf80,0x3f6d3f35,0x3ec4bf35,0xbf6d3f35,0xbec4bf35,
0x3f7b0000,0x3e480000,0xbf7b0000,0xbe480000,0xbf553ec4,0x3f0ebec4,0x3f553ec4,0xbf0ebec4,0x3f0ebf35,0x3f55bf35,0xbf0ebf35,0xbf55bf35,0xbe483f6d,0x3f7bbf6d,0x3e483f6d,0xbf7bbf6d,
0,0x3f800000,0,0xbf800000,0,0xbf800000,0,0x3f800000,0,0x3f800000,0,0xbf800000,0,0xbf800000,0,0x3f800000,
0x3f7b3f80,0xbe483f80,0xbf7b3f80,0x3e483f80,0x3f553f6d,0x3f0ebf6d,0xbf553f6d,0xbf0ebf6d,0x3f0e3f35,0xbf553f35,0xbf0e3f35,0x3f553f35,0x3e483ec4,0x3f7bbec4,0xbe483ec4,0xbf7bbec4,
0xbec40000,0xbf6d0000,0x3ec40000,0x3f6d0000,0xbf6dbf35,0x3ec43f35,0x3f6dbf35,0xbec43f35,0xbf6dbf80,0x3ec4bf80,0x3f6dbf80,0xbec4bf80,0xbec4bf35,0xbf6d3f35,0x3ec4bf35,0x3f6d3f35,
0xbf55bf80,0x3f0ebf80,0x3f55bf80,0xbf0ebf80,0x3e48bec4,0xbf7b3ec4,0xbe48bec4,0x3f7b3ec4,0x3f7b3f35,0x3e483f35,0xbf7b3f35,0xbe483f35,0x3f0e3f6d,0x3f55bf6d,0xbf0e3f6d,0xbf55bf6d,
0x3f350000,0x3f350000,0xbf350000,0xbf350000,0x3f353f80,0x3f35bf80,0xbf353f80,0xbf35bf80,0xbf350000,0xbf350000,0x3f350000,0x3f350000,0xbf35bf80,0xbf353f80,0x3f35bf80,0x3f353f80,
0x3f0e3f80,0xbf553f80,0xbf0e3f80,0x3f553f80,0xbf7bbec4,0x3e483ec4,0x3f7bbec4,0xbe483ec4,0x3e48bf35,0x3f7bbf35,0xbe48bf35,0xbf7bbf35,0x3f553f6d,0x3f0ebf6d,0xbf553f6d,0xbf0ebf6d,
0xbf6d0000,0xbec40000,0x3f6d0000,0x3ec40000,0x3ec4bf35,0xbf6d3f35,0xbec4bf35,0x3f6d3f35,0x3ec43f80,0xbf6d3f80,0xbec43f80,0x3f6d3f80,0xbf6dbf35,0xbec43f35,0x3f6dbf35,0x3ec43f35,
0xbe48bf80,0x3f7bbf80,0x3e48bf80,0xbf7bbf80,0x3f0e3f6d,0x3f55bf6d,0xbf0e3f6d,0xbf55bf6d,0xbf55bf35,0x3f0ebf35,0x3f55bf35,0xbf0ebf35,0x3f7b3ec4,0x3e48bec4,0xbf7b3ec4,0xbe48bec4,
0,0x3f800000,0,0xbf800000,0,0xbf800000,0,0x3f800000,0,0x3f800000,0,0xbf800000,0,0xbf800000,0,0x3f800000,
0xbe480000,0xbf7b0000,0x3e480000,0x3f7b0000,0xbf0ebec4,0x3f553ec4,0x3f0ebec4,0xbf553ec4,0xbf55bf35,0xbf0ebf35,0x3f55bf35,0x3f0ebf35,0xbf7bbf6d,0x3e483f6d,0x3f7bbf6d,0xbe483f6d,
0x3ec40000,0x3f6d0000,0xbec40000,0xbf6d0000,0x3f6d3f35,0xbec4bf35,0xbf6d3f35,0x3ec4bf35,0x3f6d3f80,0xbec43f80,0xbf6d3f80,0x3ec43f80,0x3ec43f35,0x3f6dbf35,0xbec43f35,0xbf6dbf35,
0xbf0e0000,0xbf550000,0x3f0e0000,0x3f550000,0xbf7bbf6d,0xbe483f6d,0x3f7bbf6d,0x3e483f6d,0xbe48bf35,0x3f7bbf35,0x3e48bf35,0xbf7bbf35,0x3f553ec4,0xbf0ebec4,0xbf553ec4,0x3f0ebec4,
0x3f350000,0x3f350000,0xbf350000,0xbf350000,0x3f353f80,0x3f35bf80,0xbf353f80,0xbf35bf80,0xbf350000,0xbf350000,0x3f350000,0x3f350000,0xbf35bf80,0xbf353f80,0x3f35bf80,0x3f353f80,
0xbf550000,0xbf0e0000,0x3f550000,0x3f0e0000,0xbe48bf6d,0xbf7b3f6d,0x3e48bf6d,0x3f7b3f6d,0x3f7b3f35,0xbe483f35,0xbf7b3f35,0x3e483f35,0xbf0e3ec4,0x3f55bec4,0x3f0e3ec4,0xbf55bec4,
0x3f6d0000,0x3ec40000,0xbf6d0000,0xbec40000,0xbec43f35,0x3f6dbf35,0x3ec43f35,0xbf6dbf35,0xbec4bf80,0x3f6dbf80,0x3ec4bf80,0xbf6dbf80,0x3f6d3f35,0x3ec4bf35,0xbf6d3f35,0xbec4bf35,
0xbf7b0000,0xbe480000,0x3f7b0000,0x3e480000,0x3f55bec4,0xbf0e3ec4,0xbf55bec4,0x3f0e3ec4,0xbf0e3f35,0xbf553f35,0x3f0e3f35,0x3f553f35,0x3e48bf6d,0xbf7b3f6d,0xbe48bf6d,0x3f7b3f6d,
0,0x3f800000,0,0xbf800000,0,0xbf800000,0,0x3f800000,0,0x3f800000,0,0xbf800000,0,0xbf800000,0,0x3f800000,
0xbf7bbf80,0x3e48bf80,0x3f7bbf80,0xbe48bf80,0xbf55bf6d,0xbf0e3f6d,0x3f55bf6d,0x3f0e3f6d,0xbf0ebf35,0x3f55bf35,0x3f0ebf35,0xbf55bf35,0xbe48bec4,0xbf7b3ec4,0x3e48bec4,0x3f7b3ec4,
0xbec40000,0xbf6d0000,0x3ec40000,0x3f6d0000,0xbf6dbf35,0x3ec43f35,0x3f6dbf35,0xbec43f35,0xbf6dbf80,0x3ec4bf80,0x3f6dbf80,0xbec4bf80,0xbec4bf35,0xbf6d3f35,0x3ec4bf35,0x3f6d3f35,
0x3f553f80,0xbf0e3f80,0xbf553f80,0x3f0e3f80,0xbe483ec4,0x3f7bbec4,0x3e483ec4,0xbf7bbec4,0xbf7bbf35,0xbe48bf35,0x3f7bbf35,0x3e48bf35,0xbf0ebf6d,0xbf553f6d,0x3f0ebf6d,0x3f553f6d,
0x3f350000,0x3f350000,0xbf350000,0xbf350000,0x3f353f80,0x3f35bf80,0xbf353f80,0xbf35bf80,0xbf350000,0xbf350000,0x3f350000,0x3f350000,0xbf35bf80,0xbf353f80,0x3f35bf80,0x3f353f80,
0xbf0ebf80,0x3f55bf80,0x3f0ebf80,0xbf55bf80,0x3f7b3ec4,0xbe48bec4,0xbf7b3ec4,0x3e48bec4,0xbe483f35,0xbf7b3f35,0x3e483f35,0x3f7b3f35,0xbf55bf6d,0xbf0e3f6d,0x3f55bf6d,0x3f0e3f6d,
0xbf6d0000,0xbec40000,0x3f6d0000,0x3ec40000,0x3ec4bf35,0xbf6d3f35,0xbec4bf35,0x3f6d3f35,0x3ec43f80,0xbf6d3f80,0xbec43f80,0x3f6d3f80,0xbf6dbf35,0xbec43f35,0x3f6dbf35,0x3ec43f35,
0x3e483f80,0xbf7b3f80,0xbe483f80,0x3f7b3f80,0xbf0ebf6d,0xbf553f6d,0x3f0ebf6d,0x3f553f6d,0x3f553f35,0xbf0e3f35,0xbf553f35,0x3f0e3f35,0xbf7bbec4,0xbe483ec4,0x3f7bbec4,0x3e483ec4,
0x3f800000,0x3f800000,0x3f800000,0x3f7ec46d,0x3f800000,0x3f800000,0x3f7b14be,0x3f74fa0b,0x3f800000,0x3f800000,0x3f6c835e,0x3f61c598,0x3f800000,0x3f800000,0x3f54db31,0x3f45e403,
0x3f800000,0x3f7ffb11,0x3f800000,0x3f7e70b0,0x3f7fec43,0x3f7fd397,0x3f79c79d,0x3f721352,0x3f7fb10f,0x3f7f84ab,0x3f676bd8,0x3f59f26a,0x3f7f4e6d,0x3f7f0e58,0x3f49d112,0x3f373a23,
0x3f800000,0x3f7fec43,0x3f800000,0x3f7e1324,0x3f7fb10f,0x3f7f4e6d,0x3f7853f8,0x3f6ed89e,0x3f7ec46d,0x3f7e1324,0x3f61c598,0x3f514d3d,0x3f7d3aac,0x3f7c3b28,0x3f3daef9,0x3f273656,
0x3f800000,0x3f7fd397,0x3f800000,0x3f7dabcc,0x3f7f4e6d,0x3f7e70b0,0x3f76ba07,0x3f6b4b0c,0x3f7d3aac,0x3f7baccd,0x3f5b941a,0x3f47de65,0x3f79c79d,0x3f778bc5,0x3f3085bb,0x3f15f6d9,
0x3f800000,0x3f7fb10f,0x3f800000,0x3f7d3aac,0x3f7ec46d,0x3f7d3aac,0x3f74fa0b,0x3f676bd8,0x3f7b14be,0x3f7853f8,0x3f54db31,0x3f3daef9,0x3f74fa0b,0x3f710908,0x3f226799,0x3f039c3d,
0x3f800000,0x3f7f84ab,0x3f800000,0x3f7cbfc9,0x3f7e1324,0x3f7baccd,0x3f731447,0x3f633c5a,0x3f7853f8,0x3f740bdd,0x3f4d9f02,0x3f32c8c9,0x3f6ed89e,0x3f68bf3c,0x3f13682a,0x3ee0924f,
0x3f800000,0x3f7f4e6d,0x3f800000,0x3f7c3b28,0x3f7d3aac,0x3f79c79d,0x3f710908,0x3f5ebe05,0x3f74fa0b,0x3f6ed89e,0x3f45e403,0x3f273656,0x3f676bd8,0x3f5ebe05,0x3f039c3d,0x3eb8442a,
0x3f800000,0x3f7f0e58,0x3f800000,0x3f7baccd,0x3f7c3b28,0x3f778bc5,0x3f6ed89e,0x3f59f26a,0x3f710908,0x3f68bf3c,0x3f3daef9,0x3f1b02c6,0x3f5ebe05,0x3f531849,0x3ee63375,0x3e8e9a22,
0x3f800000,0x3f800000,0x3f3504f3,0x3f226799,0x3f800000,0x3f800000,0x3f0e39da,0x3ef15aea,0x3f800000,0x3f800000,0x3ec3ef15,0x3e94a031,0x3f800000,0x3f800000,0x3e47c5c2,0x3dc8bd36,
0x3f7ec46d,0x3f7e70b0,0x3f226799,0x3f0b9a6b,0x3f7e1324,0x3f7dabcc,0x3ee63375,0x3eb263ef,0x3f7d3aac,0x3f7cbfc9,0x3e78cfcc,0x3e09cf86,0x3f7c3b28,0x3f7baccd,0x3cc90ab0,0xbdafb680,
0x3f7b14be,0x3f79c79d,0x3f0e39da,0x3ee63375,0x3f7853f8,0x3f76ba07,0x3eac7cd4,0x3e605c13,0x3f74fa0b,0x3f731447,0x3dc8bd36,0xbcc90ab0,0x3f710908,0x3f6ed89e,0xbe164083,0xbe888e93,
0x3f74fa0b,0x3f721352,0x3ef15aea,0x3eb263ef,0x3f6ed89e,0x3f6b4b0c,0x3e605c13,0x3dafb680,0x3f676bd8,0x3f633c5a,0xbd48fb30,0xbe3b6ecf,0x3f5ebe05,0x3f59f26a,0xbea09ae5,0xbee0924f,
0x3f6c835e,0x3f676bd8,0x3ec3ef15,0x3e78cfcc,0x3f61c598,0x3f5b941a,0x3dc8bd36,0xbd48fb30,0x3f54db31,0x3f4d9f02,0xbe47c5c2,0xbeac7cd4,0x3f45e403,0x3f3daef9,0xbef15aea,0xbf187fc0,
0x3f61c598,0x3f59f26a,0x3e94a031,0x3e09cf86,0x3f514d3d,0x3f47de65,0xbcc90ab0,0xbe3b6ecf,0x3f3daef9,0x3f32c8c9,0xbeac7cd4,0xbef6e0cb,0x3f273656,0x3f1b02c6,0xbf1d7fd1,0xbf3b8f3b,
0x3f54db31,0x3f49d112,0x3e47c5c2,0x3cc90ab0,0x3f3daef9,0x3f3085bb,0xbe164083,0xbea09ae5,0x3f226799,0x3f13682a,0xbef15aea,0xbf1d7fd1,0x3f039c3d,0x3ee63375,0xbf3daef9,0xbf584853,
0x3f45e403,0x3f373a23,0x3dc8bd36,0xbdafb680,0x3f273656,0x3f15f6d9,0xbe888e93,0xbee0924f,0x3f039c3d,0x3ee0924f,0xbf187fc0,0xbf3b8f3b,0x3eb8442a,0x3e8e9a22,0xbf584853,0xbf6db293,
0x3f800000,0x3f800000,0,0xbdc8bd36,0x3f800000,0x3f800000,0xbe47c5c2,0xbe94a031,0x3f800000,0x3f800000,0xbec3ef15,0xbef15aea,0x3f800000,0x3f800000,0xbf0e39da,0xbf226799,
0x3f7b14be,0x3f7a7302,0xbe47c5c2,0xbe9aa086,0x3f79c79d,0x3f791298,0xbecf7bca,0xbf00e7e4,0x3f7853f8,0x3f778bc5,0xbf187fc0,0xbf2e3bde,0x3f76ba07,0x3f75dec6,0xbf41d870,0xbf531849,
0x3f6c835e,0x3f6a09a7,0xbec3ef15,0xbefc5d27,0x3f676bd8,0x3f64aa59,0xbf187fc0,0xbf3085bb,0x3f61c598,0x3f5ebe05,0xbf45e403,0xbf584853,0x3f5b941a,0x3f584853,0xbf676bd8,0xbf731447,
0x3f54db31,0x3f4f7a1f,0xbf0e39da,0xbf299415,0x3f49d112,0x3f43e200,0xbf41d870,0xbf5695e5,0x3f3daef9,0x3f373a23,0xbf676bd8,0xbf740bdd,0x3f3085bb,0x3f299415,0xbf7c3b28,0xbf7fd397,
0x3f3504f3,0x3f2beb4a,0xbf3504f3,0xbf4d9f02,0x3f226799,0x3f187fc0,0xbf61c598,0xbf710908,0x3f0e39da,0x3f039c3d,0xbf7b14be,0xbf7fb10f,0x3ef15aea,0x3edae880,0xbf7ec46d,0xbf7853f8,
0x3f0e39da,0x3f00e7e4,0xbf54db31,0xbf68bf3c,0x3ee63375,0x3ec9b953,0xbf76ba07,0xbf7e70b0,0x3eac7cd4,0x3e8e9a22,0xbf7fb10f,0xbf7a7302,0x3e605c13,0x3e22abb6,0xbf6ed89e,0xbf5d2d53,
0x3ec3ef15,0x3ea09ae5,0xbf6c835e,0xbf79c79d,0x3e78cfcc,0x3e2f10a2,0xbf7fb10f,0xbf7e1324,0x3dc8bd36,0x3cc90ab0,0xbf74fa0b,0xbf64aa59,0xbd48fb30,0xbdfab273,0xbf4d9f02,0xbf3085bb,
0x3e47c5c2,0x3de1bc2e,0xbf7b14be,0xbf7ffb11,0x3cc90ab0,0xbd7b2b74,0xbf7c3b28,0xbf6ff573,0xbe164083,0xbe6c9a7f,0xbf5b941a,0xbf3fc767,0xbea09ae5,0xbec9b953,0xbf1d7fd1,0xbeebcbbb,
0x3f800000,0x3f800000,0xbf3504f3,0xbf45e403,0x3f800000,0x3f800000,0xbf54db31,0xbf61c598,0x3f800000,0x3f800000,0xbf6c835e,0xbf74fa0b,0x3f800000,0x3f800000,0xbf7b14be,0xbf7ec46d,
0x3f74fa0b,0x3f740bdd,0xbf61c598,0xbf6db293,0x3f731447,0x3f721352,0xbf76ba07,0xbf7cbfc9,0x3f710908,0x3f6ff573,0xbf7fb10f,0xbf7f84ab,0x3f6ed89e,0x3f6db293,0xbf7c3b28,0xbf75dec6,
0x3f54db31,0x3f514d3d,0xbf7b14be,0xbf7f4e6d,0x3f4d9f02,0x3f49d112,0xbf7fb10f,0xbf7c3b28,0x3f45e403,0x3f41d870,0xbf74fa0b,0xbf6a09a7,0x3f3daef9,0x3f396842,0xbf5b941a,0xbf49d112,
0x3f226799,0x3f1b02c6,0xbf7ec46d,0xbf791298,0x3f13682a,0x3f0b9a6b,0xbf6ed89e,0xbf604621,0x3f039c3d,0x3ef6e0cb,0xbf4d9f02,0xbf373a23,0x3ee63375,0x3ed53641,0xbf1d7fd1,0xbf00e7e4,
0x3ec3ef15,0x3eac7cd4,0xbf6c835e,0xbf5b941a,0x3e94a031,0x3e78cfcc,0xbf45e403,0xbf2beb4a,0x3e47c5c2,0x3e164083,0xbf0e39da,0xbedae880,0x3dc8bd36,0x3d48fb30,0xbe94a031,0xbe164083,
0x3dc8bd36,0x3d16c32c,0xbf45e403,0xbf299415,0xbcc90ab0,0xbdafb680,0xbf08f59b,0xbec9b953,0xbe164083,0xbe541501,0xbe78cfcc,0xbdafb680,0xbe888e93,0xbea68f12,0x3d96a905,0x3e6c9a7f,
0xbe47c5c2,0xbe888e93,0xbf0e39da,0xbecf7bca,0xbeac7cd4,0xbecf7bca,0xbe78cfcc,0xbd96a905,0xbef15aea,0xbf08f59b,0x3dc8bd36,0x3e888e93,0xbf187fc0,0xbf273656,0x3edae880,0x3f13682a,
0xbef15aea,0xbf0b9a6b,0xbe94a031,0xbde1bc2e,0xbf1d7fd1,0xbf2e3bde,0x3d96a905,0x3e827dc0,0xbf3daef9,0xbf4bbbf8,0x3edae880,0x3f15f6d9,0xbf584853,0xbf633c5a,0x3f396842,0x3f5695e5,
0,0,0,0x3dc8bd36,0,0,0x3e47c5c2,0x3e94a031,0,0,0x3ec3ef15,0x3ef15aea,0,0,0x3f0e39da,0x3f226799,
0,0x3c490e90,0,0x3de1bc2e,0x3cc90ab0,0x3d16c32c,0x3e605c13,0x3ea68f12,0x3d48fb30,0x3d7b2b74,0x3edae880,0x3f064b82,0x3d96a905,0x3dafb680,0x3f1d7fd1,0x3f32c8c9,
0,0x3cc90ab0,0,0x3dfab273,0x3d48fb30,0x3d96a905,0x3e78cfcc,0x3eb8442a,0x3dc8bd36,0x3dfab273,0x3ef15aea,0x3f13682a,0x3e164083,0x3e2f10a2,0x3f2beb4a,0x3f41d870,
0,0x3d16c32c,0,0x3e09cf86,0x3d96a905,0x3de1bc2e,0x3e888e93,0x3ec9b953,0x3e164083,0x3e3b6ecf,0x3f039c3d,0x3f1ff6cb,0x3e605c13,0x3e827dc0,0x3f396842,0x3f4f7a1f,
0,0x3d48fb30,0,0x3e164083,0x3dc8bd36,0x3e164083,0x3e94a031,0x3edae880,0x3e47c5c2,0x3e78cfcc,0x3f0e39da,0x3f2beb4a,0x3e94a031,0x3eac7cd4,0x3f45e403,0x3f5b941a,
0,0x3d7b2b74,0,0x3e22abb6,0x3dfab273,0x3e3b6ecf,0x3ea09ae5,0x3eebcbbb,0x3e78cfcc,0x3e9aa086,0x3f187fc0,0x3f373a23,0x3eb8442a,0x3ed53641,0x3f514d3d,0x3f660f88,
0,0x3d96a905,0,0x3e2f10a2,0x3e164083,0x3e605c13,0x3eac7cd4,0x3efc5d27,0x3e94a031,0x3eb8442a,0x3f226799,0x3f41d870,0x3edae880,0x3efc5d27,0x3f5b941a,0x3f6ed89e,
0,0x3dafb680,0,0x3e3b6ecf,0x3e2f10a2,0x3e827dc0,0x3eb8442a,0x3f064b82,0x3eac7cd4,0x3ed53641,0x3f2beb4a,0x3f4bbbf8,0x3efc5d27,0x3f10d3cd,0x3f64aa59,0x3f75dec6,
0,0,0x3f3504f3,0x3f45e403,0,0,0x3f54db31,0x3f61c598,0,0,0x3f6c835e,0x3f74fa0b,0,0,0x3f7b14be,0x3f7ec46d,
0x3dc8bd36,0x3de1bc2e,0x3f45e403,0x3f5695e5,0x3dfab273,0x3e09cf86,0x3f64aa59,0x3f6ff573,0x3e164083,0x3e22abb6,0x3f7853f8,0x3f7dabcc,0x3e2f10a2,0x3e3b6ecf,0x3f7fec43,0x3f7f0e58,
0x3e47c5c2,0x3e605c13,0x3f54db31,0x3f64aa59,0x3e78cfcc,0x3e888e93,0x3f710908,0x3f79c79d,0x3e94a031,0x3ea09ae5,0x3f7ec46d,0x3f7fec43,0x3eac7cd4,0x3eb8442a,0x3f7d3aac,0x3f76ba07,
0x3e94a031,0x3ea68f12,0x3f61c598,0x3f6ff573,0x3eb8442a,0x3ec9b953,0x3f79c79d,0x3f7f0e58,0x3edae880,0x3eebcbbb,0x3f7fb10f,0x3f7baccd,0x3efc5d27,0x3f064b82,0x3f731447,0x3f660f88,
0x3ec3ef15,0x3edae880,0x3f6c835e,0x3f7853f8,0x3ef15aea,0x3f039c3d,0x3f7ec46d,0x3f7fb10f,0x3f0e39da,0x3f187fc0,0x3f7b14be,0x3f710908,0x3f226799,0x3f2beb4a,0x3f61c598,0x3f4d9f02,
0x3ef15aea,0x3f064b82,0x3f74fa0b,0x3f7dabcc,0x3f13682a,0x3f1ff6cb,0x3f7fec43,0x3f7baccd,0x3f2beb4a,0x3f373a23,0x3f710908,0x3f604621,0x3f41d870,0x3f4bbbf8,0x3f49d112,0x3f2e3bde,
0x3f0e39da,0x3f1d7fd1,0x3f7b14be,0x3f7fec43,0x3f2beb4a,0x3f396842,0x3f7d3aac,0x3f731447,0x3f45e403,0x3f514d3d,0x3f61c598,0x3f49d112,0x3f5b941a,0x3f64aa59,0x3f2beb4a,0x3f08f59b,
0x3f226799,0x3f32c8c9,0x3f7ec46d,0x3f7f0e58,0x3f41d870,0x3f4f7a1f,0x3f76ba07,0x3f660f88,0x3f5b941a,0x3f660f88,0x3f4d9f02,0x3f2e3bde,0x3f6ed89e,0x3f75dec6,0x3f08f59b,0x3ebe1d4a,
0,0,0x3f800000,0x3f7ec46d,0,0,0x3f7b14be,0x3f74fa0b,0,0,0x3f6c835e,0x3f61c598,0,0,0x3f54db31,0x3f45e403,
0x3e47c5c2,0x3e541501,0x3f7b14be,0x3f740bdd,0x3e605c13,0x3e6c9a7f,0x3f6a09a7,0x3f5d2d53,0x3e78cfcc,0x3e827dc0,0x3f4d9f02,0x3f3b8f3b,0x3e888e93,0x3e8e9a22,0x3f273656,0x3f10d3cd,
0x3ec3ef15,0x3ecf7bca,0x3f6c835e,0x3f5ebe05,0x3edae880,0x3ee63375,0x3f4d9f02,0x3f396842,0x3ef15aea,0x3efc5d27,0x3f226799,0x3f08f59b,0x3f039c3d,0x3f08f59b,0x3edae880,0x3ea09ae5,
0x3f0e39da,0x3f15f6d9,0x3f54db31,0x3f3fc767,0x3f1d7fd1,0x3f24d225,0x3f273656,0x3f0b9a6b,0x3f2beb4a,0x3f32c8c9,0x3edae880,0x3e9aa086,0x3f396842,0x3f3fc767,0x3e2f10a2,0x3d16c32c,
0x3f3504f3,0x3f3daef9,0x3f3504f3,0x3f187fc0,0x3f45e403,0x3f4d9f02,0x3ef15aea,0x3eac7cd4,0x3f54db31,0x3f5b941a,0x3e47c5c2,0x3d48fb30,0x3f61c598,0x3f676bd8,0xbdc8bd36,0xbe78cfcc,
0x3f54db31,0x3f5d2d53,0x3f0e39da,0x3ed53641,0x3f64aa59,0x3f6b4b0c,0x3e888e93,0x3de1bc2e,0x3f710908,0x3f75dec6,0xbd48fb30,0xbe541501,0x3f79c79d,0x3f7cbfc9,0xbeb8442a,0xbf00e7e4,
0x3f6c835e,0x3f731447,0x3ec3ef15,0x3e605c13,0x3f7853f8,0x3f7c3b28,0x3d48fb30,0xbdfab273,0x3f7ec46d,0x3f7fec43,0xbe94a031,0xbee63375,0x3f7fb10f,0x3f7e1324,0xbf187fc0,0xbf396842,
0x3f7b14be,0x3f7e70b0,0x3e47c5c2,0x3c490e90,0x3f7fec43,0x3f7f84ab,0xbe2f10a2,0xbeb263ef,0x3f7d3aac,0x3f791298,0xbf039c3d,0xbf299415,0x3f731447,0x3f6b4b0c,0xbf49d112,0xbf633c5a,
0,0,0x3f3504f3,0x3f226799,0,0,0x3f0e39da,0x3ef15aea,0,0,0x3ec3ef15,0x3e94a031,0,0,0x3e47c5c2,0x3dc8bd36,
0x3e94a031,0x3e9aa086,0x3ef15aea,0x3ebe1d4a,0x3ea09ae5,0x3ea68f12,0x3e888e93,0x3e22abb6,0x3eac7cd4,0x3eb263ef,0x3d48fb30,0xbd7b2b74,0x3eb8442a,0x3ebe1d4a,0xbe2f10a2,0xbe8e9a22,
0x3f0e39da,0x3f13682a,0x3e47c5c2,0x3d96a905,0x3f187fc0,0x3f1d7fd1,0xbd48fb30,0xbe2f10a2,0x3f226799,0x3f273656,0xbe94a031,0xbecf7bca,0x3f2beb4a,0x3f3085bb,0xbf039c3d,0xbf1d7fd1,
0x3f45e403,0x3f4bbbf8,0xbdc8bd36,0xbe6c9a7f,0x3f514d3d,0x3f5695e5,0xbeb8442a,0xbef6e0cb,0x3f5b941a,0x3f604621,0xbf187fc0,0xbf32c8c9,0x3f64aa59,0x3f68bf3c,0xbf49d112,0xbf5d2d53,
0x3f6c835e,0x3f710908,0xbec3ef15,0xbf039c3d,0x3f74fa0b,0x3f7853f8,0xbf226799,0xbf3daef9,0x3f7b14be,0x3f7d3aac,0xbf54db31,0xbf676bd8,0x3f7ec46d,0x3f7fb10f,0xbf74fa0b,0xbf7d3aac,
0x3f7ec46d,0x3f7fd397,0xbf226799,0xbf3fc767,0x3f7fec43,0x3f7f0e58,0xbf584853,0xbf6b4b0c,0x3f7d3aac,0x3f7a7302,0xbf7853f8,0xbf7f0e58,0x3f76ba07,0x3f721352,0xbf7f4e6d,0xbf791298,
0x3f7b14be,0x3f76ba07,0xbf54db31,0xbf6a09a7,0x3f710908,0x3f6a09a7,0xbf7853f8,0xbf7f4e6d,0x3f61c598,0x3f584853,0xbf7ec46d,0xbf76ba07,0x3f4d9f02,0x3f41d870,0xbf676bd8,0xbf514d3d,
0x3f61c598,0x3f5695e5,0xbf74fa0b,0xbf7e70b0,0x3f49d112,0x3f3b8f3b,0xbf7f4e6d,0xbf778bc5,0x3f2beb4a,0x3f1b02c6,0xbf676bd8,0xbf4f7a1f,0x3f08f59b,0x3eebcbbb,0xbf3085bb,0xbf0b9a6b,
0x3f800000,0x3f7fffb1,0x3f7ffec4,0x3f7ffd39,0x3f7ffb11,0x3f7ff84a,0x3f7ff4e6,0x3f7ff0e3,0x3f7fec43,0x3f7fe705,0x3f7fe129,0x3f7fdaaf,0x3f7fd397,0x3f7fcbe2,0x3f7fc38f,0x3f7fba9e,
0x3f7fb10f,0x3f7fa6e3,0x3f7f9c18,0x3f7f90b1,0x3f7f84ab,0x3f7f7808,0x3f7f6ac7,0x3f7f5ce9,0x3f7f4e6d,0x3f7f3f54,0x3f7f2f9d,0x3f7f1f49,0x3f7f0e58,0x3f7efcc9,0x3f7eea9d,0x3f7ed7d4,
0x3f7ec46d,0x3f7eb069,0x3f7e9bc9,0x3f7e868b,0x3f7e70b0,0x3f7e5a38,0x3f7e4323,0x3f7e2b72,0x3f7e1324,0x3f7dfa38,0x3f7de0b1,0x3f7dc68c,0x3f7dabcc,0x3f7d906e,0x3f7d7474,0x3f7d57de,
0x3f7d3aac,0x3f7d1cdd,0x3f7cfe73,0x3f7cdf6c,0x3f7cbfc9,0x3f7c9f8a,0x3f7c7eb0,0x3f7c5d3a,0x3f7c3b28,0x3f7c187a,0x3f7bf531,0x3f7bd14d,0x3f7baccd,0x3f7b87b2,0x3f7b61fc,0x3f7b3bab,
0x3f7b14be,0x3f7aed37,0x3f7ac516,0x3f7a9c59,0x3f7a7302,0x3f7a4910,0x3f7a1e84,0x3f79f35e,0x3f79c79d,0x3f799b43,0x3f796e4e,0x3f7940c0,0x3f791298,0x3f78e3d6,0x3f78b47b,0x3f788486,
0x3f7853f8,0x3f7822d1,0x3f77f110,0x3f77beb7,0x3f778bc5,0x3f77583a,0x3f772417,0x3f76ef5b,0x3f76ba07,0x3f76841b,0x3f764d97,0x3f76167a,0x3f75dec6,0x3f75a67b,0x3f756d97,0x3f75341d,
0x3f74fa0b,0x3f74bf62,0x3f748422,0x3f74484b,0x3f740bdd,0x3f73ced9,0x3f73913f,0x3f73530e,0x3f731447,0x3f72d4eb,0x3f7294f8,0x3f725470,0x3f721352,0x3f71d19f,0x3f718f57,0x3f714c7a,
0x3f710908,0x3f70c501,0x3f708066,0x3f703b37,0x3f6ff573,0x3f6faf1b,0x3f6f6830,0x3f6f20b0,0x3f6ed89e,0x3f6e8ff8,0x3f6e46be,0x3f6dfcf2,0x3f6db293,0x3f6d67a1,0x3f6d1c1d,0x3f6cd007,
0x3f6c835e,0x3f6c3624,0x3f6be858,0x3f6b99fb,0x3f6b4b0c,0x3f6afb8c,0x3f6aab7b,0x3f6a5ad9,0x3f6a09a7,0x3f69b7e4,0x3f696591,0x3f6912ae,0x3f68bf3c,0x3f686b39,0x3f6816a8,0x3f67c187,
0x3f676bd8,0x3f671599,0x3f66becc,0x3f666771,0x3f660f88,0x3f65b710,0x3f655e0b,0x3f650479,0x3f64aa59,0x3f644fac,0x3f63f473,0x3f6398ac,0x3f633c5a,0x3f62df7b,0x3f628210,0x3f62241a,
0x3f61c598,0x3f61668a,0x3f6106f2,0x3f60a6cf,0x3f604621,0x3f5fe4e9,0x3f5f8327,0x3f5f20db,0x3f5ebe05,0x3f5e5aa6,0x3f5df6be,0x3f5d924d,0x3f5d2d53,0x3f5cc7d1,0x3f5c61c7,0x3f5bfb34,
0x3f5b941a,0x3f5b2c79,0x3f5ac450,0x3f5a5ba0,0x3f59f26a,0x3f5988ad,0x3f591e6a,0x3f58b3a1,0x3f584853,0x3f57dc7f,0x3f577026,0x3f570348,0x3f5695e5,0x3f5627fe,0x3f55b993,0x3f554aa4,
0x3f54db31,0x3f546b3b,0x3f53fac3,0x3f5389c7,0x3f531849,0x3f52a649,0x3f5233c6,0x3f51c0c2,0x3f514d3d,0x3f50d937,0x3f5064af,0x3f4fefa8,0x3f4f7a1f,0x3f4f0417,0x3f4e8d90,0x3f4e1689,
0x3f4d9f02,0x3f4d26fd,0x3f4cae79,0x3f4c3578,0x3f4bbbf8,0x3f4b41fa,0x3f4ac77f,0x3f4a4c87,0x3f49d112,0x3f495521,0x3f48d8b3,0x3f485bca,0x3f47de65,0x3f476085,0x3f46e22a,0x3f466354,
0x3f45e403,0x3f456439,0x3f44e3f5,0x3f446337,0x3f43e200,0x3f436051,0x3f42de29,0x3f425b89,0x3f41d870,0x3f4154e1,0x3f40d0da,0x3f404c5c,0x3f3fc767,0x3f3f41fc,0x3f3ebc1b,0x3f3e35c5,
0x3f3daef9,0x3f3d27b8,0x3f3ca003,0x3f3c17d9,0x3f3b8f3b,0x3f3b0629,0x3f3a7ca4,0x3f39f2ac,0x3f396842,0x3f38dd65,0x3f385216,0x3f37c655,0x3f373a23,0x3f36ad7f,0x3f36206c,0x3f3592e7,
0x3f3504f3,0x3f34768f,0x3f33e7bc,0x3f33587a,0x3f32c8c9,0x3f3238aa,0x3f31a81d,0x3f311722,0x3f3085bb,0x3f2ff3e6,0x3f2f61a5,0x3f2ecef7,0x3f2e3bde,0x3f2da859,0x3f2d1469,0x3f2c800f,
0x3f2beb4a,0x3f2b561b,0x3f2ac082,0x3f2a2a80,0x3f299415,0x3f28fd41,0x3f286605,0x3f27ce61,0x3f273656,0x3f269de3,0x3f26050a,0x3f256bcb,0x3f24d225,0x3f24381a,0x3f239da9,0x3f2302d3,
0x3f226799,0x3f21cbfb,0x3f212ff9,0x3f209393,0x3f1ff6cb,0x3f1f599f,0x3f1ebc12,0x3f1e1e22,0x3f1d7fd1,0x3f1ce11f,0x3f1c420c,0x3f1ba299,0x3f1b02c6,0x3f1a6293,0x3f19c200,0x3f19210f,
0x3f187fc0,0x3f17de12,0x3f173c07,0x3f16999f,0x3f15f6d9,0x3f1553b7,0x3f14b039,0x3f140c5f,0x3f13682a,0x3f12c39a,0x3f121eb0,0x3f11796b,0x3f10d3cd,0x3f102dd5,0x3f0f8784,0x3f0ee0db,
0x3f0e39da,0x3f0d9281,0x3f0cead0,0x3f0c42c9,0x3f0b9a6b,0x3f0af1b7,0x3f0a48ad,0x3f099f4e,0x3f08f59b,0x3f084b92,0x3f07a136,0x3f06f686,0x3f064b82,0x3f05a02c,0x3f04f484,0x3f044889,
0x3f039c3d,0x3f02ef9f,0x3f0242b1,0x3f019573,0x3f00e7e4,0x3f003a06,0x3eff17b2,0x3efdbabb,0x3efc5d27,0x3efafef7,0x3ef9a02d,0x3ef840c8,0x3ef6e0cb,0x3ef58035,0x3ef41f07,0x3ef2bd43,
0x3ef15aea,0x3eeff7fb,0x3eee9479,0x3eed3063,0x3eebcbbb,0x3eea6681,0x3ee900b7,0x3ee79a5d,0x3ee63375,0x3ee4cbfe,0x3ee363fa,0x3ee1fb6a,0x3ee0924f,0x3edf28a9,0x3eddbe79,0x3edc53c1,
0x3edae880,0x3ed97cb9,0x3ed8106b,0x3ed6a399,0x3ed53641,0x3ed3c867,0x3ed25a09,0x3ed0eb2a,0x3ecf7bca,0x3ece0bea,0x3ecc9b8b,0x3ecb2aae,0x3ec9b953,0x3ec8477c,0x3ec6d529,0x3ec5625c,
0x3ec3ef15,0x3ec27b55,0x3ec1071e,0x3ebf926f,0x3ebe1d4a,0x3ebca7af,0x3ebb31a0,0x3eb9bb1e,0x3eb8442a,0x3eb6ccc3,0x3eb554ec,0x3eb3dca5,0x3eb263ef,0x3eb0eacb,0x3eaf713a,0x3eadf73c,
0x3eac7cd4,0x3eab0201,0x3ea986c4,0x3ea80b1f,0x3ea68f12,0x3ea5129f,0x3ea395c5,0x3ea21887,0x3ea09ae5,0x3e9f1cdf,0x3e9d9e78,0x3e9c1faf,0x3e9aa086,0x3e9920fe,0x3e97a117,0x3e9620d2,
0x3e94a031,0x3e931f35,0x3e919ddd,0x3e901c2c,0x3e8e9a22,0x3e8d17c0,0x3e8b9507,0x3e8a11f7,0x3e888e93,0x3e870ada,0x3e8586ce,0x3e840270,0x3e827dc0,0x3e80f8c0,0x3e7ee6e1,0x3e7bdba4,
0x3e78cfcc,0x3e75c35a,0x3e72b651,0x3e6fa8b2,0x3e6c9a7f,0x3e698bba,0x3e667c66,0x3e636c83,0x3e605c13,0x3e5d4b1a,0x3e5a3997,0x3e57278f,0x3e541501,0x3e5101f1,0x3e4dee60,0x3e4ada4f,
0x3e47c5c2,0x3e44b0b9,0x3e419b37,0x3e3e853e,0x3e3b6ecf,0x3e3857ec,0x3e354098,0x3e3228d4,0x3e2f10a2,0x3e2bf804,0x3e28defc,0x3e25c58c,0x3e22abb6,0x3e1f917b,0x3e1c76de,0x3e195be0,
0x3e164083,0x3e1324ca,0x3e1008b7,0x3e0cec4a,0x3e09cf86,0x3e06b26e,0x3e039502,0x3e007745,0x3dfab273,0x3df475c0,0x3dee3876,0x3de7fa9a,0x3de1bc2e,0x3ddb7d37,0x3dd53db9,0x3dcefdb7,
0x3dc8bd36,0x3dc27c39,0x3dbc3ac3,0x3db5f8da,0x3dafb680,0x3da973ba,0x3da3308c,0x3d9cecf9,0x3d96a905,0x3d9064b4,0x3d8a200a,0x3d83db0a,0x3d7b2b74,0x3d6ea038,0x3d621469,0x3d55880e,
0x3d48fb30,0x3d3c6dd5,0x3d2fe007,0x3d2351cb,0x3d16c32c,0x3d0a342f,0x3cfb49ba,0x3ce22a7a,0x3cc90ab0,0x3cafea69,0x3c96c9b6,0x3c7b514b,0x3c490e90,0x3c16cb58,0x3bc90f88,0x3b490fc6,
0,0x3b490fc6,0x3bc90f88,0x3c16cb58,0x3c490e90,0x3c7b514b,0x3c96c9b6,0x3cafea69,0x3cc90ab0,0x3ce22a7a,0x3cfb49ba,0x3d0a342f,0x3d16c32c,0x3d2351cb,0x3d2fe007,0x3d3c6dd5,
0x3d48fb30,0x3d55880e,0x3d621469,0x3d6ea038,0x3d7b2b74,0x3d83db0a,0x3d8a200a,0x3d9064b4,0x3d96a905,0x3d9cecf9,0x3da3308c,0x3da973ba,0x3dafb680,0x3db5f8da,0x3dbc3ac3,0x3dc27c39,
0x3dc8bd36,0x3dcefdb7,0x3dd53db9,0x3ddb7d37,0x3de1bc2e,0x3de7fa9a,0x3dee3876,0x3df475c0,0x3dfab273,0x3e007745,0x3e039502,0x3e06b26e,0x3e09cf86,0x3e0cec4a,0x3e1008b7,0x3e1324ca,
0x3e164083,0x3e195be0,0x3e1c76de,0x3e1f917b,0x3e22abb6,0x3e25c58c,0x3e28defc,0x3e2bf804,0x3e2f10a2,0x3e3228d4,0x3e354098,0x3e3857ec,0x3e3b6ecf,0x3e3e853e,0x3e419b37,0x3e44b0b9,
0x3e47c5c2,0x3e4ada4f,0x3e4dee60,0x3e5101f1,0x3e541501,0x3e57278f,0x3e5a3997,0x3e5d4b1a,0x3e605c13,0x3e636c83,0x3e667c66,0x3e698bba,0x3e6c9a7f,0x3e6fa8b2,0x3e72b651,0x3e75c35a,
0x3e78cfcc,0x3e7bdba4,0x3e7ee6e1,0x3e80f8c0,0x3e827dc0,0x3e840270,0x3e8586ce,0x3e870ada,0x3e888e93,0x3e8a11f7,0x3e8b9507,0x3e8d17c0,0x3e8e9a22,0x3e901c2c,0x3e919ddd,0x3e931f35,
0x3e94a031,0x3e9620d2,0x3e97a117,0x3e9920fe,0x3e9aa086,0x3e9c1faf,0x3e9d9e78,0x3e9f1cdf,0x3ea09ae5,0x3ea21887,0x3ea395c5,0x3ea5129f,0x3ea68f12,0x3ea80b1f,0x3ea986c4,0x3eab0201,
0x3eac7cd4,0x3eadf73c,0x3eaf713a,0x3eb0eacb,0x3eb263ef,0x3eb3dca5,0x3eb554ec,0x3eb6ccc3,0x3eb8442a,0x3eb9bb1e,0x3ebb31a0,0x3ebca7af,0x3ebe1d4a,0x3ebf926f,0x3ec1071e,0x3ec27b55,
0x3ec3ef15,0x3ec5625c,0x3ec6d529,0x3ec8477c,0x3ec9b953,0x3ecb2aae,0x3ecc9b8b,0x3ece0bea,0x3ecf7bca,0x3ed0eb2a,0x3ed25a09,0x3ed3c867,0x3ed53641,0x3ed6a399,0x3ed8106b,0x3ed97cb9,
0x3edae880,0x3edc53c1,0x3eddbe79,0x3edf28a9,0x3ee0924f,0x3ee1fb6a,0x3ee363fa,0x3ee4cbfe,0x3ee63375,0x3ee79a5d,0x3ee900b7,0x3eea6681,0x3eebcbbb,0x3eed3063,0x3eee9479,0x3eeff7fb,
0x3ef15aea,0x3ef2bd43,0x3ef41f07,0x3ef58035,0x3ef6e0cb,0x3ef840c8,0x3ef9a02d,0x3efafef7,0x3efc5d27,0x3efdbabb,0x3eff17b2,0x3f003a06,0x3f00e7e4,0x3f019573,0x3f0242b1,0x3f02ef9f,
0x3f039c3d,0x3f044889,0x3f04f484,0x3f05a02c,0x3f064b82,0x3f06f686,0x3f07a136,0x3f084b92,0x3f08f59b,0x3f099f4e,0x3f0a48ad,0x3f0af1b7,0x3f0b9a6b,0x3f0c42c9,0x3f0cead0,0x3f0d9281,
0x3f0e39da,0x3f0ee0db,0x3f0f8784,0x3f102dd5,0x3f10d3cd,0x3f11796b,0x3f121eb0,0x3f12c39a,0x3f13682a,0x3f140c5f,0x3f14b039,0x3f1553b7,0x3f15f6d9,0x3f16999f,0x3f173c07,0x3f17de12,
0x3f187fc0,0x3f19210f,0x3f19c200,0x3f1a6293,0x3f1b02c6,0x3f1ba299,0x3f1c420c,0x3f1ce11f,0x3f1d7fd1,0x3f1e1e22,0x3f1ebc12,0x3f1f599f,0x3f1ff6cb,0x3f209393,0x3f212ff9,0x3f21cbfb,
0x3f226799,0x3f2302d3,0x3f239da9,0x3f24381a,0x3f24d225,0x3f256bcb,0x3f26050a,0x3f269de3,0x3f273656,0x3f27ce61,0x3f286605,0x3f28fd41,0x3f299415,0x3f2a2a80,0x3f2ac082,0x3f2b561b,
0x3f2beb4a,0x3f2c800f,0x3f2d1469,0x3f2da859,0x3f2e3bde,0x3f2ecef7,0x3f2f61a5,0x3f2ff3e6,0x3f3085bb,0x3f311722,0x3f31a81d,0x3f3238aa,0x3f32c8c9,0x3f33587a,0x3f33e7bc,0x3f34768f,
0x3f3504f3,0x3f3592e7,0x3f36206c,0x3f36ad7f,0x3f373a23,0x3f37c655,0x3f385216,0x3f38dd65,0x3f396842,0x3f39f2ac,0x3f3a7ca4,0x3f3b0629,0x3f3b8f3b,0x3f3c17d9,0x3f3ca003,0x3f3d27b8,
0x3f3daef9,0x3f3e35c5,0x3f3ebc1b,0x3f3f41fc,0x3f3fc767,0x3f404c5c,0x3f40d0da,0x3f4154e1,0x3f41d870,0x3f425b89,0x3f42de29,0x3f436051,0x3f43e200,0x3f446337,0x3f44e3f5,0x3f456439,
0x3f45e403,0x3f466354,0x3f46e22a,0x3f476085,0x3f47de65,0x3f485bca,0x3f48d8b3,0x3f495521,0x3f49d112,0x3f4a4c87,0x3f4ac77f,0x3f4b41fa,0x3f4bbbf8,0x3f4c3578,0x3f4cae79,0x3f4d26fd,
0x3f4d9f02,0x3f4e1689,0x3f4e8d90,0x3f4f0417,0x3f4f7a1f,0x3f4fefa8,0x3f5064af,0x3f50d937,0x3f514d3d,0x3f51c0c2,0x3f5233c6,0x3f52a649,0x3f531849,0x3f5389c7,0x3f53fac3,0x3f546b3b,
0x3f54db31,0x3f554aa4,0x3f55b993,0x3f5627fe,0x3f5695e5,0x3f570348,0x3f577026,0x3f57dc7f,0x3f584853,0x3f58b3a1,0x3f591e6a,0x3f5988ad,0x3f59f26a,0x3f5a5ba0,0x3f5ac450,0x3f5b2c79,
0x3f5b941a,0x3f5bfb34,0x3f5c61c7,0x3f5cc7d1,0x3f5d2d53,0x3f5d924d,0x3f5df6be,0x3f5e5aa6,0x3f5ebe05,0x3f5f20db,0x3f5f8327,0x3f5fe4e9,0x3f604621,0x3f60a6cf,0x3f6106f2,0x3f61668a,
0x3f61c598,0x3f62241a,0x3f628210,0x3f62df7b,0x3f633c5a,0x3f6398ac,0x3f63f473,0x3f644fac,0x3f64aa59,0x3f650479,0x3f655e0b,0x3f65b710,0x3f660f88,0x3f666771,0x3f66becc,0x3f671599,
0x3f676bd8,0x3f67c187,0x3f6816a8,0x3f686b39,0x3f68bf3c,0x3f6912ae,0x3f696591,0x3f69b7e4,0x3f6a09a7,0x3f6a5ad9,0x3f6aab7b,0x3f6afb8c,0x3f6b4b0c,0x3f6b99fb,0x3f6be858,0x3f6c3624,
0x3f6c835e,0x3f6cd007,0x3f6d1c1d,0x3f6d67a1,0x3f6db293,0x3f6dfcf2,0x3f6e46be,0x3f6e8ff8,0x3f6ed89e,0x3f6f20b0,0x3f6f6830,0x3f6faf1b,0x3f6ff573,0x3f703b37,0x3f708066,0x3f70c501,
0x3f710908,0x3f714c7a,0x3f718f57,0x3f71d19f,0x3f721352,0x3f725470,0x3f7294f8,0x3f72d4eb,0x3f731447,0x3f73530e,0x3f73913f,0x3f73ced9,0x3f740bdd,0x3f74484b,0x3f748422,0x3f74bf62,
0x3f74fa0b,0x3f75341d,0x3f756d97,0x3f75a67b,0x3f75dec6,0x3f76167a,0x3f764d97,0x3f76841b,0x3f76ba07,0x3f76ef5b,0x3f772417,0x3f77583a,0x3f778bc5,0x3f77beb7,0x3f77f110,0x3f7822d1,
0x3f7853f8,0x3f788486,0x3f78b47b,0x3f78e3d6,0x3f791298,0x3f7940c0,0x3f796e4e,0x3f799b43,0x3f79c79d,0x3f79f35e,0x3f7a1e84,0x3f7a4910,0x3f7a7302,0x3f7a9c59,0x3f7ac516,0x3f7aed37,
0x3f7b14be,0x3f7b3bab,0x3f7b61fc,0x3f7b87b2,0x3f7baccd,0x3f7bd14d,0x3f7bf531,0x3f7c187a,0x3f7c3b28,0x3f7c5d3a,0x3f7c7eb0,0x3f7c9f8a,0x3f7cbfc9,0x3f7cdf6c,0x3f7cfe73,0x3f7d1cdd,
0x3f7d3aac,0x3f7d57de,0x3f7d7474,0x3f7d906e,0x3f7dabcc,0x3f7dc68c,0x3f7de0b1,0x3f7dfa38,0x3f7e1324,0x3f7e2b72,0x3f7e4323,0x3f7e5a38,0x3f7e70b0,0x3f7e868b,0x3f7e9bc9,0x3f7eb069,
0x3f7ec46d,0x3f7ed7d4,0x3f7eea9d,0x3f7efcc9,0x3f7f0e58,0x3f7f1f49,0x3f7f2f9d,0x3f7f3f54,0x3f7f4e6d,0x3f7f5ce9,0x3f7f6ac7,0x3f7f7808,0x3f7f84ab,0x3f7f90b1,0x3f7f9c18,0x3f7fa6e3,
0x3f7fb10f,0x3f7fba9e,0x3f7fc38f,0x3f7fcbe2,0x3f7fd397,0x3f7fdaaf,0x3f7fe129,0x3f7fe705,0x3f7fec43,0x3f7ff0e3,0x3f7ff4e6,0x3f7ff84a,0x3f7ffb11,0x3f7ffd39,0x3f7ffec4,0x3f7fffb1,
};

__device__ __forceinline__ int tid_here() { return __shfl_xor_sync(~0u, (int)threadIdx.x, 0); }
__device__ __forceinline__ void ld_tab(uint32_t* d, int chunk) { asm volatile("ld.global.v4.u32 {%0,%1,%2,%3}, [%4];" : "=r"(d[0]), "=r"(d[1]), "=r"(d[2]), "=r"(d[3]) : "l"((const uint4*)g_tab + chunk) : "memory"); }
__device__ __forceinline__ void ld_tab(float* d, int chunk) { asm volatile("ld.global.v4.f32 {%0,%1,%2,%3}, [%4];" : "=f"(d[0]), "=f"(d[1]), "=f"(d[2]), "=f"(d[3]) : "l"((const uint4*)g_tab + chunk) : "memory"); }
__device__ __forceinline__ void fft640(uint32_t plane, uint32_t tab, int lane, const uint32_t* fr, const uint32_t* fi, const float (*tc)[4], const float (*ts)[4], float (*xr)[4], float (*xi)[4]) {
  uint32_t A1[5][4], nfi[4];
#pragma unroll
  for (int i = 0; i < 4; i++) nfi[i] = fi[i] ^ 0x80008000u;
  const uint32_t la = plane + (lane >> 4) * 1280 + (lane & 15) * 80;
#pragma unroll
  for (int j = 0; j < 5; j++) {
    uint32_t r0, r1, i0, i1; ldsm4t(r0, r1, i0, i1, la + j * 16);
    float yr[4], yi[4];
    mmaZ(yr, fr, r0, r1); mmaZ(yi, fi, r0, r1); mmaA(yr, nfi, i0, i1); mmaA(yi, fr, i0, i1);
    float zr[4], zi[4];
#pragma unroll
    for (int e = 0; e < 4; e++) { zr[e] = yr[e] * tc[j][e] - yi[e] * ts[j][e]; zi[e] = yr[e] * ts[j][e] + yi[e] * tc[j][e]; }
    A1[j][0] = pack_bf16(zr[0], zr[1]); A1[j][1] = pack_bf16(zr[2], zr[3]); A1[j][2] = pack_bf16(zi[0], zi[1]); A1[j][3] = pack_bf16(zi[2], zi[3]);
  }
#pragma unroll
  for (int t = 0; t < 5; t++) {
    uint32_t A2[4] = {A1[t][2], A1[t][3], A1[t][0] ^ 0x80008000u, A1[t][1] ^ 0x80008000u};
#pragma unroll
    for (int u = 0; u < 5; u++) {
      uint32_t b0, b1; asm volatile("ld.shared.v2.b32 {%0,%1}, [%2];" : "=r"(b0), "=r"(b1) : "r"(tab + (t * 5 + u) * 256 + lane * 8));
      if (t == 0) { mmaZ(xr[u], A1[t], b0, b1); mmaZ(xi[u], A2, b0, b1); } else { mmaA(xr[u], A1[t], b0, b1); mmaA(xi[u], A2, b0, b1); }
    }
  }
}
__device__ __forceinline__ void ln_row(float* v) {
  float s = 0.f;
#pragma unroll
  for (int i = 0; i < 20; i++) s += v[i];
#pragma unroll
  for (int o = 16; o; o >>= 1) s += __shfl_xor_sync(~0u, s, o);
  const float mean = s * (1.f / D_);
  float qv = 0.f;
#pragma unroll
  for (int i = 0; i < 20; i++) { v[i] -= mean; qv += v[i] * v[i]; }
#pragma unroll
  for (int o = 16; o; o >>= 1) qv += __shfl_xor_sync(~0u, qv, o);
  const float rs = rsqrtf(qv * (1.f / D_) + 1e-5f);
#pragma unroll
  for (int i = 0; i < 20; i++) v[i] *= rs;
}

struct AParams { const bf16* x; uint32_t* ZT; const uint32_t* WT; bf16 *x1, *hN; uint32_t* sync; const uint32_t* rowdone; int nw; };
constexpr int SY_1 = 0, SY_2 = 32, SY_3 = 64, SY_W = 96;
__device__ __forceinline__ void red_release(uint32_t* p) { asm volatile("red.release.gpu.global.add.u32 [%0], 1;" :: "l"(p) : "memory"); }
__device__ __forceinline__ void spin_count(const uint32_t* p, uint32_t n) {
  uint32_t v; int guard = 0;
  do { asm volatile("ld.relaxed.gpu.global.u32 %0, [%1];" : "=r"(v) : "l"(p) : "memory"); } while (v < n && ++guard < 400000);
}

constexpr int WP_RUN = 2592 + 32;
__device__ __forceinline__ void filter_prep(const bf16* wr, const bf16* wi, uint32_t* WT, uint32_t sm, uint32_t bar, int kg) {
  const int tid = threadIdx.x, lane = tid & 31, w = tid >> 5;
  auto row = [&](int j) { return 4 * ((kg >> 2) + 8 * ((j >> 1) & 1) + 16 * (8 * (j >> 2) + 2 * (kg & 3) + (j & 1))); };
  if (lane < 4 && w < 8) {
    const int j = 2 * w + (lane >> 1), o = row(j) * 642, o0 = o & ~15, n = ((o + 2568 + 15) & ~15) - o0;
    mbar_expect(bar, n);
    asm volatile("cp.async.bulk.shared::cluster.global.mbarrier::complete_tx::bytes [%0], [%1], %2, [%3];" :: "r"(sm + ((lane & 1) * 16 + (j & 3) * 4 + (j >> 2)) * WP_RUN), "l"((const char*)((lane & 1) ? wi : wr) + o0), "r"(n), "r"(bar) : "memory");
  }
  __syncwarp();
  const int u = lane & 3, r = w & 3;
  uint32_t src[4];
#pragma unroll
  for (int e = 0; e < 4; e++) src[e] = sm + (e * 4 + u) * WP_RUN + ((row(4 * u + e) * 642) & 15) + r * 642;
  mbar_wait(bar, 0);
#pragma unroll 2
  for (int f = (w >> 2) * 8 + (lane >> 2); f < 321; f += 24) {
    uint32_t v[4];
#pragma unroll
    for (int e = 0; e < 4; e++) {
      unsigned short lo, hi;
      asm volatile("ld.shared.u16 %0, [%1];" : "=h"(lo) : "r"(src[e] + f * 2)); asm volatile("ld.shared.u16 %0, [%1];" : "=h"(hi) : "r"(src[e] + f * 2 + 16 * WP_RUN));
      v[e] = lo | ((uint32_t)hi << 16);
    }
    stg128(WT + (size_t)f * 2048 + r * 512 + kg * 16 + u * 4, v[0], v[1], v[2], v[3]);
  }
}

__device__ __forceinline__ void a_phase2(const AParams& a, float* buf, int f TLP) {
  const int t0 = tid_here(), tid = t0 & 127, lane = tid & 31, w = tid >> 5, g = lane >> 2, q = lane & 3, barid = 5 + (t0 >> 7);
  const int f2 = (640 - f) % 640;
  uint32_t* ZT = a.ZT;
#define WGBAR() asm volatile("bar.sync %0, 128;" :: "r"(barid) : "memory")
  uint32_t fr[4], fi[4], nfi[4], br[4][4], bi[4][4];
  float tc[4][4], ts[4][4], wc[4], ws[4];
  ld_tab(wc, TB_2048 + tid); ld_tab(ws, TB_2048 + 128 + tid); ld_tab(fr, TB_F16 + lane); ld_tab(fi, TB_F16 + 32 + lane);
#pragma unroll
  for (int j = 0; j < 4; j++) { ld_tab(tc[j], TB_512 + j * 32 + lane); ld_tab(ts[j], TB_512 + 128 + j * 32 + lane); }
  asm volatile("prefetch.global.L1 [%0];" :: "l"((const uint4*)g_tab + TB_F32 + lane * 8));
  if (tid == 0) { spin_count(a.sync + SY_1, 96); TL_MIN(tlid - 3, 1); TL_MAX(tlid - 3, 3); }
  WGBAR();
  const uint32_t sbuf = smem_u32(buf);
  {
    uint2 P[4], Q[4];
#pragma unroll
    for (int j = 0; j < 4; j++) { P[j] = __ldcg((const uint2*)(ZT + (size_t)f * 1024 + j * 256 + 2 * tid)); Q[j] = __ldcg((const uint2*)(ZT + (size_t)f2 * 1024 + j * 256 + 2 * tid)); }
    float ur[4][4], ui[4][4];
#pragma unroll
    for (int i = 0; i < 4; i++) {
      float ar[4], ai[4];
#pragma unroll
      for (int j = 0; j < 4; j++) {
        const uint32_t p = (i >> 1) ? P[j].y : P[j].x, z = (i >> 1) ? Q[j].y : Q[j].x;
        if (!(i & 1)) { ar[j] = bf_lo(p) + bf_lo(z); ai[j] = bf_hi(p) - bf_hi(z); }
        else { ar[j] = bf_hi(p) + bf_hi(z); ai[j] = bf_lo(z) - bf_lo(p); }
      }
      const float s0r = ar[0] + ar[2], s0i = ai[0] + ai[2], d0r = ar[0] - ar[2], d0i = ai[0] - ai[2];
      const float s1r = ar[1] + ar[3], s1i = ai[1] + ai[3], d1r = ar[1] - ar[3], d1i = ai[1] - ai[3];
      ur[0][i] = s0r + s1r; ui[0][i] = s0i + s1i;
      const float vr[3] = {d0r + d1i, s0r - s1r, d0r - d1i}, vi[3] = {d0i - d1r, s0i - s1i, d0i + d1r};
      const float c2 = wc[i] * wc[i] - ws[i] * ws[i], s2 = 2.f * wc[i] * ws[i];
      const float twc[4] = {1.f, wc[i], c2, c2 * wc[i] - s2 * ws[i]}, tws[4] = {0.f, ws[i], s2, s2 * wc[i] + c2 * ws[i]};
#pragma unroll
      for (int r = 1; r < 4; r++) { const float c = twc[r], s = tws[r]; ur[r][i] = vr[r - 1] * c + vi[r - 1] * s; ui[r][i] = vi[r - 1] * c - vr[r - 1] * s; }
    }
    const uint32_t o = sbuf + (tid >> 3) * 80 + (tid & 7) * 8;
#pragma unroll
    for (int r = 0; r < 4; r++) {
      asm volatile("st.shared.v2.b32 [%0], {%1,%2};" :: "r"(o + r * 5120), "r"(pack_bf16(ur[r][0], ur[r][1])), "r"(pack_bf16(ur[r][2], ur[r][3])) : "memory");
      asm volatile("st.shared.v2.b32 [%0], {%1,%2};" :: "r"(o + r * 5120 + 1280), "r"(pack_bf16(ui[r][0], ui[r][1])), "r"(pack_bf16(ui[r][2], ui[r][3])) : "memory");
    }
  }
#pragma unroll
  for (int j = 0; j < 4; j++) { ld_tab(br[j], TB_F32 + j * 32 + lane); ld_tab(bi[j], TB_F32 + 128 + j * 32 + lane); }
  if (tid == 0 && a.nw) spin_count(a.sync + SY_W, a.nw);
  WGBAR();
  if (tid == 0) TL_MAX(tlid - 3, 5);
  uint4 wt[4];
#pragma unroll
  for (int u = 0; u < 4; u++) wt[u] = __ldcg((const uint4*)(a.WT + (size_t)f * 2048 + w * 512 + lane * 16 + u * 4));
  {
    uint32_t A1[4][4], A2[4][4];
#pragma unroll
    for (int i = 0; i < 4; i++) nfi[i] = fi[i] ^ 0x80008000u;
    const uint32_t la = sbuf + w * 5120 + (lane >> 4) * 1280 + (lane & 15) * 80;
#pragma unroll
    for (int j = 0; j < 4; j++) {
      uint32_t r0, r1, i0, i1; ldsm4t(r0, r1, i0, i1, la + j * 16);
      float yr[4], yi[4];
      mmaZ(yr, fr, r0, r1); mmaZ(yi, fi, r0, r1); mmaA(yr, nfi, i0, i1); mmaA(yi, fr, i0, i1);
      float zr[4], zi[4];
#pragma unroll
      for (int e = 0; e < 4; e++) { zr[e] = yr[e] * tc[j][e] + yi[e] * ts[j][e]; zi[e] = yi[e] * tc[j][e] - yr[e] * ts[j][e]; }
      A1[j][0] = pack_bf16(zr[0], zr[1]); A1[j][1] = pack_bf16(zr[2], zr[3]); A1[j][2] = pack_bf16(zi[0], zi[1]); A1[j][3] = pack_bf16(zi[2], zi[3]);
      A2[j][0] = A1[j][2]; A2[j][1] = A1[j][3]; A2[j][2] = A1[j][0] ^ 0x80008000u; A2[j][3] = A1[j][1] ^ 0x80008000u;
    }
    float xr[4][4], xi[4][4];
#pragma unroll
    for (int t = 0; t < 4; t++)
#pragma unroll
      for (int u = 0; u < 4; u++) {
        if (t == 0) { mmaZ(xr[u], A1[t], br[t][u], bi[t][u]); mmaZ(xi[u], A2[t], br[t][u], bi[t][u]); } else { mmaA(xr[u], A1[t], br[t][u], bi[t][u]); mmaA(xi[u], A2[t], br[t][u], bi[t][u]); }
      }
#pragma unroll
    for (int u = 0; u < 4; u++) {
      const uint32_t wv[4] = {wt[u].x, wt[u].y, wt[u].z, wt[u].w};
      float zr[4], zi[4];
#pragma unroll
      for (int e = 0; e < 4; e++) { const float c = bf_lo(wv[e]), b = bf_hi(wv[e]); zr[e] = xr[u][e] * c - xi[u][e] * b; zi[e] = xr[u][e] * b + xi[u][e] * c; }
      A2[u][2] = pack_bf16(zr[0], zr[1]); A2[u][3] = pack_bf16(zr[2], zr[3]); A2[u][0] = pack_bf16(zi[0], zi[1]); A2[u][1] = pack_bf16(zi[2], zi[3]);
      A1[u][0] = A2[u][2]; A1[u][1] = A2[u][3]; A1[u][2] = A2[u][0] ^ 0x80008000u; A1[u][3] = A2[u][1] ^ 0x80008000u;
    }
#pragma unroll
    for (int t = 0; t < 4; t++)
#pragma unroll
      for (int u = 0; u < 4; u++) {
        if (t == 0) { mmaZ(xr[u], A1[t], br[t][u], bi[t][u]); mmaZ(xi[u], A2[t], br[t][u], bi[t][u]); } else { mmaA(xr[u], A1[t], br[t][u], bi[t][u]); mmaA(xi[u], A2[t], br[t][u], bi[t][u]); }
      }
    __syncwarp();
    float* pl = buf + w * 1280;
    const float nrm = 0.5f / (2048.f * 640.f);
#pragma unroll
    for (int j = 0; j < 4; j++) {
      float zr[4], zi[4];
#pragma unroll
      for (int e = 0; e < 4; e++) { zr[e] = xr[j][e] * tc[j][e] - xi[j][e] * ts[j][e]; zi[e] = xi[j][e] * tc[j][e] + xr[j][e] * ts[j][e]; }
      const uint32_t r0 = movm(pack_bf16(zr[0], zr[1])), r1 = movm(pack_bf16(zr[2], zr[3])), i0 = movm(pack_bf16(zi[0], zi[1])), i1 = movm(pack_bf16(zi[2], zi[3]));
      float yr[4], yi[4];
      mmaZ(yr, fr, r0, r1); mmaZ(yi, nfi, r0, r1); mmaA(yr, fi, i0, i1); mmaA(yi, fr, i0, i1);
      *(float2*)(pl + g * 40 + 8 * j + 2 * q) = make_float2(yr[0] * nrm, yr[1] * nrm); *(float2*)(pl + (g + 8) * 40 + 8 * j + 2 * q) = make_float2(yr[2] * nrm, yr[3] * nrm);
      *(float2*)(pl + 640 + g * 40 + 8 * j + 2 * q) = make_float2(yi[0] * nrm, yi[1] * nrm); *(float2*)(pl + 640 + (g + 8) * 40 + 8 * j + 2 * q) = make_float2(yi[2] * nrm, yi[3] * nrm);
    }
  }
  ld_tab(wc, TB_2048 + tid); ld_tab(ws, TB_2048 + 128 + tid);
  WGBAR();
  if (tid == 0) TL_MAX(tlid - 3, 6);
  {
    float4 Ur[4], Ui[4];
#pragma unroll
    for (int r = 0; r < 4; r++) { Ur[r] = *(const float4*)(buf + r * 1280 + (tid >> 3) * 40 + (tid & 7) * 4); Ui[r] = *(const float4*)(buf + r * 1280 + 640 + (tid >> 3) * 40 + (tid & 7) * 4); }
    float yr[4][4], yi[4][4];
#pragma unroll
    for (int i = 0; i < 4; i++) {
      float ar[4], ai[4];
      const float c2 = wc[i] * wc[i] - ws[i] * ws[i], s2 = 2.f * wc[i] * ws[i];
      const float twc[4] = {1.f, wc[i], c2, c2 * wc[i] - s2 * ws[i]}, tws[4] = {0.f, ws[i], s2, s2 * wc[i] + c2 * ws[i]};
#pragma unroll
      for (int r = 0; r < 4; r++) {
        const float a = i == 0 ? Ur[r].x : i == 1 ? Ur[r].y : i == 2 ? Ur[r].z : Ur[r].w, b = i == 0 ? Ui[r].x : i == 1 ? Ui[r].y : i == 2 ? Ui[r].z : Ui[r].w;
        if (r == 0) { ar[r] = a; ai[r] = b; } else { const float c = twc[r], s = tws[r]; ar[r] = a * c - b * s; ai[r] = b * c + a * s; }
      }
      const float s0r = ar[0] + ar[2], s0i = ai[0] + ai[2], d0r = ar[0] - ar[2], d0i = ai[0] - ai[2];
      const float s1r = ar[1] + ar[3], s1i = ai[1] + ai[3], d1r = ar[1] - ar[3], d1i = ai[1] - ai[3];
      yr[0][i] = s0r + s1r; yi[0][i] = s0i + s1i; yr[2][i] = s0r - s1r; yi[2][i] = s0i - s1i;
      yr[1][i] = d0r - d1i; yi[1][i] = d0i + d1r; yr[3][i] = d0r + d1i; yi[3][i] = d0i - d1r;
    }
    const float im = (f == f2) ? 0.f : 1.f;
#pragma unroll
    for (int j = 0; j < 4; j++) {
      *(uint2*)(ZT + (size_t)f * 1024 + j * 256 + 2 * tid) = make_uint2(pack_bf16(yr[j][0] - im * yi[j][1], yr[j][1] + im * yi[j][0]), pack_bf16(yr[j][2] - im * yi[j][3], yr[j][3] + im * yi[j][2]));
      if (f != f2) *(uint2*)(ZT + (size_t)f2 * 1024 + j * 256 + 2 * tid) = make_uint2(pack_bf16(yr[j][0] + yi[j][1], yr[j][1] - yi[j][0]), pack_bf16(yr[j][2] + yi[j][3], yr[j][3] - yi[j][2]));
    }
  }
  if (tid == 0) TL_MAX(tlid - 3, 2);
}

constexpr int KA_TR_STRIDE = 804;
template <typename F0, typename F1> __device__ __forceinline__ void a_layer(const AParams& a, char* scratch, int v, int w, F0 after_load, F1 after_phase2 TLP) {
  const int tid = tid_here(), lane = tid & 31;
  uint32_t raw[2][10], fr[4], fi[4];
  float tc[5][4], ts[5][4];
  bool act = v < 86;
  int m = min(v * 12 + w, 1023);
  uint32_t* buf = (uint32_t*)(scratch + 6400) + (w & 3) * KA_TR_STRIDE + (w >> 2) * 3244;
  auto load_rows = [&]() {
    const int lane = tid_here() & 31;
#pragma unroll
    for (int i = 0; i < 10; i++) asm volatile("ld.global.cg.v2.u32 {%0,%1}, [%2];" : "=r"(raw[i / 5][2 * (i % 5)]), "=r"(raw[i / 5][2 * (i % 5) + 1]) : "l"(a.x + (size_t)(2 * m) * D_ + i * 128 + lane * 4) : "memory");
  };
  auto load_tabs = [&]() {
    uint32_t t[2][4];
    const int tid = tid_here(), lane = tid & 31;
    ld_tab(t[0], TB_F40 + (tid & 255)); ld_tab(t[1], TB_F40 + 144 + (tid & 255));
    ld_tab(fr, TB_F16 + lane); ld_tab(fi, TB_F16 + 32 + lane);
#pragma unroll
    for (int j = 0; j < 5; j++) { ld_tab(tc[j], TB_640 + j * 32 + lane); ld_tab(ts[j], TB_640 + 160 + j * 32 + lane); }
    sts128(smem_u32(scratch) + (tid & 255) * 16, t[0][0], t[0][1], t[0][2], t[0][3]); sts128(smem_u32(scratch) + 2304 + (tid & 255) * 16, t[1][0], t[1][1], t[1][2], t[1][3]);
  };
  if (a.rowdone) { load_tabs(); if (act) spin_count(a.rowdone + (m >> 4) * 16, 32); load_rows(); }
  else { load_rows(); load_tabs(); }
  __syncthreads();
  if (tid == 0) TL_MAX(tlid - 5, 3);
#pragma unroll 1
  for (int it = 0;; it++) {
    if (act) {
#pragma unroll
      for (int r = 0; r < 2; r++) {
        float x[20];
#pragma unroll
        for (int i = 0; i < 10; i++) { x[2 * i] = bf_lo(raw[r][i]); x[2 * i + 1] = bf_hi(raw[r][i]); }
        ln_row(x);
#pragma unroll
        for (int i = 0; i < 10; i++) raw[r][i] = pack_bf16(x[2 * i], x[2 * i + 1]);
      }
    }
    if (it) break;
    if (act) {
#pragma unroll
      for (int i = 0; i < 10; i++) *(uint2*)(buf + i * 64 + lane * 2) = make_uint2(raw[i / 5][2 * (i % 5)], raw[i / 5][2 * (i % 5) + 1]);
      __syncwarp();
    }
    if (tid == 0) TL_MAX(tlid - 5, 5);
#pragma unroll 1
    for (int ph = 0;; ph++) {
      if (act) {
        float xr[5][4], xi[5][4];
        const int lane = tid_here() & 31, g = lane >> 2, q = lane & 3;
        fft640(smem_u32(buf), smem_u32(scratch), lane, fr, fi, tc, ts, xr, xi);
        __syncwarp();
#pragma unroll
        for (int u = 0; u < 5; u++)
#pragma unroll
          for (int e = 0; e < 4; e++) { const int f = g + 8 * (e >> 1) + 16 * (8 * u + 2 * q + (e & 1)); buf[f + 8 * (f >> 5)] = pack_bf16(xr[u][e], xi[u][e]); }
        __syncwarp();
      }
      if (ph) break;
      __syncthreads();
      if (tid == 0) TL_MAX(tlid - 5, 6);
      const int t1 = tid_here(), f0 = t1 / 3, part = t1 % 3;
      if (v * 12 + part * 4 < 1024) {
        const uint32_t* src = (const uint32_t*)(scratch + 6400) + part * 3244 + f0 + 8 * (f0 >> 5);
        uint32_t ov[5][4];
#pragma unroll
        for (int i = 0; i < 5; i++)
#pragma unroll
          for (int k = 0; k < 4; k++) ov[i][k] = src[k * KA_TR_STRIDE + i * 160];
#pragma unroll
        for (int i = 0; i < 5; i++) stg128(a.ZT + (size_t)(i * 128 + f0) * 1024 + v * 12 + part * 4, ov[i][0], ov[i][1], ov[i][2], ov[i][3]);
      }
      if (tid == 0) TL_MAX(tlid - 5, 7);
      __syncthreads();
      if (tid == 32 && v < 96) { red_release(a.sync + SY_1); TL_MAX(tlid - 5, 2); }
      after_load();
      const int f = (w >> 2) * 131 + 130 - v;
      if (f < 321) a_phase2(a, (float*)(scratch + (w >> 2) * 20480), f TLA(tlid));
      asm volatile("fence.proxy.async.shared::cta;" ::: "memory");
      __syncthreads();
      if (tid == 32) red_release(a.sync + SY_2);
      after_phase2();
      if (w >= 8 || v >= 128) return;
      act = true; m = v * 8 + w;
      scratch += 32768; buf = (uint32_t*)(scratch + 6400);
      {
        load_rows(); load_tabs();
        if (tid == 0) { spin_count(a.sync + SY_2, 131); TL_MIN(tlid - 2, 1); TL_MAX(tlid - 2, 3); }
        bar_sync<5, 256>();
        uint4 za[3], zb[3];
        const int tid = tid_here();
#pragma unroll
        for (int i = 0; i < 3; i++) {
          const uint32_t* s = a.ZT + (size_t)(i * 256 + (tid & (i < 2 ? 254 : 126))) * 1024 + v * 8 + (tid & 1) * 4;
          za[i] = __ldcg((const uint4*)s); zb[i] = __ldcg((const uint4*)(s + 1024));
        }
        sched_fence();
#pragma unroll
        for (int i = 0; i < 3; i++) if (i < 2 || tid < 128) {
          const uint4 c = za[i], b = zb[i];
          uint32_t* d = buf + (tid & 1) * 4 * KA_TR_STRIDE + i * 128 + (tid >> 1);
          d[320] = __byte_perm(c.x, b.x, 0x5410); d[0] = __byte_perm(c.x, b.x, 0x7632); d += KA_TR_STRIDE;
          d[320] = __byte_perm(c.y, b.y, 0x5410); d[0] = __byte_perm(c.y, b.y, 0x7632); d += KA_TR_STRIDE;
          d[320] = __byte_perm(c.z, b.z, 0x5410); d[0] = __byte_perm(c.z, b.z, 0x7632); d += KA_TR_STRIDE;
          d[320] = __byte_perm(c.w, b.w, 0x5410); d[0] = __byte_perm(c.w, b.w, 0x7632);
        }
        bar_sync<5, 256>();
        if (tid == 0) TL_MAX(tlid - 2, 5);
      }
      buf += w * KA_TR_STRIDE;
    }
    {
      if (tid == 0) TL_MAX(tlid - 2, 6);
      const int lane = tid_here() & 31;
#pragma unroll
      for (int i = 0; i < 5; i++) {
        const uint4 y = *(const uint4*)(buf + i * 160 + lane * 4 + 8 * (lane >> 3));
        raw[0][2 * i] = hadd2(raw[0][2 * i], __byte_perm(y.x, y.y, 0x7632)); raw[0][2 * i + 1] = hadd2(raw[0][2 * i + 1], __byte_perm(y.z, y.w, 0x7632));
        raw[1][2 * i] = hadd2(raw[1][2 * i], __byte_perm(y.x, y.y, 0x5410)); raw[1][2 * i + 1] = hadd2(raw[1][2 * i + 1], __byte_perm(y.z, y.w, 0x5410));
      }
#pragma unroll
      for (int i = 0; i < 10; i++) *(uint2*)(a.x1 + (size_t)(2 * m) * D_ + i * 128 + lane * 4) = make_uint2(raw[i / 5][2 * (i % 5)], raw[i / 5][2 * (i % 5) + 1]);
    }
  }
  {
#pragma unroll
    for (int i = 0; i < 10; i++) *(uint2*)(a.hN + (size_t)(2 * m) * D_ + i * 128 + lane * 4) = make_uint2(raw[i / 5][2 * (i % 5)], raw[i / 5][2 * (i % 5) + 1]);
    if (tid == 0) TL_MAX(tlid - 2, 7);
    bar_sync<5, 256>();
    if (tid == 0) { red_release(a.sync + SY_3); TL_MAX(tlid - 2, 2); }
  }
}

__device__ __forceinline__ void tma2d(uint32_t dst, const CUtensorMap* tm, int c0, int c1, uint32_t bar) {
  asm volatile("cp.async.bulk.tensor.2d.shared::cluster.global.mbarrier::complete_tx::bytes [%0], [%1, {%3, %4}], [%2];" :: "r"(dst), "l"(tm), "r"(bar), "r"(c0), "r"(c1) : "memory");
}
__device__ __forceinline__ void bulk_g2s(uint32_t dst, const void* src, int bytes, uint32_t bar) {
  asm volatile("cp.async.bulk.shared::cluster.global.mbarrier::complete_tx::bytes [%0], [%1], %2, [%3];" :: "r"(dst), "l"(src), "r"(bytes), "r"(bar) : "memory");
}
__device__ __forceinline__ uint64_t desc128(uint32_t a) { return (uint64_t)((a & 0x3FFFF) >> 4) | (1ull << 16) | (64ull << 32) | (1ull << 62); }
#define WG_FENCE() asm volatile("wgmma.fence.sync.aligned;" ::: "memory")
#define WG_COMMIT() asm volatile("wgmma.commit_group.sync.aligned;" ::: "memory")
#define WG_WAIT(n) asm volatile("wgmma.wait_group.sync.aligned " #n ";" ::: "memory")
__device__ __forceinline__ void wg_rs_n64(float* d, const uint32_t* a, uint64_t db, int acc) {
  asm volatile("{.reg .pred p; setp.ne.b32 p, %37, 0;\n"
    "wgmma.mma_async.sync.aligned.m64n64k16.f32.bf16.bf16 {%0,%1,%2,%3,%4,%5,%6,%7,%8,%9,%10,%11,%12,%13,%14,%15,%16,%17,%18,%19,%20,%21,%22,%23,%24,%25,%26,%27,%28,%29,%30,%31}, {%32,%33,%34,%35}, %36, p, 1, 1, 0;}"
    : "+f"(d[0]), "+f"(d[1]), "+f"(d[2]), "+f"(d[3]), "+f"(d[4]), "+f"(d[5]), "+f"(d[6]), "+f"(d[7]), "+f"(d[8]), "+f"(d[9]), "+f"(d[10]), "+f"(d[11]), "+f"(d[12]), "+f"(d[13]), "+f"(d[14]), "+f"(d[15]),
      "+f"(d[16]), "+f"(d[17]), "+f"(d[18]), "+f"(d[19]), "+f"(d[20]), "+f"(d[21]), "+f"(d[22]), "+f"(d[23]), "+f"(d[24]), "+f"(d[25]), "+f"(d[26]), "+f"(d[27]), "+f"(d[28]), "+f"(d[29]), "+f"(d[30]), "+f"(d[31])
    : "r"(a[0]), "r"(a[1]), "r"(a[2]), "r"(a[3]), "l"(db), "r"(acc));
}
__device__ __forceinline__ void wg_rs_n32(float* d, const uint32_t* a, uint64_t db, int acc) {
  asm volatile("{.reg .pred p; setp.ne.b32 p, %21, 0;\n"
    "wgmma.mma_async.sync.aligned.m64n32k16.f32.bf16.bf16 {%0,%1,%2,%3,%4,%5,%6,%7,%8,%9,%10,%11,%12,%13,%14,%15}, {%16,%17,%18,%19}, %20, p, 1, 1, 0;}"
    : "+f"(d[0]), "+f"(d[1]), "+f"(d[2]), "+f"(d[3]), "+f"(d[4]), "+f"(d[5]), "+f"(d[6]), "+f"(d[7]), "+f"(d[8]), "+f"(d[9]), "+f"(d[10]), "+f"(d[11]), "+f"(d[12]), "+f"(d[13]), "+f"(d[14]), "+f"(d[15])
    : "r"(a[0]), "r"(a[1]), "r"(a[2]), "r"(a[3]), "l"(db), "r"(acc));
}
__device__ __forceinline__ void wg_ss_n40_tt(float* d, uint64_t da, uint64_t db, int acc) {
  asm volatile("{.reg .pred p; setp.ne.b32 p, %22, 0;\n"
    "wgmma.mma_async.sync.aligned.m64n40k16.f32.bf16.bf16 {%0,%1,%2,%3,%4,%5,%6,%7,%8,%9,%10,%11,%12,%13,%14,%15,%16,%17,%18,%19}, %20, %21, p, 1, 1, 1, 1;}"
    : "+f"(d[0]), "+f"(d[1]), "+f"(d[2]), "+f"(d[3]), "+f"(d[4]), "+f"(d[5]), "+f"(d[6]), "+f"(d[7]), "+f"(d[8]), "+f"(d[9]), "+f"(d[10]), "+f"(d[11]), "+f"(d[12]), "+f"(d[13]), "+f"(d[14]), "+f"(d[15]),
      "+f"(d[16]), "+f"(d[17]), "+f"(d[18]), "+f"(d[19])
    : "l"(da), "l"(db), "r"(acc));
}
__device__ __forceinline__ void wg_ss_n32_ta(float* d, uint64_t da, uint64_t db, int acc) {
  asm volatile("{.reg .pred p; setp.ne.b32 p, %18, 0;\n"
    "wgmma.mma_async.sync.aligned.m64n32k16.f32.bf16.bf16 {%0,%1,%2,%3,%4,%5,%6,%7,%8,%9,%10,%11,%12,%13,%14,%15}, %16, %17, p, 1, 1, 1, 0;}"
    : "+f"(d[0]), "+f"(d[1]), "+f"(d[2]), "+f"(d[3]), "+f"(d[4]), "+f"(d[5]), "+f"(d[6]), "+f"(d[7]), "+f"(d[8]), "+f"(d[9]), "+f"(d[10]), "+f"(d[11]), "+f"(d[12]), "+f"(d[13]), "+f"(d[14]), "+f"(d[15])
    : "l"(da), "l"(db), "r"(acc));
}
__device__ __forceinline__ uint64_t desc_ns(uint32_t a, uint32_t lbo, uint32_t sbo) { return (uint64_t)((a & 0x3FFFF) >> 4) | ((uint64_t)(lbo >> 4) << 16) | ((uint64_t)(sbo >> 4) << 32); }
__device__ __forceinline__ void wait_count(const uint32_t* p, uint32_t n) {
  uint32_t v; int guard = 0;
  while (true) { asm volatile("ld.relaxed.gpu.global.u32 %0, [%1];" : "=r"(v) : "l"(p) : "memory"); if (v >= n || ++guard > 200000) break; __nanosleep(40); }
}

constexpr int SD_WS = 0, SD_REC = 16384, SD_O = SD_REC + 2 * 30720, SD_OI = SD_O + 2 * 8192, SD_OUT = SD_OI + 2 * 40960, SD_FIN = SD_OUT + 8192, SD_BAR = SD_FIN + 10240;
constexpr int SD_SMEM = SD_BAR + 256 + 1024;
#define QRING 4
constexpr int ORING = 4, PRING = 2 * ORING;
constexpr int FL_MEM = 162 * 1024, FL_RDY = 166 * 1024;
struct SideParams { CUtensorMap tmWo, tmP; const char* QKV; char *O, *part; const bf16* x1; bf16* out; uint32_t *comm, *sync; int first, dbgf; };
#define DBGF(m) false
#define ELECT "{.reg .pred p; elect.sync _|p, 0xffffffff;\n"
#define ATS(i)
__global__ void __launch_bounds__(512, 1) side_kernel(const __grid_constant__ SideParams p TLP) {
  extern __shared__ __align__(1024) char smem_raw[];
  const uint32_t sb = (smem_u32(smem_raw) + 1023) & ~1023u, wfull = sb + SD_BAR, rland = wfull + 8, ofull = wfull + 16, ofree = wfull + 32,
    ifull = wfull + 48, ifree = wfull + 64, rfull = wfull + 80, rfree = wfull + 96, fdone = wfull + 112, ffull = wfull + 128;
  const int tid = threadIdx.x, lane = tid & 31, w = tid >> 5, h = blockIdx.x;
  const int cb = h % 5, ks = h / 5, h0 = ks < 4 ? 5 * ks : 4 + 4 * ks, nh = ks < 4 ? 5 : 4;
  const int nseg = DBGF(16) ? 0 : NSEG;
  if (tid == 0) { TL_MIN(tlid, 0); TL_MAX(tlid, 4); }
  if (!DBGF(16)) pdl_launch();
  if (tid == 0) {
    mbar_init(wfull, 1); mbar_init(rland, 1); mbar_init(ffull, 1);
    for (int i = 0; i < 2; i++) { mbar_init(ofull + i * 8, 2); mbar_init(ofree + i * 8, 1); mbar_init(ifull + i * 8, 1); mbar_init(ifree + i * 8, 8); mbar_init(rfull + i * 8, 1); mbar_init(rfree + i * 8, 4); }
    sts128(fdone, 0, 0, 0, 0);
    asm volatile("fence.proxy.async.shared::cta;" ::: "memory");
    mbar_expect(wfull, nh * 32768);
#pragma unroll 1
    for (int b = 0; b < 4 * nh; b++) tma2d(sb + ((b + 2) % 20) * 8192, &p.tmWo, cb * 128 + (b & 1) * 64, h0 * 128 + (b >> 1) * 64, wfull);
    spin_count(p.sync + SY_2, 131);
  }
  __syncthreads();
  if (w < 8) {
    asm volatile("setmaxnreg.inc.sync.aligned.u32 192;");
    const int c = __shfl_sync(~0u, w >> 2, 0), mg = w & 3;
    const uint32_t boxoff = (((lane >> 4) << 3) + (lane & 7)) * 128 + (((2 * mg + ((lane >> 3) & 1)) ^ (lane & 7)) << 4);
    uint32_t A[36][4];
    mbar_wait(wfull, 0);
#pragma unroll
    for (int f = 0; f < 36; f++) ldsm4t(A[f][0], A[f][1], A[f][2], A[f][3], sb + 16384 + c * 8192 + boxoff + (f >> 2) * 16384 + (f & 3) * 2048);
    asm volatile("fence.proxy.async.shared::cta;" ::: "memory");
    bar_sync<1, 320>();
    if (tid == 0) TL_MAX(tlid, 3);
    const uint32_t oa = sb + SD_OUT + c * 4096 + boxoff;
#pragma unroll 1
    for (int s = 0; s < nseg; s++) {
      const int b = s & 1;
      const uint64_t db = desc128(sb + SD_OI + b * 40960), da = desc128(sb + SD_WS + c * 8192);
      float acc[16];
      mbar_wait_long(ifull + b * 8, (s >> 1) & 1);
      ATS(0)
      WG_FENCE();
#pragma unroll
      for (int k = 0; k < 32; k++) wg_rs_n32(acc, A[k], db + (k >> 2) * 256 + (k & 3) * 2, k);
      if (nh == 5) {
#pragma unroll
        for (int k = 32; k < 36; k++) wg_rs_n32(acc, A[k], db + 2048 + (k & 3) * 2, 1);
#pragma unroll
        for (int k = 0; k < 4; k++) wg_ss_n32_ta(acc, da + k * 128, db + 2304 + k * 2, 1);
      }
      WG_COMMIT();
      bar_sync<2, 256>();
      WG_WAIT(0);
      ATS(1)
      if (lane == 0) mbar_arrive(ifree + b * 8);
#pragma unroll
      for (int u = 0; u < 2; u++)
        asm volatile("stmatrix.sync.aligned.m8n8.x4.trans.shared.b16 [%0], {%1,%2,%3,%4};" :: "r"(oa + u * 2048),
          "r"(pack_bf16(acc[8 * u], acc[8 * u + 1])), "r"(pack_bf16(acc[8 * u + 2], acc[8 * u + 3])), "r"(pack_bf16(acc[8 * u + 4], acc[8 * u + 5])), "r"(pack_bf16(acc[8 * u + 6], acc[8 * u + 7])) : "memory");
      asm volatile("fence.proxy.async.shared::cta;" ::: "memory");
      if (w > 0) bar_arrive<4, 256>();
      else {
        bar_sync<4, 256>();
        asm volatile(ELECT "@p cp.async.bulk.tensor.3d.global.shared::cta.bulk_group [%0, {%2, %3, %4}], [%1];\n"
          "cp.async.bulk.commit_group;\ncp.async.bulk.wait_group 0;\n@p fence.proxy.async.global;\n@p red.release.gpu.global.add.u32 [%5], 1;}"
          :: "l"(&p.tmP), "r"(sb + SD_OUT), "r"(0), "r"((s % PRING) * 32), "r"(ks * 10 + cb * 2), "l"(p.comm + FL_RDY + s * 16 + 8) : "memory");
        ATS(2)
      }
    }
    if (tid == 0) TL_MAX(tlid, 6);
  } else if (w < 12) {
    asm volatile("setmaxnreg.dec.sync.aligned.u32 72;");
    const int a = __shfl_sync(~0u, w - 8, 0), g = lane >> 2, q = lane & 3;
    const float sc2 = 0.08838834764831845f * 1.4426950408889634f;
#pragma unroll 1
    for (int s = 0; s < (h < 32 ? nseg : 0); s++) {
      const int b = s & 1;
      const uint32_t rec = sb + SD_REC + b * 30720;
      mbar_wait_long(rfull + b * 8, (s >> 1) & 1);
      ATS(1)
      if (s == 0 && tid == 256) TL_MIN(tlid, 1);
      uint32_t P[3][4]; float inv[2];
      {
        float sc[20];
        const uint64_t dq = desc_ns(rec + 1024, 128, 1024), dk = desc_ns(rec + 5120, 128, 1024);
        WG_FENCE();
#pragma unroll
        for (int k = 0; k < 8; k++) wg_ss_n40_tt(sc, dq + (k >> 2) * 640 + (k & 3) * 16, dk + (k >> 2) * 640 + (k & 3) * 16, k);
        WG_COMMIT(); WG_WAIT(0);
        ATS(2)
#pragma unroll
        for (int rh = 0; rh < 2; rh++) {
          const int row = 16 * a + 8 * rh + g;
          float v[5][2], mx = -3.0e38f;
#pragma unroll
          for (int n = 0; n < 5; n++)
#pragma unroll
            for (int e = 0; e < 2; e++) {
              const bool ok = n == 0 || (8 * (n - 1) + 2 * q + e) <= row;
              v[n][e] = ok ? sc[4 * n + 2 * rh + e] * sc2 : -1.0e9f * 1.4426950408889634f; mx = fmaxf(mx, v[n][e]);
            }
          mx = fmaxf(mx, __shfl_xor_sync(~0u, mx, 1)); mx = fmaxf(mx, __shfl_xor_sync(~0u, mx, 2));
          float sum = 0.f;
#pragma unroll
          for (int n = 0; n < 5; n++) { const float e0 = ex2(v[n][0] - mx), e1 = ex2(v[n][1] - mx); sum += e0 + e1; P[n >> 1][(n & 1) * 2 + rh] = pack_bf16(e0, e1); }
          P[2][2 + rh] = 0u;
          sum += __shfl_xor_sync(~0u, sum, 1); sum += __shfl_xor_sync(~0u, sum, 2);
          asm("rcp.approx.ftz.f32 %0, %1;" : "=f"(inv[rh]) : "f"(sum));
        }
      }
      ATS(3)
      mbar_wait_long(ofree + b * 8, ((s >> 1) & 1) ^ 1);
      ATS(4)
      const uint32_t od = sb + SD_O + b * 8192 + (16 * a + (lane & 15)) * 128;
#pragma unroll
      for (int hf = 0; hf < 2; hf++) {
        float o[32];
        const uint64_t dv = desc_ns(rec + 20480 + hf * 5120, 1024, 128);
        WG_FENCE();
        wg_rs_n64(o, P[0], dv, 0); wg_rs_n64(o, P[1], dv + 128, 1); wg_rs_n64(o, P[2], desc_ns(rec + 20480 + hf * 5120 + 4096, 0, 128), 1);
        WG_COMMIT(); WG_WAIT(0);
        if (a < 2) {
#pragma unroll
          for (int n = 0; n < 8; n += 2) {
            const float* x = o + 4 * n;
            asm volatile("stmatrix.sync.aligned.m8n8.x4.shared.b16 [%0], {%1,%2,%3,%4};" :: "r"(od + hf * 4096 + (((n + (lane >> 4)) ^ (lane & 7)) << 4)),
              "r"(pack_bf16(x[0] * inv[0], x[1] * inv[0])), "r"(pack_bf16(x[2] * inv[1], x[3] * inv[1])), "r"(pack_bf16(x[4] * inv[0], x[5] * inv[0])), "r"(pack_bf16(x[6] * inv[1], x[7] * inv[1])) : "memory");
          }
        }
      }
      if (a < 2) {
        asm volatile("fence.proxy.async.shared::cta;" ::: "memory");
        __syncwarp();
        if (lane == 0) mbar_arrive(ofull + b * 8);
      }
      if (lane == 0) mbar_arrive(rfree + b * 8);
      ATS(5)
    }
    if (tid == 256) TL_MAX(tlid, 5);
  } else {
    asm volatile("setmaxnreg.dec.sync.aligned.u32 56;");
    if (w == 13) {
      bar_sync<1, 320>();
#pragma unroll 1
      for (int s = 0; s < nseg; s++) {
        mbar_wait_long(ifree + (s & 1) * 8, ((s >> 1) & 1) ^ 1);
        wait_count(p.comm + FL_RDY + s * 16 + ks, nh);
        ATS(0)
        asm volatile(ELECT "@p mbarrier.arrive.expect_tx.shared.b64 _, [%2], %3;\n@p cp.async.bulk.shared::cluster.global.mbarrier::complete_tx::bytes [%0], [%1], %3, [%2];}"
          :: "r"(sb + SD_OI + (s & 1) * 40960), "l"(p.O + (size_t)((s % ORING) * 32 + h0) * 8192), "r"(ifull + (s & 1) * 8), "r"(nh * 8192) : "memory");
      }
    } else if (h >= 32) {
      if (w == 15) bar_sync<1, 320>();
    } else if (w == 12) {
#pragma unroll 1
      for (int s = 0; s < nseg; s++) {
        mbar_wait_long(ofull + (s & 1) * 8, (s >> 1) & 1);
        int fin, guard = 0;
        do { asm volatile("ld.volatile.shared.b32 %0, [%1];" : "=r"(fin) : "r"(fdone) : "memory"); } while (fin + ORING <= s && ++guard < 1000000);
        ATS(0)
        asm volatile(ELECT "@p cp.async.bulk.global.shared::cta.bulk_group [%0], [%1], 8192;\n"
          "cp.async.bulk.commit_group;\ncp.async.bulk.wait_group 0;\n@p mbarrier.arrive.shared.b64 _, [%3];\n@p fence.proxy.async.global;\n@p red.release.gpu.global.add.u32 [%2], 1;}"
          :: "l"(p.O + (size_t)((s % ORING) * 32 + h) * 8192), "r"(sb + SD_O + (s & 1) * 8192), "l"(p.comm + FL_RDY + s * 16 + (h < 20 ? h / 5 : (h - 4) >> 2)), "r"(ofree + (s & 1) * 8) : "memory");
        ATS(1)
      }
      if (lane == 0) TL_MAX(tlid, 7);
    } else if (w == 14) {
      if (DBGF(16)) pdl_wait(); else
      mbar_wait_long(ofull, 0);
#pragma unroll 1
      for (int s = 0; s < nseg; s++) {
        asm volatile("fence.proxy.async.shared::cta;" ::: "memory");
        __syncwarp();
        asm volatile(ELECT "@p mbarrier.arrive.expect_tx.shared.b64 _, [%2], 10240;\n@p cp.async.bulk.shared::cluster.global.mbarrier::complete_tx::bytes [%0], [%1], 1280, [%2];}"
          :: "r"(sb + SD_FIN + 8960), "l"(p.x1 + (size_t)(s * 32 + h) * D_), "r"(ffull) : "memory");
        wait_count(p.comm + FL_RDY + s * 16 + 8, 35);
        ATS(0)
        asm volatile(ELECT "@p cp.async.bulk.shared::cluster.global.mbarrier::complete_tx::bytes [%0], [%1], 8960, [%2];}"
          :: "r"(sb + SD_FIN), "l"(p.part + (size_t)((s % PRING) * 32 + h) * 8960), "r"(ffull) : "memory");
        mbar_wait_long(ffull, s & 1);
        ATS(1)
        asm volatile("st.volatile.shared.b32 [%0], %1;" :: "r"(fdone), "r"(s + 1) : "memory");
#pragma unroll
        for (int i = 0; i < 5; i++) {
          uint32_t v[8][2];
#pragma unroll
          for (int u = 0; u < 8; u++) asm volatile("ld.shared.v2.b32 {%0,%1}, [%2];" : "=r"(v[u][0]), "=r"(v[u][1]) : "r"(sb + SD_FIN + u * 1280 + i * 256 + lane * 8) : "memory");
          uint32_t y[2];
#pragma unroll
          for (int k = 0; k < 2; k++) {
            y[k] = pack_bf16(((bf_lo(v[0][k]) + bf_lo(v[1][k])) + (bf_lo(v[2][k]) + bf_lo(v[3][k]))) + ((bf_lo(v[4][k]) + bf_lo(v[5][k])) + bf_lo(v[6][k])),
                             ((bf_hi(v[0][k]) + bf_hi(v[1][k])) + (bf_hi(v[2][k]) + bf_hi(v[3][k]))) + ((bf_hi(v[4][k]) + bf_hi(v[5][k])) + bf_hi(v[6][k])));
            asm("add.rn.bf16x2 %0, %0, %1;" : "+r"(y[k]) : "r"(v[7][k]));
          }
          *(uint2*)(p.out + (size_t)(s * 32 + h) * D_ + i * 128 + lane * 4) = make_uint2(y[0], y[1]);
        }
        __syncwarp();
        if (lane == 0 && p.first) red_release(p.comm + FL_RDY + s * 16 + 12);
        ATS(2)
      }
    } else {
      uint32_t lp = 0, known = 0;
      bar_sync<1, 320>();
#pragma unroll 1
      for (int s = 0; s < nseg; s++) {
        const int b = s & 1;
        const uint32_t rec = sb + SD_REC + b * 30720;
        mbar_wait_long(rfree + b * 8, ((s >> 1) & 1) ^ 1);
        for (int tries = 0; tries < 2000; tries++) {
          int guard = 0;
          while (known <= (uint32_t)s && ++guard < 100000) {
            uint32_t f = ~0u;
            if (lane < 3) asm volatile("ld.relaxed.gpu.global.u32 %0, [%1];" : "=r"(f) : "l"(p.comm + FL_MEM + h * 32 + lane * 8) : "memory");
            known = __reduce_min_sync(~0u, f);
          }
          ATS(0)
          if (lane == 0) {
            asm volatile("fence.proxy.async.shared::cta;" ::: "memory");
            mbar_expect(rland, 30720);
            bulk_g2s(rec, p.QKV + (size_t)((s % QRING) * 32 + h) * 30720, 30720, rland);
          }
          __syncwarp();
          mbar_wait_long(rland, lp); lp ^= 1;
          uint32_t mx = 0;
#pragma unroll
          for (int k = 0; k < 4; k++) { uint32_t v; asm volatile("ld.shared.b32 %0, [%1];" : "=r"(v) : "r"(rec + (k == 0 ? 5120 : 10240 + k * 5120) + lane * 32 + (lane >> 2) * 4) : "memory"); mx = max(mx, v); }
          if (__all_sync(~0u, mx != ~0u)) break;
        }
        if (lane == 0) { mbar_arrive(rfull + b * 8); asm volatile("st.relaxed.gpu.global.u32 [%0], %1;" :: "l"(p.comm + FL_MEM + h * 32 + 24), "r"(s + 1) : "memory"); }
      }
    }
    if (lane == 0) TL_MAX(tlid, 2);
    if (!p.first && tid == 448 && h == 0) { for (int i = 0; i < 8; i++) p.sync[i * 32 - 128] = 0; }
  }
}

__device__ __forceinline__ uint32_t ld_relaxed(const void* p) { uint32_t v; asm volatile("ld.relaxed.gpu.global.u32 %0, [%1];" : "=r"(v) : "l"(p) : "memory"); return v; }
__device__ __forceinline__ void st_relaxed(void* p, uint32_t v) { asm volatile("st.relaxed.gpu.global.u32 [%0], %1;" :: "l"(p), "r"(v) : "memory"); }
__device__ __forceinline__ void st_relaxed_if(void* p, uint32_t v, uint32_t c) { asm volatile("{.reg .pred p; setp.ne.u32 p, %2, 0; @p st.relaxed.gpu.global.u32 [%0], %1;}" :: "l"(p), "r"(v), "r"(c) : "memory"); }
__device__ __forceinline__ uint32_t clk32() { uint32_t c; asm volatile("mov.u32 %0, %%clock;" : "=r"(c) :: "memory"); return c; }
__device__ __forceinline__ uint32_t gt32() { uint64_t c; asm volatile("mov.u64 %0, %%globaltimer;" : "=l"(c) :: "memory"); return (uint32_t)c; }
__device__ __forceinline__ void wait_gt(uint32_t T) {
  asm volatile("{\n.reg .pred p;\n.reg .u64 t;\n.reg .u32 lo, hi;\nLG%=:\nmov.u64 t, %%globaltimer;\nmov.b64 {lo, hi}, t;\nsub.u32 lo, lo, %0;\nsetp.lt.s32 p, lo, 0;\n@p bra.uni LG%=;\n}" :: "r"(T) : "memory");
}
template <int LUT> __device__ __forceinline__ uint32_t lop3(uint32_t a, uint32_t b, uint32_t c) { uint32_t r; asm("lop3.b32 %0, %1, %2, %3, %4;" : "=r"(r) : "r"(a), "r"(b), "r"(c), "n"(LUT)); return r; }
__device__ __forceinline__ uint32_t ldsm1t(uint32_t a) { uint32_t r; asm volatile("ldmatrix.sync.aligned.m8n8.x1.trans.shared.b16 {%0}, [%1];" : "=r"(r) : "r"(a) : "memory"); return r; }
__device__ __forceinline__ uint32_t hmax2(uint32_t a, uint32_t b) { uint32_t r; asm("max.bf16x2 %0, %1, %2;" : "=r"(r) : "r"(a), "r"(b)); return r; }
__device__ __forceinline__ uint32_t lds32(uint32_t a) { uint32_t v; asm volatile("ld.shared.b32 %0, [%1];" : "=r"(v) : "r"(a) : "memory"); return v; }
__device__ __forceinline__ void sts32(uint32_t a, uint32_t v) { asm volatile("st.shared.b32 [%0], %1;" :: "r"(a), "r"(v) : "memory"); }
__device__ __forceinline__ uint32_t mapa(uint32_t a, int rank) { uint32_t r; asm("mapa.shared::cluster.u32 %0, %1, %2;" : "=r"(r) : "r"(a), "r"(rank)); return r; }
template <int OFF> __device__ __forceinline__ void stas32(uint32_t a, uint32_t v, uint32_t bar) {
  asm volatile("st.async.weak.shared::cluster.mbarrier::complete_tx::bytes.b32 [%0+%3], %1, [%2];" :: "r"(a), "r"(v), "r"(bar), "n"(OFF) : "memory");
}
#define OPAQUE(x) x = __shfl_sync(~0u, x, lane)
#define CLUSTER_SYNC() asm volatile("barrier.cluster.arrive.release.aligned; barrier.cluster.wait.acquire.aligned;" ::: "memory")

constexpr int SM_BAR = 0;
constexpr int SM_WO = 2048;
constexpr int SM_VR = 43008;
constexpr int SM_RED = 59392;
constexpr int SM_AT = 67584;
constexpr int SM_MEMT = 108544;
constexpr int SM_QK = 118784;
constexpr int SM_SC = 122880;
constexpr int SM_OX = 124928;
constexpr int SM_VM = 127488;
constexpr int SM_ST = 139264;
constexpr int SM_X = 149504;
constexpr int SM_WST = 2048;
constexpr int SM_WS = 67584;
constexpr int REC_SMEM = 231424 + 1024;
constexpr int MB_A = 0, MB_QK = 24, MB_V = 56, MB_KV = 64, MB_X = 80, MB_IA = 96, MB_IC = 104, MB_TK = 112, MB_PRB = 120, MB_DP = 128, MB_TAB = 256, MB_T2 = 512;
#define NTQ 10
#define NTV 5
#define NB0 4
#define PINK 14
#define NB1 8
#define PINT 5
#define GATEK 4
#define TOLQ 96
#define TOLV 160
constexpr int POLL_LIMIT = 20000;
constexpr int CM_X3 = 160, CM_MISC = 172;
__device__ __forceinline__ uint32_t x3_slot(int slot) { return (CM_X3 + (slot & 1) * 64 + (slot & 2) * 128) * 4096; }
__device__ __forceinline__ int near_page(int pg, int side) { return pg + ((__popc(pg & 0xB3) ^ side) & 1); }
__device__ __forceinline__ int mem_line(int jb) { const int ks = jb >> 1, c = ks >= 20, kk = ks - 20 * c; return (kk >> 2) * 16 + c * 8 + (kk & 3) * 2 + (jb & 1); }

struct RecParams {
  CUtensorMap tmW[3], tmWo, tmX;
  AParams a[2];
  const bf16 *mem0, *Wo, *wr, *wi;
  char* QKV;
  uint32_t* comm;
  int period, c3, slack, xlate, gap, zero, helper, layer, dbgf;
  uint32_t *dbg, *log;
};
#define PRB(k)
#define LDW(d, a) ldsm4t(d[0], d[1], d[2], d[3], a)

#define PRBASE (mbar + w * 16)
#define PRIMM 1024
#define PROFF 0
template <bool VR>
__device__ __forceinline__ void rec_gemm_warps(const RecParams& p, const uint32_t sb, const int h, const int r, const int L, const int w TLP) {
  const int tid = tid_here(), lane = tid & 31;
  const int mg = w & 3, c = w >> 2;
  constexpr int NT = VR ? NTV : NTQ, NW = VR ? 8 : 16;
  uint32_t R[20][4], P[20][4], Wr[NW - NT][4];
  const uint32_t mbar = sb + SM_BAR;
  uint32_t l16 = lane * 16, lm = (lane >> 4) * 1024 + (lane & 15) * 16;
  OPAQUE(l16); OPAQUE(lm);
#define wl16 (l16 + (sb + w * 512))
  {
    const uint32_t boxoff = (((lane >> 4) << 3) + (lane & 7)) * 128 + (((2 * mg + ((lane >> 3) & 1)) ^ (lane & 7)) << 4);
    mbar_wait(mbar + MB_IA, 0);
    if (tid == 0) TL_MAX(tlid, 5);
    const uint32_t wa = sb + SM_WS + c * 40960 + boxoff;
#pragma unroll
    for (int k = 0; k < 20; k++) LDW(R[k], wa + 81920 + k * 2048);
    bar_arrive<4, 288>();
#pragma unroll
    for (int k = 0; k < 20; k++) LDW(P[k], wa + k * 2048);
    bar_sync<2, 256>();
#pragma unroll
    for (int i = 0; i < NT; i++) sts128(wl16 + SM_AT + i * 4096, P[i][0], P[i][1], P[i][2], P[i][3]);
    mbar_wait(mbar + MB_IC, 0);
    if (tid == 0) TL_MAX(tlid, 6);
    const uint32_t woa = sb + SM_WST + c * 16384 + boxoff;
#pragma unroll
    for (int i = 0; i < NW; i++) {
      const uint32_t a = woa + (VR ? i * 2048 : (i & 1) * 32768 + (i >> 1) * 2048);
      if (i >= 4 && i < 4 + NW - NT) LDW(Wr[i - 4], a); else LDW(P[i < 4 ? i : i - (NW - NT)], a);
    }
    asm volatile("fence.proxy.async.shared::cta;" ::: "memory");
    bar_sync<1, 384>();
#pragma unroll
    for (int i = 0; i < NT; i++) sts128(wl16 + SM_WO + i * 4096, P[i][0], P[i][1], P[i][2], P[i][3]);
    asm volatile("barrier.cluster.arrive.relaxed.aligned; barrier.cluster.wait.aligned;" ::: "memory");
  }
#define LDT(i) lds128(P[i], wl16 + SM_AT + (i) * 4096)
  auto stream = [&](int n) {
    float ta[16], tb[16];
    const uint32_t dR = (((sb + SM_X + c * 20480) >> 4) | 0x10000) + (n & 1) * 2560, dP = dR + (~n & p.zero);
#define WGX(acc, A, ks, sc) wg_rs_n32(acc, A[ks], (uint64_t)(d##A + ((ks) >> 2) * 256 + ((ks) & 3) * 2) | (0x40000040ull << 32), sc)
    WG_FENCE();
    constexpr int NE = NT - 4;
#pragma unroll
    for (int k = 0; k < 20; k++) { WGX(ta, R, k, k); if ((k & 1) && k / 2 < NE) LDT(k / 2); }
    WG_COMMIT();
    constexpr int K2 = VR ? NT + 2 : 16;
#pragma unroll
    for (int k = K2; k < 20; k++) {
      if (VR && k == K2 + GATEK) asm volatile("bar.sync 12, %0;" :: "r"((h & 1) ? 320 : 352) : "memory");
      WGX(tb, P, k, k - K2);
    }
    WG_COMMIT();
    WG_WAIT(1);
#pragma unroll
    for (int i = 0; i < 2; i++)
      sts128(l16 + (sb + (w ^ 4) * 512) + SM_RED + i * 4096, pack_bf16(ta[8 * i], ta[8 * i + 1]), pack_bf16(ta[8 * i + 2], ta[8 * i + 3]), pack_bf16(ta[8 * i + 4], ta[8 * i + 5]), pack_bf16(ta[8 * i + 6], ta[8 * i + 7]));
#pragma unroll
    for (int i = NE; i < NT; i++) LDT(i);
#pragma unroll
    for (int k = NT; k < K2; k++) WGX(tb, P, k, 1);
    WG_FENCE();
#pragma unroll
    for (int k = 0; k < NE; k++) WGX(tb, P, k, 1);
    bar_sync<11, 384>();
    uint32_t o[2][4];
    lds128(o[0], wl16 + SM_RED); lds128(o[1], wl16 + SM_RED + 4096);
    WG_FENCE();
#pragma unroll
    for (int k = NE; k < NT; k++) WGX(tb, P, k, 1);
    WG_COMMIT();
    WG_WAIT(0);
#pragma unroll
    for (int i = 0; i < 2; i++)
      asm volatile("stmatrix.sync.aligned.m8n8.x4.shared.b16 [%0], {%1,%2,%3,%4};" :: "r"(lm + (sb + (c ^ 1) * 5120 + mg * 256) + SM_ST + 1024 + i * 2048),
        "r"(hadd2(pack_bf16(tb[8 * i], tb[8 * i + 1]), o[i][0])), "r"(hadd2(pack_bf16(tb[8 * i + 2], tb[8 * i + 3]), o[i][1])),
        "r"(hadd2(pack_bf16(tb[8 * i + 4], tb[8 * i + 5]), o[i][2])), "r"(hadd2(pack_bf16(tb[8 * i + 6], tb[8 * i + 7]), o[i][3])) : "memory");
    bar_arrive<14, 320>();
  };
  int s = -2, att = 0;
#pragma unroll 1
  while (true) {
    if (s >= 0) {
    uint32_t B[10][4], Wf[NT][4], dp[4];
    float ap[2][4], ar[2][4];
#define LDO(i, base) lds128(Wf[i], (base) + SM_WO + (i) * 4096)
#define LDB(k2) ldsm4t(B[k2][0], B[k2][1], B[k2][2], B[k2][3], l16 + (sb + c * 1024) + SM_MEMT + ((k2) >> 1) * 2048 + ((k2) & 1) * 512)
#define BK(k) B[(k) >> 1][((k) & 1) * 2], B[(k) >> 1][((k) & 1) * 2 + 1]
    mbar_wait(mbar + MB_A, att & 1);
    PRB(0)
    LDB(0); LDB(1);
#pragma unroll
    for (int k = 0; k < 20; k++) {
      if (!(k & 1) && k < 16) LDB(k / 2 + 2);
      if (k == PINK) {
        const uint32_t wb = lop3<0xF8>(l16, __float_as_uint(ap[0][0]), p.zero) + (sb + w * 512);
#pragma unroll
        for (int u = 0; u < NB0 && u < NT; u++) LDO(u, wb);
      }
      if (k < 2) { mmaZ(ap[k], P[k], BK(k)); mmaZ(ar[k], R[k], BK(k)); } else { mmaA(ap[k & 1], P[k], BK(k)); mmaA(ar[k & 1], R[k], BK(k)); }
    }
    asm volatile("stmatrix.sync.aligned.m8n8.x4.shared.b16 [%0], {%1,%2,%3,%4};" :: "r"(lm + (sb + c * 2048 + mg * 256) + SM_QK),
      "r"(pack_bf16(ar[0][0] + ar[1][0], ar[0][1] + ar[1][1])), "r"(pack_bf16(ar[0][2] + ar[1][2], ar[0][3] + ar[1][3])),
      "r"(pack_bf16(ap[0][0] + ap[1][0], ap[0][1] + ap[1][1])), "r"(pack_bf16(ap[0][2] + ap[1][2], ap[0][3] + ap[1][3])) : "memory");
    bar_arrive<9, 384>();
    PRB(1)
    att++;
    uint32_t bad;
    asm volatile("{.reg .pred p; setp.ne.u32 p, 0, 0; bar.red.or.pred p, 8, 384, p; selp.u32 %0, 1, 0, p;}" : "=r"(bad) :: "memory");
    if (bad) {
#pragma unroll
      for (int i = 0; i < NT; i++) LDT(i);
      continue;
    }
    if (s == NSEG - 1) break;
    lds128(dp, mbar + MB_DP + w * 16);
#pragma unroll
    for (int i = NB0; i < NT && (VR || i < NB1); i++) LDO(i, wl16);
    uint32_t fmask = (~(l16 | dp[0]) >> 4) & 1, bit = ((s >> 1) & 1) ? 0u : fmask;
    char* cb = (char*)p.comm + ((s & 1) * (256 * 4096) + (l16 >> 2));
    char *d0 = cb + dp[0], *d1 = cb + dp[1], *d2 = cb + dp[2], *d3 = cb + dp[3];
    if (VR) asm volatile("" : "+l"(d0), "+l"(d1), "+r"(bit), "+r"(fmask)); else asm volatile("" : "+l"(d0), "+l"(d1), "+l"(d2), "+l"(d3), "+r"(bit), "+r"(fmask));
    sched_fence();
    if (!VR) {
      bar_sync<2, 384>();
#pragma unroll
      for (int i = NB1; i < NT; i++) LDO(i, wl16);
    }
    bar_sync<3, 384>();
    PRB(2)
    uint32_t ob[4][4];
    float z0, z1;
#pragma unroll
    for (int i = 0; i < 4; i++) LDW(ob[i], l16 + sb + SM_OX + i * 512);
    asm volatile("ld.shared.v2.f32 {%0,%1}, [%2];" : "=f"(z0), "=f"(z1) : "r"(l16 + sb + SM_OX + 2048) : "memory");
#define WO(i) ((i) >= 4 && (i) < 4 + NW - NT ? Wr[(i) >= 4 && (i) < 4 + NW - NT ? (i) - 4 : 0] : Wf[(i) < 4 ? (i) : (i) < 4 + NW - NT ? 0 : (i) - (NW - NT)])
    float ga[4][4];
#pragma unroll
    for (int i = 0; i < NW; i++) {
      const int ks = VR ? i : i >> 1;
      if (i < 4) mmaZ(ga[i], WO(i), ob[ks >> 1][(ks & 1) * 2], ob[ks >> 1][(ks & 1) * 2 + 1]); else mmaA(ga[i & 3], WO(i), ob[ks >> 1][(ks & 1) * 2], ob[ks >> 1][(ks & 1) * 2 + 1]);
    }
    asm("rcp.approx.ftz.f32 %0, %0;" : "+f"(z0)); asm("rcp.approx.ftz.f32 %0, %0;" : "+f"(z1));
#pragma unroll
    for (int i = 0; i < 4; i++) { ga[0][i] += ga[2][i]; ga[1][i] += ga[3][i]; if (VR) ga[0][i] += ga[1][i]; }
#pragma unroll
    for (int t = 0; t < NW / 8; t++) {
      st_relaxed(t ? d2 : d0, lop3<0xF4>(bit, pack_bf16(ga[t][0] * z0, ga[t][1] * z1), fmask));
      st_relaxed(t ? d3 : d1, lop3<0xF4>(bit, pack_bf16(ga[t][2] * z0, ga[t][3] * z1), fmask));
    }
    PRB(3)
    } else mbar_wait(mbar + MB_X + (s & 1) * 8, 0);
    bar_sync<10, 256>();
    stream(s);
    PRB(4)
    s++;
  }
  if (L == p.zero) {
#pragma unroll
    for (int i = 0; i < NT; i++) LDT(i);
    bar_sync<1, 384>();
    const int ln = l16 >> 4;
    const uint32_t wa = sb + SM_WS + c * 40960 + (((ln >> 4) << 3) + (ln & 7)) * 128 + (((2 * mg + ((ln >> 3) & 1)) ^ (ln & 7)) << 4);
#pragma unroll
    for (int k = 0; k < 40; k++) {
      const uint32_t* f = k < 20 ? R[k % 20] : P[k % 20];
      asm volatile("stmatrix.sync.aligned.m8n8.x4.trans.shared.b16 [%0], {%1,%2,%3,%4};" :: "r"(wa + (k < 20 ? 81920 : 0) + (k % 20) * 2048), "r"(f[0]), "r"(f[1]), "r"(f[2]), "r"(f[3]) : "memory");
    }
  }
#undef wl16
}

#undef PRBASE
#undef PRIMM
#undef PROFF
#define PRBASE (mbar + j * 16)
#define PRIMM (1024 + 4)
#define PROFF 8
__device__ __forceinline__ void x_load(const RecParams& p, const uint32_t sb, int n) {
  if (DBGF(32)) { if ((threadIdx.x & 31) == 0) mbar_arrive(sb + SM_BAR + MB_X + (n & 1) * 8); return; }
  asm volatile(ELECT "@p mbarrier.arrive.expect_tx.shared.b64 _, [%2], 40960;\n"
    "@p cp.async.bulk.tensor.3d.shared::cluster.global.mbarrier::complete_tx::bytes [%0], [%1, {%3, %4, %3}], [%2];}"
      :: "r"(sb + SM_X + (n & 1) * 40960), "l"(&p.tmX), "r"(sb + SM_BAR + MB_X + (n & 1) * 8), "r"(0), "r"(n * 32) : "memory");
}
__device__ __forceinline__ int rec_attn_setup(const RecParams& p, const uint32_t sb, const int h, const int r, const int L, const int j TLP) {
  const int ct = tid_here() - 256, lane = ct & 31;
  const uint32_t mbar = sb + SM_BAR;
  uint32_t* misc = p.comm + CM_MISC * 1024;
  if (j >= 2 && lane == 0 && L == 0) {
    uint32_t best = ~0u; uint32_t* a = misc + (j & 1) * 1024 + 128 + blockIdx.x * 8;
#pragma unroll 1
    for (int it = 0; it < 5; it++) {
      const uint32_t t0 = clk32();
      uint32_t v; asm volatile("atom.relaxed.gpu.global.exch.b32 %0, [%1], %2;" : "=r"(v) : "l"(a), "r"(t0) : "memory");
      st_relaxed_if(a, 0, v == t0 + 1);
      best = min(best, clk32() - t0);
    }
    sts32(mbar + MB_PRB + (j & 1) * 4, best);
  }
  if (blockIdx.x == 0 && ct == 0 && L == 0) st_relaxed(misc + 96, gt32() & ~31u);
  bar_sync<15, 128>();
  const uint32_t b0 = lds32(mbar + MB_PRB), b1 = lds32(mbar + MB_PRB + 4);
  const int side = __shfl_sync(~0u, ((b1 < b0) ^ __popc(CM_MISC & 0xB3)) & 1, 0);
  if (r == 2 && lane == 0 && j + (h & 1) < 3) st_relaxed(misc + (j < 2 ? 2 * h + j : 64 + (h >> 1)), side);
  if (j < 2) {
    const int job = 2 * (16 * r + (lane >> 2) + ((lane & 2) && r < 2 ? 8 : 0)) + (lane & 1);
    uint32_t v; int guard = 0;
    do { v = ld_relaxed(misc + (j ? 96 : job)); } while (v == 0xFFFFFFFFu && ++guard < 1000000);
    sts32(mbar + (j ? MB_TK : MB_DP + lane * 4), j ? v + (gt32() - v) / p.slack * p.slack : near_page(2 * job, v) * 4096 + h * 128);
    __syncwarp();
  }
  uint32_t m0[5][4];
#pragma unroll
  for (int i = 0; i < 20; i++) m0[i >> 2][i & 3] = *(const uint32_t*)(p.mem0 + (lane >> 2) * D_ + (j * 20 + i) * 8 + (lane & 3) * 2);
  if (j == 3) {
    spin_count(p.a[L].sync + SY_3, 128);
    bar_sync<4, 288>();
    asm volatile("fence.proxy.async;" ::: "memory");
    x_load(p, sb, 0); x_load(p, sb, 1);
    if (lane == 0) TL_MIN(tlid, 1);
  }
  bar_sync<1, 384>();
  asm volatile("barrier.cluster.arrive.relaxed.aligned;" ::: "memory");
#pragma unroll
  for (int i = 0; i < 5; i++)
    asm volatile("stmatrix.sync.aligned.m8n8.x4.trans.shared.b16 [%0], {%1,%2,%3,%4};" :: "r"(sb + SM_MEMT + mem_line(j * 20 + i * 4) * 128 + lane * 16), "r"(m0[i][0]), "r"(m0[i][1]), "r"(m0[i][2]), "r"(m0[i][3]) : "memory");
  sts128(sb + SM_ST + (ct >> 6) * 5120 + (ct & 63) * 16, ~0u, ~0u, ~0u, ~0u);
  asm volatile("barrier.cluster.wait.aligned;" ::: "memory");
  return side;
}
template <bool VR>
__device__ __forceinline__ void rec_attn_warps(const RecParams& p, const uint32_t sb, char* smem, const int h, const int r, const int side, const int L, const int j TLP) {
  const int lane = tid_here() & 31, g = lane >> 2, q = lane & 3;
  const uint32_t mbar = sb + SM_BAR;
#define is_red (VR && j + (h & 1) < 3)
  const int mi = lane >> 3;
  uint32_t l16 = sb + lane * 16;
#define wr16 (l16 + j * 512)
#define L0 ((l16 & 511) == 0)
  uint32_t ka = j < 2 ? sb + SM_ST + 6144 + (2 * j + (mi & 1)) * 1024 + ((mi >> 1) * 8 + (lane & 7)) * 16 : sb + SM_QK + j * 512 + ((mi & 1) * 16 + (mi >> 1) * 8 + (lane & 7)) * 16;
  uint32_t va = sb + SM_VR + (j >> 1) * 4096 + (mi >> 1) * 1024 + ((j & 1) * 32 + (mi & 1) * 8 + (lane & 7)) * 16;
  uint32_t own = sb + SM_SC + (r & 1) * 1024 + (j < 2 ? j * 256 : 256 + j * 128) + lane * 4, ps[2], pb[2];
#pragma unroll
  for (int i = 0; i < 2; i++) {
    const int peer = VR ? i : i == 0 ? r ^ 1 : 2;
    ps[i] = mapa(VR ? wr16 + SM_VM : own, peer); pb[i] = mapa(mbar + (VR ? MB_V : MB_QK), peer);
    if (VR) ps[i] = mapa(sb, peer) - sb + SM_VM + j * 512; else { OPAQUE(ps[i]); OPAQUE(pb[i]); }
  }
  if (!VR) { OPAQUE(ka); OPAQUE(own); }
  OPAQUE(va); OPAQUE(l16);
  const char* comm = (const char*)p.comm;
  uint32_t s0 = (g >> 1) != q ? 0u : (g & 1) ? 0x3F800000u : 0x00003F80u, s1 = s0 | (p.zero & 0x40000000);
  const uint32_t ones = 0x3F803F80u;
  if (VR) { OPAQUE(s0); OPAQUE(s1); }
  const float sc2 = 0.08838834764831845f * 1.4426950408889634f;
  uint32_t kf[4][4], vf[4][4];
#pragma unroll
  for (int i = 0; i < 16; i++) kf[i >> 2][i & 3] = vf[i >> 2][i & 3] = p.zero;
  auto load_v = [&](int n) {
    if (n >= 0) mbar_wait(mbar + MB_KV + (n & 1) * 8, (n >> 1) & 1);
#pragma unroll
    for (int i = 0; i < 4; i++) ldsm4(vf[i][0], vf[i][1], vf[i][2], vf[i][3], va + (n & 1) * 8192 + (i >> 1) * 2048 + (i & 1) * 256);
  };
  auto v_load = [&](int n) {
    asm volatile("cp.async.bulk.wait_group 0;" ::: "memory");
    if (VR) asm volatile(ELECT
      "@p cp.async.bulk.shared::cluster.global.mbarrier::complete_tx::bytes.multicast::cluster [%0], [%1], 4096, [%2], %3;\n"
      "@p cp.async.bulk.shared::cluster.global.mbarrier::complete_tx::bytes.multicast::cluster [%0+4096], [%1+5120], 4096, [%2], %3;}"
        :: "r"(sb + SM_VR + (n & 1) * 8192), "l"(p.QKV + ((size_t)((n & (QRING - 1)) * 32 + h) * 3 + 2) * 10240 + 1024), "r"(mbar + MB_KV + (n & 1) * 8), "h"((unsigned short)7) : "memory");
  };
  auto t_store = [&](int n) {
    if (DBGF(64)) return;
    asm volatile("fence.proxy.async.shared::cta;" ::: "memory");
    asm volatile(ELECT "@p cp.async.bulk.global.shared::cta.bulk_group [%0], [%1], 10240;}" :: "l"(p.QKV + ((size_t)((n & (QRING - 1)) * 32 + h) * 3 + r) * 10240), "r"(sb + SM_ST) : "memory");
    asm volatile("cp.async.bulk.commit_group;" ::: "memory");
  };
  auto m_store = [&](int n) {
    if (VR || j < 2) {
      const int jj = VR ? j : j + 2;
      uint32_t a[4], b[4]; lds128(a, l16 + jj * 512 + SM_QK); lds128(b, l16 + (jj ^ 2) * 512 + SM_QK + 2048);
      asm volatile("st.relaxed.gpu.global.v4.u32 [%0], {%1,%2,%3,%4};" :: "l"(p.QKV + (uint32_t)(l16 + ((((n & (QRING - 1)) * 32 + h) * 3 + r) * 10240 + (jj >> 1) * 5120 + (j & 1) * 512 - sb))),
        "r"(hadd2(a[0], b[0])), "r"(hadd2(a[1], b[1])), "r"(hadd2(a[2], b[2])), "r"(hadd2(a[3], b[3])) : "memory");
    }
  };
  auto publish = [&](int n) {
    if (j == 1) st_relaxed(p.comm + FL_MEM + (L * 32 + h) * 32 + r * 8, n);
  };
  int att = 1;
  uint32_t T3 = lds32(mbar + MB_TK);
  const int jb = j < 2 ? 2 * h + j : 64 + (h >> 1), ln = mem_line(jb) + 16;
  const uint32_t inbox = near_page(2 * jb, side) * 4096, bline = (ln >> 5) * 16384 + (ln & 31) * 128;
#define VERDICT(bad) asm volatile("{.reg .pred p; setp.ne.u32 p, %0, 0; bar.red.or.pred p, 8, 384, p;}" :: "n"(bad) : "memory")
#pragma unroll 1
  for (int s = -2; s < NSEG - 1; s++) {
    const uint32_t par = s & 1;
    if (s >= 0) {
    uint32_t su[6], sw[6], vm[4];
#define LDSM2T(d, a) asm volatile("ldmatrix.sync.aligned.m8n8.x2.trans.shared.b16 {%0,%1}, [%2];" : "=r"(d[4]), "=r"(d[5]) : "r"(a) : "memory")
#define HADD4(a, b) { a[0] = hadd2(a[0], b[0]); a[1] = hadd2(a[1], b[1]); a[2] = hadd2(a[2], b[2]); a[3] = hadd2(a[3], b[3]); }
    bar_sync<9, 384>();
    PRB(0)
    if (!VR) {
      uint32_t qf[2][4], qg[2][4];
      float sa[4][4];
      if (j < 2) {
        LDW(qf[0], l16 + SM_QK); LDW(qg[0], l16 + SM_QK + 3072); LDW(qf[1], l16 + SM_QK + 512); LDW(qg[1], l16 + SM_QK + 3584);
        HADD4(qf[0], qg[0]); HADD4(qf[1], qg[1]);
#pragma unroll
        for (int i = 0; i < 4; i++) mmaZ(sa[i], kf[i], qf[i >> 1][(i & 1) * 2], qf[i >> 1][(i & 1) * 2 + 1]);
        const uint32_t t0 = pack_bf16((sa[0][0] + sa[1][0]) + (sa[2][0] + sa[3][0]), (sa[0][1] + sa[1][1]) + (sa[2][1] + sa[3][1]));
        const uint32_t t1 = pack_bf16((sa[0][2] + sa[1][2]) + (sa[2][2] + sa[3][2]), (sa[0][3] + sa[1][3]) + (sa[2][3] + sa[3][3]));
        stas32<0>(ps[0], t0, pb[0]); stas32<0>(ps[1], t0, pb[1]); stas32<128>(ps[0], t1, pb[0]); stas32<128>(ps[1], t1, pb[1]);
        sts32(own, t0); sts32(own + 128, t1);
      } else {
        LDW(qf[0], wr16 + SM_QK - 1024); LDW(qg[0], wr16 + SM_QK + 2048); LDW(qf[1], ka); LDW(qg[1], ka + 1024);
        HADD4(qf[0], qg[0]); HADD4(qf[1], qg[1]);
        mmaZ(sa[0], qf[1], qf[0][0], qf[0][1]); mmaZ(sa[1], qf[1], qf[0][2], qf[0][3]);
        const uint32_t t0 = pack_bf16(sa[0][0] + sa[1][2], sa[0][1] + sa[1][3]);
        stas32<0>(ps[0], t0, pb[0]); stas32<0>(ps[1], t0, pb[1]);
        sts32(own, t0);
      }
      PRB(1)
      VERDICT(0);
      LDW(su, l16 + SM_SC + r * 1024); LDSM2T(su, l16 + SM_SC + 512 + r * 1024);
      su[4] = hadd2(su[4], su[5]);
      mbar_wait(mbar + MB_QK, par);
      PRB(2)
      LDW(sw, l16 + SM_SC + 1024 - r * 1024); LDSM2T(sw, l16 + SM_SC + 1536 - r * 1024);
    } else {
      ldsm4(vm[0], vm[1], vm[2], vm[3], wr16 + SM_QK); ldsm4(su[0], su[1], su[2], su[3], l16 + (j ^ 2) * 512 + SM_QK + 2048);
      HADD4(vm, su);
#pragma unroll
      for (int i = 0; i < 2; i++)
        asm volatile("st.async.weak.shared::cluster.mbarrier::complete_tx::bytes.v4.b32 [%0], {%1,%2,%3,%4}, [%5];" :: "r"(ps[i] + l16), "r"(vm[0]), "r"(vm[1]), "r"(vm[2]), "r"(vm[3]), "r"(pb[i]) : "memory");
      PRB(1)
      VERDICT(0);
      char* mv = p.QKV + (uint32_t)((l16 >> 2) + ((((s & (QRING - 1)) * 32 + h) * 3 + 2) * 10240 + (j >> 1) * 5120 + (j & 1) * 512 - (sb >> 2)));
#pragma unroll
      for (int i = 0; i < 4; i++) st_relaxed(mv + i * 128, vm[i]);
      T3 = lds32(mbar + MB_TK);
      mbar_wait(mbar + MB_QK, par);
      PRB(2)
      LDW(su, l16 + SM_SC); LDW(sw, l16 + SM_SC + 1024); LDSM2T(su, l16 + SM_SC + 512); LDSM2T(sw, l16 + SM_SC + 1536);
      su[4] = hadd2(su[4], su[5]);
    }
    {
      HADD4(su, sw); su[4] = hadd2(su[4], hadd2(sw[4], sw[5]));
      uint32_t m = hmax2(hmax2(hmax2(su[0], su[1]), hmax2(su[2], su[3])), su[4]);
      const uint32_t m1 = __shfl_xor_sync(~0u, m, 1), m2 = __shfl_xor_sync(~0u, m, 2), m3 = __shfl_xor_sync(~0u, m, 3);
      float t[10];
#pragma unroll
      for (int i = 0; i < 5; i++) { t[2 * i] = bf_lo(su[i]) * sc2; t[2 * i + 1] = bf_hi(su[i]) * sc2; }
      if (!VR) {
        asm volatile("" : "+f"(t[0]), "+f"(t[1]), "+f"(t[2]), "+f"(t[3]), "+f"(t[4]), "+f"(t[5]), "+f"(t[6]), "+f"(t[7]), "+f"(t[8]), "+f"(t[9]));
        mbar_wait(mbar + MB_V, par); bar_arrive<2, 384>(); lds128(vm, wr16 + SM_VM);
      }
      if (!VR) t[PINT] = __uint_as_float(lop3<0xF8>(__float_as_uint(t[PINT]), vm[0], p.zero));
      m = hmax2(hmax2(m, m1), hmax2(m2, m3));
      const float mx = fmaxf(bf_lo(m), bf_hi(m));
#define EX(i) ex2(fmaf(mx, -sc2, t[i]))
      float o1[2][4], z[4];
      const uint32_t P0 = pack_bf16(EX(0), EX(1)), P1 = pack_bf16(EX(2), EX(3));
      mmaZ(o1[0], vf[0], P0, P1); mmaZ(o1[1], vf[1], P0, P1); mma16816z(z, ones, ones, ones, ones, P0, P1);
      const float e4 = EX(4), e5 = EX(5);
      const uint32_t P2 = pack_bf16(e4, e5), P3 = pack_bf16(EX(6), EX(7));
      mmaA(o1[0], vf[2], P2, P3); mmaA(o1[1], vf[3], P2, P3); mma16816(z, ones, ones, ones, ones, P2, P3);
      const uint32_t Pm = pack_bf16(EX(8), EX(9));
      mma1688(o1[0], vm[0], vm[1], Pm); mma1688(o1[1], vm[2], vm[3], Pm); mma1688(z, ones, ones, Pm);
      asm volatile("stmatrix.sync.aligned.m8n8.x4.shared.b16 [%0], {%1,%2,%3,%4};" :: "r"(wr16 + SM_OX),
        "r"(pack_bf16(o1[0][0], o1[0][1])), "r"(pack_bf16(o1[0][2], o1[0][3])), "r"(pack_bf16(o1[1][0], o1[1][1])), "r"(pack_bf16(o1[1][2], o1[1][3])) : "memory");
      if (j == 3) asm volatile("st.shared.v2.f32 [%0], {%1,%2};" :: "r"(l16 + SM_OX + 2048), "f"(z[0]), "f"(z[1]) : "memory");
    }
    bar_arrive<3, 384>();
    PRB(3)
    {
      const uint32_t now = gt32(), lim = now + p.c3 + p.gap;
      T3 += p.period;
      if ((int)(T3 - now) > 20000) T3 = now;
      while ((int)(lim - T3) > 0) T3 += p.slack;
    }
    if (j == 3) {
      asm volatile(ELECT "@p mbarrier.arrive.expect_tx.shared.b64 _, [%0], %2;\n@p mbarrier.arrive.expect_tx.shared.b64 _, [%1], 8192;\n@p mbarrier.arrive.expect_tx.shared.b64 _, [%3], 10240;}"
        :: "r"(mbar + MB_QK), "r"(mbar + MB_KV + par * 8), "n"(VR ? 1536 : 768), "r"(mbar + MB_A) : "memory");
      if (!VR) asm volatile(ELECT "@p mbarrier.arrive.expect_tx.shared.b64 _, [%0], 2048;}" :: "r"(mbar + MB_V) : "memory");
    }
    if (!VR) m_store(s);
    }
    if (!VR) {
      if (j < 2) {
#pragma unroll
        for (int i = 0; i < 4; i++) LDW(kf[i], ka + i * 256);
      } else {
#pragma unroll
        for (int i = 0; i < 16; i++) kf[i >> 2][i & 3] = p.zero;
      }
    }
    int used = 0;
    if (j == 2 && s >= -1) { v_load(s + 1); used = ld_relaxed(p.comm + FL_MEM + (L * 32 + h) * 32 + 24); }
    bar_arrive<11, 384>();
    if (!VR) { PRB(4) }
#define NEXT_SLOT(T, TOL) { const uint32_t now = gt32(); while ((int)(now - T) > TOL) T += p.slack; }
    auto gather = [&]() {
      if (j == 3) {
        NEXT_SLOT(T3, (VR ? TOLV : TOLQ));
        wait_gt(T3);
        asm volatile("{.reg .pred p; elect.sync _|p, 0xffffffff;\n"
          "@p cp.async.bulk.shared::cluster.global.mbarrier::complete_tx::bytes [%0], [%2+2048], 2048, [%1];\n"
          "@p cp.async.bulk.shared::cluster.global.mbarrier::complete_tx::bytes [%0+2048], [%2+16384], 4096, [%1];\n"
          "@p cp.async.bulk.shared::cluster.global.mbarrier::complete_tx::bytes [%0+6144], [%2+32768], 4096, [%1];}"
          :: "r"(sb + SM_MEMT), "r"(mbar + MB_A), "l"(comm + (x3_slot(s + 1) + side * 4096)) : "memory");
      }
    };
    if (s < 0) { if (is_red) asm volatile("bar.arrive 12, %0;" :: "r"((h & 1) ? 320 : 352) : "memory"); }
    else {
    if (is_red) {
      const uint32_t expect = ((s >> 1) & 1) ^ 1, o_wr = (l16 & 255) / 2 + (l16 & 256) / 64;
      const uint32_t* src = (const uint32_t*)(comm + (inbox + par * (256 * 4096) + (l16 & 511) / 2));
      uint32_t* wfar = (uint32_t*)(comm + (x3_slot(s + 1) + bline + (side ^ 1) * 4096 + o_wr)); uint32_t* wnear = (uint32_t*)(comm + (x3_slot(s + 1) + bline + side * 4096 + o_wr));
      asm volatile("" : "+l"(src), "+l"(wfar), "+l"(wnear));
      auto attempt = [&](int nth) {
        uint32_t x[32], ok;
#pragma unroll
        for (int i = 0; i < 16; i++) asm volatile("ld.relaxed.gpu.global.v2.u32 {%0,%1}, [%2];" : "=r"(x[2 * i]), "=r"(x[2 * i + 1]) : "l"(src + i * 64) : "memory");
        float ra[4][4];
        uint32_t bad[2];
#pragma unroll
        for (int i = 0; i < 8; i++) {
          const uint32_t u = lop3<0x7E>(x[4 * i], x[4 * i + 2], expect);
          bad[i & 1] = i < 2 ? u : (bad[i & 1] | u);
          if (i < 4) mma16816z(ra[i], x[4 * i], x[4 * i + 1], x[4 * i + 2], x[4 * i + 3], s0, s1);
          else mma16816(ra[i & 3], x[4 * i], x[4 * i + 1], x[4 * i + 2], x[4 * i + 3], s0, s1);
        }
        asm volatile("{.reg .pred p; setp.eq.u32 p, %1, 0; vote.sync.all.pred p, p, 0xffffffff; selp.u32 %0, 1, 0, p;}" : "=r"(ok) : "r"((bad[0] | bad[1]) & 1));
        const float a0 = (ra[0][0] + ra[1][0]) + (ra[2][0] + ra[3][0]), a1 = (ra[0][1] + ra[1][1]) + (ra[2][1] + ra[3][1]);
        const float a2 = (ra[0][2] + ra[1][2]) + (ra[2][2] + ra[3][2]), a3 = (ra[0][3] + ra[1][3]) + (ra[2][3] + ra[3][3]);
        const bool up = l16 & 256;
        const float r0 = __shfl_xor_sync(~0u, up ? a0 : a2, 16), r1 = __shfl_xor_sync(~0u, up ? a1 : a3, 16);
        asm volatile("{.reg .pred p; setp.eq.u32 p, %1, 0; @p bar.arrive 12, %0;}" :: "r"((h & 1) ? 320 : 352), "r"(nth) : "memory");
        const uint32_t v = pack_bf16((up ? a2 : a0) + r0, (up ? a3 : a1) + r1);
        asm volatile("{.reg .pred p; setp.ne.u32 p, %3, 0; @p st.relaxed.gpu.global.u32 [%0], %2; @p st.relaxed.gpu.global.u32 [%1], %2; @p bar.arrive 15, %4;}"
          :: "l"(wfar), "l"(wnear), "r"(v), "r"(ok), "r"((h & 1) ? 96 : 128) : "memory");
        return ok;
      };
      uint32_t T2 = T3 - p.c3;
#pragma unroll 1
      for (int nth = 0;; nth++) {
        wait_gt(T2);
        PRB(4)
        if (attempt(nth)) break;
        if (nth == POLL_LIMIT) { asm volatile("bar.arrive 15, %0;" :: "r"((h & 1) ? 96 : 128) : "memory"); break; }
        T2 += p.slack; NEXT_SLOT(T2, TOLQ);
      }
      PRB(5)
      uint32_t* wpoi = (uint32_t*)(comm + (x3_slot(s + 3) + bline + (l16 & 511) / 4));
      st_relaxed(wpoi, 0xFFFFFFFFu); st_relaxed(wpoi + 1024, 0xFFFFFFFFu);
    }
    if (VR && j == 3) { asm volatile("bar.sync 15, %0;" :: "r"((h & 1) ? 96 : 128) : "memory"); sts32(mbar + MB_TAB, 0); }
    gather();
    PRB(6)
    }
    load_v(s + 1);
    if (j < 2) {
      if (s + 3 < NSEG) mbar_wait(mbar + MB_X + (par ^ 1) * 8, ((s + 3) >> 1) & 1);
    } else {
      bar_sync<14, 320>();
      if (j == 2) {
        for (int guard = 0; used + QRING < s + 3 && guard < POLL_LIMIT && !DBGF(16); guard++) used = ld_relaxed(p.comm + FL_MEM + (L * 32 + h) * 32 + 24);
        if (s + 2 < NSEG) t_store(s + 2);
      } else if (s + 4 < NSEG) { if (s >= 0) wait_gt(T3 + p.xlate); x_load(p, sb, s + 4); }
    }
    for (int guard = 0;; guard++) {
      uint32_t m = 0, ok;
      if (j < 2 && s >= 0) {
        mbar_wait(mbar + MB_A, att & 1);
#pragma unroll
        for (int i = 0; i < 5; i++) m = max(m, lds32(l16 + (l16 & 511) + (l16 & 448) / 16 + (j * 1024 + SM_MEMT + i * 2048)));
      }
      att++;
      asm volatile("{.reg .pred p; setp.ne.u32 p, %1, 0xffffffff; bar.red.and.pred p, 13, 128, p; selp.u32 %0, 1, 0, p;}" : "=r"(ok) : "r"(m) : "memory");
      if (ok || guard == POLL_LIMIT) break;
      bar_arrive<9, 384>();
      VERDICT(1);
      if (j == 3) asm volatile(ELECT "@p mbarrier.arrive.expect_tx.shared.b64 _, [%0], 10240;}" :: "r"(mbar + MB_A) : "memory");
      T3 += p.slack;
      gather();
    }
    PRB(7)
    if (VR && j == 3) sts32(mbar + MB_TK, T3);
    if (s >= 0) publish(s + 1);
    else if (j == 0 && L0) { if (s == -2) mbar_arrive(mbar + MB_A); else TL_MAX(tlid, 3); }
  }
  bar_sync<9, 384>();
  m_store(NSEG - 1);
  VERDICT(0);
  publish(NSEG);
  if (j == 0 && L0) TL_MAX(tlid, 2);
  if (L == p.zero) {
    bar_arrive<1, 384>();
    if (is_red) {
      uint32_t* wpoi = (uint32_t*)(comm + (x3_slot(2) + bline + (l16 & 511) / 4));
      st_relaxed(wpoi, 0xFFFFFFFFu); st_relaxed(wpoi + 1024, 0xFFFFFFFFu);
#pragma unroll 1
      for (int i = 0; i < 8; i++) stg128((char*)comm + (inbox + 256 * 4096 + i * 512 + (l16 & 511)), 0, 0, 0, 0);
    }
  }
}

__global__ void __launch_bounds__(384, 1) rec_kernel(const __grid_constant__ RecParams p TLP) {
  extern __shared__ __align__(1024) char smem_raw[];
  const uint32_t sb = (smem_u32(smem_raw) + 1023) & ~1023u;
  char* smem = smem_raw + (sb - smem_u32(smem_raw));
  const int tid = threadIdx.x;
  const uint32_t mbar = sb + SM_BAR;
  pdl_launch();
  if (!p.helper) {
    if (tid == 32 || tid == 96) l2_prefetch((tid == 32 ? p.wi : p.wr) + blockIdx.x * 6848, 13696);
    if (tid == 64 && blockIdx.x < 12) l2_prefetch(g_tab + TB_F32 * 4 + blockIdx.x * 256, 1024);
#pragma unroll 1
    for (int o = blockIdx.x * 384 + tid; o < 384 * 256; o += 96 * 384) {
      const int i = o >> 8, u = i % 192, pg = (i / 192) * 256 + (u < 176 ? u : u + 48);
      const uint32_t v = (u >= 160 && !(u & 2)) ? ~0u : 0u;
      stg128((uint4*)p.comm + pg * 256 + (o & 255), v, v, v, v);
    }
  }
#pragma unroll 1
  for (int L = p.layer; L < 2; L++) {
    const int w = __shfl_sync(~0u, tid >> 5, 0), bid = blockIdx.x + (L & p.zero), h = bid / 3, r = bid % 3;
    if (tid == 0) { TL_MIN(tlid - p.helper, 0); TL_MAX(tlid - p.helper, 4); }
    if (tid == 0) {
#pragma unroll 1
      for (int i = 0; i < 14; i++) {
        if (L > p.layer) asm volatile("mbarrier.inval.shared.b64 [%0];" :: "r"(mbar + i * 8) : "memory");
        mbar_init(mbar + i * 8, i == 1 ? 32 : 1);
      }
      asm volatile("fence.mbarrier_init.release.cluster;" ::: "memory");
      asm volatile("fence.proxy.async.shared::cta;" ::: "memory");
      mbar_expect(mbar + MB_QK, r == 2 ? 1536 : 768); if (r < 2) mbar_expect(mbar + MB_V, 2048);
      mbar_expect(mbar + MB_KV, 8192); mbar_expect(mbar + MB_KV + 8, 8192);
      mbar_expect(mbar + MB_IA, L ? 0 : 163840); mbar_expect(mbar + MB_IC, r == 2 ? 32768 : 65536);
    }
    if (p.helper && L == 0 && blockIdx.x < 32) {
      __syncthreads();
      filter_prep(p.wr, p.wi, (uint32_t*)p.a[0].WT, sb + SM_WS, mbar + 8, blockIdx.x);
      __syncthreads();
      if (tid == 32) { red_release(p.a[0].sync + SY_W); TL_MAX(1, 2); }
    }
    auto wo_load = [&](int i0) {
#pragma unroll 1
      for (int i = i0; i < i0 + 4; i++)
        asm volatile(ELECT "@p cp.async.bulk.tensor.2d.shared::cluster.global.mbarrier::complete_tx::bytes [%0], [%1, {%3, %4}], [%2];}"
          :: "r"(sb + SM_WST + i * 8192), "l"(&p.tmWo), "r"(mbar + MB_IC), "r"(r * 256 + (i >> 1) * 64), "r"(h * 128 + (i & 1) * 64) : "memory");
    };
    a_layer(p.a[L], smem + SM_WST, bid + p.helper * 96, w, [&]() {
        if (!p.helper) {
          if (w == 2 && L == 0) {
#pragma unroll 1
            for (int i = 0; i < 4; i++)
              asm volatile(ELECT "@p cp.async.bulk.tensor.3d.shared::cluster.global.mbarrier::complete_tx::bytes [%0], [%1, {%3, %4, %5}], [%2];}"
                :: "r"(sb + SM_WS + ((i >> 1) + ((i ^ (i >> 1) ^ 1) & 1) * 2) * 40960), "l"(&p.tmW[r == 2 ? 2 : i & 1]), "r"(mbar + MB_IA), "r"(h * 128 + (r == 2 ? i & 1 : r) * 64), "r"(0), "r"((i >> 1) * 5) : "memory");
          }
          if (w >= 4 && w < 8 && bid < 80) asm volatile(ELECT "@p cp.async.bulk.prefetch.L2.global [%0], 16384;}" :: "l"(p.Wo + (bid * 4 + w - 4) * 8192) : "memory");
        }
      }, [&]() { if (w == 8 && !p.helper) wo_load(0); } TLA(tlid));
    if (p.helper) return;
    __syncwarp();
    if (w == 2 && r < 2) { asm volatile("fence.proxy.async.shared::cta;" ::: "memory"); wo_load(4); }
    if (w < 8) {
      if (r < 2) { asm volatile("setmaxnreg.inc.sync.aligned.u32 216;"); rec_gemm_warps<false>(p, sb, h, r, L, w TLA(tlid)); asm volatile("setmaxnreg.dec.sync.aligned.u32 168;"); }
      else { asm volatile("setmaxnreg.inc.sync.aligned.u32 208;"); rec_gemm_warps<true>(p, sb, h, r, L, w TLA(tlid)); asm volatile("setmaxnreg.dec.sync.aligned.u32 168;"); }
    } else {
      asm volatile("setmaxnreg.dec.sync.aligned.u32 72;");
      const int side = rec_attn_setup(p, sb, h, r, L, w - 8 TLA(tlid));
      if (r < 2) { rec_attn_warps<false>(p, sb, smem, h, r, side, L, w - 8 TLA(tlid)); asm volatile("setmaxnreg.inc.sync.aligned.u32 168;"); }
      else { asm volatile("setmaxnreg.inc.sync.aligned.u32 88;"); rec_attn_warps<true>(p, sb, smem, h, r, side, L, w - 8 TLA(tlid)); asm volatile("setmaxnreg.inc.sync.aligned.u32 168;"); }
    }
    asm volatile("barrier.cluster.arrive.relaxed.aligned; barrier.cluster.wait.aligned;" ::: "memory");
    __syncthreads();
  }
}

constexpr int PERIOD = 2048, C3 = 480, SLACK = 672, XLATE = 192, GAP = 288;
__device__ uint32_t g_ZT[640 * 1024];
__device__ uint32_t g_WT[321 * 2048];
__device__ bf16 g_x1[S_ * D_], g_x2[S_ * D_], g_hN[S_ * D_];
__device__ __align__(128) uint4 g_QKV[QRING * 32 * 30720 / 16], g_O[ORING * 32 * 8192 / 16];
__device__ __align__(128) uint4 g_part[PRING * 32 * 8960 / 16];
__device__ __align__(128) uint32_t g_sync[256];
__device__ uint32_t g_comm[(4 << 20) / 4];

typedef CUresult (*EncodeFn)(CUtensorMap*, CUtensorMapDataType, cuuint32_t, void*, const cuuint64_t*, const cuuint64_t*, const cuuint32_t*, const cuuint32_t*,
                             CUtensorMapInterleave, CUtensorMapSwizzle, CUtensorMapL2promotion, CUtensorMapFloatOOBfill);
static void make_map(EncodeFn fn, CUtensorMap* m, const void* base, uint64_t cols, uint64_t rows, uint32_t bc, uint32_t br) {
  cuuint64_t dims[2] = {cols, rows}, strides[1] = {cols * 2}; cuuint32_t box[2] = {bc, br}, es[2] = {1, 1};
  fn(m, CU_TENSOR_MAP_DATA_TYPE_BFLOAT16, 2, (void*)base, dims, strides, box, es, CU_TENSOR_MAP_INTERLEAVE_NONE, CU_TENSOR_MAP_SWIZZLE_128B, CU_TENSOR_MAP_L2_PROMOTION_L2_256B, CU_TENSOR_MAP_FLOAT_OOB_FILL_NONE);
}
template <typename T> static T* sym(T& s) { void* p; cudaGetSymbolAddress(&p, s); return (T*)p; }

template <typename... KA, typename... A> static void launch(void (*k)(KA...), int grid, int block, int smem, bool pdl, int cluster, A... a) {
  cudaLaunchConfig_t cfg = {};
  cfg.gridDim = dim3(grid); cfg.blockDim = dim3(block); cfg.dynamicSmemBytes = smem; cfg.stream = cudaStreamPerThread;
  cudaLaunchAttribute at[2]; int n = 0;
  if (pdl) { at[n].id = cudaLaunchAttributeProgrammaticStreamSerialization; at[n].val.programmaticStreamSerializationAllowed = 1; n++; }
  if (cluster > 1) { at[n].id = cudaLaunchAttributeClusterDimension; at[n].val.clusterDim.x = cluster; at[n].val.clusterDim.y = 1; at[n].val.clusterDim.z = 1; n++; }
  cfg.attrs = at; cfg.numAttrs = n;
  cudaLaunchKernelEx(&cfg, k, KA(a)...);
}

extern "C" void kernel_launch(void* const* d_in, const int* in_sizes, int n_in, void* d_out, int out_size) {
  const bf16 *x = (const bf16*)d_in[0], *wr = (const bf16*)d_in[1], *wi = (const bf16*)d_in[2], *mem0 = (const bf16*)d_in[4];
  const bf16 *Wq = (const bf16*)d_in[5], *Wk = (const bf16*)d_in[6], *Wv = (const bf16*)d_in[7], *Wo = (const bf16*)d_in[8];
  bf16* out = (bf16*)d_out;
  uint32_t *ZT = (uint32_t*)sym(g_ZT), *WT = (uint32_t*)sym(g_WT);
  bf16 *x1 = (bf16*)sym(g_x1), *x2 = (bf16*)sym(g_x2), *hN = (bf16*)sym(g_hN);
  char *QKV = (char*)sym(g_QKV), *part = (char*)sym(g_part);
  uint32_t* comm = (uint32_t*)(((uint64_t)sym(g_comm) + (2 << 20) - 1) & ~(uint64_t)((2 << 20) - 1));
  EncodeFn enc = nullptr; cudaDriverEntryPointQueryResult qr;
  cudaGetDriverEntryPoint("cuTensorMapEncodeTiled", (void**)&enc, cudaEnableDefault, &qr);
  CUtensorMap tmW[3], tmWo, tmX, tmP;
  { cuuint64_t dims[3] = {64, PRING * 32, 70}, strides[2] = {8960, 128}; cuuint32_t box[3] = {64, 32, 2}, es[3] = {1, 1, 1};
    enc(&tmP, CU_TENSOR_MAP_DATA_TYPE_BFLOAT16, 3, part, dims, strides, box, es, CU_TENSOR_MAP_INTERLEAVE_NONE, CU_TENSOR_MAP_SWIZZLE_128B, CU_TENSOR_MAP_L2_PROMOTION_NONE, CU_TENSOR_MAP_FLOAT_OOB_FILL_NONE); }
  { cuuint64_t dims[3] = {64, 2048, 10}, strides[2] = {1280, 128}; cuuint32_t box[3] = {64, 32, 10}, es[3] = {1, 1, 1};
    enc(&tmX, CU_TENSOR_MAP_DATA_TYPE_BFLOAT16, 3, hN, dims, strides, box, es, CU_TENSOR_MAP_INTERLEAVE_NONE, CU_TENSOR_MAP_SWIZZLE_128B, CU_TENSOR_MAP_L2_PROMOTION_L2_256B, CU_TENSOR_MAP_FLOAT_OOB_FILL_NONE); }
  for (int i = 0; i < 3; i++) {
    cuuint64_t dims[3] = {4096, 64, 10}, strides[2] = {8192, 64 * 8192}; cuuint32_t box[3] = {64, 64, 5}, es[3] = {1, 1, 1};
    enc(&tmW[i], CU_TENSOR_MAP_DATA_TYPE_BFLOAT16, 3, (void*)(i == 0 ? Wq : i == 1 ? Wk : Wv), dims, strides, box, es, CU_TENSOR_MAP_INTERLEAVE_NONE, CU_TENSOR_MAP_SWIZZLE_128B, CU_TENSOR_MAP_L2_PROMOTION_L2_256B, CU_TENSOR_MAP_FLOAT_OOB_FILL_NONE);
  }
  make_map(enc, &tmWo, Wo, 640, 4096, 64, 64);
  int dbgf = 0;
  cudaFuncSetAttribute(side_kernel, cudaFuncAttributeMaxDynamicSharedMemorySize, SD_SMEM);
  cudaFuncSetAttribute(rec_kernel, cudaFuncAttributeMaxDynamicSharedMemorySize, REC_SMEM);
  uint32_t* sy = (uint32_t*)sym(g_sync);
  RecParams rp = {{tmW[0], tmW[1], tmW[2]}, tmWo, tmX, {{x, ZT, WT, x1, hN, sy, nullptr, 32}, {x2, ZT, WT, x1, hN, sy + 128, (dbgf & 16) ? nullptr : comm + FL_RDY + 12, 0}},
                  mem0, Wo, wr, wi, QKV, comm, PERIOD, C3, SLACK, XLATE, GAP, 0, 0, 0, dbgf, nullptr, nullptr};
  launch(rec_kernel, 96, 384, REC_SMEM, false, 3, rp TLA(0));
  for (int L = 0; L < 2; L++) {
    rp.helper = 1; rp.layer = L;
    launch(rec_kernel, 35, 384, REC_SMEM, true, 1, rp TLA(0));
    SideParams sp = {tmWo, tmP, QKV, (char*)sym(g_O), part, x1, L == 0 ? x2 : out, comm + L * 1024, sy + L * 128, L == 0, dbgf};
    launch(side_kernel, 35, 512, SD_SMEM, true, 1, sp TLA(L * 10 + 6));
  }
}
```

```cpp
#include <cuda_runtime.h>
#include <cuda_bf16.h>
#include <cuda.h>
#include <stdint.h>
typedef __nv_bfloat16 bf16;
constexpr int S_ = 2048, D_ = 640, H_ = 32, DH = 128, NSEG = 64;

__device__ __forceinline__ uint32_t smem_u32(const void* p) { return (uint32_t)__cvta_generic_to_shared(p); }
__device__ __forceinline__ uint32_t pack_bf16(float lo, float hi) { uint32_t r; asm("cvt.rn.bf16x2.f32 %0, %1, %2;" : "=r"(r) : "f"(hi), "f"(lo)); return r; }
__device__ __forceinline__ float bf_lo(uint32_t v) { return __uint_as_float(v << 16); }
__device__ __forceinline__ float bf_hi(uint32_t v) { return __uint_as_float(v & 0xFFFF0000u); }
__device__ __forceinline__ void ldsm4t(uint32_t& r0, uint32_t& r1, uint32_t& r2, uint32_t& r3, uint32_t a) {
  asm volatile("ldmatrix.sync.aligned.m8n8.x4.trans.shared.b16 {%0,%1,%2,%3}, [%4];" : "=r"(r0), "=r"(r1), "=r"(r2), "=r"(r3) : "r"(a) : "memory");
}
__device__ __forceinline__ void ldsm4(uint32_t& r0, uint32_t& r1, uint32_t& r2, uint32_t& r3, uint32_t a) {
  asm volatile("ldmatrix.sync.aligned.m8n8.x4.shared.b16 {%0,%1,%2,%3}, [%4];" : "=r"(r0), "=r"(r1), "=r"(r2), "=r"(r3) : "r"(a) : "memory");
}
__device__ __forceinline__ void mma16816(float* d, uint32_t a0, uint32_t a1, uint32_t a2, uint32_t a3, uint32_t b0, uint32_t b1) {
  asm volatile("mma.sync.aligned.m16n8k16.row.col.f32.bf16.bf16.f32 {%0,%1,%2,%3}, {%4,%5,%6,%7}, {%8,%9}, {%0,%1,%2,%3};"
    : "+f"(d[0]), "+f"(d[1]), "+f"(d[2]), "+f"(d[3]) : "r"(a0), "r"(a1), "r"(a2), "r"(a3), "r"(b0), "r"(b1));
}
__device__ __forceinline__ void mma16816z(float* d, uint32_t a0, uint32_t a1, uint32_t a2, uint32_t a3, uint32_t b0, uint32_t b1) {
  asm volatile("mma.sync.aligned.m16n8k16.row.col.f32.bf16.bf16.f32 {%0,%1,%2,%3}, {%4,%5,%6,%7}, {%8,%9}, {%10,%10,%10,%10};"
    : "=f"(d[0]), "=f"(d[1]), "=f"(d[2]), "=f"(d[3]) : "r"(a0), "r"(a1), "r"(a2), "r"(a3), "r"(b0), "r"(b1), "f"(0.f));
}
__device__ __forceinline__ void mma1688z(float* d, uint32_t a0, uint32_t a1, uint32_t b0) {
  asm volatile("mma.sync.aligned.m16n8k8.row.col.f32.bf16.bf16.f32 {%0,%1,%2,%3}, {%4,%5}, {%6}, {%7,%7,%7,%7};"
    : "=f"(d[0]), "=f"(d[1]), "=f"(d[2]), "=f"(d[3]) : "r"(a0), "r"(a1), "r"(b0), "f"(0.f));
}
__device__ __forceinline__ void mma1688(float* d, uint32_t a0, uint32_t a1, uint32_t b0) {
  asm volatile("mma.sync.aligned.m16n8k8.row.col.f32.bf16.bf16.f32 {%0,%1,%2,%3}, {%4,%5}, {%6}, {%0,%1,%2,%3};"
    : "+f"(d[0]), "+f"(d[1]), "+f"(d[2]), "+f"(d[3]) : "r"(a0), "r"(a1), "r"(b0));
}
__device__ __forceinline__ void mmaA(float* d, const uint32_t* a, uint32_t b0, uint32_t b1) { mma16816(d, a[0], a[1], a[2], a[3], b0, b1); }
__device__ __forceinline__ void mmaZ(float* d, const uint32_t* a, uint32_t b0, uint32_t b1) { mma16816z(d, a[0], a[1], a[2], a[3], b0, b1); }
__device__ __forceinline__ uint32_t movm(uint32_t a) { uint32_t d; asm volatile("movmatrix.sync.aligned.m8n8.trans.b16 %0, %1;" : "=r"(d) : "r"(a)); return d; }
__device__ __forceinline__ void cp_async16(uint32_t dst, const void* src) { asm volatile("cp.async.cg.shared.global [%0], [%1], 16;" :: "r"(dst), "l"(src) : "memory"); }
__device__ __forceinline__ void cp_commit() { asm volatile("cp.async.commit_group;" ::: "memory"); }
template <int N> __device__ __forceinline__ void cp_wait() { asm volatile("cp.async.wait_group %0;" :: "n"(N) : "memory"); }
__device__ __forceinline__ void lds128(uint32_t* r, uint32_t a) { asm volatile("ld.shared.v4.b32 {%0,%1,%2,%3}, [%4];" : "=r"(r[0]), "=r"(r[1]), "=r"(r[2]), "=r"(r[3]) : "r"(a) : "memory"); }
__device__ __forceinline__ void sts128(uint32_t a, uint32_t r0, uint32_t r1, uint32_t r2, uint32_t r3) { asm volatile("st.shared.v4.b32 [%0], {%1,%2,%3,%4};" :: "r"(a), "r"(r0), "r"(r1), "r"(r2), "r"(r3) : "memory"); }
__device__ __forceinline__ void stg128(void* p, uint32_t r0, uint32_t r1, uint32_t r2, uint32_t r3) { asm volatile("st.global.v4.b32 [%0], {%1,%2,%3,%4};" :: "l"(p), "r"(r0), "r"(r1), "r"(r2), "r"(r3) : "memory"); }
template <int ID, int N> __device__ __forceinline__ void bar_sync() { asm volatile("bar.sync %0, %1;" :: "n"(ID), "n"(N) : "memory"); }
template <int ID, int N> __device__ __forceinline__ void bar_arrive() { asm volatile("bar.arrive %0, %1;" :: "n"(ID), "n"(N) : "memory"); }
__device__ __forceinline__ void mbar_wait(uint32_t bar, uint32_t parity) {
  asm volatile("{\n.reg .pred p, pq;\n.reg .u32 n;\nmov.u32 n, 0;\nLW%=:\nmbarrier.try_wait.parity.shared::cta.b64 p, [%0], %1;\n@p bra.uni LD%=;\nadd.u32 n, n, 1;\nsetp.lt.u32 pq, n, 20000;\n@pq bra.uni LW%=;\nLD%=:\n}" :: "r"(bar), "r"(parity) : "memory");
}
#define mbar_wait_long mbar_wait
__device__ __forceinline__ void mbar_init(uint32_t bar, int n) { asm volatile("mbarrier.init.shared.b64 [%0], %1;" :: "r"(bar), "r"(n) : "memory"); }
__device__ __forceinline__ void mbar_expect(uint32_t bar, int bytes) { asm volatile("mbarrier.arrive.expect_tx.shared.b64 _, [%0], %1;" :: "r"(bar), "r"(bytes) : "memory"); }
__device__ __forceinline__ void mbar_arrive(uint32_t bar) { asm volatile("mbarrier.arrive.shared.b64 _, [%0];" :: "r"(bar) : "memory"); }
__device__ __forceinline__ void l2_prefetch(const void* p, int bytes) { asm volatile("cp.async.bulk.prefetch.L2.global [%0], %1;" :: "l"(p), "r"(bytes) : "memory"); }
__device__ __forceinline__ float ex2(float x) { float y; asm("ex2.approx.ftz.f32 %0, %1;" : "=f"(y) : "f"(x)); return y; }
__device__ __forceinline__ void pdl_wait() { asm volatile("griddepcontrol.wait;" ::: "memory"); }
__device__ __forceinline__ void pdl_launch() { asm volatile("griddepcontrol.launch_dependents;" ::: "memory"); }
__device__ __forceinline__ uint32_t hadd2(uint32_t a, uint32_t b) { uint32_t r; asm("add.rn.bf16x2 %0, %1, %2;" : "=r"(r) : "r"(a), "r"(b)); return r; }
__device__ __forceinline__ void sched_fence() { asm volatile("{\n.reg .pred p;\n.reg .u32 t;\nLF%=:\nmov.u32 t, %%clock;\nsetp.eq.u32 p, t, %0;\n@p bra.uni LF%=;\n}" :: "n"(12345) : "memory"); }
#define TL(k)
#define TL_DUMP(slot, t)

constexpr int TB_F16 = 0, TB_640 = 64, TB_F40 = 384, TB_F32 = 784, TB_512 = 1040, TB_2048 = 1296;
__device__ __align__(128) const uint32_t g_tab[6208] = {
0x3f803f80,0xbf803f80,0x3f803f80,0xbf803f80,0x3f803f80,0xbf803f80,0x3f803f80,0xbf803f80,0x3f803f80,0xbf803f80,0x3f803f80,0xbf803f80,0x3f803f80,0xbf803f80,0x3f803f80,0xbf803f80,
0x3f6d3f80,0xbf6d3f80,0xbf6dbf80,0x3f6dbf80,0x3ec43f35,0xbec43f35,0xbec4bf35,0x3ec4bf35,0xbec40000,0x3ec40000,0x3ec40000,0xbec40000,0xbf6dbf35,0x3f6dbf35,0x3f6d3f35,0xbf6d3f35,
0x3f353f80,0xbf353f80,0x3f353f80,0xbf353f80,0xbf350000,0x3f350000,0xbf350000,0x3f350000,0xbf35bf80,0x3f35bf80,0xbf35bf80,0x3f35bf80,0x3f350000,0xbf350000,0x3f350000,0xbf350000,
0x3ec43f80,0xbec43f80,0xbec4bf80,0x3ec4bf80,0xbf6dbf35,0x3f6dbf35,0x3f6d3f35,0xbf6d3f35,0x3f6d0000,0xbf6d0000,0xbf6d0000,0x3f6d0000,0xbec43f35,0x3ec43f35,0x3ec4bf35,0xbec4bf35,
0x3f80,0x3f80,0x3f80,0x3f80,0xbf80,0xbf80,0xbf80,0xbf80,0x3f80,0x3f80,0x3f80,0x3f80,0xbf80,0xbf80,0xbf80,0xbf80,
0xbec43f80,0x3ec43f80,0x3ec4bf80,0xbec4bf80,0x3f6dbf35,0xbf6dbf35,0xbf6d3f35,0x3f6d3f35,0xbf6d0000,0x3f6d0000,0x3f6d0000,0xbf6d0000,0x3ec43f35,0xbec43f35,0xbec4bf35,0x3ec4bf35,
0xbf353f80,0x3f353f80,0xbf353f80,0x3f353f80,0x3f350000,0xbf350000,0x3f350000,0xbf350000,0x3f35bf80,0xbf35bf80,0x3f35bf80,0xbf35bf80,0xbf350000,0x3f350000,0xbf350000,0x3f350000,
0xbf6d3f80,0x3f6d3f80,0x3f6dbf80,0xbf6dbf80,0xbec43f35,0x3ec43f35,0x3ec4bf35,0xbec4bf35,0x3ec40000,0xbec40000,0xbec40000,0x3ec40000,0x3f6dbf35,0xbf6dbf35,0xbf6d3f35,0x3f6d3f35,
0x80008000,0x80008000,0x80008000,0x80008000,0x80008000,0x80008000,0x80008000,0x80008000,0x80008000,0x80008000,0x80008000,0x80008000,0x80008000,0x80008000,0x80008000,0x80008000,
0xbec48000,0x3ec48000,0x3ec48000,0xbec48000,0xbf6dbf35,0x3f6dbf35,0x3f6d3f35,0xbf6d3f35,0xbf6dbf80,0x3f6dbf80,0x3f6d3f80,0xbf6d3f80,0xbec4bf35,0x3ec4bf35,0x3ec43f35,0xbec43f35,
0xbf358000,0x3f358000,0xbf358000,0x3f358000,0xbf35bf80,0x3f35bf80,0xbf35bf80,0x3f35bf80,0x3f358000,0xbf358000,0x3f358000,0xbf358000,0x3f353f80,0xbf353f80,0x3f353f80,0xbf353f80,
0xbf6d8000,0x3f6d8000,0x3f6d8000,0xbf6d8000,0x3ec4bf35,0xbec4bf35,0xbec43f35,0x3ec43f35,0x3ec43f80,0xbec43f80,0xbec4bf80,0x3ec4bf80,0xbf6dbf35,0x3f6dbf35,0x3f6d3f35,0xbf6d3f35,
0xbf808000,0x3f808000,0xbf808000,0x3f808000,0x3f808000,0xbf808000,0x3f808000,0xbf808000,0xbf808000,0x3f808000,0xbf808000,0x3f808000,0x3f808000,0xbf808000,0x3f808000,0xbf808000,
0xbf6d8000,0x3f6d8000,0x3f6d8000,0xbf6d8000,0x3ec43f35,0xbec43f35,0xbec4bf35,0x3ec4bf35,0x3ec4bf80,0xbec4bf80,0xbec43f80,0x3ec43f80,0xbf6d3f35,0x3f6d3f35,0x3f6dbf35,0xbf6dbf35,
0xbf358000,0x3f358000,0xbf358000,0x3f358000,0xbf353f80,0x3f353f80,0xbf353f80,0x3f353f80,0x3f358000,0xbf358000,0x3f358000,0xbf358000,0x3f35bf80,0xbf35bf80,0x3f35bf80,0xbf35bf80,
0xbec48000,0x3ec48000,0x3ec48000,0xbec48000,0xbf6d3f35,0x3f6d3f35,0x3f6dbf35,0xbf6dbf35,0xbf6d3f80,0x3f6d3f80,0x3f6dbf80,0xbf6dbf80,0xbec43f35,0x3ec43f35,0x3ec4bf35,0xbec4bf35,
0x3f800000,0x3f800000,0x3f800000,0x3f7f35f9,0x3f800000,0x3f800000,0x3f7cd925,0x3f78ed3c,0x3f800000,0x3f800000,0x3f737871,0x3f6c835e,0x3f800000,0x3f800000,0x3f641901,0x3f5a46a0,
0x3f800000,0x3f7ffcd7,0x3f800000,0x3f7f0059,0x3f7ff35e,0x3f7fe394,0x3f7c0361,0x3f770f11,0x3f7fcd79,0x3f7fb10f,0x3f702d4f,0x3f676bd8,0x3f7f8e56,0x3f7f654e,0x3f5cdc29,0x3f50935b,
0x3f800000,0x3f7ff35e,0x3f800000,0x3f7ec46d,0x3f7fcd79,0x3f7f8e56,0x3f7b14be,0x3f74fa0b,0x3f7f35f9,0x3f7ec46d,0x3f6c835e,0x3f61c598,0x3f7e39bc,0x3f7d95f4,0x3f54db31,0x3f45e403,
0x3f800000,0x3f7fe394,0x3f800000,0x3f7e8238,0x3f7f8e56,0x3f7f0059,0x3f7a0d54,0x3f72ae9e,0x3f7e39bc,0x3f7d3aac,0x3f687c12,0x3f5b941a,0x3f7c0361,0x3f7a9421,0x3f4c1d35,0x3f3a4582,
0x3f800000,0x3f7fcd79,0x3f800000,0x3f7e39bc,0x3f7f35f9,0x3f7e39bc,0x3f78ed3c,0x3f702d4f,0x3f7cd925,0x3f7b14be,0x3f641901,0x3f54db31,0x3f78ed3c,0x3f766377,0x3f42a9f7,0x3f2dc5e3,
0x3f800000,0x3f7fb10f,0x3f800000,0x3f7deafa,0x3f7ec46d,0x3f7d3aac,0x3f77b493,0x3f6d76aa,0x3f7b14be,0x3f7853f8,0x3f5f5be6,0x3f4d9f02,0x3f74fa0b,0x3f710908,0x3f3889dc,0x3f207440,
0x3f800000,0x3f7f8e56,0x3f800000,0x3f7d95f4,0x3f7e39bc,0x3f7c0361,0x3f766377,0x3f6a8b4b,0x3f78ed3c,0x3f74fa0b,0x3f5a46a0,0x3f45e403,0x3f702d4f,0x3f6a8b4b,0x3f2dc5e3,0x3f1260b2,
0x3f800000,0x3f7f654e,0x3f800000,0x3f7d3aac,0x3f7d95f4,0x3f7a9421,0x3f74fa0b,0x3f676bd8,0x3f766377,0x3f710908,0x3f54db31,0x3f3daef9,0x3f6a8b4b,0x3f62f219,0x3f226799,0x3f039c3d,
0x3f800000,0x3f800000,0x3f4f1bbd,0x3f42a9f7,0x3f800000,0x3f800000,0x3f3504f3,0x3f26423a,0x3f800000,0x3f800000,0x3f167918,0x3f05c277,0x3f800000,0x3f800000,0x3ee87171,0x3ec3ef15,
0x3f7f35f9,0x3f7f0059,0x3f42a9f7,0x3f333bc6,0x3f7ec46d,0x3f7e8238,0x3f226799,0x3f104f0e,0x3f7e39bc,0x3f7deafa,0x3efa2c90,0x3ed1c759,0x3f7d95f4,0x3f7d3aac,0x3ea7bf25,0x3e78cfcc,
0x3f7cd925,0x3f7c0361,0x3f3504f3,0x3f226799,0x3f7b14be,0x3f7a0d54,0x3f0e39da,0x3ef15aea,0x3f78ed3c,0x3f77b493,0x3ec3ef15,0x3e94a031,0x3f766377,0x3f74fa0b,0x3e47c5c2,0x3dc8bd36,
0x3f78ed3c,0x3f770f11,0x3f26423a,0x3f104f0e,0x3f74fa0b,0x3f72ae9e,0x3ef15aea,0x3ebf47d7,0x3f702d4f,0x3f6d76aa,0x3e8afa3e,0x3e2a1c3f,0x3f6a8b4b,0x3f676bd8,0x3d712283,0xbd48fb30,
0x3f737871,0x3f702d4f,0x3f167918,0x3efa2c90,0x3f6c835e,0x3f687c12,0x3ec3ef15,0x3e8afa3e,0x3f641901,0x3f5f5be6,0x3e20305b,0x3d20cee7,0x3f5a46a0,0x3f54db31,0xbda0af2a,0xbe47c5c2,
0x3f6c835e,0x3f676bd8,0x3f05c277,0x3ed1c759,0x3f61c598,0x3f5b941a,0x3e94a031,0x3e2a1c3f,0x3f54db31,0x3f4d9f02,0x3d20cee7,0xbdb4b86a,0x3f45e403,0x3f3daef9,0xbe5b73dc,0xbeac7cd4,
0x3f641901,0x3f5cdc29,0x3ee87171,0x3ea7bf25,0x3f54db31,0x3f4c1d35,0x3e47c5c2,0x3d712283,0x3f42a9f7,0x3f3889dc,0xbda0af2a,0xbe5b73dc,0x3f2dc5e3,0x3f226799,0xbeb13641,0xbef15aea,
0x3f5a46a0,0x3f50935b,0x3ec3ef15,0x3e78cfcc,0x3f45e403,0x3f3a4582,0x3dc8bd36,0xbd48fb30,0x3f2dc5e3,0x3f207440,0xbe47c5c2,0xbeac7cd4,0x3f1260b2,0x3f039c3d,0xbef15aea,0xbf187fc0,
0x3f800000,0x3f800000,0x3e9e377a,0x3e6f0c4d,0x3f800000,0x3f800000,0x3e20305b,0x3da0af2a,0x3f800000,0x3f800000,0,0xbda0af2a,0x3f800000,0x3f800000,0xbe20305b,0xbe6f0c4d,
0x3f7cd925,0x3f7c7160,0x3e20305b,0x3d8ca1f2,0x3f7c0361,0x3f7b8f2a,0xbca0d6d6,0xbddcbd0d,0x3f7b14be,0x3f7a9421,0xbe47c5c2,0xbe8fcefe,0x3f7a0d54,0x3f79805c,0xbeba9be1,0xbee3f40d,
0x3f737871,0x3f71decf,0,0xbdc8bd36,0x3f702d4f,0x3f6e641a,0xbe47c5c2,0xbe94a031,0x3f6c835e,0x3f6a8b4b,0xbec3ef15,0xbef15aea,0x3f687c12,0x3f6655e7,0xbf0e39da,0xbf226799,
0x3f641901,0x3f609384,0xbe20305b,0xbe862210,0x3f5cdc29,0x3f58f3c4,0xbeba9be1,0xbeece91a,0x3f54db31,0x3f50935b,0xbf0e39da,0xbf2456f1,0x3f4c1d35,0x3f4779bc,0xbf3889dc,0xbf4a965e,
0x3f4f1bbd,0x3f490a88,0xbe9e377a,0xbed65a92,0x3f42a9f7,0x3f3bfc8f,0xbf05c277,0xbf1e7cf1,0x3f3504f3,0x3f2dc5e3,0xbf3504f3,0xbf490a88,0x3f26423a,0x3f1e7cf1,0xbf5a46a0,0xbf687c12,
0x3f3504f3,0x3f2beb4a,0xbee87171,0xbf104f0e,0x3f226799,0x3f187fc0,0xbf2a0c73,0xbf4105b8,0x3f0e39da,0x3f039c3d,0xbf54db31,0xbf653a48,0x3ef15aea,0x3edae880,0xbf71decf,0xbf7a9421,
0x3f167918,0x3f0a04f8,0xbf167918,0xbf316e2c,0x3efa2c90,0x3edf7108,0xbf490a88,0xbf5cdc29,0x3ec3ef15,0x3ea7bf25,0xbf6c835e,0xbf77b493,0x3e8afa3e,0x3e5b73dc,0xbf7e39bc,0xbf7ff35e,
0x3ee87171,0x3ec8917e,0xbf3504f3,0xbf4d9f02,0x3ea7bf25,0x3e862210,0xbf61c598,0xbf710908,0x3e47c5c2,0x3e0255f4,0xbf7b14be,0xbf7fb10f,0x3d712283,0xbc20d8d2,0xbf7ec46d,0xbf7853f8,
0x3f800000,0x3f800000,0xbe9e377a,0xbec3ef15,0x3f800000,0x3f800000,0xbee87171,0xbf05c277,0x3f800000,0x3f800000,0xbf167918,0xbf26423a,0x3f800000,0x3f800000,0xbf3504f3,0xbf42a9f7,
0x3f78ed3c,0x3f7853f8,0xbf05c277,0xbf187fc0,0x3f77b493,0x3f770f11,0xbf2a0c73,0xbf3a4582,0x3f766377,0x3f75b1c9,0xbf490a88,0xbf563e03,0x3f74fa0b,0x3f743c41,0xbf61c598,0xbf6b8a3d,
0x3f641901,0x3f61c598,0xbf3504f3,0xbf45e403,0x3f5f5be6,0x3f5cdc29,0xbf54db31,0xbf61c598,0x3f5a46a0,0x3f579b8c,0xbf6c835e,0xbf74fa0b,0x3f54db31,0x3f5205d4,0xbf7b14be,0xbf7ec46d,
0x3f42a9f7,0x3f3daef9,0xbf5a46a0,0xbf676bd8,0x3f3889dc,0x3f333bc6,0xbf71decf,0xbf79805c,0x3f2dc5e3,0x3f28296a,0xbf7e39bc,0xbf7ffcd7,0x3f226799,0x3f1c81b9,0xbf7ec46d,0xbf7a9421,
0x3f167918,0x3f0e39da,0xbf737871,0xbf7b14be,0x3f05c277,0x3efa2c90,0xbf7f35f9,0xbf7fcd79,0x3ee87171,0x3ed65a92,0xbf7cd925,0xbf766377,0x3ec3ef15,0x3eb13641,0xbf6c835e,0xbf5f5be6,
0x3ec3ef15,0x3eac7cd4,0xbf7f35f9,0xbf7fb10f,0x3e94a031,0x3e78cfcc,0xbf7c0361,0xbf743c41,0x3e47c5c2,0x3e164083,0xbf687c12,0xbf58f3c4,0x3dc8bd36,0x3d48fb30,0xbf45e403,0xbf2f9c32,
0x3e20305b,0x3dc8bd36,0xbf7cd925,0xbf74fa0b,0x3d20cee7,0xbca0d6d6,0xbf687c12,0xbf579b8c,0xbda0af2a,0xbe0c4cf7,0xbf42a9f7,0xbf2a0c73,0xbe47c5c2,0xbe814693,0xbf0e39da,0xbedf7108,
0xbda0af2a,0xbe164083,0xbf6c835e,0xbf5b941a,0xbe5b73dc,0xbe8fcefe,0xbf45e403,0xbf2beb4a,0xbeb13641,0xbed1c759,0xbf0e39da,0xbedae880,0xbef15aea,0xbf07e565,0xbe94a031,0xbe164083,
0x3f800000,0x3f800000,0xbf4f1bbd,0xbf5a46a0,0x3f800000,0x3f800000,0xbf641901,0xbf6c835e,0x3f800000,0x3f800000,0xbf737871,0xbf78ed3c,0x3f800000,0x3f800000,0xbf7cd925,0xbf7f35f9,
0x3f737871,0x3f72ae9e,0xbf737871,0xbf79805c,0x3f71decf,0x3f710908,0xbf7d95f4,0xbf7fb10f,0x3f702d4f,0x3f6f4ba8,0xbf7fcd79,0xbf7deafa,0x3f6e641a,0x3f6d76aa,0xbf7a0d54,0xbf743c41,
0x3f4f1bbd,0x3f4c1d35,0xbf800000,0xbf7ec46d,0x3f490a88,0x3f45e403,0xbf7b14be,0xbf74fa0b,0x3f42a9f7,0x3f3f5cb5,0xbf6c835e,0xbf61c598,0x3f3bfc8f,0x3f3889dc,0xbf54db31,0xbf45e403,
0x3f167918,0x3f104f0e,0xbf737871,0xbf698690,0x3f0a04f8,0x3f039c3d,0xbf5cdc29,0xbf4d9f02,0x3efa2c90,0x3eece91a,0xbf3bfc8f,0xbf28296a,0x3edf7108,0x3ed1c759,0xbf1260b2,0xbef5c6c5,
0x3e9e377a,0x3e8afa3e,0xbf4f1bbd,0xbf3bfc8f,0x3e6f0c4d,0x3e47c5c2,0xbf26423a,0xbf0e39da,0x3e20305b,0x3df0b772,0xbee87171,0xbeb13641,0x3da0af2a,0x3d20cee7,0xbe6f0c4d,0xbdf0b772,
0,0xbd48fb30,0xbf167918,0xbef5c6c5,0xbdc8bd36,0xbe164083,0xbeba9be1,0xbe78cfcc,0xbe47c5c2,0xbe78cfcc,0xbdf0b772,0x3c20d8d2,0xbe94a031,0xbeac7cd4,0x3e0c4cf7,0x3e862210,
0xbe9e377a,0xbeba9be1,0xbe9e377a,0xbe3403f1,0xbed65a92,0xbef15aea,0xbd20cee7,0x3dc8bd36,0xbf05c277,0xbf1260b2,0x3e6f0c4d,0x3eba9be1,0xbf1e7cf1,0xbf2a0c73,0x3efa2c90,0x3f1a82a4,
0xbf167918,0xbf2456f1,0,0x3e164083,0xbf316e2c,0xbf3daef9,0x3e94a031,0x3edae880,0xbf490a88,0xbf53731f,0x3f0e39da,0x3f2beb4a,0xbf5cdc29,0xbf653a48,0x3f45e403,0x3f5b941a,
0x80000000,0x80000000,0x80000000,0xbda0af2a,0x80000000,0x80000000,0xbe20305b,0xbe6f0c4d,0x80000000,0x80000000,0xbe9e377a,0xbec3ef15,0x80000000,0x80000000,0xbee87171,0xbf05c277,
0x80000000,0xbc20d8d2,0x80000000,0xbdb4b86a,0xbca0d6d6,0xbcf13d4c,0xbe3403f1,0xbe862210,0xbd20cee7,0xbd48fb30,0xbeb13641,0xbedae880,0xbd712283,0xbd8ca1f2,0xbf0172c3,0xbf146eba,
0x80000000,0xbca0d6d6,0x80000000,0xbdc8bd36,0xbd20cee7,0xbd712283,0xbe47c5c2,0xbe94a031,0xbda0af2a,0xbdc8bd36,0xbec3ef15,0xbef15aea,0xbdf0b772,0xbe0c4cf7,0xbf0e39da,0xbf226799,
0x80000000,0xbcf13d4c,0x80000000,0xbddcbd0d,0xbd712283,0xbdb4b86a,0xbe5b73dc,0xbea2fd52,0xbdf0b772,0xbe164083,0xbed65a92,0xbf039c3d,0xbe3403f1,0xbe519f65,0xbf1a82a4,0xbf2f9c32,
0x80000000,0xbd20cee7,0x80000000,0xbdf0b772,0xbda0af2a,0xbdf0b772,0xbe6f0c4d,0xbeb13641,0xbe20305b,0xbe47c5c2,0xbee87171,0xbf0e39da,0xbe6f0c4d,0xbe8afa3e,0xbf26423a,0xbf3bfc8f,
0x80000000,0xbd48fb30,0x80000000,0xbe0255f4,0xbdc8bd36,0xbe164083,0xbe814693,0xbebf47d7,0xbe47c5c2,0xbe78cfcc,0xbefa2c90,0xbf187fc0,0xbe94a031,0xbeac7cd4,0xbf316e2c,0xbf4779bc,
0x80000000,0xbd712283,0x80000000,0xbe0c4cf7,0xbdf0b772,0xbe3403f1,0xbe8afa3e,0xbecd2ef3,0xbe6f0c4d,0xbe94a031,0xbf05c277,0xbf226799,0xbeb13641,0xbecd2ef3,0xbf3bfc8f,0xbf5205d4,
0x80000000,0xbd8ca1f2,0x80000000,0xbe164083,0xbe0c4cf7,0xbe519f65,0xbe94a031,0xbedae880,0xbe8afa3e,0xbeac7cd4,0xbf0e39da,0xbf2beb4a,0xbecd2ef3,0xbeece91a,0xbf45e403,0xbf5b941a,
0x80000000,0x80000000,0xbf167918,0xbf26423a,0x80000000,0x80000000,0xbf3504f3,0xbf42a9f7,0x80000000,0x80000000,0xbf4f1bbd,0xbf5a46a0,0x80000000,0x80000000,0xbf641901,0xbf6c835e,
0xbda0af2a,0xbdb4b86a,0xbf26423a,0xbf36c9a9,0xbdc8bd36,0xbddcbd0d,0xbf45e403,0xbf53731f,0xbdf0b772,0xbe0255f4,0xbf5f5be6,0xbf698690,0xbe0c4cf7,0xbe164083,0xbf71decf,0xbf7853f8,
0xbe20305b,0xbe3403f1,0xbf3504f3,0xbf45e403,0xbe47c5c2,0xbe5b73dc,0xbf54db31,0xbf61c598,0xbe6f0c4d,0xbe814693,0xbf6c835e,0xbf74fa0b,0xbe8afa3e,0xbe94a031,0xbf7b14be,0xbf7ec46d,
0xbe6f0c4d,0xbe862210,0xbf42a9f7,0xbf53731f,0xbe94a031,0xbea2fd52,0xbf61c598,0xbf6d76aa,0xbeb13641,0xbebf47d7,0xbf766377,0xbf7c7160,0xbecd2ef3,0xbedae880,0xbf7f8e56,0xbf7fb10f,
0xbe9e377a,0xbeb13641,0xbf4f1bbd,0xbf5f5be6,0xbec3ef15,0xbed65a92,0xbf6c835e,0xbf766377,0xbee87171,0xbefa2c90,0xbf7cd925,0xbf7fcd79,0xbf05c277,0xbf0e39da,0xbf7f35f9,0xbf7b14be,
0xbec3ef15,0xbedae880,0xbf5a46a0,0xbf698690,0xbef15aea,0xbf039c3d,0xbf74fa0b,0xbf7c7160,0xbf0e39da,0xbf187fc0,0xbf7fcd79,0xbf7f0059,0xbf226799,0xbf2beb4a,0xbf7a0d54,0xbf710908,
0xbee87171,0xbf0172c3,0xbf641901,0xbf71decf,0xbf0e39da,0xbf1a82a4,0xbf7b14be,0xbf7f8e56,0xbf26423a,0xbf316e2c,0xbf7f35f9,0xbf7a0d54,0xbf3bfc8f,0xbf45e403,0xbf702d4f,0xbf61c598,
0xbf05c277,0xbf146eba,0xbf6c835e,0xbf7853f8,0xbf226799,0xbf2f9c32,0xbf7ec46d,0xbf7fb10f,0xbf3bfc8f,0xbf4779bc,0xbf7b14be,0xbf710908,0xbf5205d4,0xbf5b941a,0xbf61c598,0xbf4d9f02,
0x80000000,0x80000000,0xbf737871,0xbf78ed3c,0x80000000,0x80000000,0xbf7cd925,0xbf7f35f9,0x80000000,0x80000000,0xbf800000,0xbf7f35f9,0x80000000,0x80000000,0xbf7cd925,0xbf78ed3c,
0xbe20305b,0xbe2a1c3f,0xbf7cd925,0xbf7f654e,0xbe3403f1,0xbe3de731,0xbf7ff35e,0xbf7e8238,0xbe47c5c2,0xbe519f65,0xbf7b14be,0xbf75b1c9,0xbe5b73dc,0xbe6542e9,0xbf6e641a,0xbf653a48,
0xbe9e377a,0xbea7bf25,0xbf800000,0xbf7ec46d,0xbeb13641,0xbeba9be1,0xbf7b14be,0xbf74fa0b,0xbec3ef15,0xbecd2ef3,0xbf6c835e,0xbf61c598,0xbed65a92,0xbedf7108,0xbf54db31,0xbf45e403,
0xbee87171,0xbef5c6c5,0xbf7cd925,0xbf770f11,0xbf0172c3,0xbf07e565,0xbf6e641a,0xbf62f219,0xbf0e39da,0xbf146eba,0xbf54db31,0xbf444969,0xbf1a82a4,0xbf207440,0xbf316e2c,0xbf1c81b9,
0xbf167918,0xbf1e7cf1,0xbf737871,0xbf687c12,0xbf26423a,0xbf2dc5e3,0xbf5a46a0,0xbf490a88,0xbf3504f3,0xbf3bfc8f,0xbf3504f3,0xbf1e7cf1,0xbf42a9f7,0xbf490a88,0xbf05c277,0xbed65a92,
0xbf3504f3,0xbf3daef9,0xbf641901,0xbf53731f,0xbf45e403,0xbf4d9f02,0xbf3f5cb5,0xbf28296a,0xbf54db31,0xbf5b941a,0xbf0e39da,0xbee3f40d,0xbf61c598,0xbf676bd8,0xbea7bf25,0xbe519f65,
0xbf4f1bbd,0xbf579b8c,0xbf4f1bbd,0xbf3889dc,0xbf5f5be6,0xbf6655e7,0xbf1e7cf1,0xbf0172c3,0xbf6c835e,0xbf71decf,0xbec3ef15,0xbe814693,0xbf766377,0xbf7a0d54,0xbdf0b772,0x3ca0d6d6,
0xbf641901,0xbf6b8a3d,0xbf3504f3,0xbf187fc0,0xbf71decf,0xbf770f11,0xbef15aea,0xbeac7cd4,0xbf7b14be,0xbf7deafa,0xbe47c5c2,0xbd48fb30,0xbf7f8e56,0xbf7ffcd7,0x3dc8bd36,0x3e78cfcc,
0x80000000,0x80000000,0xbf737871,0xbf6c835e,0x80000000,0x80000000,0xbf641901,0xbf5a46a0,0x80000000,0x80000000,0xbf4f1bbd,0xbf42a9f7,0x80000000,0x80000000,0xbf3504f3,0xbf26423a,
0xbe6f0c4d,0xbe78cfcc,0xbf5a46a0,0xbf4d9f02,0xbe814693,0xbe862210,0xbf3f5cb5,0xbf2f9c32,0xbe8afa3e,0xbe8fcefe,0xbf1e7cf1,0xbf0c2124,0xbe94a031,0xbe996dba,0xbef15aea,0xbec8917e,
0xbee87171,0xbef15aea,0xbf3504f3,0xbf226799,0xbefa2c90,0xbf0172c3,0xbf0e39da,0xbef15aea,0xbf05c277,0xbf0a04f8,0xbec3ef15,0xbe94a031,0xbf0e39da,0xbf1260b2,0xbe47c5c2,0xbdc8bd36,
0xbf26423a,0xbf2beb4a,0xbf05c277,0xbedae880,0xbf316e2c,0xbf36c9a9,0xbea7bf25,0xbe6542e9,0xbf3bfc8f,0xbf4105b8,0xbdf0b772,0xbc20d8d2,0xbf45e403,0xbf4a965e,0x3dc8bd36,0x3e519f65,
0xbf4f1bbd,0xbf54db31,0xbe9e377a,0xbe47c5c2,0xbf5a46a0,0xbf5f5be6,0xbda0af2a,0x3d20cee7,0xbf641901,0xbf687c12,0x3e20305b,0x3e8afa3e,0xbf6c835e,0xbf702d4f,0x3ec3ef15,0x3efa2c90,
0xbf6c835e,0xbf710908,0xbda0af2a,0x3d48fb30,0xbf74fa0b,0xbf7853f8,0x3e3403f1,0x3e996dba,0xbf7b14be,0xbf7d3aac,0x3ed65a92,0x3f07e565,0xbf7ec46d,0xbf7fb10f,0x3f226799,0x3f3a4582,
0xbf7cd925,0xbf7ec46d,0x3e20305b,0x3e94a031,0xbf7fcd79,0xbf7ff35e,0x3ed65a92,0x3f0a04f8,0xbf7f35f9,0xbf7d95f4,0x3f26423a,0x3f3f5cb5,0xbf7b14be,0xbf77b493,0x3f54db31,0x3f6655e7,
0xbf7f35f9,0xbf7d3aac,0x3ec3ef15,0x3f039c3d,0xbf7a0d54,0xbf75b1c9,0x3f226799,0x3f3daef9,0xbf702d4f,0xbf698690,0x3f54db31,0x3f676bd8,0xbf61c598,0xbf58f3c4,0x3f74fa0b,0x3f7d3aac,
0x80000000,0x80000000,0xbf167918,0xbf05c277,0x80000000,0x80000000,0xbee87171,0xbec3ef15,0x80000000,0x80000000,0xbe9e377a,0xbe6f0c4d,0x80000000,0x80000000,0xbe20305b,0xbda0af2a,
0xbe9e377a,0xbea2fd52,0xbe9e377a,0xbe6542e9,0xbea7bf25,0xbeac7cd4,0xbe0c4cf7,0xbd48fb30,0xbeb13641,0xbeb5eb4f,0x3d20cee7,0x3e0255f4,0xbeba9be1,0xbebf47d7,0x3e5b73dc,0x3e996dba,
0xbf167918,0xbf1a82a4,0x80000000,0x3dc8bd36,0xbf1e7cf1,0xbf226799,0x3e47c5c2,0x3e94a031,0xbf26423a,0xbf2a0c73,0x3ec3ef15,0x3ef15aea,0xbf2dc5e3,0xbf316e2c,0x3f0e39da,0x3f226799,
0xbf4f1bbd,0xbf53731f,0x3e9e377a,0x3ed1c759,0xbf579b8c,0xbf5b941a,0x3f0172c3,0x3f187fc0,0xbf5f5be6,0xbf62f219,0x3f2dc5e3,0x3f4105b8,0xbf6655e7,0xbf698690,0x3f5205d4,0x3f609384,
0xbf737871,0xbf766377,0x3f167918,0x3f2dc5e3,0xbf78ed3c,0xbf7b14be,0x3f42a9f7,0x3f54db31,0xbf7cd925,0xbf7e39bc,0x3f641901,0x3f702d4f,0xbf7f35f9,0xbf7fcd79,0x3f78ed3c,0x3f7e39bc,
0xbf800000,0xbf7fb10f,0x3f4f1bbd,0x3f609384,0xbf7ec46d,0xbf7d3aac,0x3f6e641a,0x3f7853f8,0xbf7b14be,0xbf7853f8,0x3f7e39bc,0x3f7ffcd7,0xbf74fa0b,0xbf710908,0x3f7d95f4,0x3f770f11,
0xbf737871,0xbf6e641a,0x3f737871,0x3f7c0361,0xbf687c12,0xbf61c598,0x3f7fcd79,0x3f7ec46d,0xbf5a46a0,0xbf5205d4,0x3f78ed3c,0x3f6e641a,0xbf490a88,0xbf3f5cb5,0x3f5f5be6,0x3f4c1d35,
0xbf4f1bbd,0xbf444969,0x3f800000,0x3f7d3aac,0xbf3889dc,0xbf2beb4a,0x3f74fa0b,0x3f676bd8,0xbf1e7cf1,0xbf104f0e,0x3f54db31,0x3f3daef9,0xbf0172c3,0xbee3f40d,0x3f226799,0x3f039c3d,
0x3f803f80,0,0x3f803f80,0,0x3f803f80,0,0x3f803f80,0,0x3f7d3f80,0x3e200000,0x3f643f73,0x3ee83e9e,0x3f353f4f,0x3f353f16,0x3ee83f16,0x3f643f4f,
0x3f733f80,0x3e9e0000,0x3f163f4f,0x3f4f3f16,0x3e9e,0x3f803f73,0xbf16be9e,0x3f4f3f73,0x3f643f80,0x3ee80000,0x3e203f16,0x3f7d3f4f,0xbf35be9e,0x3f353f73,0xbf7dbf73,0xbe203e9e,
0x3f4f3f80,0x3f160000,0xbe9e3e9e,0x3f733f73,0xbf80bf4f,0x3f16,0xbe9ebf4f,0xbf73bf16,0x3f353f80,0x3f350000,0xbf350000,0x3f353f80,0xbf35bf80,0xbf350000,0x3f350000,0xbf35bf80,
0x3f163f80,0x3f4f0000,0xbf73be9e,0x3e9e3f73,0xbf4f,0xbf80bf16,0x3f733f4f,0x3e9ebf16,0x3ee83f80,0x3f640000,0xbf7dbf16,0xbe203f4f,0x3f35be9e,0xbf35bf73,0x3e203f73,0x3f7d3e9e,
0x3e9e3f80,0x3f730000,0xbf4fbf4f,0xbf163f16,0x3f803e9e,0xbf73,0xbf4f3e9e,0x3f163f73,0x3e203f80,0x3f7d0000,0xbee8bf73,0xbf643e9e,0x3f353f4f,0x3f35bf16,0xbf64bf16,0xbee83f4f,
0x3f80,0x3f800000,0xbf80,0xbf800000,0x3f80,0x3f800000,0xbf80,0xbf800000,0xbe203f80,0x3f7d0000,0x3ee8bf73,0xbf64be9e,0xbf353f4f,0x3f353f16,0x3f64bf16,0xbee8bf4f,
0xbe9e3f80,0x3f730000,0x3f4fbf4f,0xbf16bf16,0xbf803e9e,0x3f73,0x3f4f3e9e,0x3f16bf73,0xbee83f80,0x3f640000,0x3f7dbf16,0xbe20bf4f,0xbf35be9e,0xbf353f73,0xbe203f73,0x3f7dbe9e,
0xbf163f80,0x3f4f0000,0x3f73be9e,0x3e9ebf73,0xbf4f,0xbf803f16,0xbf733f4f,0x3e9e3f16,0xbf353f80,0x3f350000,0x3f350000,0x3f35bf80,0x3f35bf80,0xbf350000,0xbf350000,0xbf353f80,
0xbf4f3f80,0x3f160000,0x3e9e3e9e,0x3f73bf73,0x3f80bf4f,0xbf16,0x3e9ebf4f,0xbf733f16,0xbf643f80,0x3ee80000,0xbe203f16,0x3f7dbf4f,0x3f35be9e,0x3f35bf73,0x3f7dbf73,0xbe20be9e,
0xbf733f80,0x3e9e0000,0xbf163f4f,0x3f4fbf16,0x3e9e,0x3f80bf73,0x3f16be9e,0x3f4fbf73,0xbf7d3f80,0x3e200000,0xbf643f73,0x3ee8be9e,0xbf353f4f,0x3f35bf16,0xbee83f16,0x3f64bf4f,
0xbf803f80,0,0xbf803f80,0,0xbf803f80,0,0xbf803f80,0,0xbf7d3f80,0xbe200000,0xbf643f73,0xbee83e9e,0xbf353f4f,0xbf353f16,0xbee83f16,0xbf643f4f,
0xbf733f80,0xbe9e0000,0xbf163f4f,0xbf4f3f16,0x3e9e,0xbf803f73,0x3f16be9e,0xbf4f3f73,0xbf643f80,0xbee80000,0xbe203f16,0xbf7d3f4f,0x3f35be9e,0xbf353f73,0x3f7dbf73,0x3e203e9e,
0xbf4f3f80,0xbf160000,0x3e9e3e9e,0xbf733f73,0x3f80bf4f,0x3f16,0x3e9ebf4f,0x3f73bf16,0xbf353f80,0xbf350000,0x3f350000,0xbf353f80,0x3f35bf80,0x3f350000,0xbf350000,0x3f35bf80,
0xbf163f80,0xbf4f0000,0x3f73be9e,0xbe9e3f73,0xbf4f,0x3f80bf16,0xbf733f4f,0xbe9ebf16,0xbee83f80,0xbf640000,0x3f7dbf16,0x3e203f4f,0xbf35be9e,0x3f35bf73,0xbe203f73,0xbf7d3e9e,
0xbe9e3f80,0xbf730000,0x3f4fbf4f,0x3f163f16,0xbf803e9e,0xbf73,0x3f4f3e9e,0xbf163f73,0xbe203f80,0xbf7d0000,0x3ee8bf73,0x3f643e9e,0xbf353f4f,0xbf35bf16,0x3f64bf16,0x3ee83f4f,
0x3f80,0xbf800000,0xbf80,0x3f800000,0x3f80,0xbf800000,0xbf80,0x3f800000,0x3e203f80,0xbf7d0000,0xbee8bf73,0x3f64be9e,0x3f353f4f,0xbf353f16,0xbf64bf16,0x3ee8bf4f,
0x3e9e3f80,0xbf730000,0xbf4fbf4f,0x3f16bf16,0x3f803e9e,0x3f73,0xbf4f3e9e,0xbf16bf73,0x3ee83f80,0xbf640000,0xbf7dbf16,0x3e20bf4f,0x3f35be9e,0x3f353f73,0x3e203f73,0xbf7dbe9e,
0x3f163f80,0xbf4f0000,0xbf73be9e,0xbe9ebf73,0xbf4f,0x3f803f16,0x3f733f4f,0xbe9e3f16,0x3f353f80,0xbf350000,0xbf350000,0xbf35bf80,0xbf35bf80,0x3f350000,0x3f350000,0x3f353f80,
0x3f4f3f80,0xbf160000,0xbe9e3e9e,0xbf73bf73,0xbf80bf4f,0xbf16,0xbe9ebf4f,0x3f733f16,0x3f643f80,0xbee80000,0x3e203f16,0xbf7dbf4f,0xbf35be9e,0xbf35bf73,0xbf7dbf73,0x3e20be9e,
0x3f733f80,0xbe9e0000,0x3f163f4f,0xbf4fbf16,0x3e9e,0xbf80bf73,0xbf16be9e,0xbf4fbf73,0x3f7d3f80,0xbe200000,0x3f643f73,0xbee8be9e,0x3f353f4f,0xbf35bf16,0x3ee83f16,0xbf64bf4f,
0x3f803f80,0,0x3f803f80,0,0x3f803f80,0,0x3f803f80,0,0x3e203e9e,0x3f7d3f73,0xbe200000,0x3f7d3f80,0xbee8be9e,0x3f643f73,0xbf35bf16,0x3f353f4f,
0xbf73bf4f,0x3e9e3f16,0xbf73bf80,0xbe9e0000,0xbf16bf4f,0xbf4fbf16,0xbe9e,0xbf80bf73,0xbee8bf4f,0xbf64bf16,0x3ee80000,0xbf64bf80,0x3f7d3f4f,0xbe20bf16,0x3f353f73,0x3f353e9e,
0x3f4f3e9e,0xbf16bf73,0x3f4f3f80,0x3f160000,0xbe9e3e9e,0x3f733f73,0xbf80bf4f,0x3f16,0x3f353f80,0x3f350000,0xbf350000,0x3f353f80,0xbf35bf80,0xbf350000,0x3f350000,0xbf35bf80,
0xbf163e9e,0x3f4f3f73,0xbf16bf80,0xbf4f0000,0x3f733e9e,0xbe9ebf73,0x3f4f,0x3f803f16,0xbf64bf4f,0xbee83f16,0x3f640000,0xbee8bf80,0xbe203f4f,0x3f7d3f16,0xbf35bf73,0xbf353e9e,
0x3e9ebf4f,0xbf73bf16,0x3e9e3f80,0x3f730000,0xbf4fbf4f,0xbf163f16,0x3f803e9e,0xbf73,0x3f7d3e9e,0x3e20bf73,0xbf7d0000,0x3e203f80,0x3f64be9e,0xbee8bf73,0xbf353f16,0x3f353f4f,
0x3f80,0x3f800000,0xbf80,0xbf800000,0x3f80,0x3f800000,0xbf80,0xbf800000,0xbf7d3e9e,0x3e203f73,0x3f7d0000,0x3e20bf80,0xbf64be9e,0xbee83f73,0x3f353f16,0x3f35bf4f,
0xbe9ebf4f,0xbf733f16,0xbe9e3f80,0x3f730000,0x3f4fbf4f,0xbf16bf16,0xbf803e9e,0x3f73,0x3f64bf4f,0xbee8bf16,0xbf640000,0xbee83f80,0x3e203f4f,0x3f7dbf16,0x3f35bf73,0xbf35be9e,
0x3f163e9e,0x3f4fbf73,0x3f16bf80,0xbf4f0000,0xbf733e9e,0xbe9e3f73,0x3f4f,0x3f80bf16,0xbf353f80,0x3f350000,0x3f350000,0x3f35bf80,0x3f35bf80,0xbf350000,0xbf350000,0xbf353f80,
0xbf4f3e9e,0xbf163f73,0xbf4f3f80,0x3f160000,0x3e9e3e9e,0x3f73bf73,0x3f80bf4f,0xbf16,0x3ee8bf4f,0xbf643f16,0xbee80000,0xbf643f80,0xbf7d3f4f,0xbe203f16,0xbf353f73,0x3f35be9e,
0x3f73bf4f,0x3e9ebf16,0x3f73bf80,0xbe9e0000,0x3f16bf4f,0xbf4f3f16,0xbe9e,0xbf803f73,0xbe203e9e,0x3f7dbf73,0x3e200000,0x3f7dbf80,0x3ee8be9e,0x3f64bf73,0x3f35bf16,0x3f35bf4f,
0xbf803f80,0,0xbf803f80,0,0xbf803f80,0,0xbf803f80,0,0xbe203e9e,0xbf7d3f73,0x3e200000,0xbf7d3f80,0x3ee8be9e,0xbf643f73,0x3f35bf16,0xbf353f4f,
0x3f73bf4f,0xbe9e3f16,0x3f73bf80,0x3e9e0000,0x3f16bf4f,0x3f4fbf16,0xbe9e,0x3f80bf73,0x3ee8bf4f,0x3f64bf16,0xbee80000,0x3f64bf80,0xbf7d3f4f,0x3e20bf16,0xbf353f73,0xbf353e9e,
0xbf4f3e9e,0x3f16bf73,0xbf4f3f80,0xbf160000,0x3e9e3e9e,0xbf733f73,0x3f80bf4f,0x3f16,0xbf353f80,0xbf350000,0x3f350000,0xbf353f80,0x3f35bf80,0x3f350000,0xbf350000,0x3f35bf80,
0x3f163e9e,0xbf4f3f73,0x3f16bf80,0x3f4f0000,0xbf733e9e,0x3e9ebf73,0x3f4f,0xbf803f16,0x3f64bf4f,0x3ee83f16,0xbf640000,0x3ee8bf80,0x3e203f4f,0xbf7d3f16,0x3f35bf73,0x3f353e9e,
0xbe9ebf4f,0x3f73bf16,0xbe9e3f80,0xbf730000,0x3f4fbf4f,0x3f163f16,0xbf803e9e,0xbf73,0xbf7d3e9e,0xbe20bf73,0x3f7d0000,0xbe203f80,0xbf64be9e,0x3ee8bf73,0x3f353f16,0xbf353f4f,
0x3f80,0xbf800000,0xbf80,0x3f800000,0x3f80,0xbf800000,0xbf80,0x3f800000,0x3f7d3e9e,0xbe203f73,0xbf7d0000,0xbe20bf80,0x3f64be9e,0x3ee83f73,0xbf353f16,0xbf35bf4f,
0x3e9ebf4f,0x3f733f16,0x3e9e3f80,0xbf730000,0xbf4fbf4f,0x3f16bf16,0x3f803e9e,0x3f73,0xbf64bf4f,0x3ee8bf16,0x3f640000,0x3ee83f80,0xbe203f4f,0xbf7dbf16,0xbf35bf73,0x3f35be9e,
0xbf163e9e,0xbf4fbf73,0xbf16bf80,0x3f4f0000,0x3f733e9e,0x3e9e3f73,0x3f4f,0xbf80bf16,0x3f353f80,0xbf350000,0xbf350000,0xbf35bf80,0xbf35bf80,0x3f350000,0x3f350000,0x3f353f80,
0x3f4f3e9e,0x3f163f73,0x3f4f3f80,0xbf160000,0xbe9e3e9e,0xbf73bf73,0xbf80bf4f,0xbf16,0xbee8bf4f,0x3f643f16,0x3ee80000,0x3f643f80,0x3f7d3f4f,0x3e203f16,0x3f353f73,0xbf35be9e,
0xbf73bf4f,0xbe9ebf16,0xbf73bf80,0x3e9e0000,0xbf16bf4f,0x3f4f3f16,0xbe9e,0x3f803f73,0x3e203e9e,0xbf7dbf73,0xbe200000,0xbf7dbf80,0xbee8be9e,0xbf64bf73,0xbf35bf16,0xbf35bf4f,
0x3f803f80,0,0x3f803f80,0,0x3f803f80,0,0x3f803f80,0,0xbf64bf4f,0x3ee83f16,0xbf7dbf73,0x3e203e9e,0xbf7dbf80,0xbe200000,0xbf64bf73,0xbee8be9e,
0x3f163e9e,0xbf4fbf73,0x3f733f4f,0xbe9ebf16,0x3f733f80,0x3e9e0000,0x3f163f4f,0x3f4f3f16,0xbe203e9e,0x3f7d3f73,0xbf64bf16,0x3ee83f4f,0xbf64bf80,0xbee80000,0xbe20bf16,0xbf7dbf4f,
0xbe9ebf4f,0xbf73bf16,0x3f4f3e9e,0xbf16bf73,0x3f4f3f80,0x3f160000,0xbe9e3e9e,0x3f733f73,0x3f353f80,0x3f350000,0xbf350000,0x3f353f80,0xbf35bf80,0xbf350000,0x3f350000,0xbf35bf80,
0xbf73bf4f,0xbe9e3f16,0x3f16be9e,0xbf4fbf73,0x3f163f80,0x3f4f0000,0xbf73be9e,0x3e9e3f73,0x3f7d3e9e,0xbe20bf73,0xbee83f16,0x3f643f4f,0xbee8bf80,0xbf640000,0x3f7d3f16,0x3e20bf4f,
0xbf4f3e9e,0x3f163f73,0x3e9ebf4f,0xbf73bf16,0x3e9e3f80,0x3f730000,0xbf4fbf4f,0xbf163f16,0x3ee8bf4f,0xbf64bf16,0xbe203f73,0x3f7d3e9e,0xbe20bf80,0xbf7d0000,0x3ee83f73,0x3f64be9e,
0x3f80,0x3f800000,0xbf80,0xbf800000,0x3f80,0x3f800000,0xbf80,0xbf800000,0xbee8bf4f,0xbf643f16,0x3e203f73,0x3f7dbe9e,0x3e20bf80,0xbf7d0000,0xbee83f73,0x3f643e9e,
0x3f4f3e9e,0x3f16bf73,0xbe9ebf4f,0xbf733f16,0xbe9e3f80,0x3f730000,0x3f4fbf4f,0xbf16bf16,0xbf7d3e9e,0xbe203f73,0x3ee83f16,0x3f64bf4f,0x3ee8bf80,0xbf640000,0xbf7d3f16,0x3e203f4f,
0x3f73bf4f,0xbe9ebf16,0xbf16be9e,0xbf4f3f73,0xbf163f80,0x3f4f0000,0x3f73be9e,0x3e9ebf73,0xbf353f80,0x3f350000,0x3f350000,0x3f35bf80,0x3f35bf80,0xbf350000,0xbf350000,0xbf353f80,
0x3e9ebf4f,0xbf733f16,0xbf4f3e9e,0xbf163f73,0xbf4f3f80,0x3f160000,0x3e9e3e9e,0x3f73bf73,0x3e203e9e,0x3f7dbf73,0x3f64bf16,0x3ee8bf4f,0x3f64bf80,0xbee80000,0x3e20bf16,0xbf7d3f4f,
0xbf163e9e,0xbf4f3f73,0xbf733f4f,0xbe9e3f16,0xbf733f80,0x3e9e0000,0xbf163f4f,0x3f4fbf16,0x3f64bf4f,0x3ee8bf16,0x3f7dbf73,0x3e20be9e,0x3f7dbf80,0xbe200000,0x3f64bf73,0xbee83e9e,
0xbf803f80,0,0xbf803f80,0,0xbf803f80,0,0xbf803f80,0,0x3f64bf4f,0xbee83f16,0x3f7dbf73,0xbe203e9e,0x3f7dbf80,0x3e200000,0x3f64bf73,0x3ee8be9e,
0xbf163e9e,0x3f4fbf73,0xbf733f4f,0x3e9ebf16,0xbf733f80,0xbe9e0000,0xbf163f4f,0xbf4f3f16,0x3e203e9e,0xbf7d3f73,0x3f64bf16,0xbee83f4f,0x3f64bf80,0x3ee80000,0x3e20bf16,0x3f7dbf4f,
0x3e9ebf4f,0x3f73bf16,0xbf4f3e9e,0x3f16bf73,0xbf4f3f80,0xbf160000,0x3e9e3e9e,0xbf733f73,0xbf353f80,0xbf350000,0x3f350000,0xbf353f80,0x3f35bf80,0x3f350000,0xbf350000,0x3f35bf80,
0x3f73bf4f,0x3e9e3f16,0xbf16be9e,0x3f4fbf73,0xbf163f80,0xbf4f0000,0x3f73be9e,0xbe9e3f73,0xbf7d3e9e,0x3e20bf73,0x3ee83f16,0xbf643f4f,0x3ee8bf80,0x3f640000,0xbf7d3f16,0xbe20bf4f,
0x3f4f3e9e,0xbf163f73,0xbe9ebf4f,0x3f73bf16,0xbe9e3f80,0xbf730000,0x3f4fbf4f,0x3f163f16,0xbee8bf4f,0x3f64bf16,0x3e203f73,0xbf7d3e9e,0x3e20bf80,0x3f7d0000,0xbee83f73,0xbf64be9e,
0x3f80,0xbf800000,0xbf80,0x3f800000,0x3f80,0xbf800000,0xbf80,0x3f800000,0x3ee8bf4f,0x3f643f16,0xbe203f73,0xbf7dbe9e,0xbe20bf80,0x3f7d0000,0x3ee83f73,0xbf643e9e,
0xbf4f3e9e,0xbf16bf73,0x3e9ebf4f,0x3f733f16,0x3e9e3f80,0xbf730000,0xbf4fbf4f,0x3f16bf16,0x3f7d3e9e,0x3e203f73,0xbee83f16,0xbf64bf4f,0xbee8bf80,0x3f640000,0x3f7d3f16,0xbe203f4f,
0xbf73bf4f,0x3e9ebf16,0x3f16be9e,0x3f4f3f73,0x3f163f80,0xbf4f0000,0xbf73be9e,0xbe9ebf73,0x3f353f80,0xbf350000,0xbf350000,0xbf35bf80,0xbf35bf80,0x3f350000,0x3f350000,0x3f353f80,
0xbe9ebf4f,0x3f733f16,0x3f4f3e9e,0x3f163f73,0x3f4f3f80,0xbf160000,0xbe9e3e9e,0xbf73bf73,0xbe203e9e,0xbf7dbf73,0xbf64bf16,0xbee8bf4f,0xbf64bf80,0x3ee80000,0xbe20bf16,0x3f7d3f4f,
0x3f163e9e,0x3f4f3f73,0x3f733f4f,0x3e9e3f16,0x3f733f80,0xbe9e0000,0x3f163f4f,0xbf4fbf16,0xbf64bf4f,0xbee8bf16,0xbf7dbf73,0xbe20be9e,0xbf7dbf80,0x3e200000,0xbf64bf73,0x3ee83e9e,
0x3f803f80,0,0x3f803f80,0,0x3f803f80,0,0x3f803f80,0,0xbf35bf4f,0xbf35bf16,0xbee8bf16,0xbf64bf4f,0xbe20be9e,0xbf7dbf73,0x3e200000,0xbf7dbf80,
0x3e9e,0x3f803f73,0xbf16be9e,0x3f4f3f73,0xbf73bf4f,0x3e9e3f16,0xbf73bf80,0xbe9e0000,0x3f353e9e,0xbf35bf73,0x3f7d3f73,0x3e20be9e,0x3ee83f4f,0x3f643f16,0xbee80000,0x3f643f80,
0xbf80bf4f,0x3f16,0xbe9ebf4f,0xbf73bf16,0x3f4f3e9e,0xbf16bf73,0x3f4f3f80,0x3f160000,0x3f353f80,0x3f350000,0xbf350000,0x3f353f80,0xbf35bf80,0xbf350000,0x3f350000,0xbf35bf80,
0xbf4f,0xbf80bf16,0x3f733f4f,0x3e9ebf16,0xbf163e9e,0x3f4f3f73,0xbf16bf80,0xbf4f0000,0xbf353e9e,0x3f353f73,0xbe20bf73,0xbf7dbe9e,0x3f643f4f,0x3ee8bf16,0xbf640000,0x3ee83f80,
0x3f803e9e,0xbf73,0xbf4f3e9e,0x3f163f73,0x3e9ebf4f,0xbf73bf16,0x3e9e3f80,0x3f730000,0xbf35bf4f,0xbf353f16,0x3f643f16,0x3ee8bf4f,0xbf7dbe9e,0xbe203f73,0x3f7d0000,0xbe20bf80,
0x3f80,0x3f800000,0xbf80,0xbf800000,0x3f80,0x3f800000,0xbf80,0xbf800000,0x3f35bf4f,0xbf35bf16,0xbf643f16,0x3ee83f4f,0x3f7dbe9e,0xbe20bf73,0xbf7d0000,0xbe203f80,
0xbf803e9e,0x3f73,0x3f4f3e9e,0x3f16bf73,0xbe9ebf4f,0xbf733f16,0xbe9e3f80,0x3f730000,0x3f353e9e,0x3f35bf73,0x3e20bf73,0xbf7d3e9e,0xbf643f4f,0x3ee83f16,0x3f640000,0x3ee8bf80,
0xbf4f,0xbf803f16,0xbf733f4f,0x3e9e3f16,0x3f163e9e,0x3f4fbf73,0x3f16bf80,0xbf4f0000,0xbf353f80,0x3f350000,0x3f350000,0x3f35bf80,0x3f35bf80,0xbf350000,0xbf350000,0xbf353f80,
0x3f80bf4f,0xbf16,0x3e9ebf4f,0xbf733f16,0xbf4f3e9e,0xbf163f73,0xbf4f3f80,0x3f160000,0xbf353e9e,0xbf353f73,0xbf7d3f73,0x3e203e9e,0xbee83f4f,0x3f64bf16,0x3ee80000,0x3f64bf80,
0x3e9e,0x3f80bf73,0x3f16be9e,0x3f4fbf73,0x3f73bf4f,0x3e9ebf16,0x3f73bf80,0xbe9e0000,0x3f35bf4f,0xbf353f16,0x3ee8bf16,0xbf643f4f,0x3e20be9e,0xbf7d3f73,0xbe200000,0xbf7d3f80,
0xbf803f80,0,0xbf803f80,0,0xbf803f80,0,0xbf803f80,0,0x3f35bf4f,0x3f35bf16,0x3ee8bf16,0x3f64bf4f,0x3e20be9e,0x3f7dbf73,0xbe200000,0x3f7dbf80,
0x3e9e,0xbf803f73,0x3f16be9e,0xbf4f3f73,0x3f73bf4f,0xbe9e3f16,0x3f73bf80,0x3e9e0000,0xbf353e9e,0x3f35bf73,0xbf7d3f73,0xbe20be9e,0xbee83f4f,0xbf643f16,0x3ee80000,0xbf643f80,
0x3f80bf4f,0x3f16,0x3e9ebf4f,0x3f73bf16,0xbf4f3e9e,0x3f16bf73,0xbf4f3f80,0xbf160000,0xbf353f80,0xbf350000,0x3f350000,0xbf353f80,0x3f35bf80,0x3f350000,0xbf350000,0x3f35bf80,
0xbf4f,0x3f80bf16,0xbf733f4f,0xbe9ebf16,0x3f163e9e,0xbf4f3f73,0x3f16bf80,0x3f4f0000,0x3f353e9e,0xbf353f73,0x3e20bf73,0x3f7dbe9e,0xbf643f4f,0xbee8bf16,0x3f640000,0xbee83f80,
0xbf803e9e,0xbf73,0x3f4f3e9e,0xbf163f73,0xbe9ebf4f,0x3f73bf16,0xbe9e3f80,0xbf730000,0x3f35bf4f,0x3f353f16,0xbf643f16,0xbee8bf4f,0x3f7dbe9e,0x3e203f73,0xbf7d0000,0x3e20bf80,
0x3f80,0xbf800000,0xbf80,0x3f800000,0x3f80,0xbf800000,0xbf80,0x3f800000,0xbf35bf4f,0x3f35bf16,0x3f643f16,0xbee83f4f,0xbf7dbe9e,0x3e20bf73,0x3f7d0000,0x3e203f80,
0x3f803e9e,0x3f73,0xbf4f3e9e,0xbf16bf73,0x3e9ebf4f,0x3f733f16,0x3e9e3f80,0xbf730000,0xbf353e9e,0xbf35bf73,0xbe20bf73,0x3f7d3e9e,0x3f643f4f,0xbee83f16,0xbf640000,0xbee8bf80,
0xbf4f,0x3f803f16,0x3f733f4f,0xbe9e3f16,0xbf163e9e,0xbf4fbf73,0xbf16bf80,0x3f4f0000,0x3f353f80,0xbf350000,0xbf350000,0xbf35bf80,0xbf35bf80,0x3f350000,0x3f350000,0x3f353f80,
0xbf80bf4f,0xbf16,0xbe9ebf4f,0x3f733f16,0x3f4f3e9e,0x3f163f73,0x3f4f3f80,0xbf160000,0x3f353e9e,0x3f353f73,0x3f7d3f73,0xbe203e9e,0x3ee83f4f,0xbf64bf16,0xbee80000,0xbf64bf80,
0x3e9e,0xbf80bf73,0xbf16be9e,0xbf4fbf73,0xbf73bf4f,0xbe9ebf16,0xbf73bf80,0x3e9e0000,0xbf35bf4f,0x3f353f16,0xbee8bf16,0x3f643f4f,0xbe20be9e,0x3f7d3f73,0x3e200000,0x3f7d3f80,
0x3f803f80,0,0x3f803f80,0,0x3f803f80,0,0x3f803f80,0,0x3ee83e9e,0xbf64bf73,0x3f353f16,0xbf35bf4f,0x3f643f4f,0xbee8bf16,0x3f7d3f73,0xbe20be9e,
0xbf16bf4f,0xbf4fbf16,0xbe9e,0xbf80bf73,0x3f163e9e,0xbf4fbf73,0x3f733f4f,0xbe9ebf16,0xbf7dbf4f,0x3e203f16,0xbf35bf73,0xbf35be9e,0x3e20be9e,0xbf7dbf73,0x3f643f16,0xbee8bf4f,
0xbe9e3e9e,0x3f733f73,0xbf80bf4f,0x3f16,0xbe9ebf4f,0xbf73bf16,0x3f4f3e9e,0xbf16bf73,0x3f353f80,0x3f350000,0xbf350000,0x3f353f80,0xbf35bf80,0xbf350000,0x3f350000,0xbf35bf80,
0x3f733e9e,0xbe9ebf73,0x3f4f,0x3f803f16,0xbf73bf4f,0xbe9e3f16,0x3f16be9e,0xbf4fbf73,0x3e20bf4f,0xbf7dbf16,0x3f353f73,0x3f35be9e,0xbf7dbe9e,0x3e203f73,0x3ee8bf16,0xbf64bf4f,
0xbf4fbf4f,0xbf163f16,0x3f803e9e,0xbf73,0xbf4f3e9e,0x3f163f73,0x3e9ebf4f,0xbf73bf16,0xbf643e9e,0x3ee83f73,0x3f35bf16,0xbf35bf4f,0xbee83f4f,0x3f643f16,0x3e20bf73,0xbf7dbe9e,
0x3f80,0x3f800000,0xbf80,0xbf800000,0x3f80,0x3f800000,0xbf80,0xbf800000,0x3f643e9e,0x3ee8bf73,0xbf35bf16,0xbf353f4f,0x3ee83f4f,0x3f64bf16,0xbe20bf73,0xbf7d3e9e,
0x3f4fbf4f,0xbf16bf16,0xbf803e9e,0x3f73,0x3f4f3e9e,0x3f16bf73,0xbe9ebf4f,0xbf733f16,0xbe20bf4f,0xbf7d3f16,0xbf353f73,0x3f353e9e,0x3f7dbe9e,0x3e20bf73,0xbee8bf16,0xbf643f4f,
0xbf733e9e,0xbe9e3f73,0x3f4f,0x3f80bf16,0x3f73bf4f,0xbe9ebf16,0xbf16be9e,0xbf4f3f73,0xbf353f80,0x3f350000,0x3f350000,0x3f35bf80,0x3f35bf80,0xbf350000,0xbf350000,0xbf353f80,
0x3e9e3e9e,0x3f73bf73,0x3f80bf4f,0xbf16,0x3e9ebf4f,0xbf733f16,0xbf4f3e9e,0xbf163f73,0x3f7dbf4f,0x3e20bf16,0x3f35bf73,0xbf353e9e,0xbe20be9e,0xbf7d3f73,0xbf643f16,0xbee83f4f,
0x3f16bf4f,0xbf4f3f16,0xbe9e,0xbf803f73,0xbf163e9e,0xbf4f3f73,0xbf733f4f,0xbe9e3f16,0xbee83e9e,0xbf643f73,0xbf353f16,0xbf353f4f,0xbf643f4f,0xbee83f16,0xbf7d3f73,0xbe203e9e,
0xbf803f80,0,0xbf803f80,0,0xbf803f80,0,0xbf803f80,0,0xbee83e9e,0x3f64bf73,0xbf353f16,0x3f35bf4f,0xbf643f4f,0x3ee8bf16,0xbf7d3f73,0x3e20be9e,
0x3f16bf4f,0x3f4fbf16,0xbe9e,0x3f80bf73,0xbf163e9e,0x3f4fbf73,0xbf733f4f,0x3e9ebf16,0x3f7dbf4f,0xbe203f16,0x3f35bf73,0x3f35be9e,0xbe20be9e,0x3f7dbf73,0xbf643f16,0x3ee8bf4f,
0x3e9e3e9e,0xbf733f73,0x3f80bf4f,0x3f16,0x3e9ebf4f,0x3f73bf16,0xbf4f3e9e,0x3f16bf73,0xbf353f80,0xbf350000,0x3f350000,0xbf353f80,0x3f35bf80,0x3f350000,0xbf350000,0x3f35bf80,
0xbf733e9e,0x3e9ebf73,0x3f4f,0xbf803f16,0x3f73bf4f,0x3e9e3f16,0xbf16be9e,0x3f4fbf73,0xbe20bf4f,0x3f7dbf16,0xbf353f73,0xbf35be9e,0x3f7dbe9e,0xbe203f73,0xbee8bf16,0x3f64bf4f,
0x3f4fbf4f,0x3f163f16,0xbf803e9e,0xbf73,0x3f4f3e9e,0xbf163f73,0xbe9ebf4f,0x3f73bf16,0x3f643e9e,0xbee83f73,0xbf35bf16,0x3f35bf4f,0x3ee83f4f,0xbf643f16,0xbe20bf73,0x3f7dbe9e,
0x3f80,0xbf800000,0xbf80,0x3f800000,0x3f80,0xbf800000,0xbf80,0x3f800000,0xbf643e9e,0xbee8bf73,0x3f35bf16,0x3f353f4f,0xbee83f4f,0xbf64bf16,0x3e20bf73,0x3f7d3e9e,
0xbf4fbf4f,0x3f16bf16,0x3f803e9e,0x3f73,0xbf4f3e9e,0xbf16bf73,0x3e9ebf4f,0x3f733f16,0x3e20bf4f,0x3f7d3f16,0x3f353f73,0xbf353e9e,0xbf7dbe9e,0xbe20bf73,0x3ee8bf16,0x3f643f4f,
0x3f733e9e,0x3e9e3f73,0x3f4f,0xbf80bf16,0xbf73bf4f,0x3e9ebf16,0x3f16be9e,0x3f4f3f73,0x3f353f80,0xbf350000,0xbf350000,0xbf35bf80,0xbf35bf80,0x3f350000,0x3f350000,0x3f353f80,
0xbe9e3e9e,0xbf73bf73,0xbf80bf4f,0xbf16,0xbe9ebf4f,0x3f733f16,0x3f4f3e9e,0x3f163f73,0xbf7dbf4f,0xbe20bf16,0xbf35bf73,0x3f353e9e,0x3e20be9e,0x3f7d3f73,0x3f643f16,0x3ee83f4f,
0xbf16bf4f,0x3f4f3f16,0xbe9e,0x3f803f73,0x3f163e9e,0x3f4f3f73,0x3f733f4f,0x3e9e3f16,0x3ee83e9e,0x3f643f73,0x3f353f16,0x3f353f4f,0x3f643f4f,0x3ee83f16,0x3f7d3f73,0x3e203e9e,
0x3f803f80,0x3f80,0xbf803f80,0x3f80,0x3f803f80,0xbf80,0xbf803f80,0xbf80,0x3f803f80,0x3f80,0xbf803f80,0x3f80,0x3f803f80,0xbf80,0xbf803f80,0xbf80,
0x3f7b3f80,0xbe483f80,0xbf7b3f80,0x3e483f80,0x3f553f6d,0x3f0ebf6d,0xbf553f6d,0xbf0ebf6d,0x3f0e3f35,0xbf553f35,0xbf0e3f35,0x3f553f35,0x3e483ec4,0x3f7bbec4,0xbe483ec4,0xbf7bbec4,
0x3f6d3f80,0xbec43f80,0xbf6d3f80,0x3ec43f80,0x3ec43f35,0x3f6dbf35,0xbec43f35,0xbf6dbf35,0xbec40000,0xbf6d0000,0x3ec40000,0x3f6d0000,0xbf6dbf35,0x3ec43f35,0x3f6dbf35,0xbec43f35,
0x3f553f80,0xbf0e3f80,0xbf553f80,0x3f0e3f80,0xbe483ec4,0x3f7bbec4,0x3e483ec4,0xbf7bbec4,0xbf7bbf35,0xbe48bf35,0x3f7bbf35,0x3e48bf35,0xbf0ebf6d,0xbf553f6d,0x3f0ebf6d,0x3f553f6d,
0x3f353f80,0xbf353f80,0xbf353f80,0x3f353f80,0xbf350000,0x3f350000,0x3f350000,0xbf350000,0xbf35bf80,0x3f35bf80,0x3f35bf80,0xbf35bf80,0x3f350000,0xbf350000,0xbf350000,0x3f350000,
0x3f0e3f80,0xbf553f80,0xbf0e3f80,0x3f553f80,0xbf7bbec4,0x3e483ec4,0x3f7bbec4,0xbe483ec4,0x3e48bf35,0x3f7bbf35,0xbe48bf35,0xbf7bbf35,0x3f553f6d,0x3f0ebf6d,0xbf553f6d,0xbf0ebf6d,
0x3ec43f80,0xbf6d3f80,0xbec43f80,0x3f6d3f80,0xbf6dbf35,0xbec43f35,0x3f6dbf35,0x3ec43f35,0x3f6d0000,0x3ec40000,0xbf6d0000,0xbec40000,0xbec43f35,0x3f6dbf35,0x3ec43f35,0xbf6dbf35,
0x3e483f80,0xbf7b3f80,0xbe483f80,0x3f7b3f80,0xbf0ebf6d,0xbf553f6d,0x3f0ebf6d,0x3f553f6d,0x3f553f35,0xbf0e3f35,0xbf553f35,0x3f0e3f35,0xbf7bbec4,0xbe483ec4,0x3f7bbec4,0x3e483ec4,
0x3f803f80,0x3f80,0xbf803f80,0x3f80,0x3f803f80,0xbf80,0xbf803f80,0xbf80,0x3f803f80,0x3f80,0xbf803f80,0x3f80,0x3f803f80,0xbf80,0xbf803f80,0xbf80,
0xbe480000,0xbf7b0000,0x3e480000,0x3f7b0000,0xbf0ebec4,0x3f553ec4,0x3f0ebec4,0xbf553ec4,0xbf55bf35,0xbf0ebf35,0x3f55bf35,0x3f0ebf35,0xbf7bbf6d,0x3e483f6d,0x3f7bbf6d,0xbe483f6d,
0xbf6dbf80,0x3ec4bf80,0x3f6dbf80,0xbec4bf80,0xbec4bf35,0xbf6d3f35,0x3ec4bf35,0x3f6d3f35,0x3ec40000,0x3f6d0000,0xbec40000,0xbf6d0000,0x3f6d3f35,0xbec4bf35,0xbf6d3f35,0x3ec4bf35,
0x3f0e0000,0x3f550000,0xbf0e0000,0xbf550000,0x3f7b3f6d,0x3e48bf6d,0xbf7b3f6d,0xbe48bf6d,0x3e483f35,0xbf7b3f35,0xbe483f35,0x3f7b3f35,0xbf55bec4,0x3f0e3ec4,0x3f55bec4,0xbf0e3ec4,
0x3f353f80,0xbf353f80,0xbf353f80,0x3f353f80,0xbf350000,0x3f350000,0x3f350000,0xbf350000,0xbf35bf80,0x3f35bf80,0x3f35bf80,0xbf35bf80,0x3f350000,0xbf350000,0xbf350000,0x3f350000,
0xbf550000,0xbf0e0000,0x3f550000,0x3f0e0000,0xbe48bf6d,0xbf7b3f6d,0x3e48bf6d,0x3f7b3f6d,0x3f7b3f35,0xbe483f35,0xbf7b3f35,0x3e483f35,0xbf0e3ec4,0x3f55bec4,0x3f0e3ec4,0xbf55bec4,
0xbec4bf80,0x3f6dbf80,0x3ec4bf80,0xbf6dbf80,0x3f6d3f35,0x3ec4bf35,0xbf6d3f35,0xbec4bf35,0xbf6d0000,0xbec40000,0x3f6d0000,0x3ec40000,0x3ec4bf35,0xbf6d3f35,0xbec4bf35,0x3f6d3f35,
0x3f7b0000,0x3e480000,0xbf7b0000,0xbe480000,0xbf553ec4,0x3f0ebec4,0x3f553ec4,0xbf0ebec4,0x3f0ebf35,0x3f55bf35,0xbf0ebf35,0xbf55bf35,0xbe483f6d,0x3f7bbf6d,0x3e483f6d,0xbf7bbf6d,
0x3f803f80,0x3f80,0xbf803f80,0x3f80,0x3f803f80,0xbf80,0xbf803f80,0xbf80,0x3f803f80,0x3f80,0xbf803f80,0x3f80,0x3f803f80,0xbf80,0xbf803f80,0xbf80,
0xbf7bbf80,0x3e48bf80,0x3f7bbf80,0xbe48bf80,0xbf55bf6d,0xbf0e3f6d,0x3f55bf6d,0x3f0e3f6d,0xbf0ebf35,0x3f55bf35,0x3f0ebf35,0xbf55bf35,0xbe48bec4,0xbf7b3ec4,0x3e48bec4,0x3f7b3ec4,
0x3f6d3f80,0xbec43f80,0xbf6d3f80,0x3ec43f80,0x3ec43f35,0x3f6dbf35,0xbec43f35,0xbf6dbf35,0xbec40000,0xbf6d0000,0x3ec40000,0x3f6d0000,0xbf6dbf35,0x3ec43f35,0x3f6dbf35,0xbec43f35,
0xbf55bf80,0x3f0ebf80,0x3f55bf80,0xbf0ebf80,0x3e48bec4,0xbf7b3ec4,0xbe48bec4,0x3f7b3ec4,0x3f7b3f35,0x3e483f35,0xbf7b3f35,0xbe483f35,0x3f0e3f6d,0x3f55bf6d,0xbf0e3f6d,0xbf55bf6d,
0x3f353f80,0xbf353f80,0xbf353f80,0x3f353f80,0xbf350000,0x3f350000,0x3f350000,0xbf350000,0xbf35bf80,0x3f35bf80,0x3f35bf80,0xbf35bf80,0x3f350000,0xbf350000,0xbf350000,0x3f350000,
0xbf0ebf80,0x3f55bf80,0x3f0ebf80,0xbf55bf80,0x3f7b3ec4,0xbe48bec4,0xbf7b3ec4,0x3e48bec4,0xbe483f35,0xbf7b3f35,0x3e483f35,0x3f7b3f35,0xbf55bf6d,0xbf0e3f6d,0x3f55bf6d,0x3f0e3f6d,
0x3ec43f80,0xbf6d3f80,0xbec43f80,0x3f6d3f80,0xbf6dbf35,0xbec43f35,0x3f6dbf35,0x3ec43f35,0x3f6d0000,0x3ec40000,0xbf6d0000,0xbec40000,0xbec43f35,0x3f6dbf35,0x3ec43f35,0xbf6dbf35,
0xbe48bf80,0x3f7bbf80,0x3e48bf80,0xbf7bbf80,0x3f0e3f6d,0x3f55bf6d,0xbf0e3f6d,0xbf55bf6d,0xbf55bf35,0x3f0ebf35,0x3f55bf35,0xbf0ebf35,0x3f7b3ec4,0x3e48bec4,0xbf7b3ec4,0xbe48bec4,
0x3f803f80,0x3f80,0xbf803f80,0x3f80,0x3f803f80,0xbf80,0xbf803f80,0xbf80,0x3f803f80,0x3f80,0xbf803f80,0x3f80,0x3f803f80,0xbf80,0xbf803f80,0xbf80,
0x3e480000,0x3f7b0000,0xbe480000,0xbf7b0000,0x3f0e3ec4,0xbf55bec4,0xbf0e3ec4,0x3f55bec4,0x3f553f35,0x3f0e3f35,0xbf553f35,0xbf0e3f35,0x3f7b3f6d,0xbe48bf6d,0xbf7b3f6d,0x3e48bf6d,
0xbf6dbf80,0x3ec4bf80,0x3f6dbf80,0xbec4bf80,0xbec4bf35,0xbf6d3f35,0x3ec4bf35,0x3f6d3f35,0x3ec40000,0x3f6d0000,0xbec40000,0xbf6d0000,0x3f6d3f35,0xbec4bf35,0xbf6d3f35,0x3ec4bf35,
0xbf0e0000,0xbf550000,0x3f0e0000,0x3f550000,0xbf7bbf6d,0xbe483f6d,0x3f7bbf6d,0x3e483f6d,0xbe48bf35,0x3f7bbf35,0x3e48bf35,0xbf7bbf35,0x3f553ec4,0xbf0ebec4,0xbf553ec4,0x3f0ebec4,
0x3f353f80,0xbf353f80,0xbf353f80,0x3f353f80,0xbf350000,0x3f350000,0x3f350000,0xbf350000,0xbf35bf80,0x3f35bf80,0x3f35bf80,0xbf35bf80,0x3f350000,0xbf350000,0xbf350000,0x3f350000,
0x3f550000,0x3f0e0000,0xbf550000,0xbf0e0000,0x3e483f6d,0x3f7bbf6d,0xbe483f6d,0xbf7bbf6d,0xbf7bbf35,0x3e48bf35,0x3f7bbf35,0xbe48bf35,0x3f0ebec4,0xbf553ec4,0xbf0ebec4,0x3f553ec4,
0xbec4bf80,0x3f6dbf80,0x3ec4bf80,0xbf6dbf80,0x3f6d3f35,0x3ec4bf35,0xbf6d3f35,0xbec4bf35,0xbf6d0000,0xbec40000,0x3f6d0000,0x3ec40000,0x3ec4bf35,0xbf6d3f35,0xbec4bf35,0x3f6d3f35,
0xbf7b0000,0xbe480000,0x3f7b0000,0x3e480000,0x3f55bec4,0xbf0e3ec4,0xbf55bec4,0x3f0e3ec4,0xbf0e3f35,0xbf553f35,0x3f0e3f35,0x3f553f35,0x3e48bf6d,0xbf7b3f6d,0xbe48bf6d,0x3f7b3f6d,
0,0x3f800000,0,0xbf800000,0,0xbf800000,0,0x3f800000,0,0x3f800000,0,0xbf800000,0,0xbf800000,0,0x3f800000,
0x3e480000,0x3f7b0000,0xbe480000,0xbf7b0000,0x3f0e3ec4,0xbf55bec4,0xbf0e3ec4,0x3f55bec4,0x3f553f35,0x3f0e3f35,0xbf553f35,0xbf0e3f35,0x3f7b3f6d,0xbe48bf6d,0xbf7b3f6d,0x3e48bf6d,
0x3ec40000,0x3f6d0000,0xbec40000,0xbf6d0000,0x3f6d3f35,0xbec4bf35,0xbf6d3f35,0x3ec4bf35,0x3f6d3f80,0xbec43f80,0xbf6d3f80,0x3ec43f80,0x3ec43f35,0x3f6dbf35,0xbec43f35,0xbf6dbf35,
0x3f0e0000,0x3f550000,0xbf0e0000,0xbf550000,0x3f7b3f6d,0x3e48bf6d,0xbf7b3f6d,0xbe48bf6d,0x3e483f35,0xbf7b3f35,0xbe483f35,0x3f7b3f35,0xbf55bec4,0x3f0e3ec4,0x3f55bec4,0xbf0e3ec4,
0x3f350000,0x3f350000,0xbf350000,0xbf350000,0x3f353f80,0x3f35bf80,0xbf353f80,0xbf35bf80,0xbf350000,0xbf350000,0x3f350000,0x3f350000,0xbf35bf80,0xbf353f80,0x3f35bf80,0x3f353f80,
0x3f550000,0x3f0e0000,0xbf550000,0xbf0e0000,0x3e483f6d,0x3f7bbf6d,0xbe483f6d,0xbf7bbf6d,0xbf7bbf35,0x3e48bf35,0x3f7bbf35,0xbe48bf35,0x3f0ebec4,0xbf553ec4,0xbf0ebec4,0x3f553ec4,
0x3f6d0000,0x3ec40000,0xbf6d0000,0xbec40000,0xbec43f35,0x3f6dbf35,0x3ec43f35,0xbf6dbf35,0xbec4bf80,0x3f6dbf80,0x3ec4bf80,0xbf6dbf80,0x3f6d3f35,0x3ec4bf35,0xbf6d3f35,0xbec4bf35,
0x3f7b0000,0x3e480000,0xbf7b0000,0xbe480000,0xbf553ec4,0x3f0ebec4,0x3f553ec4,0xbf0ebec4,0x3f0ebf35,0x3f55bf35,0xbf0ebf35,0xbf55bf35,0xbe483f6d,0x3f7bbf6d,0x3e483f6d,0xbf7bbf6d,
0,0x3f800000,0,0xbf800000,0,0xbf800000,0,0x3f800000,0,0x3f800000,0,0xbf800000,0,0xbf800000,0,0x3f800000,
0x3f7b3f80,0xbe483f80,0xbf7b3f80,0x3e483f80,0x3f553f6d,0x3f0ebf6d,0xbf553f6d,0xbf0ebf6d,0x3f0e3f35,0xbf553f35,0xbf0e3f35,0x3f553f35,0x3e483ec4,0x3f7bbec4,0xbe483ec4,0xbf7bbec4,
0xbec40000,0xbf6d0000,0x3ec40000,0x3f6d0000,0xbf6dbf35,0x3ec43f35,0x3f6dbf35,0xbec43f35,0xbf6dbf80,0x3ec4bf80,0x3f6dbf80,0xbec4bf80,0xbec4bf35,0xbf6d3f35,0x3ec4bf35,0x3f6d3f35,
0xbf55bf80,0x3f0ebf80,0x3f55bf80,0xbf0ebf80,0x3e48bec4,0xbf7b3ec4,0xbe48bec4,0x3f7b3ec4,0x3f7b3f35,0x3e483f35,0xbf7b3f35,0xbe483f35,0x3f0e3f6d,0x3f55bf6d,0xbf0e3f6d,0xbf55bf6d,
0x3f350000,0x3f350000,0xbf350000,0xbf350000,0x3f353f80,0x3f35bf80,0xbf353f80,0xbf35bf80,0xbf350000,0xbf350000,0x3f350000,0x3f350000,0xbf35bf80,0xbf353f80,0x3f35bf80,0x3f353f80,
0x3f0e3f80,0xbf553f80,0xbf0e3f80,0x3f553f80,0xbf7bbec4,0x3e483ec4,0x3f7bbec4,0xbe483ec4,0x3e48bf35,0x3f7bbf35,0xbe48bf35,0xbf7bbf35,0x3f553f6d,0x3f0ebf6d,0xbf553f6d,0xbf0ebf6d,
0xbf6d0000,0xbec40000,0x3f6d0000,0x3ec40000,0x3ec4bf35,0xbf6d3f35,0xbec4bf35,0x3f6d3f35,0x3ec43f80,0xbf6d3f80,0xbec43f80,0x3f6d3f80,0xbf6dbf35,0xbec43f35,0x3f6dbf35,0x3ec43f35,
0xbe48bf80,0x3f7bbf80,0x3e48bf80,0xbf7bbf80,0x3f0e3f6d,0x3f55bf6d,0xbf0e3f6d,0xbf55bf6d,0xbf55bf35,0x3f0ebf35,0x3f55bf35,0xbf0ebf35,0x3f7b3ec4,0x3e48bec4,0xbf7b3ec4,0xbe48bec4,
0,0x3f800000,0,0xbf800000,0,0xbf800000,0,0x3f800000,0,0x3f800000,0,0xbf800000,0,0xbf800000,0,0x3f800000,
0xbe480000,0xbf7b0000,0x3e480000,0x3f7b0000,0xbf0ebec4,0x3f553ec4,0x3f0ebec4,0xbf553ec4,0xbf55bf35,0xbf0ebf35,0x3f55bf35,0x3f0ebf35,0xbf7bbf6d,0x3e483f6d,0x3f7bbf6d,0xbe483f6d,
0x3ec40000,0x3f6d0000,0xbec40000,0xbf6d0000,0x3f6d3f35,0xbec4bf35,0xbf6d3f35,0x3ec4bf35,0x3f6d3f80,0xbec43f80,0xbf6d3f80,0x3ec43f80,0x3ec43f35,0x3f6dbf35,0xbec43f35,0xbf6dbf35,
0xbf0e0000,0xbf550000,0x3f0e0000,0x3f550000,0xbf7bbf6d,0xbe483f6d,0x3f7bbf6d,0x3e483f6d,0xbe48bf35,0x3f7bbf35,0x3e48bf35,0xbf7bbf35,0x3f553ec4,0xbf0ebec4,0xbf553ec4,0x3f0ebec4,
0x3f350000,0x3f350000,0xbf350000,0xbf350000,0x3f353f80,0x3f35bf80,0xbf353f80,0xbf35bf80,0xbf350000,0xbf350000,0x3f350000,0x3f350000,0xbf35bf80,0xbf353f80,0x3f35bf80,0x3f353f80,
0xbf550000,0xbf0e0000,0x3f550000,0x3f0e0000,0xbe48bf6d,0xbf7b3f6d,0x3e48bf6d,0x3f7b3f6d,0x3f7b3f35,0xbe483f35,0xbf7b3f35,0x3e483f35,0xbf0e3ec4,0x3f55bec4,0x3f0e3ec4,0xbf55bec4,
0x3f6d0000,0x3ec40000,0xbf6d0000,0xbec40000,0xbec43f35,0x3f6dbf35,0x3ec43f35,0xbf6dbf35,0xbec4bf80,0x3f6dbf80,0x3ec4bf80,0xbf6dbf80,0x3f6d3f35,0x3ec4bf35,0xbf6d3f35,0xbec4bf35,
0xbf7b0000,0xbe480000,0x3f7b0000,0x3e480000,0x3f55bec4,0xbf0e3ec4,0xbf55bec4,0x3f0e3ec4,0xbf0e3f35,0xbf553f35,0x3f0e3f35,0x3f553f35,0x3e48bf6d,0xbf7b3f6d,0xbe48bf6d,0x3f7b3f6d,
0,0x3f800000,0,0xbf800000,0,0xbf800000,0,0x3f800000,0,0x3f800000,0,0xbf800000,0,0xbf800000,0,0x3f800000,
0xbf7bbf80,0x3e48bf80,0x3f7bbf80,0xbe48bf80,0xbf55bf6d,0xbf0e3f6d,0x3f55bf6d,0x3f0e3f6d,0xbf0ebf35,0x3f55bf35,0x3f0ebf35,0xbf55bf35,0xbe48bec4,0xbf7b3ec4,0x3e48bec4,0x3f7b3ec4,
0xbec40000,0xbf6d0000,0x3ec40000,0x3f6d0000,0xbf6dbf35,0x3ec43f35,0x3f6dbf35,0xbec43f35,0xbf6dbf80,0x3ec4bf80,0x3f6dbf80,0xbec4bf80,0xbec4bf35,0xbf6d3f35,0x3ec4bf35,0x3f6d3f35,
0x3f553f80,0xbf0e3f80,0xbf553f80,0x3f0e3f80,0xbe483ec4,0x3f7bbec4,0x3e483ec4,0xbf7bbec4,0xbf7bbf35,0xbe48bf35,0x3f7bbf35,0x3e48bf35,0xbf0ebf6d,0xbf553f6d,0x3f0ebf6d,0x3f553f6d,
0x3f350000,0x3f350000,0xbf350000,0xbf350000,0x3f353f80,0x3f35bf80,0xbf353f80,0xbf35bf80,0xbf350000,0xbf350000,0x3f350000,0x3f350000,0xbf35bf80,0xbf353f80,0x3f35bf80,0x3f353f80,
0xbf0ebf80,0x3f55bf80,0x3f0ebf80,0xbf55bf80,0x3f7b3ec4,0xbe48bec4,0xbf7b3ec4,0x3e48bec4,0xbe483f35,0xbf7b3f35,0x3e483f35,0x3f7b3f35,0xbf55bf6d,0xbf0e3f6d,0x3f55bf6d,0x3f0e3f6d,
0xbf6d0000,0xbec40000,0x3f6d0000,0x3ec40000,0x3ec4bf35,0xbf6d3f35,0xbec4bf35,0x3f6d3f35,0x3ec43f80,0xbf6d3f80,0xbec43f80,0x3f6d3f80,0xbf6dbf35,0xbec43f35,0x3f6dbf35,0x3ec43f35,
0x3e483f80,0xbf7b3f80,0xbe483f80,0x3f7b3f80,0xbf0ebf6d,0xbf553f6d,0x3f0ebf6d,0x3f553f6d,0x3f553f35,0xbf0e3f35,0xbf553f35,0x3f0e3f35,0xbf7bbec4,0xbe483ec4,0x3f7bbec4,0x3e483ec4,
0x3f800000,0x3f800000,0x3f800000,0x3f7ec46d,0x3f800000,0x3f800000,0x3f7b14be,0x3f74fa0b,0x3f800000,0x3f800000,0x3f6c835e,0x3f61c598,0x3f800000,0x3f800000,0x3f54db31,0x3f45e403,
0x3f800000,0x3f7ffb11,0x3f800000,0x3f7e70b0,0x3f7fec43,0x3f7fd397,0x3f79c79d,0x3f721352,0x3f7fb10f,0x3f7f84ab,0x3f676bd8,0x3f59f26a,0x3f7f4e6d,0x3f7f0e58,0x3f49d112,0x3f373a23,
0x3f800000,0x3f7fec43,0x3f800000,0x3f7e1324,0x3f7fb10f,0x3f7f4e6d,0x3f7853f8,0x3f6ed89e,0x3f7ec46d,0x3f7e1324,0x3f61c598,0x3f514d3d,0x3f7d3aac,0x3f7c3b28,0x3f3daef9,0x3f273656,
0x3f800000,0x3f7fd397,0x3f800000,0x3f7dabcc,0x3f7f4e6d,0x3f7e70b0,0x3f76ba07,0x3f6b4b0c,0x3f7d3aac,0x3f7baccd,0x3f5b941a,0x3f47de65,0x3f79c79d,0x3f778bc5,0x3f3085bb,0x3f15f6d9,
0x3f800000,0x3f7fb10f,0x3f800000,0x3f7d3aac,0x3f7ec46d,0x3f7d3aac,0x3f74fa0b,0x3f676bd8,0x3f7b14be,0x3f7853f8,0x3f54db31,0x3f3daef9,0x3f74fa0b,0x3f710908,0x3f226799,0x3f039c3d,
0x3f800000,0x3f7f84ab,0x3f800000,0x3f7cbfc9,0x3f7e1324,0x3f7baccd,0x3f731447,0x3f633c5a,0x3f7853f8,0x3f740bdd,0x3f4d9f02,0x3f32c8c9,0x3f6ed89e,0x3f68bf3c,0x3f13682a,0x3ee0924f,
0x3f800000,0x3f7f4e6d,0x3f800000,0x3f7c3b28,0x3f7d3aac,0x3f79c79d,0x3f710908,0x3f5ebe05,0x3f74fa0b,0x3f6ed89e,0x3f45e403,0x3f273656,0x3f676bd8,0x3f5ebe05,0x3f039c3d,0x3eb8442a,
0x3f800000,0x3f7f0e58,0x3f800000,0x3f7baccd,0x3f7c3b28,0x3f778bc5,0x3f6ed89e,0x3f59f26a,0x3f710908,0x3f68bf3c,0x3f3daef9,0x3f1b02c6,0x3f5ebe05,0x3f531849,0x3ee63375,0x3e8e9a22,
0x3f800000,0x3f800000,0x3f3504f3,0x3f226799,0x3f800000,0x3f800000,0x3f0e39da,0x3ef15aea,0x3f800000,0x3f800000,0x3ec3ef15,0x3e94a031,0x3f800000,0x3f800000,0x3e47c5c2,0x3dc8bd36,
0x3f7ec46d,0x3f7e70b0,0x3f226799,0x3f0b9a6b,0x3f7e1324,0x3f7dabcc,0x3ee63375,0x3eb263ef,0x3f7d3aac,0x3f7cbfc9,0x3e78cfcc,0x3e09cf86,0x3f7c3b28,0x3f7baccd,0x3cc90ab0,0xbdafb680,
0x3f7b14be,0x3f79c79d,0x3f0e39da,0x3ee63375,0x3f7853f8,0x3f76ba07,0x3eac7cd4,0x3e605c13,0x3f74fa0b,0x3f731447,0x3dc8bd36,0xbcc90ab0,0x3f710908,0x3f6ed89e,0xbe164083,0xbe888e93,
0x3f74fa0b,0x3f721352,0x3ef15aea,0x3eb263ef,0x3f6ed89e,0x3f6b4b0c,0x3e605c13,0x3dafb680,0x3f676bd8,0x3f633c5a,0xbd48fb30,0xbe3b6ecf,0x3f5ebe05,0x3f59f26a,0xbea09ae5,0xbee0924f,
0x3f6c835e,0x3f676bd8,0x3ec3ef15,0x3e78cfcc,0x3f61c598,0x3f5b941a,0x3dc8bd36,0xbd48fb30,0x3f54db31,0x3f4d9f02,0xbe47c5c2,0xbeac7cd4,0x3f45e403,0x3f3daef9,0xbef15aea,0xbf187fc0,
0x3f61c598,0x3f59f26a,0x3e94a031,0x3e09cf86,0x3f514d3d,0x3f47de65,0xbcc90ab0,0xbe3b6ecf,0x3f3daef9,0x3f32c8c9,0xbeac7cd4,0xbef6e0cb,0x3f273656,0x3f1b02c6,0xbf1d7fd1,0xbf3b8f3b,
0x3f54db31,0x3f49d112,0x3e47c5c2,0x3cc90ab0,0x3f3daef9,0x3f3085bb,0xbe164083,0xbea09ae5,0x3f226799,0x3f13682a,0xbef15aea,0xbf1d7fd1,0x3f039c3d,0x3ee63375,0xbf3daef9,0xbf584853,
0x3f45e403,0x3f373a23,0x3dc8bd36,0xbdafb680,0x3f273656,0x3f15f6d9,0xbe888e93,0xbee0924f,0x3f039c3d,0x3ee0924f,0xbf187fc0,0xbf3b8f3b,0x3eb8442a,0x3e8e9a22,0xbf584853,0xbf6db293,
0x3f800000,0x3f800000,0,0xbdc8bd36,0x3f800000,0x3f800000,0xbe47c5c2,0xbe94a031,0x3f800000,0x3f800000,0xbec3ef15,0xbef15aea,0x3f800000,0x3f800000,0xbf0e39da,0xbf226799,
0x3f7b14be,0x3f7a7302,0xbe47c5c2,0xbe9aa086,0x3f79c79d,0x3f791298,0xbecf7bca,0xbf00e7e4,0x3f7853f8,0x3f778bc5,0xbf187fc0,0xbf2e3bde,0x3f76ba07,0x3f75dec6,0xbf41d870,0xbf531849,
0x3f6c835e,0x3f6a09a7,0xbec3ef15,0xbefc5d27,0x3f676bd8,0x3f64aa59,0xbf187fc0,0xbf3085bb,0x3f61c598,0x3f5ebe05,0xbf45e403,0xbf584853,0x3f5b941a,0x3f584853,0xbf676bd8,0xbf731447,
0x3f54db31,0x3f4f7a1f,0xbf0e39da,0xbf299415,0x3f49d112,0x3f43e200,0xbf41d870,0xbf5695e5,0x3f3daef9,0x3f373a23,0xbf676bd8,0xbf740bdd,0x3f3085bb,0x3f299415,0xbf7c3b28,0xbf7fd397,
0x3f3504f3,0x3f2beb4a,0xbf3504f3,0xbf4d9f02,0x3f226799,0x3f187fc0,0xbf61c598,0xbf710908,0x3f0e39da,0x3f039c3d,0xbf7b14be,0xbf7fb10f,0x3ef15aea,0x3edae880,0xbf7ec46d,0xbf7853f8,
0x3f0e39da,0x3f00e7e4,0xbf54db31,0xbf68bf3c,0x3ee63375,0x3ec9b953,0xbf76ba07,0xbf7e70b0,0x3eac7cd4,0x3e8e9a22,0xbf7fb10f,0xbf7a7302,0x3e605c13,0x3e22abb6,0xbf6ed89e,0xbf5d2d53,
0x3ec3ef15,0x3ea09ae5,0xbf6c835e,0xbf79c79d,0x3e78cfcc,0x3e2f10a2,0xbf7fb10f,0xbf7e1324,0x3dc8bd36,0x3cc90ab0,0xbf74fa0b,0xbf64aa59,0xbd48fb30,0xbdfab273,0xbf4d9f02,0xbf3085bb,
0x3e47c5c2,0x3de1bc2e,0xbf7b14be,0xbf7ffb11,0x3cc90ab0,0xbd7b2b74,0xbf7c3b28,0xbf6ff573,0xbe164083,0xbe6c9a7f,0xbf5b941a,0xbf3fc767,0xbea09ae5,0xbec9b953,0xbf1d7fd1,0xbeebcbbb,
0x3f800000,0x3f800000,0xbf3504f3,0xbf45e403,0x3f800000,0x3f800000,0xbf54db31,0xbf61c598,0x3f800000,0x3f800000,0xbf6c835e,0xbf74fa0b,0x3f800000,0x3f800000,0xbf7b14be,0xbf7ec46d,
0x3f74fa0b,0x3f740bdd,0xbf61c598,0xbf6db293,0x3f731447,0x3f721352,0xbf76ba07,0xbf7cbfc9,0x3f710908,0x3f6ff573,0xbf7fb10f,0xbf7f84ab,0x3f6ed89e,0x3f6db293,0xbf7c3b28,0xbf75dec6,
0x3f54db31,0x3f514d3d,0xbf7b14be,0xbf7f4e6d,0x3f4d9f02,0x3f49d112,0xbf7fb10f,0xbf7c3b28,0x3f45e403,0x3f41d870,0xbf74fa0b,0xbf6a09a7,0x3f3daef9,0x3f396842,0xbf5b941a,0xbf49d112,
0x3f226799,0x3f1b02c6,0xbf7ec46d,0xbf791298,0x3f13682a,0x3f0b9a6b,0xbf6ed89e,0xbf604621,0x3f039c3d,0x3ef6e0cb,0xbf4d9f02,0xbf373a23,0x3ee63375,0x3ed53641,0xbf1d7fd1,0xbf00e7e4,
0x3ec3ef15,0x3eac7cd4,0xbf6c835e,0xbf5b941a,0x3e94a031,0x3e78cfcc,0xbf45e403,0xbf2beb4a,0x3e47c5c2,0x3e164083,0xbf0e39da,0xbedae880,0x3dc8bd36,0x3d48fb30,0xbe94a031,0xbe164083,
0x3dc8bd36,0x3d16c32c,0xbf45e403,0xbf299415,0xbcc90ab0,0xbdafb680,0xbf08f59b,0xbec9b953,0xbe164083,0xbe541501,0xbe78cfcc,0xbdafb680,0xbe888e93,0xbea68f12,0x3d96a905,0x3e6c9a7f,
0xbe47c5c2,0xbe888e93,0xbf0e39da,0xbecf7bca,0xbeac7cd4,0xbecf7bca,0xbe78cfcc,0xbd96a905,0xbef15aea,0xbf08f59b,0x3dc8bd36,0x3e888e93,0xbf187fc0,0xbf273656,0x3edae880,0x3f13682a,
0xbef15aea,0xbf0b9a6b,0xbe94a031,0xbde1bc2e,0xbf1d7fd1,0xbf2e3bde,0x3d96a905,0x3e827dc0,0xbf3daef9,0xbf4bbbf8,0x3edae880,0x3f15f6d9,0xbf584853,0xbf633c5a,0x3f396842,0x3f5695e5,
0,0,0,0x3dc8bd36,0,0,0x3e47c5c2,0x3e94a031,0,0,0x3ec3ef15,0x3ef15aea,0,0,0x3f0e39da,0x3f226799,
0,0x3c490e90,0,0x3de1bc2e,0x3cc90ab0,0x3d16c32c,0x3e605c13,0x3ea68f12,0x3d48fb30,0x3d7b2b74,0x3edae880,0x3f064b82,0x3d96a905,0x3dafb680,0x3f1d7fd1,0x3f32c8c9,
0,0x3cc90ab0,0,0x3dfab273,0x3d48fb30,0x3d96a905,0x3e78cfcc,0x3eb8442a,0x3dc8bd36,0x3dfab273,0x3ef15aea,0x3f13682a,0x3e164083,0x3e2f10a2,0x3f2beb4a,0x3f41d870,
0,0x3d16c32c,0,0x3e09cf86,0x3d96a905,0x3de1bc2e,0x3e888e93,0x3ec9b953,0x3e164083,0x3e3b6ecf,0x3f039c3d,0x3f1ff6cb,0x3e605c13,0x3e827dc0,0x3f396842,0x3f4f7a1f,
0,0x3d48fb30,0,0x3e164083,0x3dc8bd36,0x3e164083,0x3e94a031,0x3edae880,0x3e47c5c2,0x3e78cfcc,0x3f0e39da,0x3f2beb4a,0x3e94a031,0x3eac7cd4,0x3f45e403,0x3f5b941a,
0,0x3d7b2b74,0,0x3e22abb6,0x3dfab273,0x3e3b6ecf,0x3ea09ae5,0x3eebcbbb,0x3e78cfcc,0x3e9aa086,0x3f187fc0,0x3f373a23,0x3eb8442a,0x3ed53641,0x3f514d3d,0x3f660f88,
0,0x3d96a905,0,0x3e2f10a2,0x3e164083,0x3e605c13,0x3eac7cd4,0x3efc5d27,0x3e94a031,0x3eb8442a,0x3f226799,0x3f41d870,0x3edae880,0x3efc5d27,0x3f5b941a,0x3f6ed89e,
0,0x3dafb680,0,0x3e3b6ecf,0x3e2f10a2,0x3e827dc0,0x3eb8442a,0x3f064b82,0x3eac7cd4,0x3ed53641,0x3f2beb4a,0x3f4bbbf8,0x3efc5d27,0x3f10d3cd,0x3f64aa59,0x3f75dec6,
0,0,0x3f3504f3,0x3f45e403,0,0,0x3f54db31,0x3f61c598,0,0,0x3f6c835e,0x3f74fa0b,0,0,0x3f7b14be,0x3f7ec46d,
0x3dc8bd36,0x3de1bc2e,0x3f45e403,0x3f5695e5,0x3dfab273,0x3e09cf86,0x3f64aa59,0x3f6ff573,0x3e164083,0x3e22abb6,0x3f7853f8,0x3f7dabcc,0x3e2f10a2,0x3e3b6ecf,0x3f7fec43,0x3f7f0e58,
0x3e47c5c2,0x3e605c13,0x3f54db31,0x3f64aa59,0x3e78cfcc,0x3e888e93,0x3f710908,0x3f79c79d,0x3e94a031,0x3ea09ae5,0x3f7ec46d,0x3f7fec43,0x3eac7cd4,0x3eb8442a,0x3f7d3aac,0x3f76ba07,
0x3e94a031,0x3ea68f12,0x3f61c598,0x3f6ff573,0x3eb8442a,0x3ec9b953,0x3f79c79d,0x3f7f0e58,0x3edae880,0x3eebcbbb,0x3f7fb10f,0x3f7baccd,0x3efc5d27,0x3f064b82,0x3f731447,0x3f660f88,
0x3ec3ef15,0x3edae880,0x3f6c835e,0x3f7853f8,0x3ef15aea,0x3f039c3d,0x3f7ec46d,0x3f7fb10f,0x3f0e39da,0x3f187fc0,0x3f7b14be,0x3f710908,0x3f226799,0x3f2beb4a,0x3f61c598,0x3f4d9f02,
0x3ef15aea,0x3f064b82,0x3f74fa0b,0x3f7dabcc,0x3f13682a,0x3f1ff6cb,0x3f7fec43,0x3f7baccd,0x3f2beb4a,0x3f373a23,0x3f710908,0x3f604621,0x3f41d870,0x3f4bbbf8,0x3f49d112,0x3f2e3bde,
0x3f0e39da,0x3f1d7fd1,0x3f7b14be,0x3f7fec43,0x3f2beb4a,0x3f396842,0x3f7d3aac,0x3f731447,0x3f45e403,0x3f514d3d,0x3f61c598,0x3f49d112,0x3f5b941a,0x3f64aa59,0x3f2beb4a,0x3f08f59b,
0x3f226799,0x3f32c8c9,0x3f7ec46d,0x3f7f0e58,0x3f41d870,0x3f4f7a1f,0x3f76ba07,0x3f660f88,0x3f5b941a,0x3f660f88,0x3f4d9f02,0x3f2e3bde,0x3f6ed89e,0x3f75dec6,0x3f08f59b,0x3ebe1d4a,
0,0,0x3f800000,0x3f7ec46d,0,0,0x3f7b14be,0x3f74fa0b,0,0,0x3f6c835e,0x3f61c598,0,0,0x3f54db31,0x3f45e403,
0x3e47c5c2,0x3e541501,0x3f7b14be,0x3f740bdd,0x3e605c13,0x3e6c9a7f,0x3f6a09a7,0x3f5d2d53,0x3e78cfcc,0x3e827dc0,0x3f4d9f02,0x3f3b8f3b,0x3e888e93,0x3e8e9a22,0x3f273656,0x3f10d3cd,
0x3ec3ef15,0x3ecf7bca,0x3f6c835e,0x3f5ebe05,0x3edae880,0x3ee63375,0x3f4d9f02,0x3f396842,0x3ef15aea,0x3efc5d27,0x3f226799,0x3f08f59b,0x3f039c3d,0x3f08f59b,0x3edae880,0x3ea09ae5,
0x3f0e39da,0x3f15f6d9,0x3f54db31,0x3f3fc767,0x3f1d7fd1,0x3f24d225,0x3f273656,0x3f0b9a6b,0x3f2beb4a,0x3f32c8c9,0x3edae880,0x3e9aa086,0x3f396842,0x3f3fc767,0x3e2f10a2,0x3d16c32c,
0x3f3504f3,0x3f3daef9,0x3f3504f3,0x3f187fc0,0x3f45e403,0x3f4d9f02,0x3ef15aea,0x3eac7cd4,0x3f54db31,0x3f5b941a,0x3e47c5c2,0x3d48fb30,0x3f61c598,0x3f676bd8,0xbdc8bd36,0xbe78cfcc,
0x3f54db31,0x3f5d2d53,0x3f0e39da,0x3ed53641,0x3f64aa59,0x3f6b4b0c,0x3e888e93,0x3de1bc2e,0x3f710908,0x3f75dec6,0xbd48fb30,0xbe541501,0x3f79c79d,0x3f7cbfc9,0xbeb8442a,0xbf00e7e4,
0x3f6c835e,0x3f731447,0x3ec3ef15,0x3e605c13,0x3f7853f8,0x3f7c3b28,0x3d48fb30,0xbdfab273,0x3f7ec46d,0x3f7fec43,0xbe94a031,0xbee63375,0x3f7fb10f,0x3f7e1324,0xbf187fc0,0xbf396842,
0x3f7b14be,0x3f7e70b0,0x3e47c5c2,0x3c490e90,0x3f7fec43,0x3f7f84ab,0xbe2f10a2,0xbeb263ef,0x3f7d3aac,0x3f791298,0xbf039c3d,0xbf299415,0x3f731447,0x3f6b4b0c,0xbf49d112,0xbf633c5a,
0,0,0x3f3504f3,0x3f226799,0,0,0x3f0e39da,0x3ef15aea,0,0,0x3ec3ef15,0x3e94a031,0,0,0x3e47c5c2,0x3dc8bd36,
0x3e94a031,0x3e9aa086,0x3ef15aea,0x3ebe1d4a,0x3ea09ae5,0x3ea68f12,0x3e888e93,0x3e22abb6,0x3eac7cd4,0x3eb263ef,0x3d48fb30,0xbd7b2b74,0x3eb8442a,0x3ebe1d4a,0xbe2f10a2,0xbe8e9a22,
0x3f0e39da,0x3f13682a,0x3e47c5c2,0x3d96a905,0x3f187fc0,0x3f1d7fd1,0xbd48fb30,0xbe2f10a2,0x3f226799,0x3f273656,0xbe94a031,0xbecf7bca,0x3f2beb4a,0x3f3085bb,0xbf039c3d,0xbf1d7fd1,
0x3f45e403,0x3f4bbbf8,0xbdc8bd36,0xbe6c9a7f,0x3f514d3d,0x3f5695e5,0xbeb8442a,0xbef6e0cb,0x3f5b941a,0x3f604621,0xbf187fc0,0xbf32c8c9,0x3f64aa59,0x3f68bf3c,0xbf49d112,0xbf5d2d53,
0x3f6c835e,0x3f710908,0xbec3ef15,0xbf039c3d,0x3f74fa0b,0x3f7853f8,0xbf226799,0xbf3daef9,0x3f7b14be,0x3f7d3aac,0xbf54db31,0xbf676bd8,0x3f7ec46d,0x3f7fb10f,0xbf74fa0b,0xbf7d3aac,
0x3f7ec46d,0x3f7fd397,0xbf226799,0xbf3fc767,0x3f7fec43,0x3f7f0e58,0xbf584853,0xbf6b4b0c,0x3f7d3aac,0x3f7a7302,0xbf7853f8,0xbf7f0e58,0x3f76ba07,0x3f721352,0xbf7f4e6d,0xbf791298,
0x3f7b14be,0x3f76ba07,0xbf54db31,0xbf6a09a7,0x3f710908,0x3f6a09a7,0xbf7853f8,0xbf7f4e6d,0x3f61c598,0x3f584853,0xbf7ec46d,0xbf76ba07,0x3f4d9f02,0x3f41d870,0xbf676bd8,0xbf514d3d,
0x3f61c598,0x3f5695e5,0xbf74fa0b,0xbf7e70b0,0x3f49d112,0x3f3b8f3b,0xbf7f4e6d,0xbf778bc5,0x3f2beb4a,0x3f1b02c6,0xbf676bd8,0xbf4f7a1f,0x3f08f59b,0x3eebcbbb,0xbf3085bb,0xbf0b9a6b,
0x3f800000,0x3f7fffb1,0x3f7ffec4,0x3f7ffd39,0x3f7ffb11,0x3f7ff84a,0x3f7ff4e6,0x3f7ff0e3,0x3f7fec43,0x3f7fe705,0x3f7fe129,0x3f7fdaaf,0x3f7fd397,0x3f7fcbe2,0x3f7fc38f,0x3f7fba9e,
0x3f7fb10f,0x3f7fa6e3,0x3f7f9c18,0x3f7f90b1,0x3f7f84ab,0x3f7f7808,0x3f7f6ac7,0x3f7f5ce9,0x3f7f4e6d,0x3f7f3f54,0x3f7f2f9d,0x3f7f1f49,0x3f7f0e58,0x3f7efcc9,0x3f7eea9d,0x3f7ed7d4,
0x3f7ec46d,0x3f7eb069,0x3f7e9bc9,0x3f7e868b,0x3f7e70b0,0x3f7e5a38,0x3f7e4323,0x3f7e2b72,0x3f7e1324,0x3f7dfa38,0x3f7de0b1,0x3f7dc68c,0x3f7dabcc,0x3f7d906e,0x3f7d7474,0x3f7d57de,
0x3f7d3aac,0x3f7d1cdd,0x3f7cfe73,0x3f7cdf6c,0x3f7cbfc9,0x3f7c9f8a,0x3f7c7eb0,0x3f7c5d3a,0x3f7c3b28,0x3f7c187a,0x3f7bf531,0x3f7bd14d,0x3f7baccd,0x3f7b87b2,0x3f7b61fc,0x3f7b3bab,
0x3f7b14be,0x3f7aed37,0x3f7ac516,0x3f7a9c59,0x3f7a7302,0x3f7a4910,0x3f7a1e84,0x3f79f35e,0x3f79c79d,0x3f799b43,0x3f796e4e,0x3f7940c0,0x3f791298,0x3f78e3d6,0x3f78b47b,0x3f788486,
0x3f7853f8,0x3f7822d1,0x3f77f110,0x3f77beb7,0x3f778bc5,0x3f77583a,0x3f772417,0x3f76ef5b,0x3f76ba07,0x3f76841b,0x3f764d97,0x3f76167a,0x3f75dec6,0x3f75a67b,0x3f756d97,0x3f75341d,
0x3f74fa0b,0x3f74bf62,0x3f748422,0x3f74484b,0x3f740bdd,0x3f73ced9,0x3f73913f,0x3f73530e,0x3f731447,0x3f72d4eb,0x3f7294f8,0x3f725470,0x3f721352,0x3f71d19f,0x3f718f57,0x3f714c7a,
0x3f710908,0x3f70c501,0x3f708066,0x3f703b37,0x3f6ff573,0x3f6faf1b,0x3f6f6830,0x3f6f20b0,0x3f6ed89e,0x3f6e8ff8,0x3f6e46be,0x3f6dfcf2,0x3f6db293,0x3f6d67a1,0x3f6d1c1d,0x3f6cd007,
0x3f6c835e,0x3f6c3624,0x3f6be858,0x3f6b99fb,0x3f6b4b0c,0x3f6afb8c,0x3f6aab7b,0x3f6a5ad9,0x3f6a09a7,0x3f69b7e4,0x3f696591,0x3f6912ae,0x3f68bf3c,0x3f686b39,0x3f6816a8,0x3f67c187,
0x3f676bd8,0x3f671599,0x3f66becc,0x3f666771,0x3f660f88,0x3f65b710,0x3f655e0b,0x3f650479,0x3f64aa59,0x3f644fac,0x3f63f473,0x3f6398ac,0x3f633c5a,0x3f62df7b,0x3f628210,0x3f62241a,
0x3f61c598,0x3f61668a,0x3f6106f2,0x3f60a6cf,0x3f604621,0x3f5fe4e9,0x3f5f8327,0x3f5f20db,0x3f5ebe05,0x3f5e5aa6,0x3f5df6be,0x3f5d924d,0x3f5d2d53,0x3f5cc7d1,0x3f5c61c7,0x3f5bfb34,
0x3f5b941a,0x3f5b2c79,0x3f5ac450,0x3f5a5ba0,0x3f59f26a,0x3f5988ad,0x3f591e6a,0x3f58b3a1,0x3f584853,0x3f57dc7f,0x3f577026,0x3f570348,0x3f5695e5,0x3f5627fe,0x3f55b993,0x3f554aa4,
0x3f54db31,0x3f546b3b,0x3f53fac3,0x3f5389c7,0x3f531849,0x3f52a649,0x3f5233c6,0x3f51c0c2,0x3f514d3d,0x3f50d937,0x3f5064af,0x3f4fefa8,0x3f4f7a1f,0x3f4f0417,0x3f4e8d90,0x3f4e1689,
0x3f4d9f02,0x3f4d26fd,0x3f4cae79,0x3f4c3578,0x3f4bbbf8,0x3f4b41fa,0x3f4ac77f,0x3f4a4c87,0x3f49d112,0x3f495521,0x3f48d8b3,0x3f485bca,0x3f47de65,0x3f476085,0x3f46e22a,0x3f466354,
0x3f45e403,0x3f456439,0x3f44e3f5,0x3f446337,0x3f43e200,0x3f436051,0x3f42de29,0x3f425b89,0x3f41d870,0x3f4154e1,0x3f40d0da,0x3f404c5c,0x3f3fc767,0x3f3f41fc,0x3f3ebc1b,0x3f3e35c5,
0x3f3daef9,0x3f3d27b8,0x3f3ca003,0x3f3c17d9,0x3f3b8f3b,0x3f3b0629,0x3f3a7ca4,0x3f39f2ac,0x3f396842,0x3f38dd65,0x3f385216,0x3f37c655,0x3f373a23,0x3f36ad7f,0x3f36206c,0x3f3592e7,
0x3f3504f3,0x3f34768f,0x3f33e7bc,0x3f33587a,0x3f32c8c9,0x3f3238aa,0x3f31a81d,0x3f311722,0x3f3085bb,0x3f2ff3e6,0x3f2f61a5,0x3f2ecef7,0x3f2e3bde,0x3f2da859,0x3f2d1469,0x3f2c800f,
0x3f2beb4a,0x3f2b561b,0x3f2ac082,0x3f2a2a80,0x3f299415,0x3f28fd41,0x3f286605,0x3f27ce61,0x3f273656,0x3f269de3,0x3f26050a,0x3f256bcb,0x3f24d225,0x3f24381a,0x3f239da9,0x3f2302d3,
0x3f226799,0x3f21cbfb,0x3f212ff9,0x3f209393,0x3f1ff6cb,0x3f1f599f,0x3f1ebc12,0x3f1e1e22,0x3f1d7fd1,0x3f1ce11f,0x3f1c420c,0x3f1ba299,0x3f1b02c6,0x3f1a6293,0x3f19c200,0x3f19210f,
0x3f187fc0,0x3f17de12,0x3f173c07,0x3f16999f,0x3f15f6d9,0x3f1553b7,0x3f14b039,0x3f140c5f,0x3f13682a,0x3f12c39a,0x3f121eb0,0x3f11796b,0x3f10d3cd,0x3f102dd5,0x3f0f8784,0x3f0ee0db,
0x3f0e39da,0x3f0d9281,0x3f0cead0,0x3f0c42c9,0x3f0b9a6b,0x3f0af1b7,0x3f0a48ad,0x3f099f4e,0x3f08f59b,0x3f084b92,0x3f07a136,0x3f06f686,0x3f064b82,0x3f05a02c,0x3f04f484,0x3f044889,
0x3f039c3d,0x3f02ef9f,0x3f0242b1,0x3f019573,0x3f00e7e4,0x3f003a06,0x3eff17b2,0x3efdbabb,0x3efc5d27,0x3efafef7,0x3ef9a02d,0x3ef840c8,0x3ef6e0cb,0x3ef58035,0x3ef41f07,0x3ef2bd43,
0x3ef15aea,0x3eeff7fb,0x3eee9479,0x3eed3063,0x3eebcbbb,0x3eea6681,0x3ee900b7,0x3ee79a5d,0x3ee63375,0x3ee4cbfe,0x3ee363fa,0x3ee1fb6a,0x3ee0924f,0x3edf28a9,0x3eddbe79,0x3edc53c1,
0x3edae880,0x3ed97cb9,0x3ed8106b,0x3ed6a399,0x3ed53641,0x3ed3c867,0x3ed25a09,0x3ed0eb2a,0x3ecf7bca,0x3ece0bea,0x3ecc9b8b,0x3ecb2aae,0x3ec9b953,0x3ec8477c,0x3ec6d529,0x3ec5625c,
0x3ec3ef15,0x3ec27b55,0x3ec1071e,0x3ebf926f,0x3ebe1d4a,0x3ebca7af,0x3ebb31a0,0x3eb9bb1e,0x3eb8442a,0x3eb6ccc3,0x3eb554ec,0x3eb3dca5,0x3eb263ef,0x3eb0eacb,0x3eaf713a,0x3eadf73c,
0x3eac7cd4,0x3eab0201,0x3ea986c4,0x3ea80b1f,0x3ea68f12,0x3ea5129f,0x3ea395c5,0x3ea21887,0x3ea09ae5,0x3e9f1cdf,0x3e9d9e78,0x3e9c1faf,0x3e9aa086,0x3e9920fe,0x3e97a117,0x3e9620d2,
0x3e94a031,0x3e931f35,0x3e919ddd,0x3e901c2c,0x3e8e9a22,0x3e8d17c0,0x3e8b9507,0x3e8a11f7,0x3e888e93,0x3e870ada,0x3e8586ce,0x3e840270,0x3e827dc0,0x3e80f8c0,0x3e7ee6e1,0x3e7bdba4,
0x3e78cfcc,0x3e75c35a,0x3e72b651,0x3e6fa8b2,0x3e6c9a7f,0x3e698bba,0x3e667c66,0x3e636c83,0x3e605c13,0x3e5d4b1a,0x3e5a3997,0x3e57278f,0x3e541501,0x3e5101f1,0x3e4dee60,0x3e4ada4f,
0x3e47c5c2,0x3e44b0b9,0x3e419b37,0x3e3e853e,0x3e3b6ecf,0x3e3857ec,0x3e354098,0x3e3228d4,0x3e2f10a2,0x3e2bf804,0x3e28defc,0x3e25c58c,0x3e22abb6,0x3e1f917b,0x3e1c76de,0x3e195be0,
0x3e164083,0x3e1324ca,0x3e1008b7,0x3e0cec4a,0x3e09cf86,0x3e06b26e,0x3e039502,0x3e007745,0x3dfab273,0x3df475c0,0x3dee3876,0x3de7fa9a,0x3de1bc2e,0x3ddb7d37,0x3dd53db9,0x3dcefdb7,
0x3dc8bd36,0x3dc27c39,0x3dbc3ac3,0x3db5f8da,0x3dafb680,0x3da973ba,0x3da3308c,0x3d9cecf9,0x3d96a905,0x3d9064b4,0x3d8a200a,0x3d83db0a,0x3d7b2b74,0x3d6ea038,0x3d621469,0x3d55880e,
0x3d48fb30,0x3d3c6dd5,0x3d2fe007,0x3d2351cb,0x3d16c32c,0x3d0a342f,0x3cfb49ba,0x3ce22a7a,0x3cc90ab0,0x3cafea69,0x3c96c9b6,0x3c7b514b,0x3c490e90,0x3c16cb58,0x3bc90f88,0x3b490fc6,
0,0x3b490fc6,0x3bc90f88,0x3c16cb58,0x3c490e90,0x3c7b514b,0x3c96c9b6,0x3cafea69,0x3cc90ab0,0x3ce22a7a,0x3cfb49ba,0x3d0a342f,0x3d16c32c,0x3d2351cb,0x3d2fe007,0x3d3c6dd5,
0x3d48fb30,0x3d55880e,0x3d621469,0x3d6ea038,0x3d7b2b74,0x3d83db0a,0x3d8a200a,0x3d9064b4,0x3d96a905,0x3d9cecf9,0x3da3308c,0x3da973ba,0x3dafb680,0x3db5f8da,0x3dbc3ac3,0x3dc27c39,
0x3dc8bd36,0x3dcefdb7,0x3dd53db9,0x3ddb7d37,0x3de1bc2e,0x3de7fa9a,0x3dee3876,0x3df475c0,0x3dfab273,0x3e007745,0x3e039502,0x3e06b26e,0x3e09cf86,0x3e0cec4a,0x3e1008b7,0x3e1324ca,
0x3e164083,0x3e195be0,0x3e1c76de,0x3e1f917b,0x3e22abb6,0x3e25c58c,0x3e28defc,0x3e2bf804,0x3e2f10a2,0x3e3228d4,0x3e354098,0x3e3857ec,0x3e3b6ecf,0x3e3e853e,0x3e419b37,0x3e44b0b9,
0x3e47c5c2,0x3e4ada4f,0x3e4dee60,0x3e5101f1,0x3e541501,0x3e57278f,0x3e5a3997,0x3e5d4b1a,0x3e605c13,0x3e636c83,0x3e667c66,0x3e698bba,0x3e6c9a7f,0x3e6fa8b2,0x3e72b651,0x3e75c35a,
0x3e78cfcc,0x3e7bdba4,0x3e7ee6e1,0x3e80f8c0,0x3e827dc0,0x3e840270,0x3e8586ce,0x3e870ada,0x3e888e93,0x3e8a11f7,0x3e8b9507,0x3e8d17c0,0x3e8e9a22,0x3e901c2c,0x3e919ddd,0x3e931f35,
0x3e94a031,0x3e9620d2,0x3e97a117,0x3e9920fe,0x3e9aa086,0x3e9c1faf,0x3e9d9e78,0x3e9f1cdf,0x3ea09ae5,0x3ea21887,0x3ea395c5,0x3ea5129f,0x3ea68f12,0x3ea80b1f,0x3ea986c4,0x3eab0201,
0x3eac7cd4,0x3eadf73c,0x3eaf713a,0x3eb0eacb,0x3eb263ef,0x3eb3dca5,0x3eb554ec,0x3eb6ccc3,0x3eb8442a,0x3eb9bb1e,0x3ebb31a0,0x3ebca7af,0x3ebe1d4a,0x3ebf926f,0x3ec1071e,0x3ec27b55,
0x3ec3ef15,0x3ec5625c,0x3ec6d529,0x3ec8477c,0x3ec9b953,0x3ecb2aae,0x3ecc9b8b,0x3ece0bea,0x3ecf7bca,0x3ed0eb2a,0x3ed25a09,0x3ed3c867,0x3ed53641,0x3ed6a399,0x3ed8106b,0x3ed97cb9,
0x3edae880,0x3edc53c1,0x3eddbe79,0x3edf28a9,0x3ee0924f,0x3ee1fb6a,0x3ee363fa,0x3ee4cbfe,0x3ee63375,0x3ee79a5d,0x3ee900b7,0x3eea6681,0x3eebcbbb,0x3eed3063,0x3eee9479,0x3eeff7fb,
0x3ef15aea,0x3ef2bd43,0x3ef41f07,0x3ef58035,0x3ef6e0cb,0x3ef840c8,0x3ef9a02d,0x3efafef7,0x3efc5d27,0x3efdbabb,0x3eff17b2,0x3f003a06,0x3f00e7e4,0x3f019573,0x3f0242b1,0x3f02ef9f,
0x3f039c3d,0x3f044889,0x3f04f484,0x3f05a02c,0x3f064b82,0x3f06f686,0x3f07a136,0x3f084b92,0x3f08f59b,0x3f099f4e,0x3f0a48ad,0x3f0af1b7,0x3f0b9a6b,0x3f0c42c9,0x3f0cead0,0x3f0d9281,
0x3f0e39da,0x3f0ee0db,0x3f0f8784,0x3f102dd5,0x3f10d3cd,0x3f11796b,0x3f121eb0,0x3f12c39a,0x3f13682a,0x3f140c5f,0x3f14b039,0x3f1553b7,0x3f15f6d9,0x3f16999f,0x3f173c07,0x3f17de12,
0x3f187fc0,0x3f19210f,0x3f19c200,0x3f1a6293,0x3f1b02c6,0x3f1ba299,0x3f1c420c,0x3f1ce11f,0x3f1d7fd1,0x3f1e1e22,0x3f1ebc12,0x3f1f599f,0x3f1ff6cb,0x3f209393,0x3f212ff9,0x3f21cbfb,
0x3f226799,0x3f2302d3,0x3f239da9,0x3f24381a,0x3f24d225,0x3f256bcb,0x3f26050a,0x3f269de3,0x3f273656,0x3f27ce61,0x3f286605,0x3f28fd41,0x3f299415,0x3f2a2a80,0x3f2ac082,0x3f2b561b,
0x3f2beb4a,0x3f2c800f,0x3f2d1469,0x3f2da859,0x3f2e3bde,0x3f2ecef7,0x3f2f61a5,0x3f2ff3e6,0x3f3085bb,0x3f311722,0x3f31a81d,0x3f3238aa,0x3f32c8c9,0x3f33587a,0x3f33e7bc,0x3f34768f,
0x3f3504f3,0x3f3592e7,0x3f36206c,0x3f36ad7f,0x3f373a23,0x3f37c655,0x3f385216,0x3f38dd65,0x3f396842,0x3f39f2ac,0x3f3a7ca4,0x3f3b0629,0x3f3b8f3b,0x3f3c17d9,0x3f3ca003,0x3f3d27b8,
0x3f3daef9,0x3f3e35c5,0x3f3ebc1b,0x3f3f41fc,0x3f3fc767,0x3f404c5c,0x3f40d0da,0x3f4154e1,0x3f41d870,0x3f425b89,0x3f42de29,0x3f436051,0x3f43e200,0x3f446337,0x3f44e3f5,0x3f456439,
0x3f45e403,0x3f466354,0x3f46e22a,0x3f476085,0x3f47de65,0x3f485bca,0x3f48d8b3,0x3f495521,0x3f49d112,0x3f4a4c87,0x3f4ac77f,0x3f4b41fa,0x3f4bbbf8,0x3f4c3578,0x3f4cae79,0x3f4d26fd,
0x3f4d9f02,0x3f4e1689,0x3f4e8d90,0x3f4f0417,0x3f4f7a1f,0x3f4fefa8,0x3f5064af,0x3f50d937,0x3f514d3d,0x3f51c0c2,0x3f5233c6,0x3f52a649,0x3f531849,0x3f5389c7,0x3f53fac3,0x3f546b3b,
0x3f54db31,0x3f554aa4,0x3f55b993,0x3f5627fe,0x3f5695e5,0x3f570348,0x3f577026,0x3f57dc7f,0x3f584853,0x3f58b3a1,0x3f591e6a,0x3f5988ad,0x3f59f26a,0x3f5a5ba0,0x3f5ac450,0x3f5b2c79,
0x3f5b941a,0x3f5bfb34,0x3f5c61c7,0x3f5cc7d1,0x3f5d2d53,0x3f5d924d,0x3f5df6be,0x3f5e5aa6,0x3f5ebe05,0x3f5f20db,0x3f5f8327,0x3f5fe4e9,0x3f604621,0x3f60a6cf,0x3f6106f2,0x3f61668a,
0x3f61c598,0x3f62241a,0x3f628210,0x3f62df7b,0x3f633c5a,0x3f6398ac,0x3f63f473,0x3f644fac,0x3f64aa59,0x3f650479,0x3f655e0b,0x3f65b710,0x3f660f88,0x3f666771,0x3f66becc,0x3f671599,
0x3f676bd8,0x3f67c187,0x3f6816a8,0x3f686b39,0x3f68bf3c,0x3f6912ae,0x3f696591,0x3f69b7e4,0x3f6a09a7,0x3f6a5ad9,0x3f6aab7b,0x3f6afb8c,0x3f6b4b0c,0x3f6b99fb,0x3f6be858,0x3f6c3624,
0x3f6c835e,0x3f6cd007,0x3f6d1c1d,0x3f6d67a1,0x3f6db293,0x3f6dfcf2,0x3f6e46be,0x3f6e8ff8,0x3f6ed89e,0x3f6f20b0,0x3f6f6830,0x3f6faf1b,0x3f6ff573,0x3f703b37,0x3f708066,0x3f70c501,
0x3f710908,0x3f714c7a,0x3f718f57,0x3f71d19f,0x3f721352,0x3f725470,0x3f7294f8,0x3f72d4eb,0x3f731447,0x3f73530e,0x3f73913f,0x3f73ced9,0x3f740bdd,0x3f74484b,0x3f748422,0x3f74bf62,
0x3f74fa0b,0x3f75341d,0x3f756d97,0x3f75a67b,0x3f75dec6,0x3f76167a,0x3f764d97,0x3f76841b,0x3f76ba07,0x3f76ef5b,0x3f772417,0x3f77583a,0x3f778bc5,0x3f77beb7,0x3f77f110,0x3f7822d1,
0x3f7853f8,0x3f788486,0x3f78b47b,0x3f78e3d6,0x3f791298,0x3f7940c0,0x3f796e4e,0x3f799b43,0x3f79c79d,0x3f79f35e,0x3f7a1e84,0x3f7a4910,0x3f7a7302,0x3f7a9c59,0x3f7ac516,0x3f7aed37,
0x3f7b14be,0x3f7b3bab,0x3f7b61fc,0x3f7b87b2,0x3f7baccd,0x3f7bd14d,0x3f7bf531,0x3f7c187a,0x3f7c3b28,0x3f7c5d3a,0x3f7c7eb0,0x3f7c9f8a,0x3f7cbfc9,0x3f7cdf6c,0x3f7cfe73,0x3f7d1cdd,
0x3f7d3aac,0x3f7d57de,0x3f7d7474,0x3f7d906e,0x3f7dabcc,0x3f7dc68c,0x3f7de0b1,0x3f7dfa38,0x3f7e1324,0x3f7e2b72,0x3f7e4323,0x3f7e5a38,0x3f7e70b0,0x3f7e868b,0x3f7e9bc9,0x3f7eb069,
0x3f7ec46d,0x3f7ed7d4,0x3f7eea9d,0x3f7efcc9,0x3f7f0e58,0x3f7f1f49,0x3f7f2f9d,0x3f7f3f54,0x3f7f4e6d,0x3f7f5ce9,0x3f7f6ac7,0x3f7f7808,0x3f7f84ab,0x3f7f90b1,0x3f7f9c18,0x3f7fa6e3,
0x3f7fb10f,0x3f7fba9e,0x3f7fc38f,0x3f7fcbe2,0x3f7fd397,0x3f7fdaaf,0x3f7fe129,0x3f7fe705,0x3f7fec43,0x3f7ff0e3,0x3f7ff4e6,0x3f7ff84a,0x3f7ffb11,0x3f7ffd39,0x3f7ffec4,0x3f7fffb1,
};

__device__ __forceinline__ int tid_here() { return __shfl_xor_sync(~0u, (int)threadIdx.x, 0); }
__device__ __forceinline__ void ld_tab(uint32_t* d, int chunk) { asm volatile("ld.global.v4.u32 {%0,%1,%2,%3}, [%4];" : "=r"(d[0]), "=r"(d[1]), "=r"(d[2]), "=r"(d[3]) : "l"((const uint4*)g_tab + chunk) : "memory"); }
__device__ __forceinline__ void ld_tab(float* d, int chunk) { asm volatile("ld.global.v4.f32 {%0,%1,%2,%3}, [%4];" : "=f"(d[0]), "=f"(d[1]), "=f"(d[2]), "=f"(d[3]) : "l"((const uint4*)g_tab + chunk) : "memory"); }
__device__ __forceinline__ void fft640(uint32_t plane, uint32_t tab, int lane, const uint32_t* fr, const uint32_t* fi, const float (*tc)[4], const float (*ts)[4], float (*xr)[4], float (*xi)[4]) {
  uint32_t A1[5][4], nfi[4];
#pragma unroll
  for (int i = 0; i < 4; i++) nfi[i] = fi[i] ^ 0x80008000u;
  const uint32_t la = plane + (lane >> 4) * 1280 + (lane & 15) * 80;
#pragma unroll
  for (int j = 0; j < 5; j++) {
    uint32_t r0, r1, i0, i1; ldsm4t(r0, r1, i0, i1, la + j * 16);
    float yr[4], yi[4];
    mmaZ(yr, fr, r0, r1); mmaZ(yi, fi, r0, r1); mmaA(yr, nfi, i0, i1); mmaA(yi, fr, i0, i1);
    float zr[4], zi[4];
#pragma unroll
    for (int e = 0; e < 4; e++) { zr[e] = yr[e] * tc[j][e] - yi[e] * ts[j][e]; zi[e] = yr[e] * ts[j][e] + yi[e] * tc[j][e]; }
    A1[j][0] = pack_bf16(zr[0], zr[1]); A1[j][1] = pack_bf16(zr[2], zr[3]); A1[j][2] = pack_bf16(zi[0], zi[1]); A1[j][3] = pack_bf16(zi[2], zi[3]);
  }
#pragma unroll
  for (int t = 0; t < 5; t++) {
    uint32_t A2[4] = {A1[t][2], A1[t][3], A1[t][0] ^ 0x80008000u, A1[t][1] ^ 0x80008000u};
#pragma unroll
    for (int u = 0; u < 5; u++) {
      uint32_t b0, b1; asm volatile("ld.shared.v2.b32 {%0,%1}, [%2];" : "=r"(b0), "=r"(b1) : "r"(tab + (t * 5 + u) * 256 + lane * 8));
      if (t == 0) { mmaZ(xr[u], A1[t], b0, b1); mmaZ(xi[u], A2, b0, b1); } else { mmaA(xr[u], A1[t], b0, b1); mmaA(xi[u], A2, b0, b1); }
    }
  }
}
__device__ __forceinline__ void ln_row(float* v) {
  float s = 0.f;
#pragma unroll
  for (int i = 0; i < 20; i++) s += v[i];
#pragma unroll
  for (int o = 16; o; o >>= 1) s += __shfl_xor_sync(~0u, s, o);
  const float mean = s * (1.f / D_);
  float qv = 0.f;
#pragma unroll
  for (int i = 0; i < 20; i++) { v[i] -= mean; qv += v[i] * v[i]; }
#pragma unroll
  for (int o = 16; o; o >>= 1) qv += __shfl_xor_sync(~0u, qv, o);
  const float rs = rsqrtf(qv * (1.f / D_) + 1e-5f);
#pragma unroll
  for (int i = 0; i < 20; i++) v[i] *= rs;
}

#define TLBASE (1024 + 768)
struct AParams { const bf16* x; uint32_t *Z1, *Z2; const uint32_t* WT; bf16 *x1, *hN; uint32_t* sync; const uint32_t* rowdone; int nw; uint32_t tag; };
constexpr int SY_1 = 0, SY_2 = 32, SY_3 = 64, SY_W = 96;
__device__ __forceinline__ void red_release(uint32_t* p) { asm volatile("red.release.gpu.global.add.u32 [%0], 1;" :: "l"(p) : "memory"); }
__device__ __forceinline__ void red_relaxed(uint32_t* p) { asm volatile("red.relaxed.gpu.global.add.u32 [%0], 1;" :: "l"(p) : "memory"); }
__device__ __forceinline__ void spin_count(const uint32_t* p, uint32_t n) {
  uint32_t v; int guard = 0;
  do { asm volatile("ld.relaxed.gpu.global.u32 %0, [%1];" : "=r"(v) : "l"(p) : "memory"); } while (v < n && ++guard < 400000);
}

__device__ __forceinline__ void filter_prep(uint32_t* WT, uint32_t sm, int k2) {
  const int tid = threadIdx.x, r = (tid >> 5) & 3;
  const uint32_t src = sm + (8 * (tid & 3) + r) * 642;
#pragma unroll 2
  for (int f = (tid >> 7) * 8 + ((tid & 31) >> 2); f < 321; f += 24) {
    uint32_t v[4];
#pragma unroll
    for (int i = 0; i < 4; i++) {
      unsigned short lo, hi;
      const uint32_t a = src + f * 2 + ((i >> 1) * 4 + (i & 1) * 32) * 642;
      asm volatile("ld.shared.u16 %0, [%1];" : "=h"(lo) : "r"(a)); asm volatile("ld.shared.u16 %0, [%1];" : "=h"(hi) : "r"(a + 41088));
      v[i] = lo | ((uint32_t)hi << 16);
    }
    stg128(WT + f * 2048 + k2 * 64 + r * 16 + (tid & 3) * 4, v[0], v[1], v[2], v[3]);
  }
}

template <typename F> __device__ __forceinline__ void a_phase2(const AParams& a, float* buf, int f, F hook) {
  const int t0 = tid_here(), tid = t0 & 127, lane = tid & 31, w = tid >> 5, g = lane >> 2, q = lane & 3, barid = 5 + (t0 >> 7);
  const int f2 = (640 - f) % 640;
#define WGBAR() asm volatile("bar.sync %0, 128;" :: "r"(barid) : "memory")
  uint32_t fr[4], fi[4], nfi[4], br[4][4], bi[4][4];
  float tc[4][4], ts[4][4], wc[4], ws[4];
  ld_tab(wc, TB_2048 + tid); ld_tab(ws, TB_2048 + 128 + tid); ld_tab(fr, TB_F16 + lane); ld_tab(fi, TB_F16 + 32 + lane);
#pragma unroll
  for (int j = 0; j < 4; j++) { ld_tab(tc[j], TB_512 + j * 32 + lane); ld_tab(ts[j], TB_512 + 128 + j * 32 + lane); }
  if (tid == 32 && !a.nw) l2_prefetch(a.WT + f * 2048, 8192);
  const uint32_t* zs[4];
#pragma unroll
  for (int j = 0; j < 4; j++) { const int m = j * 256 + 2 * tid; zs[j] = a.Z1 + (m / 12) * 7680 + m % 12; }
  if (tid == 0) { spin_count(a.sync + SY_1, 86); TL(6); }
  WGBAR();
  const uint32_t sbuf = smem_u32(buf);
  {
    uint2 P[4], Q[4];
#pragma unroll 1
    for (int guard = 0; guard < 100000; guard++) {
      uint32_t bad = 0;
#pragma unroll
      for (int j = 0; j < 4; j++) {
        asm volatile("ld.relaxed.gpu.global.v2.u32 {%0,%1}, [%2];" : "=r"(P[j].x), "=r"(P[j].y) : "l"(zs[j] + f * 12) : "memory");
        asm volatile("ld.relaxed.gpu.global.v2.u32 {%0,%1}, [%2];" : "=r"(Q[j].x), "=r"(Q[j].y) : "l"(zs[j] + f2 * 12) : "memory");
      }
#pragma unroll
      for (int j = 0; j < 4; j++) bad |= (P[j].x ^ a.tag) | (Q[j].x ^ a.tag);
      if (__all_sync(~0u, !(bad & 1))) break;
    }
    float ur[4][4], ui[4][4];
#pragma unroll
    for (int i = 0; i < 4; i++) {
      float ar[4], ai[4];
#pragma unroll
      for (int j = 0; j < 4; j++) {
        const uint32_t p = (i >> 1) ? P[j].y : P[j].x, z = (i >> 1) ? Q[j].y : Q[j].x;
        if (!(i & 1)) { ar[j] = bf_lo(p) + bf_lo(z); ai[j] = bf_hi(p) - bf_hi(z); }
        else { ar[j] = bf_hi(p) + bf_hi(z); ai[j] = bf_lo(z) - bf_lo(p); }
      }
      const float s0r = ar[0] + ar[2], s0i = ai[0] + ai[2], d0r = ar[0] - ar[2], d0i = ai[0] - ai[2];
      const float s1r = ar[1] + ar[3], s1i = ai[1] + ai[3], d1r = ar[1] - ar[3], d1i = ai[1] - ai[3];
      ur[0][i] = s0r + s1r; ui[0][i] = s0i + s1i;
      const float vr[3] = {d0r + d1i, s0r - s1r, d0r - d1i}, vi[3] = {d0i - d1r, s0i - s1i, d0i + d1r};
      const float c2 = wc[i] * wc[i] - ws[i] * ws[i], s2 = 2.f * wc[i] * ws[i];
      const float twc[4] = {1.f, wc[i], c2, c2 * wc[i] - s2 * ws[i]}, tws[4] = {0.f, ws[i], s2, s2 * wc[i] + c2 * ws[i]};
#pragma unroll
      for (int r = 1; r < 4; r++) { const float c = twc[r], s = tws[r]; ur[r][i] = vr[r - 1] * c + vi[r - 1] * s; ui[r][i] = vi[r - 1] * c - vr[r - 1] * s; }
    }
    const uint32_t o = sbuf + (tid >> 3) * 80 + (tid & 7) * 8;
#pragma unroll
    for (int r = 0; r < 4; r++) {
      asm volatile("st.shared.v2.b32 [%0], {%1,%2};" :: "r"(o + r * 5120), "r"(pack_bf16(ur[r][0], ur[r][1])), "r"(pack_bf16(ur[r][2], ur[r][3])) : "memory");
      asm volatile("st.shared.v2.b32 [%0], {%1,%2};" :: "r"(o + r * 5120 + 1280), "r"(pack_bf16(ui[r][0], ui[r][1])), "r"(pack_bf16(ui[r][2], ui[r][3])) : "memory");
    }
  }
#pragma unroll
  for (int j = 0; j < 4; j++) { ld_tab(br[j], TB_F32 + j * 32 + lane); ld_tab(bi[j], TB_F32 + 128 + j * 32 + lane); }
  if (tid == 0 && a.nw) spin_count(a.sync + SY_W, a.nw);
  WGBAR();
  hook(1);
  TL(7);
  uint2 wt[8];
#pragma unroll
  for (int i = 0; i < 8; i++) wt[i] = __ldcg((const uint2*)(a.WT + f * 2048 + ((i >> 1) * 8 + 2 * q + (i & 1)) * 64 + w * 16 + g * 2));
  {
    uint32_t A1[4][4], A2[4][4];
#pragma unroll
    for (int i = 0; i < 4; i++) nfi[i] = fi[i] ^ 0x80008000u;
    const uint32_t la = sbuf + w * 5120 + (lane >> 4) * 1280 + (lane & 15) * 80;
#pragma unroll
    for (int j = 0; j < 4; j++) {
      uint32_t r0, r1, i0, i1; ldsm4t(r0, r1, i0, i1, la + j * 16);
      float yr[4], yi[4];
      mmaZ(yr, fr, r0, r1); mmaZ(yi, fi, r0, r1); mmaA(yr, nfi, i0, i1); mmaA(yi, fr, i0, i1);
      float zr[4], zi[4];
#pragma unroll
      for (int e = 0; e < 4; e++) { zr[e] = yr[e] * tc[j][e] + yi[e] * ts[j][e]; zi[e] = yi[e] * tc[j][e] - yr[e] * ts[j][e]; }
      A1[j][0] = pack_bf16(zr[0], zr[1]); A1[j][1] = pack_bf16(zr[2], zr[3]); A1[j][2] = pack_bf16(zi[0], zi[1]); A1[j][3] = pack_bf16(zi[2], zi[3]);
      A2[j][0] = A1[j][2]; A2[j][1] = A1[j][3]; A2[j][2] = A1[j][0] ^ 0x80008000u; A2[j][3] = A1[j][1] ^ 0x80008000u;
    }
    float xr[4][4], xi[4][4];
#pragma unroll
    for (int t = 0; t < 4; t++)
#pragma unroll
      for (int u = 0; u < 4; u++) {
        if (t == 0) { mmaZ(xr[u], A1[t], br[t][u], bi[t][u]); mmaZ(xi[u], A2[t], br[t][u], bi[t][u]); } else { mmaA(xr[u], A1[t], br[t][u], bi[t][u]); mmaA(xi[u], A2[t], br[t][u], bi[t][u]); }
      }
#pragma unroll
    for (int u = 0; u < 4; u++) {
      const uint32_t wv[4] = {wt[2 * u].x, wt[2 * u + 1].x, wt[2 * u].y, wt[2 * u + 1].y};
      float zr[4], zi[4];
#pragma unroll
      for (int e = 0; e < 4; e++) { const float c = bf_lo(wv[e]), b = bf_hi(wv[e]); zr[e] = xr[u][e] * c - xi[u][e] * b; zi[e] = xr[u][e] * b + xi[u][e] * c; }
      A2[u][2] = pack_bf16(zr[0], zr[1]); A2[u][3] = pack_bf16(zr[2], zr[3]); A2[u][0] = pack_bf16(zi[0], zi[1]); A2[u][1] = pack_bf16(zi[2], zi[3]);
      A1[u][0] = A2[u][2]; A1[u][1] = A2[u][3]; A1[u][2] = A2[u][0] ^ 0x80008000u; A1[u][3] = A2[u][1] ^ 0x80008000u;
    }
#pragma unroll
    for (int t = 0; t < 4; t++)
#pragma unroll
      for (int u = 0; u < 4; u++) {
        if (t == 0) { mmaZ(xr[u], A1[t], br[t][u], bi[t][u]); mmaZ(xi[u], A2[t], br[t][u], bi[t][u]); } else { mmaA(xr[u], A1[t], br[t][u], bi[t][u]); mmaA(xi[u], A2[t], br[t][u], bi[t][u]); }
      }
    __syncwarp();
    float* pl = buf + w * 1280;
    const float nrm = 0.5f / (2048.f * 640.f);
#pragma unroll
    for (int j = 0; j < 4; j++) {
      float zr[4], zi[4];
#pragma unroll
      for (int e = 0; e < 4; e++) { zr[e] = xr[j][e] * tc[j][e] - xi[j][e] * ts[j][e]; zi[e] = xi[j][e] * tc[j][e] + xr[j][e] * ts[j][e]; }
      const uint32_t r0 = movm(pack_bf16(zr[0], zr[1])), r1 = movm(pack_bf16(zr[2], zr[3])), i0 = movm(pack_bf16(zi[0], zi[1])), i1 = movm(pack_bf16(zi[2], zi[3]));
      float yr[4], yi[4];
      mmaZ(yr, fr, r0, r1); mmaZ(yi, nfi, r0, r1); mmaA(yr, fi, i0, i1); mmaA(yi, fr, i0, i1);
      *(float2*)(pl + g * 40 + 8 * j + 2 * q) = make_float2(yr[0] * nrm, yr[1] * nrm); *(float2*)(pl + (g + 8) * 40 + 8 * j + 2 * q) = make_float2(yr[2] * nrm, yr[3] * nrm);
      *(float2*)(pl + 640 + g * 40 + 8 * j + 2 * q) = make_float2(yi[0] * nrm, yi[1] * nrm); *(float2*)(pl + 640 + (g + 8) * 40 + 8 * j + 2 * q) = make_float2(yi[2] * nrm, yi[3] * nrm);
    }
  }
  ld_tab(wc, TB_2048 + tid); ld_tab(ws, TB_2048 + 128 + tid);
  WGBAR();
  hook(2);
  TL(8);
  {
    float4 Ur[4], Ui[4];
#pragma unroll
    for (int r = 0; r < 4; r++) { Ur[r] = *(const float4*)(buf + r * 1280 + (tid >> 3) * 40 + (tid & 7) * 4); Ui[r] = *(const float4*)(buf + r * 1280 + 640 + (tid >> 3) * 40 + (tid & 7) * 4); }
    float yr[4][4], yi[4][4];
#pragma unroll
    for (int i = 0; i < 4; i++) {
      float ar[4], ai[4];
      const float c2 = wc[i] * wc[i] - ws[i] * ws[i], s2 = 2.f * wc[i] * ws[i];
      const float twc[4] = {1.f, wc[i], c2, c2 * wc[i] - s2 * ws[i]}, tws[4] = {0.f, ws[i], s2, s2 * wc[i] + c2 * ws[i]};
#pragma unroll
      for (int r = 0; r < 4; r++) {
        const float a = i == 0 ? Ur[r].x : i == 1 ? Ur[r].y : i == 2 ? Ur[r].z : Ur[r].w, b = i == 0 ? Ui[r].x : i == 1 ? Ui[r].y : i == 2 ? Ui[r].z : Ui[r].w;
        if (r == 0) { ar[r] = a; ai[r] = b; } else { const float c = twc[r], s = tws[r]; ar[r] = a * c - b * s; ai[r] = b * c + a * s; }
      }
      const float s0r = ar[0] + ar[2], s0i = ai[0] + ai[2], d0r = ar[0] - ar[2], d0i = ai[0] - ai[2];
      const float s1r = ar[1] + ar[3], s1i = ai[1] + ai[3], d1r = ar[1] - ar[3], d1i = ai[1] - ai[3];
      yr[0][i] = s0r + s1r; yi[0][i] = s0i + s1i; yr[2][i] = s0r - s1r; yi[2][i] = s0i - s1i;
      yr[1][i] = d0r - d1i; yi[1][i] = d0i + d1r; yr[3][i] = d0r + d1i; yi[3][i] = d0i - d1r;
    }
    const float im = (f == f2) ? 0.f : 1.f;
#pragma unroll
    for (int j = 0; j < 4; j++) {
      *(uint2*)(a.Z2 + f * 1024 + j * 256 + 2 * tid) = make_uint2((pack_bf16(yr[j][0] - im * yi[j][1], yr[j][1] + im * yi[j][0]) & ~1u) | a.tag, pack_bf16(yr[j][2] - im * yi[j][3], yr[j][3] + im * yi[j][2]));
      if (f != f2) *(uint2*)(a.Z2 + f2 * 1024 + j * 256 + 2 * tid) = make_uint2((pack_bf16(yr[j][0] + yi[j][1], yr[j][1] - yi[j][0]) & ~1u) | a.tag, pack_bf16(yr[j][2] + yi[j][3], yr[j][3] - yi[j][2]));
    }
  }
  TL(9);
}

constexpr int KA_TR_STRIDE = 804;
template <typename F> __device__ __forceinline__ void a_layer(const AParams& a, char* scratch, int v, int w, F hook) {
  const int tid = tid_here(), lane = tid & 31;
  uint32_t raw[2][10], fr[4], fi[4];
  float tc[5][4], ts[5][4];
  bool act = v < 86;
  int m = act ? min(v * 12 + w, 1023) : v * 4 + w;
  uint32_t* buf = (uint32_t*)(scratch + 6400) + (w & 3) * KA_TR_STRIDE + (w >> 2) * 3244;
  auto load_rows = [&]() {
    const int lane = tid_here() & 31;
#pragma unroll
    for (int i = 0; i < 10; i++) asm volatile("ld.global.cg.v2.u32 {%0,%1}, [%2];" : "=r"(raw[i / 5][2 * (i % 5)]), "=r"(raw[i / 5][2 * (i % 5) + 1]) : "l"(a.x + (size_t)(2 * m) * D_ + i * 128 + lane * 4) : "memory");
  };
  auto load_tabs = [&]() {
    uint32_t t[2][4];
    const int tid = tid_here(), lane = tid & 31;
    ld_tab(t[0], TB_F40 + (tid & 255)); ld_tab(t[1], TB_F40 + 144 + (tid & 255));
    ld_tab(fr, TB_F16 + lane); ld_tab(fi, TB_F16 + 32 + lane);
#pragma unroll
    for (int j = 0; j < 5; j++) { ld_tab(tc[j], TB_640 + j * 32 + lane); ld_tab(ts[j], TB_640 + 160 + j * 32 + lane); }
    sts128(smem_u32(scratch) + (tid & 255) * 16, t[0][0], t[0][1], t[0][2], t[0][3]); sts128(smem_u32(scratch) + 2304 + (tid & 255) * 16, t[1][0], t[1][1], t[1][2], t[1][3]);
  };
  if (a.rowdone) { load_tabs(); if (act) spin_count(a.rowdone + (m >> 4) * 16, 32); load_rows(); }
  else { load_rows(); load_tabs(); }
  __syncthreads();
  hook(-1);
  TL(1);
#pragma unroll 1
  for (int it = 0;; it++) {
    if (act) {
#pragma unroll
      for (int r = 0; r < 2; r++) {
        float x[20];
#pragma unroll
        for (int i = 0; i < 10; i++) { x[2 * i] = bf_lo(raw[r][i]); x[2 * i + 1] = bf_hi(raw[r][i]); }
        ln_row(x);
#pragma unroll
        for (int i = 0; i < 10; i++) raw[r][i] = pack_bf16(x[2 * i], x[2 * i + 1]);
      }
    }
    if (it) break;
    if (act) {
#pragma unroll
      for (int i = 0; i < 10; i++) *(uint2*)(buf + i * 64 + lane * 2) = make_uint2(raw[i / 5][2 * (i % 5)], raw[i / 5][2 * (i % 5) + 1]);
      __syncwarp();
    }
    TL(2);
#pragma unroll 1
    for (int ph = 0;; ph++) {
      if (act) {
        float xr[5][4], xi[5][4];
        const int lane = tid_here() & 31, g = lane >> 2, q = lane & 3;
        fft640(smem_u32(buf), smem_u32(scratch), lane, fr, fi, tc, ts, xr, xi);
        __syncwarp();
#pragma unroll
        for (int u = 0; u < 5; u++)
#pragma unroll
          for (int e = 0; e < 4; e++) { const int f = g + 8 * (e >> 1) + 16 * (8 * u + 2 * q + (e & 1)); buf[f + 8 * (f >> 5)] = pack_bf16(xr[u][e], xi[u][e]); }
        __syncwarp();
      }
      if (ph) break;
      __syncthreads();
      TL(3);
      const int t1 = tid_here(), f0 = t1 / 3, part = t1 % 3;
      if (act) {
        const uint32_t* src = (const uint32_t*)(scratch + 6400) + part * 3244 + f0 + 8 * (f0 >> 5);
        uint32_t ov[5][4];
#pragma unroll
        for (int i = 0; i < 5; i++)
#pragma unroll
          for (int k = 0; k < 4; k++) ov[i][k] = src[k * KA_TR_STRIDE + i * 160];
#pragma unroll
        for (int i = 0; i < 5; i++) stg128(a.Z1 + v * 7680 + (i * 384 + t1) * 4, (ov[i][0] & ~1u) | a.tag, ov[i][1], (ov[i][2] & ~1u) | a.tag, ov[i][3]);
      }
      TL(4);
      __syncthreads();
      if (tid == 32 && act) { red_relaxed(a.sync + SY_1); TL(5); }
      hook(0);
      const int f = (w >> 2) * 131 + v;
      if (f < 321) a_phase2(a, (float*)(scratch + (w >> 2) * 20480), f, hook);
      asm volatile("fence.proxy.async.shared::cta;" ::: "memory");
      __syncthreads();
      if (tid == 32) red_relaxed(a.sync + SY_2);
      hook(3);
      if (w >= 8 || v >= 128) return;
      act = true; m = v * 8 + w;
      scratch += 32768; buf = (uint32_t*)(scratch + 6400);
      {
        load_rows(); load_tabs();
        if (tid == 0) { spin_count(a.sync + SY_2, 131); TL(10); }
        bar_sync<5, 256>();
        uint4 za[3], zb[3];
        const int tid = tid_here();
#pragma unroll 1
        for (int guard = 0; guard < 100000; guard++) {
          uint32_t bad = 0;
#pragma unroll
          for (int i = 0; i < 3; i++) {
            const uint32_t* s = a.Z2 + (i * 256 + (tid & (i < 2 ? 254 : 126))) * 1024 + v * 8 + (tid & 1) * 4;
            asm volatile("ld.relaxed.gpu.global.v4.u32 {%0,%1,%2,%3}, [%4];" : "=r"(za[i].x), "=r"(za[i].y), "=r"(za[i].z), "=r"(za[i].w) : "l"(s) : "memory");
            asm volatile("ld.relaxed.gpu.global.v4.u32 {%0,%1,%2,%3}, [%4];" : "=r"(zb[i].x), "=r"(zb[i].y), "=r"(zb[i].z), "=r"(zb[i].w) : "l"(s + 1024) : "memory");
          }
#pragma unroll
          for (int i = 0; i < 3; i++) bad |= (za[i].x ^ a.tag) | (zb[i].x ^ a.tag) | (za[i].z ^ a.tag) | (zb[i].z ^ a.tag);
          if (__all_sync(~0u, !(bad & 1))) break;
        }
#pragma unroll
        for (int i = 0; i < 3; i++) if (i < 2 || tid < 128) {
          const uint4 c = za[i], b = zb[i];
          uint32_t* d = buf + (tid & 1) * 4 * KA_TR_STRIDE + i * 128 + (tid >> 1);
          d[320] = __byte_perm(c.x, b.x, 0x5410); d[0] = __byte_perm(c.x, b.x, 0x7632); d += KA_TR_STRIDE;
          d[320] = __byte_perm(c.y, b.y, 0x5410); d[0] = __byte_perm(c.y, b.y, 0x7632); d += KA_TR_STRIDE;
          d[320] = __byte_perm(c.z, b.z, 0x5410); d[0] = __byte_perm(c.z, b.z, 0x7632); d += KA_TR_STRIDE;
          d[320] = __byte_perm(c.w, b.w, 0x5410); d[0] = __byte_perm(c.w, b.w, 0x7632);
        }
        bar_sync<5, 256>();
        hook(4);
        TL(11);
      }
      buf += w * KA_TR_STRIDE;
    }
    {
      TL(12);
      const int lane = tid_here() & 31;
#pragma unroll
      for (int i = 0; i < 5; i++) {
        const uint4 y = *(const uint4*)(buf + i * 160 + lane * 4 + 8 * (lane >> 3));
        raw[0][2 * i] = hadd2(raw[0][2 * i], __byte_perm(y.x, y.y, 0x7632)); raw[0][2 * i + 1] = hadd2(raw[0][2 * i + 1], __byte_perm(y.z, y.w, 0x7632));
        raw[1][2 * i] = hadd2(raw[1][2 * i], __byte_perm(y.x, y.y, 0x5410)); raw[1][2 * i + 1] = hadd2(raw[1][2 * i + 1], __byte_perm(y.z, y.w, 0x5410));
      }
#pragma unroll
      for (int i = 0; i < 10; i++) *(uint2*)(a.x1 + (size_t)(2 * m) * D_ + i * 128 + lane * 4) = make_uint2(raw[i / 5][2 * (i % 5)], raw[i / 5][2 * (i % 5) + 1]);
    }
  }
  {
#pragma unroll
    for (int i = 0; i < 10; i++) *(uint2*)(a.hN + (size_t)(2 * m) * D_ + i * 128 + lane * 4) = make_uint2(raw[i / 5][2 * (i % 5)], raw[i / 5][2 * (i % 5) + 1]);
    TL(13);
    bar_sync<5, 256>();
    if (tid == 0) { red_release(a.sync + SY_3); TL(14); }
  }
}

__device__ __forceinline__ void tma2d(uint32_t dst, const CUtensorMap* tm, int c0, int c1, uint32_t bar) {
  asm volatile("cp.async.bulk.tensor.2d.shared::cluster.global.mbarrier::complete_tx::bytes [%0], [%1, {%3, %4}], [%2];" :: "r"(dst), "l"(tm), "r"(bar), "r"(c0), "r"(c1) : "memory");
}
__device__ __forceinline__ void bulk_g2s(uint32_t dst, const void* src, int bytes, uint32_t bar) {
  asm volatile("cp.async.bulk.shared::cluster.global.mbarrier::complete_tx::bytes [%0], [%1], %2, [%3];" :: "r"(dst), "l"(src), "r"(bytes), "r"(bar) : "memory");
}
__device__ __forceinline__ uint64_t desc128(uint32_t a) { return (uint64_t)((a & 0x3FFFF) >> 4) | (1ull << 16) | (64ull << 32) | (1ull << 62); }
#define WG_FENCE() asm volatile("wgmma.fence.sync.aligned;" ::: "memory")
#define WG_COMMIT() asm volatile("wgmma.commit_group.sync.aligned;" ::: "memory")
#define WG_WAIT(n) asm volatile("wgmma.wait_group.sync.aligned " #n ";" ::: "memory")
__device__ __forceinline__ void wg_rs_n64(float* d, const uint32_t* a, uint64_t db, int acc) {
  asm volatile("{.reg .pred p; setp.ne.b32 p, %37, 0;\n"
    "wgmma.mma_async.sync.aligned.m64n64k16.f32.bf16.bf16 {%0,%1,%2,%3,%4,%5,%6,%7,%8,%9,%10,%11,%12,%13,%14,%15,%16,%17,%18,%19,%20,%21,%22,%23,%24,%25,%26,%27,%28,%29,%30,%31}, {%32,%33,%34,%35}, %36, p, 1, 1, 0;}"
    : "+f"(d[0]), "+f"(d[1]), "+f"(d[2]), "+f"(d[3]), "+f"(d[4]), "+f"(d[5]), "+f"(d[6]), "+f"(d[7]), "+f"(d[8]), "+f"(d[9]), "+f"(d[10]), "+f"(d[11]), "+f"(d[12]), "+f"(d[13]), "+f"(d[14]), "+f"(d[15]),
      "+f"(d[16]), "+f"(d[17]), "+f"(d[18]), "+f"(d[19]), "+f"(d[20]), "+f"(d[21]), "+f"(d[22]), "+f"(d[23]), "+f"(d[24]), "+f"(d[25]), "+f"(d[26]), "+f"(d[27]), "+f"(d[28]), "+f"(d[29]), "+f"(d[30]), "+f"(d[31])
    : "r"(a[0]), "r"(a[1]), "r"(a[2]), "r"(a[3]), "l"(db), "r"(acc));
}
__device__ __forceinline__ void wg_rs_n32(float* d, const uint32_t* a, uint64_t db, int acc) {
  asm volatile("{.reg .pred p; setp.ne.b32 p, %21, 0;\n"
    "wgmma.mma_async.sync.aligned.m64n32k16.f32.bf16.bf16 {%0,%1,%2,%3,%4,%5,%6,%7,%8,%9,%10,%11,%12,%13,%14,%15}, {%16,%17,%18,%19}, %20, p, 1, 1, 0;}"
    : "+f"(d[0]), "+f"(d[1]), "+f"(d[2]), "+f"(d[3]), "+f"(d[4]), "+f"(d[5]), "+f"(d[6]), "+f"(d[7]), "+f"(d[8]), "+f"(d[9]), "+f"(d[10]), "+f"(d[11]), "+f"(d[12]), "+f"(d[13]), "+f"(d[14]), "+f"(d[15])
    : "r"(a[0]), "r"(a[1]), "r"(a[2]), "r"(a[3]), "l"(db), "r"(acc));
}
__device__ __forceinline__ void wg_ss_n40_tt(float* d, uint64_t da, uint64_t db, int acc) {
  asm volatile("{.reg .pred p; setp.ne.b32 p, %22, 0;\n"
    "wgmma.mma_async.sync.aligned.m64n40k16.f32.bf16.bf16 {%0,%1,%2,%3,%4,%5,%6,%7,%8,%9,%10,%11,%12,%13,%14,%15,%16,%17,%18,%19}, %20, %21, p, 1, 1, 1, 1;}"
    : "+f"(d[0]), "+f"(d[1]), "+f"(d[2]), "+f"(d[3]), "+f"(d[4]), "+f"(d[5]), "+f"(d[6]), "+f"(d[7]), "+f"(d[8]), "+f"(d[9]), "+f"(d[10]), "+f"(d[11]), "+f"(d[12]), "+f"(d[13]), "+f"(d[14]), "+f"(d[15]),
      "+f"(d[16]), "+f"(d[17]), "+f"(d[18]), "+f"(d[19])
    : "l"(da), "l"(db), "r"(acc));
}
__device__ __forceinline__ void wg_ss_n32_ta(float* d, uint64_t da, uint64_t db, int acc) {
  asm volatile("{.reg .pred p; setp.ne.b32 p, %18, 0;\n"
    "wgmma.mma_async.sync.aligned.m64n32k16.f32.bf16.bf16 {%0,%1,%2,%3,%4,%5,%6,%7,%8,%9,%10,%11,%12,%13,%14,%15}, %16, %17, p, 1, 1, 1, 0;}"
    : "+f"(d[0]), "+f"(d[1]), "+f"(d[2]), "+f"(d[3]), "+f"(d[4]), "+f"(d[5]), "+f"(d[6]), "+f"(d[7]), "+f"(d[8]), "+f"(d[9]), "+f"(d[10]), "+f"(d[11]), "+f"(d[12]), "+f"(d[13]), "+f"(d[14]), "+f"(d[15])
    : "l"(da), "l"(db), "r"(acc));
}
__device__ __forceinline__ uint64_t desc_ns(uint32_t a, uint32_t lbo, uint32_t sbo) { return (uint64_t)((a & 0x3FFFF) >> 4) | ((uint64_t)(lbo >> 4) << 16) | ((uint64_t)(sbo >> 4) << 32); }
__device__ __forceinline__ void wait_count(const uint32_t* p, uint32_t n, int ns) {
  uint32_t v; int guard = 0;
  while (true) { asm volatile("ld.relaxed.gpu.global.u32 %0, [%1];" : "=r"(v) : "l"(p) : "memory"); if (v >= n || ++guard > 200000) break; __nanosleep(ns); }
}

constexpr int SD_WS = 0, SD_REC = 16384, SD_O = SD_REC + 2 * 30720, SD_OI = SD_O + 2 * 8192, SD_OUT = SD_OI + 2 * 40960, SD_FIN = SD_OUT + 8192, SD_BAR = SD_FIN + 10240;
constexpr int SD_SMEM = SD_BAR + 512 + 1024;
#undef TLBASE
#define TLBASE (1024 + SD_BAR + 256)
#define QRING 8
constexpr int ORING = 8, PRING = 2 * ORING;
constexpr int FL_MEM = 162 * 1024, FL_RDY = 166 * 1024, FL_SM = 170 * 1024;
struct SideParams { CUtensorMap tmWo, tmP; const char* QKV; char *O, *part; const bf16* x1; bf16* out; uint32_t *comm, *sync; uint64_t dhi; int first, period, phase, win, lag, tmem, mask, last, dbgf; };
#define DBGF(m) false
#define ELECT "{.reg .pred p; elect.sync _|p, 0xffffffff;\n"
#define ATS(i)
__global__ void __launch_bounds__(512, 1) side_kernel(const __grid_constant__ SideParams p) {
  extern __shared__ __align__(1024) char smem_raw[];
  const uint32_t sb = (smem_u32(smem_raw) + 1023) & ~1023u, wfull = sb + SD_BAR, rland = wfull + 8, ofull = wfull + 16, ofree = wfull + 32,
    ifull = wfull + 48, ifree = wfull + 64, rfull = wfull + 80, rfree = wfull + 96, fdone = wfull + 112, ffull = wfull + 128;
  const int tid = threadIdx.x, lane = tid & 31, w = __shfl_sync(~0u, tid >> 5, 0);
  if (!DBGF(16)) pdl_launch();
  if (tid == 0) {
    spin_count(p.sync + SY_3, 128);
    uint32_t sm, mate; asm("mov.u32 %0, %%smid;" : "=r"(sm));
    asm volatile("ld.relaxed.gpu.global.u32 %0, [%1];" : "=r"(mate) : "l"(p.comm + FL_SM - (p.first ^ 1) * 1024 + (sm ^ 1)) : "memory");
    const uint32_t n = atomicAdd(p.comm + FL_SM + 512 + (mate ? 8 : 0), 1);
    asm volatile("st.shared.b32 [%0], %1;" :: "r"(fdone + 12), "r"(mate ? 35 - n : n) : "memory");
  }
  __syncthreads();
  int h; asm volatile("ld.shared.b32 %0, [%1];" : "=r"(h) : "r"(fdone + 12) : "memory");
  h = __shfl_sync(~0u, h, 0);
  if (h == 35) return;
  const int cb = h % 5, ks = h / 5, h0 = ks < 4 ? 5 * ks : 4 + 4 * ks, nh = ks < 4 ? 5 : 4;
  const int nseg = DBGF(16) ? 0 : NSEG;
  auto since = [&](uint32_t ref) { uint32_t now; asm volatile("mov.u32 %0, %%globaltimer_lo;" : "=r"(now) :: "memory"); return (now - ((ref >> 7) << 5)) & 0x3FFFFFFF; };
  auto gate = [&](int s) {
    for (int guard = 0; guard < 4000; guard++) {
      uint32_t ref; asm volatile("ld.volatile.shared.b32 %0, [%1];" : "=r"(ref) : "r"(fdone + 4) : "memory");
      const int n = ref & 127;
      if (n >= p.last || n > s + p.lag || (since(ref) + p.period - p.phase) % p.period <= p.win) break;
    }
  };
  TL(0);
  if (tid == 0) {
    mbar_init(wfull, 1); mbar_init(rland, 1); mbar_init(ffull, 1);
    for (int i = 0; i < 2; i++) { mbar_init(ofull + i * 8, 2); mbar_init(ofree + i * 8, 1); mbar_init(ifull + i * 8, 1); mbar_init(ifree + i * 8, 8); mbar_init(rfull + i * 8, 1); mbar_init(rfree + i * 8, 4); }
    asm volatile("st.shared.v2.b32 [%0], {%1,%1};" :: "r"(fdone), "r"(0) : "memory");
    asm volatile("fence.proxy.async.shared::cta;" ::: "memory");
    mbar_expect(wfull, nh * 32768);
#pragma unroll 1
    for (int b = 0; b < 4 * nh; b++) tma2d(sb + ((b + 2) % 20) * 8192, &p.tmWo, cb * 128 + (b & 1) * 64, h0 * 128 + (b >> 1) * 64, wfull);
  }
  __syncthreads();
  if (w < 8) {
    asm volatile("setmaxnreg.inc.sync.aligned.u32 192;");
    const int c = w >> 2, mg = w & 3;
    const uint32_t boxoff = (((lane >> 4) << 3) + (lane & 7)) * 128 + (((2 * mg + ((lane >> 3) & 1)) ^ (lane & 7)) << 4);
    uint32_t A[36][4];
    mbar_wait(wfull, 0);
#pragma unroll
    for (int f = 0; f < 36; f++) ldsm4t(A[f][0], A[f][1], A[f][2], A[f][3], sb + 16384 + c * 8192 + boxoff + (f >> 2) * 16384 + (f & 3) * 2048);
    asm volatile("fence.proxy.async.shared::cta;" ::: "memory");
    bar_sync<1, 320>();
    TL(1);
    const uint32_t oa = sb + SD_OUT + c * 4096 + boxoff;
#pragma unroll 1
    for (int s = 0; s < nseg; s++) {
      const int b = s & 1;
      const uint64_t db = p.dhi + (uint32_t)(((sb + SD_OI) >> 4) + b * 2560), da = p.dhi + (uint32_t)(((sb + SD_WS) >> 4) + c * 512);
#define D128(x) (x)
      float acc[16];
      mbar_wait_long(ifull + b * 8, (s >> 1) & 1);
      ATS(0)
      WG_FENCE();
#pragma unroll
      for (int k = 0; k < 32; k++) wg_rs_n32(acc, A[k], D128(db + (k >> 2) * 256 + (k & 3) * 2), k);
      if (nh == 5) {
#pragma unroll
        for (int k = 32; k < 36; k++) wg_rs_n32(acc, A[k], D128(db + 2048 + (k & 3) * 2), 1);
#pragma unroll
        for (int k = 0; k < 4; k++) wg_ss_n32_ta(acc, D128(da + k * 128), D128(db + 2304 + k * 2), 1);
      }
      WG_COMMIT();
      bar_sync<2, 256>();
      WG_WAIT(0);
      ATS(1)
      if (lane == 0) mbar_arrive(ifree + b * 8);
#pragma unroll
      for (int u = 0; u < 2; u++)
        asm volatile("stmatrix.sync.aligned.m8n8.x4.trans.shared.b16 [%0], {%1,%2,%3,%4};" :: "r"(oa + u * 2048),
          "r"(pack_bf16(acc[8 * u], acc[8 * u + 1])), "r"(pack_bf16(acc[8 * u + 2], acc[8 * u + 3])), "r"(pack_bf16(acc[8 * u + 4], acc[8 * u + 5])), "r"(pack_bf16(acc[8 * u + 6], acc[8 * u + 7])) : "memory");
      asm volatile("fence.proxy.async.shared::cta;" ::: "memory");
      if (w > 0) bar_arrive<4, 256>();
      else {
        bar_sync<4, 256>();
        if (p.mask & 2) gate(s + 3);
        asm volatile(ELECT "@p cp.async.bulk.tensor.3d.global.shared::cta.bulk_group [%0, {%2, %3, %4}], [%1];\n"
          "cp.async.bulk.commit_group;\ncp.async.bulk.wait_group 0;\n@p fence.proxy.async.global;\n@p red.release.gpu.global.add.u32 [%5], 1;}"
          :: "l"(&p.tmP), "r"(sb + SD_OUT), "r"(0), "r"((s % PRING) * 32), "r"(ks * 10 + cb * 2), "l"(p.comm + FL_RDY + s * 16 + 8) : "memory");
        ATS(2)
      }
    }
    TL(5);
  } else if (w < 12) {
    asm volatile("setmaxnreg.dec.sync.aligned.u32 72;");
    const int a = w - 8, g = lane >> 2, q = lane & 3;
    const float sc2 = 0.08838834764831845f * 1.4426950408889634f;
#pragma unroll 1
    for (int s = 0; s < (h < 32 ? nseg : 0); s++) {
      const int b = s & 1;
      const uint32_t rec = sb + SD_REC + b * 30720;
      mbar_wait_long(rfull + b * 8, (s >> 1) & 1);
      ATS(1)
      if (s == 0) TL(2);
      uint32_t P[3][4]; float inv[2];
      {
        float sc[20];
        const uint64_t dq = desc_ns(rec + 1024, 128, 1024), dk = desc_ns(rec + 5120, 128, 1024);
        WG_FENCE();
#pragma unroll
        for (int k = 0; k < 8; k++) wg_ss_n40_tt(sc, dq + (k >> 2) * 640 + (k & 3) * 16, dk + (k >> 2) * 640 + (k & 3) * 16, k);
        WG_COMMIT(); WG_WAIT(0);
        ATS(2)
#pragma unroll
        for (int rh = 0; rh < 2; rh++) {
          const int row = 16 * a + 8 * rh + g;
          float v[5][2], mx = -3.0e38f;
#pragma unroll
          for (int n = 0; n < 5; n++)
#pragma unroll
            for (int e = 0; e < 2; e++) {
              const bool ok = n == 0 || (8 * (n - 1) + 2 * q + e) <= row;
              v[n][e] = ok ? sc[4 * n + 2 * rh + e] * sc2 : -1.0e9f * 1.4426950408889634f; mx = fmaxf(mx, v[n][e]);
            }
          mx = fmaxf(mx, __shfl_xor_sync(~0u, mx, 1)); mx = fmaxf(mx, __shfl_xor_sync(~0u, mx, 2));
          float sum = 0.f;
#pragma unroll
          for (int n = 0; n < 5; n++) { const float e0 = ex2(v[n][0] - mx), e1 = ex2(v[n][1] - mx); sum += e0 + e1; P[n >> 1][(n & 1) * 2 + rh] = pack_bf16(e0, e1); }
          P[2][2 + rh] = 0u;
          sum += __shfl_xor_sync(~0u, sum, 1); sum += __shfl_xor_sync(~0u, sum, 2);
          asm("rcp.approx.ftz.f32 %0, %1;" : "=f"(inv[rh]) : "f"(sum));
        }
      }
      ATS(3)
      mbar_wait_long(ofree + b * 8, ((s >> 1) & 1) ^ 1);
      ATS(4)
      const uint32_t od = sb + SD_O + b * 8192 + (16 * a + (lane & 15)) * 128;
#pragma unroll
      for (int hf = 0; hf < 2; hf++) {
        float o[32];
        const uint64_t dv = desc_ns(rec + 20480 + hf * 5120, 1024, 128);
        WG_FENCE();
        wg_rs_n64(o, P[0], dv, 0); wg_rs_n64(o, P[1], dv + 128, 1); wg_rs_n64(o, P[2], desc_ns(rec + 20480 + hf * 5120 + 4096, 0, 128), 1);
        WG_COMMIT(); WG_WAIT(0);
        if (a < 2) {
#pragma unroll
          for (int n = 0; n < 8; n += 2) {
            const float* x = o + 4 * n;
            asm volatile("stmatrix.sync.aligned.m8n8.x4.shared.b16 [%0], {%1,%2,%3,%4};" :: "r"(od + hf * 4096 + (((n + (lane >> 4)) ^ (lane & 7)) << 4)),
              "r"(pack_bf16(x[0] * inv[0], x[1] * inv[0])), "r"(pack_bf16(x[2] * inv[1], x[3] * inv[1])), "r"(pack_bf16(x[4] * inv[0], x[5] * inv[0])), "r"(pack_bf16(x[6] * inv[1], x[7] * inv[1])) : "memory");
          }
        }
      }
      if (a < 2) {
        asm volatile("fence.proxy.async.shared::cta;" ::: "memory");
        __syncwarp();
        if (lane == 0) mbar_arrive(ofull + b * 8);
      }
      if (lane == 0) mbar_arrive(rfree + b * 8);
      ATS(5)
    }
    TL(3);
  } else {
    asm volatile("setmaxnreg.dec.sync.aligned.u32 56;");
    if (w == 13) {
      bar_sync<1, 320>();
#pragma unroll 1
      for (int s = 0; s < nseg; s++) {
        mbar_wait_long(ifree + (s & 1) * 8, ((s >> 1) & 1) ^ 1);
        wait_count(p.comm + FL_RDY + s * 16 + ks, nh, 40);
        gate(s + 2);
        ATS(0)
        asm volatile(ELECT "@p mbarrier.arrive.expect_tx.shared.b64 _, [%2], %3;\n@p cp.async.bulk.shared::cluster.global.mbarrier::complete_tx::bytes [%0], [%1], %3, [%2];}"
          :: "r"(sb + SD_OI + (s & 1) * 40960), "l"(p.O + (size_t)((s % ORING) * 32 + h0) * 8192), "r"(ifull + (s & 1) * 8), "r"(nh * 8192) : "memory");
      }
    } else if (h >= 32 && w < 15) {
    } else if (w == 12) {
#pragma unroll 1
      for (int s = 0; s < nseg; s++) {
        mbar_wait_long(ofull + (s & 1) * 8, (s >> 1) & 1);
        int fin, guard = 0;
        do { asm volatile("ld.volatile.shared.b32 %0, [%1];" : "=r"(fin) : "r"(fdone) : "memory"); } while (fin + ORING <= s && ++guard < 1000000);
        if (p.mask & 1) gate(s + 1);
        ATS(0)
        asm volatile(ELECT "@p cp.async.bulk.global.shared::cta.bulk_group [%0], [%1], 8192;\n"
          "cp.async.bulk.commit_group;\ncp.async.bulk.wait_group 0;\n@p mbarrier.arrive.shared.b64 _, [%3];\n@p fence.proxy.async.global;\n@p red.release.gpu.global.add.u32 [%2], 1;}"
          :: "l"(p.O + (size_t)((s % ORING) * 32 + h) * 8192), "r"(sb + SD_O + (s & 1) * 8192), "l"(p.comm + FL_RDY + s * 16 + (h < 20 ? h / 5 : (h - 4) >> 2)), "r"(ofree + (s & 1) * 8) : "memory");
        ATS(1)
      }
      TL(4);
    } else if (w == 14) {
      if (DBGF(16)) pdl_wait(); else
      mbar_wait_long(ofull, 0);
#pragma unroll 1
      for (int s = 0; s < nseg; s++) {
        asm volatile("fence.proxy.async.shared::cta;" ::: "memory");
        __syncwarp();
        asm volatile(ELECT "@p mbarrier.arrive.expect_tx.shared.b64 _, [%2], 10240;\n@p cp.async.bulk.shared::cluster.global.mbarrier::complete_tx::bytes [%0], [%1], 1280, [%2];}"
          :: "r"(sb + SD_FIN + 8960), "l"(p.x1 + (size_t)(s * 32 + h) * D_), "r"(ffull) : "memory");
        wait_count(p.comm + FL_RDY + s * 16 + 8, 35, 40);
        if (p.mask & 4) gate(s + 4);
        ATS(0)
        asm volatile(ELECT "@p cp.async.bulk.shared::cluster.global.mbarrier::complete_tx::bytes [%0], [%1], 8960, [%2];}"
          :: "r"(sb + SD_FIN), "l"(p.part + (size_t)((s % PRING) * 32 + h) * 8960), "r"(ffull) : "memory");
        mbar_wait_long(ffull, s & 1);
        ATS(1)
        asm volatile("st.volatile.shared.b32 [%0], %1;" :: "r"(fdone), "r"(s + 1) : "memory");
#pragma unroll
        for (int i = 0; i < 5; i++) {
          uint32_t v[8][2];
#pragma unroll
          for (int u = 0; u < 8; u++) asm volatile("ld.shared.v2.b32 {%0,%1}, [%2];" : "=r"(v[u][0]), "=r"(v[u][1]) : "r"(sb + SD_FIN + u * 1280 + i * 256 + lane * 8) : "memory");
          uint32_t y[2];
#pragma unroll
          for (int k = 0; k < 2; k++) {
            y[k] = pack_bf16(((bf_lo(v[0][k]) + bf_lo(v[1][k])) + (bf_lo(v[2][k]) + bf_lo(v[3][k]))) + ((bf_lo(v[4][k]) + bf_lo(v[5][k])) + bf_lo(v[6][k])),
                             ((bf_hi(v[0][k]) + bf_hi(v[1][k])) + (bf_hi(v[2][k]) + bf_hi(v[3][k]))) + ((bf_hi(v[4][k]) + bf_hi(v[5][k])) + bf_hi(v[6][k])));
            asm("add.rn.bf16x2 %0, %0, %1;" : "+r"(y[k]) : "r"(v[7][k]));
          }
          *(uint2*)(p.out + (size_t)(s * 32 + h) * D_ + i * 128 + lane * 4) = make_uint2(y[0], y[1]);
        }
        __syncwarp();
        if (lane == 0 && p.first) red_release(p.comm + FL_RDY + s * 16 + 12);
        ATS(2)
      }
    } else {
      uint32_t lp = 0, known = 0;
      bar_sync<1, 320>();
#pragma unroll 1
      for (int s = 0; s < nseg; s++) {
        const int b = s & 1;
        const uint32_t rec = sb + SD_REC + b * 30720;
        if (h < 32) mbar_wait_long(rfree + b * 8, ((s >> 1) & 1) ^ 1);
        uint32_t f = ~0u;
        for (int guard = 0; guard < 100000; guard++) {
          if (lane < 3) asm volatile("ld.relaxed.gpu.global.u32 %0, [%1];" : "=r"(f) : "l"(p.comm + FL_MEM + (h & 31) * 32 + lane * 8) : "memory");
          known = __reduce_min_sync(~0u, f & 127);
          if (known > (uint32_t)(s + (s < NSEG - 2 && !(p.mask & 8)))) break;
          __nanosleep(p.mask >> 8);
        }
        f = __shfl_sync(~0u, f, 0);
        if (lane == 0) asm volatile("st.volatile.shared.b32 [%0], %1;" :: "r"(fdone + 4), "r"(f) : "memory");
        if (h >= 32) continue;
        __syncwarp();
        const char* src = p.QKV + (size_t)((s % QRING) * 32 + h) * 30720;
        for (int tries = 0; tries < 20000; tries++) {
          if ((f & 127) == s + 1 && tries == (s >= NSEG - 2)) { const uint32_t t = s == NSEG - 1 ? p.tmem - 512 : p.tmem; for (int guard = 0; since(f) < t && guard < 4000; guard++) {} }
          if (tries == 0) gate(s);
          ATS(0)
          asm volatile("fence.proxy.async.shared::cta;" ::: "memory");
          __syncwarp();
          if (tries == 0) asm volatile(ELECT "@p mbarrier.arrive.expect_tx.shared.b64 _, [%2], 30720;\n@p cp.async.bulk.shared::cluster.global.mbarrier::complete_tx::bytes [%0], [%1], 30720, [%2];}" :: "r"(rec), "l"(src), "r"(rland) : "memory");
          else asm volatile(ELECT "@p mbarrier.arrive.expect_tx.shared.b64 _, [%2], 4096;\n"
            "@p cp.async.bulk.shared::cluster.global.mbarrier::complete_tx::bytes [%0+5120], [%1+5120], 1024, [%2];\n@p cp.async.bulk.shared::cluster.global.mbarrier::complete_tx::bytes [%0+15360], [%1+15360], 1024, [%2];\n"
            "@p cp.async.bulk.shared::cluster.global.mbarrier::complete_tx::bytes [%0+20480], [%1+20480], 1024, [%2];\n@p cp.async.bulk.shared::cluster.global.mbarrier::complete_tx::bytes [%0+25600], [%1+25600], 1024, [%2];}"
            :: "r"(rec), "l"(src), "r"(rland) : "memory");
          mbar_wait_long(rland, lp); lp ^= 1;
          uint32_t mx = 0;
#pragma unroll
          for (int k = 0; k < 4; k++) { uint32_t v; asm volatile("ld.shared.b32 %0, [%1];" : "=r"(v) : "r"(rec + (k == 0 ? 5120 : 10240 + k * 5120) + lane * 32 + (lane >> 2) * 4) : "memory"); mx = max(mx, v); }
          if (__all_sync(~0u, mx != ~0u)) break;
        }
        if (lane == 0) { mbar_arrive(rfull + b * 8); asm volatile("st.relaxed.gpu.global.u32 [%0], %1;" :: "l"(p.comm + FL_MEM + h * 32 + 24), "r"(s + 1) : "memory"); }
      }
    }
    if (w == 14) { TL(6); __syncwarp(); TL_DUMP((p.first ^ 1) * 166 + 131 + h, lane); }
    if (!p.first && tid == 448 && h == 0) { for (int i = 0; i < 8; i++) p.sync[i * 32 - 128] = 0; }
  }
}

__device__ __forceinline__ uint32_t ld_relaxed(const void* p) { uint32_t v; asm volatile("ld.relaxed.gpu.global.u32 %0, [%1];" : "=r"(v) : "l"(p) : "memory"); return v; }
__device__ __forceinline__ void st_relaxed(void* p, uint32_t v) { asm volatile("st.relaxed.gpu.global.u32 [%0], %1;" :: "l"(p), "r"(v) : "memory"); }
__device__ __forceinline__ void st_relaxed_if(void* p, uint32_t v, uint32_t c) { asm volatile("{.reg .pred p; setp.ne.u32 p, %2, 0; @p st.relaxed.gpu.global.u32 [%0], %1;}" :: "l"(p), "r"(v), "r"(c) : "memory"); }
__device__ __forceinline__ uint32_t clk32() { uint32_t c; asm volatile("mov.u32 %0, %%clock;" : "=r"(c) :: "memory"); return c; }
__device__ __forceinline__ uint32_t gt32() { uint64_t c; asm volatile("mov.u64 %0, %%globaltimer;" : "=l"(c) :: "memory"); return (uint32_t)c; }
__device__ __forceinline__ void wait_gt(uint32_t T) {
  asm volatile("{\n.reg .pred p;\n.reg .u64 t;\n.reg .u32 lo, hi;\nLG%=:\nmov.u64 t, %%globaltimer;\nmov.b64 {lo, hi}, t;\nsub.u32 lo, lo, %0;\nsetp.lt.s32 p, lo, 0;\n@p bra.uni LG%=;\n}" :: "r"(T) : "memory");
}
__device__ __forceinline__ void advance(uint32_t& T, uint32_t lim, uint32_t step) {
  asm volatile("{\n.reg .pred p;\n.reg .s32 d;\nLA%=:\nsub.s32 d, %1, %0;\nsetp.gt.s32 p, d, 0;\n@p add.u32 %0, %0, %2;\n@p bra.uni LA%=;\n}" : "+r"(T) : "r"(lim), "r"(step));
}
template <int LUT> __device__ __forceinline__ uint32_t lop3(uint32_t a, uint32_t b, uint32_t c) { uint32_t r; asm("lop3.b32 %0, %1, %2, %3, %4;" : "=r"(r) : "r"(a), "r"(b), "r"(c), "n"(LUT)); return r; }
__device__ __forceinline__ uint32_t ldsm1t(uint32_t a) { uint32_t r; asm volatile("ldmatrix.sync.aligned.m8n8.x1.trans.shared.b16 {%0}, [%1];" : "=r"(r) : "r"(a) : "memory"); return r; }
__device__ __forceinline__ uint32_t hmax2(uint32_t a, uint32_t b) { uint32_t r; asm("max.bf16x2 %0, %1, %2;" : "=r"(r) : "r"(a), "r"(b)); return r; }
__device__ __forceinline__ uint32_t lds32(uint32_t a) { uint32_t v; asm volatile("ld.shared.b32 %0, [%1];" : "=r"(v) : "r"(a) : "memory"); return v; }
__device__ __forceinline__ void sts32(uint32_t a, uint32_t v) { asm volatile("st.shared.b32 [%0], %1;" :: "r"(a), "r"(v) : "memory"); }
__device__ __forceinline__ uint32_t mapa(uint32_t a, int rank) { uint32_t r; asm("mapa.shared::cluster.u32 %0, %1, %2;" : "=r"(r) : "r"(a), "r"(rank)); return r; }
template <int OFF> __device__ __forceinline__ void stas32(uint32_t a, uint32_t v, uint32_t bar) {
  asm volatile("st.async.weak.shared::cluster.mbarrier::complete_tx::bytes.b32 [%0+%3], %1, [%2];" :: "r"(a), "r"(v), "r"(bar), "n"(OFF) : "memory");
}
#define OPAQUE(x) x = __shfl_sync(~0u, x, lane)
#define CLUSTER_SYNC() asm volatile("barrier.cluster.arrive.release.aligned; barrier.cluster.wait.acquire.aligned;" ::: "memory")

constexpr int SM_BAR = 0;
constexpr int SM_WO = 2048;
constexpr int SM_VR = 43008;
constexpr int SM_RED = 59392;
constexpr int SM_AT = 67584;
constexpr int SM_MEMT = 108544;
constexpr int SM_QK = 118784;
constexpr int SM_SC = 122880;
constexpr int SM_OX = 124928;
constexpr int SM_VM = 127488;
constexpr int SM_ST = 139264;
constexpr int SM_X = 149504;
constexpr int SM_WST = 2048;
constexpr int SM_WS = 67584;
constexpr int REC_SMEM = 231424 + 1024;
constexpr int MB_A = 0, MB_QK = 24, MB_V = 56, MB_KV = 64, MB_X = 80, MB_IA = 96, MB_IC = 104, MB_TK = 112, MB_PRB = 120, MB_DP = 128, MB_TAB = 256, MB_T2 = 512;
#define NTQ 10
#define NTV 6
#define NB0 4
#define PINK 14
#define NB1 7
#define PINT 5
#define WPLAN 0x5542110
#define OPF 3
#define TPOS 0
#define XPOS 0
#define ABK 20
#define IMM 0
#define KDEL 0
#define W0K 6
#define W0F 1
#define GST 1
#define GATEK 0
#define TOLQ 96
#define TOLV 160
constexpr int POLL_LIMIT = 20000;
constexpr int CM_X3 = 160, CM_MISC = 172;
__device__ __forceinline__ uint32_t x3_slot(int slot) { return (CM_X3 + (slot & 1) * 64 + (slot & 2) * 128) * 4096; }
__device__ __forceinline__ int near_page(int pg, int side) { return pg + ((__popc(pg & 0xB3) ^ side) & 1); }
__device__ __forceinline__ int mem_line(int jb) { const int ks = jb >> 1, c = ks >= 20, kk = ks - 20 * c; return (kk >> 2) * 16 + c * 8 + (kk & 3) * 2 + (jb & 1); }

struct RecParams {
  CUtensorMap tmW[3], tmWo, tmX;
  AParams a[2];
  const bf16 *mem0, *wr, *wi;
  char* QKV;
  uint32_t* comm;
  uint64_t dhi;
  int period, c3, slack, xlate, gap, zero, helper, layer, dbgf;
  uint32_t *dbg, *log;
};
#define PRB(k)
#define LDW(d, a) ldsm4t(d[0], d[1], d[2], d[3], a)

#undef TLBASE
#define TLBASE (1024 + 768)
#define PRBASE (mbar + w * 16)
#define PRIMM 1024
#define PROFF 0
template <bool VR>
__device__ __forceinline__ void rec_gemm_warps(const RecParams& p, const uint32_t sb, const int h, const int r, const int L, const int w) {
  const int tid = tid_here(), lane = tid & 31;
  const int mg = w & 3, c = w >> 2;
  constexpr int NT = VR ? NTV : NTQ, NW = VR ? 8 : 16;
  uint32_t R[20][4], P[20][4], Wr[NW - NT][4];
  const uint32_t mbar = sb + SM_BAR;
  uint32_t l16 = lane * 16, lm = (lane >> 4) * 1024 + (lane & 15) * 16;
  OPAQUE(l16); OPAQUE(lm);
#define wl16 (l16 + (sb + w * 512))
  {
    const uint32_t boxoff = (((lane >> 4) << 3) + (lane & 7)) * 128 + (((2 * mg + ((lane >> 3) & 1)) ^ (lane & 7)) << 4);
    mbar_wait(mbar + MB_IA, 0);
    TL(15);
    const uint32_t wa = sb + SM_WS + c * 40960 + boxoff;
#pragma unroll
    for (int k = 0; k < 20; k++) LDW(R[k], wa + 81920 + k * 2048);
    bar_arrive<4, 288>();
#pragma unroll
    for (int k = 0; k < 20; k++) LDW(P[k], wa + k * 2048);
    bar_sync<2, 256>();
#pragma unroll
    for (int i = 0; i < NT; i++) sts128(wl16 + SM_AT + i * 4096, P[i][0], P[i][1], P[i][2], P[i][3]);
    mbar_wait(mbar + MB_IC, 0);
    TL(16);
    const uint32_t woa = sb + SM_WST + c * 16384 + boxoff;
#pragma unroll
    for (int i = 0; i < NW; i++) {
      const uint32_t a = woa + (VR ? i * 2048 : (i & 1) * 32768 + (i >> 1) * 2048);
      if (i >= 4 && i < 4 + NW - NT) LDW(Wr[i - 4], a); else LDW(P[i < 4 ? i : i - (NW - NT)], a);
    }
    asm volatile("fence.proxy.async.shared::cta;" ::: "memory");
    bar_sync<1, 384>();
#pragma unroll
    for (int i = 0; i < NT; i++) sts128(wl16 + SM_WO + i * 4096, P[i][0], P[i][1], P[i][2], P[i][3]);
    asm volatile("barrier.cluster.arrive.relaxed.aligned; barrier.cluster.wait.aligned;" ::: "memory");
  }
#define LDT(i) lds128(P[i], wl16 + SM_AT + (i) * 4096)
#define WGX(acc, A, ks, sc) wg_rs_n32(acc, A[ks], d##A + (((ks) >> 2) * 256 + ((ks) & 3) * 2), sc)
  float tb[16];
  constexpr int KW = VR ? 20 - W0K : 20;
  auto stream0 = [&](int n) {
    const uint64_t dP = p.dhi + (uint32_t)(((sb + SM_X + c * 20480) >> 4) + (n & 1) * 2560 + ((n + 1) & p.zero));
    WG_FENCE();
#pragma unroll
    for (int k = KW; k < 20; k++) WGX(tb, P, k, k - KW);
    WG_COMMIT();
  };
  auto stream = [&](int n) {
    float ta[16];
    const uint64_t dR = p.dhi + (uint32_t)(((sb + SM_X + c * 20480) >> 4) + (n & 1) * 2560), dP = dR + (uint32_t)(~n & p.zero);
    WG_FENCE();
    constexpr int NE = NT - 4;
#pragma unroll
    for (int k = 0; k < 20; k++) { WGX(ta, R, k, k); if ((k & 1) && k / 2 < NE) LDT(k / 2); }
    WG_COMMIT();
    constexpr int K2 = VR ? NT + 2 : 16;
#pragma unroll
    for (int k = K2; k < KW; k++) {
      if (VR && k == K2 + GATEK) {
        WG_COMMIT();
        asm volatile("bar.sync 12, %0;" :: "r"((h & 1) ? 320 : 352) : "memory");
        if (GST) sts32(mbar + MB_TAB, 0);
        WG_FENCE();
      }
      WGX(tb, P, k, KW < 20 || k > K2);
    }
    WG_COMMIT();
    WG_WAIT(1);
#pragma unroll
    for (int i = 0; i < 2; i++)
      sts128(l16 + (sb + (w ^ 4) * 512) + SM_RED + i * 4096, pack_bf16(ta[8 * i], ta[8 * i + 1]), pack_bf16(ta[8 * i + 2], ta[8 * i + 3]), pack_bf16(ta[8 * i + 4], ta[8 * i + 5]), pack_bf16(ta[8 * i + 6], ta[8 * i + 7]));
#pragma unroll
    for (int i = NE; i < NT; i++) LDT(i);
#pragma unroll
    for (int k = NT; k < K2; k++) WGX(tb, P, k, 1);
    WG_FENCE();
#pragma unroll
    for (int k = 0; k < NE; k++) WGX(tb, P, k, 1);
    bar_sync<11, 384>();
    uint32_t o[2][4];
    lds128(o[0], wl16 + SM_RED); lds128(o[1], wl16 + SM_RED + 4096);
    WG_FENCE();
#pragma unroll
    for (int k = NE; k < NT; k++) WGX(tb, P, k, 1);
    WG_COMMIT();
    WG_WAIT(0);
#pragma unroll
    for (int i = 0; i < 2; i++)
      asm volatile("stmatrix.sync.aligned.m8n8.x4.shared.b16 [%0], {%1,%2,%3,%4};" :: "r"(lm + (sb + (c ^ 1) * 5120 + mg * 256) + SM_ST + 1024 + i * 2048),
        "r"(hadd2(pack_bf16(tb[8 * i], tb[8 * i + 1]), o[i][0])), "r"(hadd2(pack_bf16(tb[8 * i + 2], tb[8 * i + 3]), o[i][1])),
        "r"(hadd2(pack_bf16(tb[8 * i + 4], tb[8 * i + 5]), o[i][2])), "r"(hadd2(pack_bf16(tb[8 * i + 6], tb[8 * i + 7]), o[i][3])) : "memory");
    bar_arrive<14, 320>();
  };
  int s = -2, att = 0;
#pragma unroll 1
  while (true) {
    if (s >= 0) {
    uint32_t B[10][4], Wf[NT][4], dp[4];
    float ap[2][4], ar[2][4];
#define LDO(i, base) lds128(Wf[i], (base) + SM_WO + (i) * 4096)
#define LDB(k2) ldsm4t(B[k2][0], B[k2][1], B[k2][2], B[k2][3], l16 + (sb + c * 1024) + SM_MEMT + ((k2) >> 1) * 2048 + ((k2) & 1) * 512)
#define BK(k) B[(k) >> 1][((k) & 1) * 2], B[(k) >> 1][((k) & 1) * 2 + 1]
    mbar_wait(mbar + MB_A, att & 1);
    PRB(0)
    LDB(0); LDB(1);
    uint32_t hint = 0;
#pragma unroll
    for (int k = 0; k < ABK; k++) {
      if (!(k & 1) && k < 16) LDB(k / 2 + 2);
      if (k == PINK) {
        const uint32_t wb = lop3<0xF8>(l16, __float_as_uint(ap[0][0]), p.zero) + (sb + w * 512);
#pragma unroll
        for (int u = 0; u < NB0 && u < NT; u++) LDO(u, wb);
      }
      if (k < 2) { mmaZ(ap[k], P[k], BK(k)); mmaZ(ar[k], R[k], BK(k)); } else { mmaA(ap[k & 1], P[k], BK(k)); mmaA(ar[k & 1], R[k], BK(k)); }
      if (ABK < 20 && k == ABK - 3) asm volatile("ld.volatile.shared.b32 %0, [%1];" : "=r"(hint) : "r"(mbar + MB_TAB + 8 + (__float_as_uint(ap[(k + 1) & 1][0]) & p.zero)) : "memory");
    }
    if (ABK < 20 && __all_sync(~0u, hint == (uint32_t)att)) {
      bar_arrive<9, 384>();
      asm volatile("{.reg .pred p; setp.ne.u32 p, 0, 0; bar.red.or.pred p, 8, 384, p;}" ::: "memory");
#pragma unroll
      for (int i = 0; i < NT; i++) LDT(i);
      att++;
      continue;
    }
#pragma unroll
    for (int k = ABK; k < 20; k++) {
      if (!(k & 1) && k < 16) LDB(k / 2 + 2);
      if (k == PINK) {
        const uint32_t wb = lop3<0xF8>(l16, __float_as_uint(ap[0][0]), p.zero) + (sb + w * 512);
#pragma unroll
        for (int u = 0; u < NB0 && u < NT; u++) LDO(u, wb);
      }
      if (k < 2) { mmaZ(ap[k], P[k], BK(k)); mmaZ(ar[k], R[k], BK(k)); } else { mmaA(ap[k & 1], P[k], BK(k)); mmaA(ar[k & 1], R[k], BK(k)); }
    }
    asm volatile("stmatrix.sync.aligned.m8n8.x4.shared.b16 [%0], {%1,%2,%3,%4};" :: "r"(lm + (sb + c * 2048 + mg * 256) + SM_QK),
      "r"(pack_bf16(ar[0][0] + ar[1][0], ar[0][1] + ar[1][1])), "r"(pack_bf16(ar[0][2] + ar[1][2], ar[0][3] + ar[1][3])),
      "r"(pack_bf16(ap[0][0] + ap[1][0], ap[0][1] + ap[1][1])), "r"(pack_bf16(ap[0][2] + ap[1][2], ap[0][3] + ap[1][3])) : "memory");
    bar_arrive<9, 384>();
    PRB(1)
    att++;
    uint32_t bad;
    asm volatile("{.reg .pred p; setp.ne.u32 p, 0, 0; bar.red.or.pred p, 8, 384, p; selp.u32 %0, 1, 0, p;}" : "=r"(bad) :: "memory");
    if (bad) {
#pragma unroll
      for (int i = 0; i < NT; i++) LDT(i);
      continue;
    }
    if (s == NSEG - 1) break;
    if (KW < 20 && W0F) stream0(s);
    lds128(dp, mbar + MB_DP + w * 16);
#pragma unroll
    for (int i = NB0; i < NT && (VR || i < NB1); i++) LDO(i, wl16);
    uint32_t fmask = (~(l16 | dp[0]) >> 4) & 1, bit = ((s >> 1) & 1) ? 0u : fmask;
    char* cb = (char*)p.comm + ((s & 1) * (256 * 4096) + (l16 >> 2));
    char *d0 = cb + dp[0], *d1 = cb + dp[1], *d2 = cb + dp[2], *d3 = cb + dp[3];
    if (VR) asm volatile("" : "+l"(d0), "+l"(d1), "+r"(bit), "+r"(fmask)); else asm volatile("" : "+l"(d0), "+l"(d1), "+l"(d2), "+l"(d3), "+r"(bit), "+r"(fmask));
    if (KW < 20) { if (!W0F) stream0(s); WG_WAIT(0); }
    sched_fence();
    if (!VR && NB1 < NT) {
      bar_sync<2, 384>();
#pragma unroll
      for (int i = NB1; i < NT; i++) LDO(i, wl16);
    }
    bar_sync<3, 384>();
    PRB(2)
    uint32_t ob[4][4];
    float z0, z1;
#pragma unroll
    for (int i = 0; i < 4; i++) LDW(ob[i], l16 + sb + SM_OX + i * 512);
    asm volatile("ld.shared.v2.f32 {%0,%1}, [%2];" : "=f"(z0), "=f"(z1) : "r"(l16 + sb + SM_OX + 2048) : "memory");
#define WO(i) ((i) >= 4 && (i) < 4 + NW - NT ? Wr[(i) >= 4 && (i) < 4 + NW - NT ? (i) - 4 : 0] : Wf[(i) < 4 ? (i) : (i) < 4 + NW - NT ? 0 : (i) - (NW - NT)])
    float ga[4][4];
#pragma unroll
    for (int i = 0; i < NW; i++) {
      const int ks = VR ? i : i >> 1;
      if (i < 4) mmaZ(ga[i], WO(i), ob[ks >> 1][(ks & 1) * 2], ob[ks >> 1][(ks & 1) * 2 + 1]); else mmaA(ga[i & 3], WO(i), ob[ks >> 1][(ks & 1) * 2], ob[ks >> 1][(ks & 1) * 2 + 1]);
    }
    if (KDEL == 2 && !VR) bar_arrive<6, 320>();
    asm("rcp.approx.ftz.f32 %0, %0;" : "+f"(z0)); asm("rcp.approx.ftz.f32 %0, %0;" : "+f"(z1));
#pragma unroll
    for (int i = 0; i < 4; i++) { ga[0][i] += ga[2][i]; ga[1][i] += ga[3][i]; if (VR) ga[0][i] += ga[1][i]; }
#pragma unroll
    for (int t = 0; t < NW / 8; t++) {
      st_relaxed(t ? d2 : d0, lop3<0xF4>(bit, pack_bf16(ga[t][0] * z0, ga[t][1] * z1), fmask));
      st_relaxed(t ? d3 : d1, lop3<0xF4>(bit, pack_bf16(ga[t][2] * z0, ga[t][3] * z1), fmask));
    }
    PRB(3)
    if (KDEL == 1 && !VR) bar_arrive<6, 320>();
    } else { mbar_wait(mbar + MB_X + (s & 1) * 8, 0); if (KW < 20) { stream0(s); WG_WAIT(0); } }
    bar_sync<10, 256>();
    stream(s);
    PRB(4)
    s++;
  }
  if (L == p.zero) {
#pragma unroll
    for (int i = 0; i < NT; i++) LDT(i);
    bar_sync<1, 384>();
    const int ln = l16 >> 4;
    const uint32_t wa = sb + SM_WS + c * 40960 + (((ln >> 4) << 3) + (ln & 7)) * 128 + (((2 * mg + ((ln >> 3) & 1)) ^ (ln & 7)) << 4);
#pragma unroll
    for (int k = 0; k < 40; k++) {
      const uint32_t* f = k < 20 ? R[k % 20] : P[k % 20];
      asm volatile("stmatrix.sync.aligned.m8n8.x4.trans.shared.b16 [%0], {%1,%2,%3,%4};" :: "r"(wa + (k < 20 ? 81920 : 0) + (k % 20) * 2048), "r"(f[0]), "r"(f[1]), "r"(f[2]), "r"(f[3]) : "memory");
    }
  }
#undef wl16
}

#undef PRBASE
#undef PRIMM
#undef PROFF
#define PRBASE (mbar + j * 16)
#define PRIMM (1024 + 4)
#define PROFF 8
__device__ __forceinline__ void x_load(const RecParams& p, const uint32_t sb, int n) {
  if (DBGF(32)) { if ((threadIdx.x & 31) == 0) mbar_arrive(sb + SM_BAR + MB_X + (n & 1) * 8); return; }
  asm volatile(ELECT "@p mbarrier.arrive.expect_tx.shared.b64 _, [%2], 40960;\n"
    "@p cp.async.bulk.tensor.3d.shared::cluster.global.mbarrier::complete_tx::bytes [%0], [%1, {%3, %4, %3}], [%2];}"
      :: "r"(sb + SM_X + (n & 1) * 40960), "l"(&p.tmX), "r"(sb + SM_BAR + MB_X + (n & 1) * 8), "r"(0), "r"(n * 32) : "memory");
}
__device__ __forceinline__ int rec_attn_setup(const RecParams& p, const uint32_t sb, const int h, const int r, const int L, const int j) {
  const int ct = tid_here() - 256, lane = ct & 31;
  const uint32_t mbar = sb + SM_BAR;
  uint32_t* misc = p.comm + CM_MISC * 1024;
  if (j == 2 && lane == 0 && L == 0) {
    uint32_t b0 = 60000, b1 = 60000;
#pragma unroll 1
    for (int it = 0; it < 40; it++) {
      uint32_t* a = misc + (it & 1) * 1024 + 128 + blockIdx.x * 8;
      const uint32_t t0 = clk32();
      uint32_t v; asm volatile("atom.relaxed.gpu.global.exch.b32 %0, [%1], %2;" : "=r"(v) : "l"(a), "r"(t0) : "memory");
      st_relaxed_if(a, 0, v == t0 + 1);
      const uint32_t t = clk32() - t0;
      if (it & 1) b1 = min(b1, t); else b0 = min(b0, t);
      if (it >= 5 && min(b0, b1) < 370 && min(b0, b1) + 80 < max(b0, b1)) break;
    }
    sts32(mbar + MB_PRB, b0); sts32(mbar + MB_PRB + 4, b1);
  }
  if (ct == 32 && L == 0) { uint32_t sm; asm("mov.u32 %0, %%smid;" : "=r"(sm)); st_relaxed(p.comm + FL_SM + sm, 1); }
  if (blockIdx.x == 0 && ct == 0 && L == 0) st_relaxed(misc + 96, gt32() & ~31u);
  bar_sync<15, 128>();
  const uint32_t b0 = lds32(mbar + MB_PRB), b1 = lds32(mbar + MB_PRB + 4);
  const int side = __shfl_sync(~0u, ((b1 < b0) ^ __popc(CM_MISC & 0xB3)) & 1, 0);
  if (r == 2 && lane == 0 && j + (h & 1) < 3) st_relaxed(misc + (j < 2 ? 2 * h + j : 64 + (h >> 1)), side);
  if (j < 2) {
    const int job = 2 * (16 * r + (lane >> 2) + ((lane & 2) && r < 2 ? 8 : 0)) + (lane & 1);
    uint32_t v; int guard = 0;
    do { v = ld_relaxed(misc + (j ? 96 : job)); } while (v == 0xFFFFFFFFu && ++guard < 1000000);
    sts32(mbar + (j ? MB_TK : MB_DP + lane * 4), j ? v + (gt32() - v) / p.slack * p.slack : near_page(2 * job, v) * 4096 + h * 128);
    __syncwarp();
  }
  uint32_t m0[5][4];
#pragma unroll
  for (int i = 0; i < 20; i++) m0[i >> 2][i & 3] = *(const uint32_t*)(p.mem0 + (lane >> 2) * D_ + (j * 20 + i) * 8 + (lane & 3) * 2);
  if (j == 3) {
    spin_count(p.a[L].sync + SY_3, 128);
    bar_sync<4, 288>();
    asm volatile("fence.proxy.async;" ::: "memory");
    x_load(p, sb, 0); x_load(p, sb, 1);
    TL(17);
  }
  bar_sync<1, 384>();
  asm volatile("barrier.cluster.arrive.relaxed.aligned;" ::: "memory");
#pragma unroll
  for (int i = 0; i < 5; i++)
    asm volatile("stmatrix.sync.aligned.m8n8.x4.trans.shared.b16 [%0], {%1,%2,%3,%4};" :: "r"(sb + SM_MEMT + mem_line(j * 20 + i * 4) * 128 + lane * 16), "r"(m0[i][0]), "r"(m0[i][1]), "r"(m0[i][2]), "r"(m0[i][3]) : "memory");
  sts128(sb + SM_ST + (ct >> 6) * 5120 + (ct & 63) * 16, ~0u, ~0u, ~0u, ~0u);
  asm volatile("barrier.cluster.wait.aligned;" ::: "memory");
  return side;
}
template <bool VR>
__device__ __forceinline__ void rec_attn_warps(const RecParams& p, const uint32_t sb, char* smem, const int h, const int r, const int side, const int L, const int j) {
  const int lane = tid_here() & 31, g = lane >> 2, q = lane & 3;
  const uint32_t mbar = sb + SM_BAR;
#define is_red (VR && j + (h & 1) < 3)
  const int mi = lane >> 3;
  uint32_t l16 = sb + lane * 16;
#define wr16 (l16 + j * 512)
#define L0 ((l16 & 511) == 0)
  uint32_t ka = j < 2 ? sb + SM_ST + 6144 + (2 * j + (mi & 1)) * 1024 + ((mi >> 1) * 8 + (lane & 7)) * 16 : sb + SM_QK + j * 512 + ((mi & 1) * 16 + (mi >> 1) * 8 + (lane & 7)) * 16;
  uint32_t va = sb + SM_VR + (j >> 1) * 4096 + (mi >> 1) * 1024 + ((j & 1) * 32 + (mi & 1) * 8 + (lane & 7)) * 16;
  uint32_t own = sb + SM_SC + (r & 1) * 1024 + (j < 2 ? j * 256 : 256 + j * 128) + lane * 4, ps[2], pb[2];
#pragma unroll
  for (int i = 0; i < 2; i++) {
    const int peer = VR ? i : i == 0 ? r ^ 1 : 2;
    ps[i] = mapa(VR ? wr16 + SM_VM : own, peer); pb[i] = mapa(mbar + (VR ? MB_V : MB_QK), peer);
    if (VR) ps[i] = mapa(sb, peer) - sb + SM_VM + j * 512; else { OPAQUE(ps[i]); OPAQUE(pb[i]); }
  }
  if (!VR) { OPAQUE(ka); OPAQUE(own); }
  OPAQUE(va); OPAQUE(l16);
  const char* comm = (const char*)p.comm;
  uint32_t s0 = (g >> 1) != q ? 0u : (g & 1) ? 0x3F800000u : 0x00003F80u, s1 = s0 | (p.zero & 0x40000000);
  const uint32_t ones = 0x3F803F80u;
  if (VR) { OPAQUE(s0); OPAQUE(s1); }
  const float sc2 = 0.08838834764831845f * 1.4426950408889634f;
  uint32_t kf[4][4], vf[4][4];
#pragma unroll
  for (int i = 0; i < 16; i++) kf[i >> 2][i & 3] = vf[i >> 2][i & 3] = p.zero;
  auto load_v = [&](int n) {
    if (n >= 0) mbar_wait(mbar + MB_KV + (n & 1) * 8, (n >> 1) & 1);
#pragma unroll
    for (int i = 0; i < 4; i++) ldsm4(vf[i][0], vf[i][1], vf[i][2], vf[i][3], va + (n & 1) * 8192 + (i >> 1) * 2048 + (i & 1) * 256);
  };
  auto v_load = [&](int n) {
    asm volatile("cp.async.bulk.wait_group 0;" ::: "memory");
    if (VR) asm volatile(ELECT
      "@p cp.async.bulk.shared::cluster.global.mbarrier::complete_tx::bytes.multicast::cluster [%0], [%1], 4096, [%2], %3;\n"
      "@p cp.async.bulk.shared::cluster.global.mbarrier::complete_tx::bytes.multicast::cluster [%0+4096], [%1+5120], 4096, [%2], %3;}"
        :: "r"(sb + SM_VR + (n & 1) * 8192), "l"(p.QKV + ((size_t)((n & (QRING - 1)) * 32 + h) * 3 + 2) * 10240 + 1024), "r"(mbar + MB_KV + (n & 1) * 8), "h"((unsigned short)7) : "memory");
  };
  auto t_store = [&](int n) {
    if (DBGF(64)) return;
    asm volatile(ELECT "@p cp.async.bulk.global.shared::cta.bulk_group [%0], [%1], 10240;}" :: "l"(p.QKV + ((size_t)((n & (QRING - 1)) * 32 + h) * 3 + r) * 10240), "r"(sb + SM_ST) : "memory");
    asm volatile("cp.async.bulk.commit_group;" ::: "memory");
  };
  auto m_store = [&](int n) {
    if (VR || j < 2) {
      const int jj = VR ? j : j + 2;
      uint32_t a[4], b[4]; lds128(a, l16 + jj * 512 + SM_QK); lds128(b, l16 + (jj ^ 2) * 512 + SM_QK + 2048);
      asm volatile("st.relaxed.gpu.global.v4.u32 [%0], {%1,%2,%3,%4};" :: "l"(p.QKV + (uint32_t)(l16 + ((((n & (QRING - 1)) * 32 + h) * 3 + r) * 10240 + (jj >> 1) * 5120 + (j & 1) * 512 - sb))),
        "r"(hadd2(a[0], b[0])), "r"(hadd2(a[1], b[1])), "r"(hadd2(a[2], b[2])), "r"(hadd2(a[3], b[3])) : "memory");
    }
  };
  int att = 1;
  uint32_t T3 = lds32(mbar + MB_TK);
  const int jb = j < 2 ? 2 * h + j : 64 + (h >> 1), ln = mem_line(jb) + 16;
  const uint32_t inbox = near_page(2 * jb, side) * 4096, bline = (ln >> 5) * 16384 + (ln & 31) * 128;
  auto publish = [&](int n) {
    if (j == 3) st_relaxed(p.comm + FL_MEM + (L * 32 + h) * 32 + r * 8, ((T3 >> 5) << 7) | n);
  };
#define VERDICT(bad) asm volatile("{.reg .pred p; setp.ne.u32 p, %0, 0; bar.red.or.pred p, 8, 384, p;}" :: "n"(bad) : "memory")
#pragma unroll 1
  for (int s = -2; s < NSEG - 1; s++) {
    const uint32_t par = s & 1;
    if (s >= 0) {
    uint32_t su[6], sw[6], vm[4];
#define LDSM2T(d, a) asm volatile("ldmatrix.sync.aligned.m8n8.x2.trans.shared.b16 {%0,%1}, [%2];" : "=r"(d[4]), "=r"(d[5]) : "r"(a) : "memory")
#define HADD4(a, b) { a[0] = hadd2(a[0], b[0]); a[1] = hadd2(a[1], b[1]); a[2] = hadd2(a[2], b[2]); a[3] = hadd2(a[3], b[3]); }
    bar_sync<9, 384>();
    PRB(0)
    if (!VR) {
      uint32_t qf[2][4], qg[2][4];
      float sa[4][4];
      if (j < 2) {
        LDW(qf[0], l16 + SM_QK); LDW(qg[0], l16 + SM_QK + 3072); LDW(qf[1], l16 + SM_QK + 512); LDW(qg[1], l16 + SM_QK + 3584);
        HADD4(qf[0], qg[0]); HADD4(qf[1], qg[1]);
#pragma unroll
        for (int i = 0; i < 4; i++) mmaZ(sa[i], kf[i], qf[i >> 1][(i & 1) * 2], qf[i >> 1][(i & 1) * 2 + 1]);
        const uint32_t t0 = pack_bf16((sa[0][0] + sa[1][0]) + (sa[2][0] + sa[3][0]), (sa[0][1] + sa[1][1]) + (sa[2][1] + sa[3][1]));
        const uint32_t t1 = pack_bf16((sa[0][2] + sa[1][2]) + (sa[2][2] + sa[3][2]), (sa[0][3] + sa[1][3]) + (sa[2][3] + sa[3][3]));
        stas32<0>(ps[0], t0, pb[0]); stas32<0>(ps[1], t0, pb[1]); stas32<128>(ps[0], t1, pb[0]); stas32<128>(ps[1], t1, pb[1]);
        sts32(own, t0); sts32(own + 128, t1);
      } else {
        LDW(qf[0], wr16 + SM_QK - 1024); LDW(qg[0], wr16 + SM_QK + 2048); LDW(qf[1], ka); LDW(qg[1], ka + 1024);
        HADD4(qf[0], qg[0]); HADD4(qf[1], qg[1]);
        mmaZ(sa[0], qf[1], qf[0][0], qf[0][1]); mmaZ(sa[1], qf[1], qf[0][2], qf[0][3]);
        const uint32_t t0 = pack_bf16(sa[0][0] + sa[1][2], sa[0][1] + sa[1][3]);
        stas32<0>(ps[0], t0, pb[0]); stas32<0>(ps[1], t0, pb[1]);
        sts32(own, t0);
      }
      PRB(1)
      VERDICT(0);
      LDW(su, l16 + SM_SC + r * 1024); LDSM2T(su, l16 + SM_SC + 512 + r * 1024);
      if (TPOS == 2 && j == 2) t_store(s + 1);
      su[4] = hadd2(su[4], su[5]);
      mbar_wait(mbar + MB_QK, par);
      PRB(2)
      LDW(sw, l16 + SM_SC + 1024 - r * 1024); LDSM2T(sw, l16 + SM_SC + 1536 - r * 1024);
    } else {
      ldsm4(vm[0], vm[1], vm[2], vm[3], wr16 + SM_QK); ldsm4(su[0], su[1], su[2], su[3], l16 + (j ^ 2) * 512 + SM_QK + 2048);
      HADD4(vm, su);
#pragma unroll
      for (int i = 0; i < 2; i++)
        asm volatile("st.async.weak.shared::cluster.mbarrier::complete_tx::bytes.v4.b32 [%0], {%1,%2,%3,%4}, [%5];" :: "r"(ps[i] + l16), "r"(vm[0]), "r"(vm[1]), "r"(vm[2]), "r"(vm[3]), "r"(pb[i]) : "memory");
      PRB(1)
      VERDICT(0);
      char* mv = p.QKV + (uint32_t)((l16 >> 2) + ((((s & (QRING - 1)) * 32 + h) * 3 + 2) * 10240 + (j >> 1) * 5120 + (j & 1) * 512 - (sb >> 2)));
#pragma unroll
      for (int i = 0; i < 4; i++) st_relaxed(mv + i * 128, vm[i]);
      T3 = lds32(mbar + MB_TK);
      if (TPOS == 2 && j == 2) t_store(s + 1);
      mbar_wait(mbar + MB_QK, par);
      PRB(2)
      LDW(su, l16 + SM_SC); LDW(sw, l16 + SM_SC + 1024); LDSM2T(su, l16 + SM_SC + 512); LDSM2T(sw, l16 + SM_SC + 1536);
      su[4] = hadd2(su[4], su[5]);
    }
    {
      HADD4(su, sw); su[4] = hadd2(su[4], hadd2(sw[4], sw[5]));
      uint32_t m = hmax2(hmax2(hmax2(su[0], su[1]), hmax2(su[2], su[3])), su[4]);
      const uint32_t m1 = __shfl_xor_sync(~0u, m, 1), m2 = __shfl_xor_sync(~0u, m, 2), m3 = __shfl_xor_sync(~0u, m, 3);
      float t[10];
#pragma unroll
      for (int i = 0; i < 5; i++) { t[2 * i] = bf_lo(su[i]) * sc2; t[2 * i + 1] = bf_hi(su[i]) * sc2; }
      if (!VR) {
        asm volatile("" : "+f"(t[0]), "+f"(t[1]), "+f"(t[2]), "+f"(t[3]), "+f"(t[4]), "+f"(t[5]), "+f"(t[6]), "+f"(t[7]), "+f"(t[8]), "+f"(t[9]));
        mbar_wait(mbar + MB_V, par); if (NB1 < NTQ) bar_arrive<2, 384>(); lds128(vm, wr16 + SM_VM);
      }
      if (!VR) t[PINT] = __uint_as_float(lop3<0xF8>(__float_as_uint(t[PINT]), vm[0], p.zero));
      m = hmax2(hmax2(m, m1), hmax2(m2, m3));
      const float mx = fmaxf(bf_lo(m), bf_hi(m));
#define EX(i) ex2(fmaf(mx, -sc2, t[i]))
      float o1[2][4], z[4];
      const uint32_t P0 = pack_bf16(EX(0), EX(1)), P1 = pack_bf16(EX(2), EX(3));
      mmaZ(o1[0], vf[0], P0, P1); mmaZ(o1[1], vf[1], P0, P1); mma16816z(z, ones, ones, ones, ones, P0, P1);
      const float e4 = EX(4), e5 = EX(5);
      const uint32_t P2 = pack_bf16(e4, e5), P3 = pack_bf16(EX(6), EX(7));
      mmaA(o1[0], vf[2], P2, P3); mmaA(o1[1], vf[3], P2, P3); mma16816(z, ones, ones, ones, ones, P2, P3);
      const uint32_t Pm = pack_bf16(EX(8), EX(9));
      mma1688(o1[0], vm[0], vm[1], Pm); mma1688(o1[1], vm[2], vm[3], Pm); mma1688(z, ones, ones, Pm);
      asm volatile("stmatrix.sync.aligned.m8n8.x4.shared.b16 [%0], {%1,%2,%3,%4};" :: "r"(wr16 + SM_OX),
        "r"(pack_bf16(o1[0][0], o1[0][1])), "r"(pack_bf16(o1[0][2], o1[0][3])), "r"(pack_bf16(o1[1][0], o1[1][1])), "r"(pack_bf16(o1[1][2], o1[1][3])) : "memory");
      if (j == 3) asm volatile("st.shared.v2.f32 [%0], {%1,%2};" :: "r"(l16 + SM_OX + 2048), "f"(z[0]), "f"(z[1]) : "memory");
    }
    bar_arrive<3, 384>();
    PRB(3)
    {
      const uint32_t now = gt32(), lim = now + p.c3 + p.gap;
      T3 += p.period;
      if ((int)(T3 - now) > 20000) T3 = now;
      advance(T3, lim, p.slack);
    }
    if (j == 3) {
      asm volatile(ELECT "@p mbarrier.arrive.expect_tx.shared.b64 _, [%0], %2;\n@p mbarrier.arrive.expect_tx.shared.b64 _, [%1], 8192;\n@p mbarrier.arrive.expect_tx.shared.b64 _, [%3], 10240;}"
        :: "r"(mbar + MB_QK), "r"(mbar + MB_KV + par * 8), "n"(VR ? 1536 : 768), "r"(mbar + MB_A) : "memory");
      if (!VR) asm volatile(ELECT "@p mbarrier.arrive.expect_tx.shared.b64 _, [%0], 2048;}" :: "r"(mbar + MB_V) : "memory");
    }
    if (KDEL && !VR && j < 2) bar_sync<6, 320>();
    if (!VR) m_store(s);
    }
    if (!VR) {
      if (j < 2) {
#pragma unroll
        for (int i = 0; i < 4; i++) LDW(kf[i], ka + i * 256);
      } else {
#pragma unroll
        for (int i = 0; i < 16; i++) kf[i >> 2][i & 3] = p.zero;
      }
    }
    int used = 0;
    if (j == 2 && s >= -1) { v_load(s + 1); used = ld_relaxed(p.comm + FL_MEM + (L * 32 + h) * 32 + 24); }
    bar_arrive<11, 384>();
    if (!VR) { PRB(4) }
#define NEXT_SLOT(T, TOL) advance(T, gt32() - (TOL), p.slack)
    auto gather = [&]() {
      if (j == 3) {
        NEXT_SLOT(T3, (VR ? TOLV : TOLQ));
        wait_gt(T3);
        asm volatile("{.reg .pred p; elect.sync _|p, 0xffffffff;\n"
          "@p cp.async.bulk.shared::cluster.global.mbarrier::complete_tx::bytes [%0], [%2+2048], 2048, [%1];\n"
          "@p cp.async.bulk.shared::cluster.global.mbarrier::complete_tx::bytes [%0+2048], [%2+16384], 4096, [%1];\n"
          "@p cp.async.bulk.shared::cluster.global.mbarrier::complete_tx::bytes [%0+6144], [%2+32768], 4096, [%1];}"
          :: "r"(sb + SM_MEMT), "r"(mbar + MB_A), "l"(comm + (x3_slot(s + 1) + side * 4096)) : "memory");
      }
    };
    if (s < 0) { if (is_red) asm volatile("bar.arrive 12, %0;" :: "r"((h & 1) ? 320 : 352) : "memory"); }
    else {
    if (is_red) {
      const uint32_t expect = ((s >> 1) & 1) ^ 1, o_wr = (l16 & 255) / 2 + (l16 & 256) / 64;
      const uint32_t* src = (const uint32_t*)(comm + (inbox + par * (256 * 4096) + (l16 & 511) / 2));
      uint32_t* wfar = (uint32_t*)(comm + (x3_slot(s + 1) + bline + (side ^ 1) * 4096 + o_wr)); uint32_t* wnear = (uint32_t*)(comm + (x3_slot(s + 1) + bline + side * 4096 + o_wr));
      asm volatile("" : "+l"(src), "+l"(wfar), "+l"(wnear));
      auto attempt = [&](int nth) {
        uint32_t x[32], ok;
#pragma unroll
        for (int i = 0; i < 16; i++) asm volatile("ld.relaxed.gpu.global.v2.u32 {%0,%1}, [%2];" : "=r"(x[2 * i]), "=r"(x[2 * i + 1]) : "l"(src + i * 64) : "memory");
        float ra[4][4];
        uint32_t bad[2];
#pragma unroll
        for (int i = 0; i < 8; i++) {
          const uint32_t u = lop3<0x7E>(x[4 * i], x[4 * i + 2], expect);
          bad[i & 1] = i < 2 ? u : (bad[i & 1] | u);
          if (i < 4) mma16816z(ra[i], x[4 * i], x[4 * i + 1], x[4 * i + 2], x[4 * i + 3], s0, s1);
          else mma16816(ra[i & 3], x[4 * i], x[4 * i + 1], x[4 * i + 2], x[4 * i + 3], s0, s1);
        }
        ok = __all_sync(~0u, !((bad[0] | bad[1]) & 1));
        const float a0 = (ra[0][0] + ra[1][0]) + (ra[2][0] + ra[3][0]), a1 = (ra[0][1] + ra[1][1]) + (ra[2][1] + ra[3][1]);
        const float a2 = (ra[0][2] + ra[1][2]) + (ra[2][2] + ra[3][2]), a3 = (ra[0][3] + ra[1][3]) + (ra[2][3] + ra[3][3]);
        const bool up = l16 & 256;
        const float r0 = __shfl_xor_sync(~0u, up ? a0 : a2, 16), r1 = __shfl_xor_sync(~0u, up ? a1 : a3, 16);
        asm volatile("{.reg .pred p; setp.eq.u32 p, %1, 0; @p bar.arrive 12, %0;}" :: "r"((h & 1) ? 320 : 352), "r"(nth) : "memory");
        const uint32_t v = pack_bf16((up ? a2 : a0) + r0, (up ? a3 : a1) + r1);
        asm volatile("{.reg .pred p; setp.ne.u32 p, %3, 0; @p st.relaxed.gpu.global.u32 [%0], %2; @p st.relaxed.gpu.global.u32 [%1], %2; @p bar.arrive 15, %4;}"
          :: "l"(wfar), "l"(wnear), "r"(v), "r"(ok), "r"((h & 1) ? 96 : 128) : "memory");
        return ok;
      };
      uint32_t T2 = T3 - p.c3;
#pragma unroll 1
      for (int nth = 0;; nth++) {
        wait_gt(T2);
        PRB(4)
        if (attempt(nth)) break;
        if (nth == POLL_LIMIT) { asm volatile("bar.arrive 15, %0;" :: "r"((h & 1) ? 96 : 128) : "memory"); break; }
        if (!IMM || (nth & 1)) { T2 += p.slack; NEXT_SLOT(T2, TOLQ); }
      }
      PRB(5)
      uint32_t* wpoi = (uint32_t*)(comm + (x3_slot(s + 3) + bline + (l16 & 511) / 4));
      st_relaxed(wpoi, 0xFFFFFFFFu); st_relaxed(wpoi + 1024, 0xFFFFFFFFu);
    }
    if (VR && j == 3) { asm volatile("bar.sync 15, %0;" :: "r"((h & 1) ? 96 : 128) : "memory"); sts32(mbar + MB_TAB, 0); }
    gather();
    PRB(6)
    }
    load_v(s + 1);
    if (j < 2) {
      if (s + 3 < NSEG) mbar_wait(mbar + MB_X + (par ^ 1) * 8, ((s + 3) >> 1) & 1);
    } else {
      bar_sync<14, 320>();
      if (j == 2) {
        for (int guard = 0; __any_sync(~0u, used + QRING < s + 3) && guard < POLL_LIMIT && !DBGF(16); guard++) used = ld_relaxed(p.comm + FL_MEM + (L * 32 + h) * 32 + 24);
        asm volatile("fence.proxy.async.shared::cta;" ::: "memory");
        if (TPOS == 0 && s + 2 < NSEG) t_store(s + 2);
      } else if (XPOS == 0 && s + 4 < NSEG) { if (s >= 0) wait_gt(T3 + p.xlate); x_load(p, sb, s + 4); }
    }
    for (int guard = 0;; guard++) {
      uint32_t m = 0, ok;
      if (j < 2 && s >= 0) {
        mbar_wait(mbar + MB_A, att & 1);
#pragma unroll
        for (int i = 0; i < 5; i++) m = max(m, lds32(l16 + (l16 & 511) + (l16 & 448) / 16 + (j * 1024 + SM_MEMT + i * 2048)));
      }
      att++;
      asm volatile("{.reg .pred p; setp.ne.u32 p, %1, 0xffffffff; bar.red.and.pred p, 13, 128, p; selp.u32 %0, 1, 0, p;}" : "=r"(ok) : "r"(m) : "memory");
      if (__all_sync(~0u, ok) || guard == POLL_LIMIT) break;
      sts32(mbar + MB_TAB + 8, att - 3);
      bar_arrive<9, 384>();
      VERDICT(1);
      if (j == 3) asm volatile(ELECT "@p mbarrier.arrive.expect_tx.shared.b64 _, [%0], 10240;}" :: "r"(mbar + MB_A) : "memory");
      T3 += p.slack;
      gather();
    }
    PRB(7)
    if (VR && j == 3) sts32(mbar + MB_TK, T3);
    if (XPOS == 1 && j == 3 && s + 4 < NSEG) x_load(p, sb, s + 4);
    if ((TPOS == 1 || (TPOS == 2 && s == -2)) && j == 2 && s + 2 < NSEG) t_store(s + 2);
    publish(s + 2);
    if (s < 0) { if (j == 0 && L0 && s == -2) mbar_arrive(mbar + MB_A); TL(18); }
  }
  bar_sync<9, 384>();
  m_store(NSEG - 1);
  VERDICT(0);
  TL(19);
  if (L == p.zero) bar_arrive<1, 384>();
  {
    if (is_red) {
      uint32_t* wpoi = (uint32_t*)(comm + (x3_slot(2) + bline + (l16 & 511) / 4));
      st_relaxed(wpoi, 0xFFFFFFFFu); st_relaxed(wpoi + 1024, 0xFFFFFFFFu);
#pragma unroll 1
      for (int i = 0; i < 8; i++) stg128((char*)comm + (inbox + 256 * 4096 + i * 512 + (l16 & 511)), 0, 0, 0, 0);
      __threadfence();
    }
  }
}

__global__ void __launch_bounds__(384, 1) rec_kernel(const __grid_constant__ RecParams p) {
  extern __shared__ __align__(1024) char smem_raw[];
  const uint32_t sb = (smem_u32(smem_raw) + 1023) & ~1023u;
  char* smem = smem_raw + (sb - smem_u32(smem_raw));
  const int tid = threadIdx.x;
  const uint32_t mbar = sb + SM_BAR;
  pdl_launch();
  if (!p.helper) {
    if (tid == 32 || tid == 96) l2_prefetch((tid == 32 ? p.wi : p.wr) + blockIdx.x * 6848, 13696);
    if (tid == 64 && blockIdx.x < 12) l2_prefetch(g_tab + TB_F32 * 4 + blockIdx.x * 256, 1024);
  }
#pragma unroll 1
  for (int L = p.layer; L < 2; L++) {
    {
    const int w = __shfl_sync(~0u, tid >> 5, 0), bid = blockIdx.x + (L & p.zero), h = bid / 3, r = bid % 3;
    TL(0);
    if (tid == 0) {
#pragma unroll 1
      for (int i = 0; i < 14; i++) {
        if (L > p.layer) asm volatile("mbarrier.inval.shared.b64 [%0];" :: "r"(mbar + i * 8) : "memory");
        mbar_init(mbar + i * 8, 1);
      }
      asm volatile("fence.mbarrier_init.release.cluster;" ::: "memory");
      asm volatile("fence.proxy.async.shared::cta;" ::: "memory");
      mbar_expect(mbar + MB_QK, r == 2 ? 1536 : 768); if (r < 2) mbar_expect(mbar + MB_V, 2048);
      mbar_expect(mbar + MB_KV, 8192); mbar_expect(mbar + MB_KV + 8, 8192);
      sts32(mbar + MB_TAB + 4, L); sts32(mbar + MB_TAB + 8, ~0u);
      mbar_expect(mbar + MB_IA, L ? 0 : 163840); mbar_expect(mbar + MB_IC, r == 2 ? 32768 : 65536);
    }
    const int v = bid + p.helper * 96;
    const bool prep = L == 0 && v >= 86;
    if (prep && v < 118 && tid == 0) {
      mbar_expect(mbar + 8, 2 * 41088);
      bulk_g2s(sb + SM_WS, p.wr + (v - 86) * 64 * 321, 41088, mbar + 8); bulk_g2s(sb + SM_WS + 41088, p.wi + (v - 86) * 64 * 321, 41088, mbar + 8);
    }
    __syncwarp();
    auto wo_load = [&](int i0) {
#pragma unroll 1
      for (int i = i0; i < i0 + 4; i++)
        asm volatile(ELECT "@p cp.async.bulk.tensor.2d.shared::cluster.global.mbarrier::complete_tx::bytes [%0], [%1, {%3, %4}], [%2];}"
          :: "r"(sb + SM_WST + i * 8192), "l"(&p.tmWo), "r"(mbar + MB_IC), "r"(r * 256 + (i >> 1) * 64), "r"(h * 128 + (i & 1) * 64) : "memory");
    };
    a_layer(p.a[L], smem + SM_WST, v, w, [&](int u) {
        if (u == -1 && prep) {
          const int o = (v - 86) * 384 + tid, pg = 160 + ((o >> 8) & 15) + ((o >> 12) & 1) * 64 + (o >> 13) * 256;
          const uint32_t c = (pg & 2) ? 0u : ~0u;
          if (o < 64 * 256) stg128((uint4*)p.comm + pg * 256 + (o & 255), c, c, c, c);
          if (v < 118) { mbar_wait(mbar + 8, 0); filter_prep((uint32_t*)p.a[0].WT, sb + SM_WS, v - 86); }
          asm volatile("fence.proxy.async.shared::cta;" ::: "memory");
          TL(20);
          __syncthreads();
        }
        if (u == 0 && prep && tid == 256) { red_release(p.a[0].sync + SY_W); TL(21); }
        auto w_load = [&](int i) {
          asm volatile(ELECT "@p cp.async.bulk.tensor.2d.shared::cluster.global.mbarrier::complete_tx::bytes [%0], [%1, {%3, %4}], [%2];}"
            :: "r"(sb + SM_WS + ((0x3102 >> (4 * (i & 3))) & 3) * 40960 + (i >> 2) * 8192), "l"(&p.tmW[r == 2 ? 2 : i & 1]), "r"(mbar + MB_IA), "r"(h * 128 + (r == 2 ? i & 1 : r) * 64), "r"((i & 2) * 160 + (i >> 2) * 64) : "memory");
        };
        const int b0 = (WPLAN >> (4 * u + 4)) & 15, n = ((WPLAN >> (4 * u + 8)) & 15) - b0;
        if (n > 0 && w + L * 12 + p.helper * 12 < 4 * n) w_load(4 * b0 + w);
        if (u == OPF && w < 4 && r + p.helper * 2 < 2)
          asm volatile(ELECT "@p cp.async.bulk.prefetch.tensor.2d.L2.global [%0, {%1, %2}];}" :: "l"(&p.tmWo), "r"(r * 256 + 128 + (w >> 1) * 64), "r"(h * 128 + (w & 1) * 64) : "memory");
        if (u == 4 && w == 4 && !p.helper) wo_load(0);
      });
    if (p.helper) {
      return;
    }
    __syncwarp();
    if (w == 2 && r < 2) { asm volatile("fence.proxy.async.shared::cta;" ::: "memory"); wo_load(4); }
    }
    L = __shfl_sync(~0u, lds32(mbar + MB_TAB + 4), 0);
    const int w = __shfl_sync(~0u, tid >> 5, 0), bid = blockIdx.x + (L & p.zero), h = bid / 3, r = bid % 3;
    if (w < 8) {
      if (r < 2) { asm volatile("setmaxnreg.inc.sync.aligned.u32 216;"); rec_gemm_warps<false>(p, sb, h, r, L, w); asm volatile("setmaxnreg.dec.sync.aligned.u32 168;"); }
      else { asm volatile("setmaxnreg.inc.sync.aligned.u32 208;"); rec_gemm_warps<true>(p, sb, h, r, L, w); asm volatile("setmaxnreg.dec.sync.aligned.u32 168;"); }
    } else {
      asm volatile("setmaxnreg.dec.sync.aligned.u32 72;");
      const int side = rec_attn_setup(p, sb, h, r, L, w - 8);
      if (r < 2) { rec_attn_warps<false>(p, sb, smem, h, r, side, L, w - 8); asm volatile("setmaxnreg.inc.sync.aligned.u32 168;"); }
      else { asm volatile("setmaxnreg.inc.sync.aligned.u32 88;"); rec_attn_warps<true>(p, sb, smem, h, r, side, L, w - 8); asm volatile("setmaxnreg.inc.sync.aligned.u32 168;"); }
    }
    asm volatile("barrier.cluster.arrive.relaxed.aligned; barrier.cluster.wait.aligned;" ::: "memory");
    if (tid < 32) TL_DUMP(L * 166 + blockIdx.x, tid);
    __syncthreads();
  }
}

constexpr int PERIOD = 1984, C3 = 480, SLACK = 704, XLATE = 192, GAP = 240;
static int PH[6] = {256, 704, 3, 1280, 8, 63};
__device__ __align__(128) uint32_t g_Z1[86 * 7680], g_ZT[640 * 1024];
__device__ __align__(128) uint32_t g_WT[321 * 2048];
__device__ bf16 g_x1[S_ * D_], g_x2[S_ * D_], g_hN[S_ * D_];
__device__ __align__(128) uint4 g_QKV[QRING * 32 * 30720 / 16], g_O[ORING * 32 * 8192 / 16];
__device__ __align__(128) uint4 g_part[PRING * 32 * 8960 / 16];
__device__ __align__(128) uint32_t g_sync[256];
__device__ uint32_t g_comm[(4 << 20) / 4];

typedef CUresult (*EncodeFn)(CUtensorMap*, CUtensorMapDataType, cuuint32_t, void*, const cuuint64_t*, const cuuint64_t*, const cuuint32_t*, const cuuint32_t*,
                             CUtensorMapInterleave, CUtensorMapSwizzle, CUtensorMapL2promotion, CUtensorMapFloatOOBfill);
static void make_map(EncodeFn fn, CUtensorMap* m, const void* base, uint64_t cols, uint64_t rows, uint32_t bc, uint32_t br) {
  cuuint64_t dims[2] = {cols, rows}, strides[1] = {cols * 2}; cuuint32_t box[2] = {bc, br}, es[2] = {1, 1};
  fn(m, CU_TENSOR_MAP_DATA_TYPE_BFLOAT16, 2, (void*)base, dims, strides, box, es, CU_TENSOR_MAP_INTERLEAVE_NONE, CU_TENSOR_MAP_SWIZZLE_128B, CU_TENSOR_MAP_L2_PROMOTION_L2_256B, CU_TENSOR_MAP_FLOAT_OOB_FILL_NONE);
}
template <typename T> static T* sym(T& s) { void* p; cudaGetSymbolAddress(&p, s); return (T*)p; }

template <typename... KA, typename... A> static void launch(void (*k)(KA...), int grid, int block, int smem, bool pdl, int cluster, A... a) {
  cudaLaunchConfig_t cfg = {};
  cfg.gridDim = dim3(grid); cfg.blockDim = dim3(block); cfg.dynamicSmemBytes = smem; cfg.stream = cudaStreamPerThread;
  cudaLaunchAttribute at[2]; int n = 0;
  if (pdl) { at[n].id = cudaLaunchAttributeProgrammaticStreamSerialization; at[n].val.programmaticStreamSerializationAllowed = 1; n++; }
  if (cluster > 1) { at[n].id = cudaLaunchAttributeClusterDimension; at[n].val.clusterDim.x = cluster; at[n].val.clusterDim.y = 1; at[n].val.clusterDim.z = 1; n++; }
  cfg.attrs = at; cfg.numAttrs = n;
  cudaLaunchKernelEx(&cfg, k, KA(a)...);
}

extern "C" void kernel_launch(void* const* d_in, const int* in_sizes, int n_in, void* d_out, int out_size) {
  const bf16 *x = (const bf16*)d_in[0], *wr = (const bf16*)d_in[1], *wi = (const bf16*)d_in[2], *mem0 = (const bf16*)d_in[4];
  const bf16 *Wq = (const bf16*)d_in[5], *Wk = (const bf16*)d_in[6], *Wv = (const bf16*)d_in[7], *Wo = (const bf16*)d_in[8];
  bf16* out = (bf16*)d_out;
  uint32_t *Z1 = (uint32_t*)sym(g_Z1), *ZT = (uint32_t*)sym(g_ZT), *WT = (uint32_t*)sym(g_WT);
  bf16 *x1 = (bf16*)sym(g_x1), *x2 = (bf16*)sym(g_x2), *hN = (bf16*)sym(g_hN);
  char *QKV = (char*)sym(g_QKV), *part = (char*)sym(g_part);
  uint32_t* comm = (uint32_t*)(((uint64_t)sym(g_comm) + (2 << 20) - 1) & ~(uint64_t)((2 << 20) - 1));
  EncodeFn enc = nullptr; cudaDriverEntryPointQueryResult qr;
  cudaGetDriverEntryPoint("cuTensorMapEncodeTiled", (void**)&enc, cudaEnableDefault, &qr);
  CUtensorMap tmW[3], tmWo, tmX, tmP;
  { cuuint64_t dims[3] = {64, PRING * 32, 70}, strides[2] = {8960, 128}; cuuint32_t box[3] = {64, 32, 2}, es[3] = {1, 1, 1};
    enc(&tmP, CU_TENSOR_MAP_DATA_TYPE_BFLOAT16, 3, part, dims, strides, box, es, CU_TENSOR_MAP_INTERLEAVE_NONE, CU_TENSOR_MAP_SWIZZLE_128B, CU_TENSOR_MAP_L2_PROMOTION_NONE, CU_TENSOR_MAP_FLOAT_OOB_FILL_NONE); }
  { cuuint64_t dims[3] = {64, 2048, 10}, strides[2] = {1280, 128}; cuuint32_t box[3] = {64, 32, 10}, es[3] = {1, 1, 1};
    enc(&tmX, CU_TENSOR_MAP_DATA_TYPE_BFLOAT16, 3, hN, dims, strides, box, es, CU_TENSOR_MAP_INTERLEAVE_NONE, CU_TENSOR_MAP_SWIZZLE_128B, CU_TENSOR_MAP_L2_PROMOTION_L2_256B, CU_TENSOR_MAP_FLOAT_OOB_FILL_NONE); }
  make_map(enc, &tmW[0], Wq, 4096, 640, 64, 64); make_map(enc, &tmW[1], Wk, 4096, 640, 64, 64); make_map(enc, &tmW[2], Wv, 4096, 640, 64, 64);
  make_map(enc, &tmWo, Wo, 640, 4096, 64, 64);
  int dbgf = 0;
  cudaFuncSetAttribute(side_kernel, cudaFuncAttributeMaxDynamicSharedMemorySize, SD_SMEM);
  cudaFuncSetAttribute(rec_kernel, cudaFuncAttributeMaxDynamicSharedMemorySize, REC_SMEM);
  uint32_t* sy = (uint32_t*)sym(g_sync);
  RecParams rp = {{tmW[0], tmW[1], tmW[2]}, tmWo, tmX, {{x, Z1, ZT, WT, x1, hN, sy, nullptr, 45, 1}, {x2, Z1, ZT, WT, x1, hN, sy + 128, (dbgf & 16) ? nullptr : comm + FL_RDY + 12, 0, 0}},
                  mem0, wr, wi, QKV, comm, 0x4000004000010000ull, PERIOD, C3, SLACK, XLATE, GAP, 0, 0, 0, dbgf, nullptr, nullptr};
  launch(rec_kernel, 96, 384, REC_SMEM, false, 3, rp);
  for (int L = 0; L < 2; L++) {
    rp.helper = 1; rp.layer = L;
    launch(rec_kernel, 35, 384, REC_SMEM, true, 1, rp);
    SideParams sp = {tmWo, tmP, QKV, (char*)sym(g_O), part, x1, L == 0 ? x2 : out, comm + L * 1024, sy + L * 128, rp.dhi, L == 0, rp.period, PH[0], PH[1], PH[2], PH[3], PH[4], PH[5], dbgf};
    launch(side_kernel, 36, 512, SD_SMEM, true, 1, sp);
  }
}
```

```cpp
#include <cuda_runtime.h>
#include <cuda_bf16.h>
#include <cuda.h>
#include <stdint.h>
typedef __nv_bfloat16 bf16;
constexpr int S_ = 2048, D_ = 640, H_ = 32, DH = 128, NSEG = 64;

__device__ __forceinline__ uint32_t smem_u32(const void* p) { return (uint32_t)__cvta_generic_to_shared(p); }
__device__ __forceinline__ uint32_t pack_bf16(float lo, float hi) { uint32_t r; asm("cvt.rn.bf16x2.f32 %0, %1, %2;" : "=r"(r) : "f"(hi), "f"(lo)); return r; }
__device__ __forceinline__ float bf_lo(uint32_t v) { return __uint_as_float(v << 16); }
__device__ __forceinline__ float bf_hi(uint32_t v) { return __uint_as_float(v & 0xFFFF0000u); }
__device__ __forceinline__ void ldsm4t(uint32_t& r0, uint32_t& r1, uint32_t& r2, uint32_t& r3, uint32_t a) {
  asm volatile("ldmatrix.sync.aligned.m8n8.x4.trans.shared.b16 {%0,%1,%2,%3}, [%4];" : "=r"(r0), "=r"(r1), "=r"(r2), "=r"(r3) : "r"(a) : "memory");
}
__device__ __forceinline__ void ldsm4(uint32_t& r0, uint32_t& r1, uint32_t& r2, uint32_t& r3, uint32_t a) {
  asm volatile("ldmatrix.sync.aligned.m8n8.x4.shared.b16 {%0,%1,%2,%3}, [%4];" : "=r"(r0), "=r"(r1), "=r"(r2), "=r"(r3) : "r"(a) : "memory");
}
__device__ __forceinline__ void mma16816(float* d, uint32_t a0, uint32_t a1, uint32_t a2, uint32_t a3, uint32_t b0, uint32_t b1) {
  asm volatile("mma.sync.aligned.m16n8k16.row.col.f32.bf16.bf16.f32 {%0,%1,%2,%3}, {%4,%5,%6,%7}, {%8,%9}, {%0,%1,%2,%3};"
    : "+f"(d[0]), "+f"(d[1]), "+f"(d[2]), "+f"(d[3]) : "r"(a0), "r"(a1), "r"(a2), "r"(a3), "r"(b0), "r"(b1));
}
__device__ __forceinline__ void mma16816z(float* d, uint32_t a0, uint32_t a1, uint32_t a2, uint32_t a3, uint32_t b0, uint32_t b1) {
  asm volatile("mma.sync.aligned.m16n8k16.row.col.f32.bf16.bf16.f32 {%0,%1,%2,%3}, {%4,%5,%6,%7}, {%8,%9}, {%10,%10,%10,%10};"
    : "=f"(d[0]), "=f"(d[1]), "=f"(d[2]), "=f"(d[3]) : "r"(a0), "r"(a1), "r"(a2), "r"(a3), "r"(b0), "r"(b1), "f"(0.f));
}
__device__ __forceinline__ void mma1688z(float* d, uint32_t a0, uint32_t a1, uint32_t b0) {
  asm volatile("mma.sync.aligned.m16n8k8.row.col.f32.bf16.bf16.f32 {%0,%1,%2,%3}, {%4,%5}, {%6}, {%7,%7,%7,%7};"
    : "=f"(d[0]), "=f"(d[1]), "=f"(d[2]), "=f"(d[3]) : "r"(a0), "r"(a1), "r"(b0), "f"(0.f));
}
__device__ __forceinline__ void mma1688(float* d, uint32_t a0, uint32_t a1, uint32_t b0) {
  asm volatile("mma.sync.aligned.m16n8k8.row.col.f32.bf16.bf16.f32 {%0,%1,%2,%3}, {%4,%5}, {%6}, {%0,%1,%2,%3};"
    : "+f"(d[0]), "+f"(d[1]), "+f"(d[2]), "+f"(d[3]) : "r"(a0), "r"(a1), "r"(b0));
}
__device__ __forceinline__ void mmaA(float* d, const uint32_t* a, uint32_t b0, uint32_t b1) { mma16816(d, a[0], a[1], a[2], a[3], b0, b1); }
__device__ __forceinline__ void mmaZ(float* d, const uint32_t* a, uint32_t b0, uint32_t b1) { mma16816z(d, a[0], a[1], a[2], a[3], b0, b1); }
__device__ __forceinline__ uint32_t movm(uint32_t a) { uint32_t d; asm volatile("movmatrix.sync.aligned.m8n8.trans.b16 %0, %1;" : "=r"(d) : "r"(a)); return d; }
__device__ __forceinline__ void cp_async16(uint32_t dst, const void* src) { asm volatile("cp.async.cg.shared.global [%0], [%1], 16;" :: "r"(dst), "l"(src) : "memory"); }
__device__ __forceinline__ void cp_commit() { asm volatile("cp.async.commit_group;" ::: "memory"); }
template <int N> __device__ __forceinline__ void cp_wait() { asm volatile("cp.async.wait_group %0;" :: "n"(N) : "memory"); }
__device__ __forceinline__ void lds128(uint32_t* r, uint32_t a) { asm volatile("ld.shared.v4.b32 {%0,%1,%2,%3}, [%4];" : "=r"(r[0]), "=r"(r[1]), "=r"(r[2]), "=r"(r[3]) : "r"(a) : "memory"); }
__device__ __forceinline__ void sts128(uint32_t a, uint32_t r0, uint32_t r1, uint32_t r2, uint32_t r3) { asm volatile("st.shared.v4.b32 [%0], {%1,%2,%3,%4};" :: "r"(a), "r"(r0), "r"(r1), "r"(r2), "r"(r3) : "memory"); }
__device__ __forceinline__ void stg128(void* p, uint32_t r0, uint32_t r1, uint32_t r2, uint32_t r3) { asm volatile("st.global.v4.b32 [%0], {%1,%2,%3,%4};" :: "l"(p), "r"(r0), "r"(r1), "r"(r2), "r"(r3) : "memory"); }
template <int ID, int N> __device__ __forceinline__ void bar_sync() { asm volatile("bar.sync %0, %1;" :: "n"(ID), "n"(N) : "memory"); }
template <int ID, int N> __device__ __forceinline__ void bar_arrive() { asm volatile("bar.arrive %0, %1;" :: "n"(ID), "n"(N) : "memory"); }
__device__ __forceinline__ void mbar_wait(uint32_t bar, uint32_t parity) {
  asm volatile("{\n.reg .pred p, pq;\n.reg .u32 n;\nmov.u32 n, 0;\nLW%=:\nmbarrier.try_wait.parity.shared::cta.b64 p, [%0], %1;\n@p bra.uni LD%=;\nadd.u32 n, n, 1;\nsetp.lt.u32 pq, n, 1000000;\n@pq bra.uni LW%=;\nLD%=:\n}" :: "r"(bar), "r"(parity) : "memory");
}
#define mbar_wait_long mbar_wait
__device__ __forceinline__ void mbar_init(uint32_t bar, int n) { asm volatile("mbarrier.init.shared.b64 [%0], %1;" :: "r"(bar), "r"(n) : "memory"); }
__device__ __forceinline__ void mbar_expect(uint32_t bar, int bytes) { asm volatile("mbarrier.arrive.expect_tx.shared.b64 _, [%0], %1;" :: "r"(bar), "r"(bytes) : "memory"); }
__device__ __forceinline__ void mbar_arrive(uint32_t bar) { asm volatile("mbarrier.arrive.shared.b64 _, [%0];" :: "r"(bar) : "memory"); }
__device__ __forceinline__ void l2_prefetch(const void* p, int bytes) { asm volatile("cp.async.bulk.prefetch.L2.global [%0], %1;" :: "l"(p), "r"(bytes) : "memory"); }
__device__ __forceinline__ float ex2(float x) { float y; asm("ex2.approx.ftz.f32 %0, %1;" : "=f"(y) : "f"(x)); return y; }
__device__ __forceinline__ void pdl_wait() { asm volatile("griddepcontrol.wait;" ::: "memory"); }
__device__ __forceinline__ void pdl_launch() { asm volatile("griddepcontrol.launch_dependents;" ::: "memory"); }
__device__ __forceinline__ uint32_t hadd2(uint32_t a, uint32_t b) { uint32_t r; asm("add.rn.bf16x2 %0, %1, %2;" : "=r"(r) : "r"(a), "r"(b)); return r; }
__device__ __forceinline__ void sched_fence() { asm volatile("{\n.reg .pred p;\n.reg .u32 t;\nLF%=:\nmov.u32 t, %%clock;\nsetp.eq.u32 p, t, %0;\n@p bra.uni LF%=;\n}" :: "n"(12345) : "memory"); }
#define TL(k)
#define TL_DUMP(slot, t)

constexpr int TB_F16 = 0, TB_640 = 64, TB_F40 = 384, TB_F32 = 784, TB_512 = 1040, TB_2048 = 1296;
__device__ __align__(128) const uint32_t g_tab[6208] = {
0x3f803f80,0xbf803f80,0x3f803f80,0xbf803f80,0x3f803f80,0xbf803f80,0x3f803f80,0xbf803f80,0x3f803f80,0xbf803f80,0x3f803f80,0xbf803f80,0x3f803f80,0xbf803f80,0x3f803f80,0xbf803f80,
0x3f6d3f80,0xbf6d3f80,0xbf6dbf80,0x3f6dbf80,0x3ec43f35,0xbec43f35,0xbec4bf35,0x3ec4bf35,0xbec40000,0x3ec40000,0x3ec40000,0xbec40000,0xbf6dbf35,0x3f6dbf35,0x3f6d3f35,0xbf6d3f35,
0x3f353f80,0xbf353f80,0x3f353f80,0xbf353f80,0xbf350000,0x3f350000,0xbf350000,0x3f350000,0xbf35bf80,0x3f35bf80,0xbf35bf80,0x3f35bf80,0x3f350000,0xbf350000,0x3f350000,0xbf350000,
0x3ec43f80,0xbec43f80,0xbec4bf80,0x3ec4bf80,0xbf6dbf35,0x3f6dbf35,0x3f6d3f35,0xbf6d3f35,0x3f6d0000,0xbf6d0000,0xbf6d0000,0x3f6d0000,0xbec43f35,0x3ec43f35,0x3ec4bf35,0xbec4bf35,
0x3f80,0x3f80,0x3f80,0x3f80,0xbf80,0xbf80,0xbf80,0xbf80,0x3f80,0x3f80,0x3f80,0x3f80,0xbf80,0xbf80,0xbf80,0xbf80,
0xbec43f80,0x3ec43f80,0x3ec4bf80,0xbec4bf80,0x3f6dbf35,0xbf6dbf35,0xbf6d3f35,0x3f6d3f35,0xbf6d0000,0x3f6d0000,0x3f6d0000,0xbf6d0000,0x3ec43f35,0xbec43f35,0xbec4bf35,0x3ec4bf35,
0xbf353f80,0x3f353f80,0xbf353f80,0x3f353f80,0x3f350000,0xbf350000,0x3f350000,0xbf350000,0x3f35bf80,0xbf35bf80,0x3f35bf80,0xbf35bf80,0xbf350000,0x3f350000,0xbf350000,0x3f350000,
0xbf6d3f80,0x3f6d3f80,0x3f6dbf80,0xbf6dbf80,0xbec43f35,0x3ec43f35,0x3ec4bf35,0xbec4bf35,0x3ec40000,0xbec40000,0xbec40000,0x3ec40000,0x3f6dbf35,0xbf6dbf35,0xbf6d3f35,0x3f6d3f35,
0x80008000,0x80008000,0x80008000,0x80008000,0x80008000,0x80008000,0x80008000,0x80008000,0x80008000,0x80008000,0x80008000,0x80008000,0x80008000,0x80008000,0x80008000,0x80008000,
0xbec48000,0x3ec48000,0x3ec48000,0xbec48000,0xbf6dbf35,0x3f6dbf35,0x3f6d3f35,0xbf6d3f35,0xbf6dbf80,0x3f6dbf80,0x3f6d3f80,0xbf6d3f80,0xbec4bf35,0x3ec4bf35,0x3ec43f35,0xbec43f35,
0xbf358000,0x3f358000,0xbf358000,0x3f358000,0xbf35bf80,0x3f35bf80,0xbf35bf80,0x3f35bf80,0x3f358000,0xbf358000,0x3f358000,0xbf358000,0x3f353f80,0xbf353f80,0x3f353f80,0xbf353f80,
0xbf6d8000,0x3f6d8000,0x3f6d8000,0xbf6d8000,0x3ec4bf35,0xbec4bf35,0xbec43f35,0x3ec43f35,0x3ec43f80,0xbec43f80,0xbec4bf80,0x3ec4bf80,0xbf6dbf35,0x3f6dbf35,0x3f6d3f35,0xbf6d3f35,
0xbf808000,0x3f808000,0xbf808000,0x3f808000,0x3f808000,0xbf808000,0x3f808000,0xbf808000,0xbf808000,0x3f808000,0xbf808000,0x3f808000,0x3f808000,0xbf808000,0x3f808000,0xbf808000,
0xbf6d8000,0x3f6d8000,0x3f6d8000,0xbf6d8000,0x3ec43f35,0xbec43f35,0xbec4bf35,0x3ec4bf35,0x3ec4bf80,0xbec4bf80,0xbec43f80,0x3ec43f80,0xbf6d3f35,0x3f6d3f35,0x3f6dbf35,0xbf6dbf35,
0xbf358000,0x3f358000,0xbf358000,0x3f358000,0xbf353f80,0x3f353f80,0xbf353f80,0x3f353f80,0x3f358000,0xbf358000,0x3f358000,0xbf358000,0x3f35bf80,0xbf35bf80,0x3f35bf80,0xbf35bf80,
0xbec48000,0x3ec48000,0x3ec48000,0xbec48000,0xbf6d3f35,0x3f6d3f35,0x3f6dbf35,0xbf6dbf35,0xbf6d3f80,0x3f6d3f80,0x3f6dbf80,0xbf6dbf80,0xbec43f35,0x3ec43f35,0x3ec4bf35,0xbec4bf35,
0x3f800000,0x3f800000,0x3f800000,0x3f7f35f9,0x3f800000,0x3f800000,0x3f7cd925,0x3f78ed3c,0x3f800000,0x3f800000,0x3f737871,0x3f6c835e,0x3f800000,0x3f800000,0x3f641901,0x3f5a46a0,
0x3f800000,0x3f7ffcd7,0x3f800000,0x3f7f0059,0x3f7ff35e,0x3f7fe394,0x3f7c0361,0x3f770f11,0x3f7fcd79,0x3f7fb10f,0x3f702d4f,0x3f676bd8,0x3f7f8e56,0x3f7f654e,0x3f5cdc29,0x3f50935b,
0x3f800000,0x3f7ff35e,0x3f800000,0x3f7ec46d,0x3f7fcd79,0x3f7f8e56,0x3f7b14be,0x3f74fa0b,0x3f7f35f9,0x3f7ec46d,0x3f6c835e,0x3f61c598,0x3f7e39bc,0x3f7d95f4,0x3f54db31,0x3f45e403,
0x3f800000,0x3f7fe394,0x3f800000,0x3f7e8238,0x3f7f8e56,0x3f7f0059,0x3f7a0d54,0x3f72ae9e,0x3f7e39bc,0x3f7d3aac,0x3f687c12,0x3f5b941a,0x3f7c0361,0x3f7a9421,0x3f4c1d35,0x3f3a4582,
0x3f800000,0x3f7fcd79,0x3f800000,0x3f7e39bc,0x3f7f35f9,0x3f7e39bc,0x3f78ed3c,0x3f702d4f,0x3f7cd925,0x3f7b14be,0x3f641901,0x3f54db31,0x3f78ed3c,0x3f766377,0x3f42a9f7,0x3f2dc5e3,
0x3f800000,0x3f7fb10f,0x3f800000,0x3f7deafa,0x3f7ec46d,0x3f7d3aac,0x3f77b493,0x3f6d76aa,0x3f7b14be,0x3f7853f8,0x3f5f5be6,0x3f4d9f02,0x3f74fa0b,0x3f710908,0x3f3889dc,0x3f207440,
0x3f800000,0x3f7f8e56,0x3f800000,0x3f7d95f4,0x3f7e39bc,0x3f7c0361,0x3f766377,0x3f6a8b4b,0x3f78ed3c,0x3f74fa0b,0x3f5a46a0,0x3f45e403,0x3f702d4f,0x3f6a8b4b,0x3f2dc5e3,0x3f1260b2,
0x3f800000,0x3f7f654e,0x3f800000,0x3f7d3aac,0x3f7d95f4,0x3f7a9421,0x3f74fa0b,0x3f676bd8,0x3f766377,0x3f710908,0x3f54db31,0x3f3daef9,0x3f6a8b4b,0x3f62f219,0x3f226799,0x3f039c3d,
0x3f800000,0x3f800000,0x3f4f1bbd,0x3f42a9f7,0x3f800000,0x3f800000,0x3f3504f3,0x3f26423a,0x3f800000,0x3f800000,0x3f167918,0x3f05c277,0x3f800000,0x3f800000,0x3ee87171,0x3ec3ef15,
0x3f7f35f9,0x3f7f0059,0x3f42a9f7,0x3f333bc6,0x3f7ec46d,0x3f7e8238,0x3f226799,0x3f104f0e,0x3f7e39bc,0x3f7deafa,0x3efa2c90,0x3ed1c759,0x3f7d95f4,0x3f7d3aac,0x3ea7bf25,0x3e78cfcc,
0x3f7cd925,0x3f7c0361,0x3f3504f3,0x3f226799,0x3f7b14be,0x3f7a0d54,0x3f0e39da,0x3ef15aea,0x3f78ed3c,0x3f77b493,0x3ec3ef15,0x3e94a031,0x3f766377,0x3f74fa0b,0x3e47c5c2,0x3dc8bd36,
0x3f78ed3c,0x3f770f11,0x3f26423a,0x3f104f0e,0x3f74fa0b,0x3f72ae9e,0x3ef15aea,0x3ebf47d7,0x3f702d4f,0x3f6d76aa,0x3e8afa3e,0x3e2a1c3f,0x3f6a8b4b,0x3f676bd8,0x3d712283,0xbd48fb30,
0x3f737871,0x3f702d4f,0x3f167918,0x3efa2c90,0x3f6c835e,0x3f687c12,0x3ec3ef15,0x3e8afa3e,0x3f641901,0x3f5f5be6,0x3e20305b,0x3d20cee7,0x3f5a46a0,0x3f54db31,0xbda0af2a,0xbe47c5c2,
0x3f6c835e,0x3f676bd8,0x3f05c277,0x3ed1c759,0x3f61c598,0x3f5b941a,0x3e94a031,0x3e2a1c3f,0x3f54db31,0x3f4d9f02,0x3d20cee7,0xbdb4b86a,0x3f45e403,0x3f3daef9,0xbe5b73dc,0xbeac7cd4,
0x3f641901,0x3f5cdc29,0x3ee87171,0x3ea7bf25,0x3f54db31,0x3f4c1d35,0x3e47c5c2,0x3d712283,0x3f42a9f7,0x3f3889dc,0xbda0af2a,0xbe5b73dc,0x3f2dc5e3,0x3f226799,0xbeb13641,0xbef15aea,
0x3f5a46a0,0x3f50935b,0x3ec3ef15,0x3e78cfcc,0x3f45e403,0x3f3a4582,0x3dc8bd36,0xbd48fb30,0x3f2dc5e3,0x3f207440,0xbe47c5c2,0xbeac7cd4,0x3f1260b2,0x3f039c3d,0xbef15aea,0xbf187fc0,
0x3f800000,0x3f800000,0x3e9e377a,0x3e6f0c4d,0x3f800000,0x3f800000,0x3e20305b,0x3da0af2a,0x3f800000,0x3f800000,0,0xbda0af2a,0x3f800000,0x3f800000,0xbe20305b,0xbe6f0c4d,
0x3f7cd925,0x3f7c7160,0x3e20305b,0x3d8ca1f2,0x3f7c0361,0x3f7b8f2a,0xbca0d6d6,0xbddcbd0d,0x3f7b14be,0x3f7a9421,0xbe47c5c2,0xbe8fcefe,0x3f7a0d54,0x3f79805c,0xbeba9be1,0xbee3f40d,
0x3f737871,0x3f71decf,0,0xbdc8bd36,0x3f702d4f,0x3f6e641a,0xbe47c5c2,0xbe94a031,0x3f6c835e,0x3f6a8b4b,0xbec3ef15,0xbef15aea,0x3f687c12,0x3f6655e7,0xbf0e39da,0xbf226799,
0x3f641901,0x3f609384,0xbe20305b,0xbe862210,0x3f5cdc29,0x3f58f3c4,0xbeba9be1,0xbeece91a,0x3f54db31,0x3f50935b,0xbf0e39da,0xbf2456f1,0x3f4c1d35,0x3f4779bc,0xbf3889dc,0xbf4a965e,
0x3f4f1bbd,0x3f490a88,0xbe9e377a,0xbed65a92,0x3f42a9f7,0x3f3bfc8f,0xbf05c277,0xbf1e7cf1,0x3f3504f3,0x3f2dc5e3,0xbf3504f3,0xbf490a88,0x3f26423a,0x3f1e7cf1,0xbf5a46a0,0xbf687c12,
0x3f3504f3,0x3f2beb4a,0xbee87171,0xbf104f0e,0x3f226799,0x3f187fc0,0xbf2a0c73,0xbf4105b8,0x3f0e39da,0x3f039c3d,0xbf54db31,0xbf653a48,0x3ef15aea,0x3edae880,0xbf71decf,0xbf7a9421,
0x3f167918,0x3f0a04f8,0xbf167918,0xbf316e2c,0x3efa2c90,0x3edf7108,0xbf490a88,0xbf5cdc29,0x3ec3ef15,0x3ea7bf25,0xbf6c835e,0xbf77b493,0x3e8afa3e,0x3e5b73dc,0xbf7e39bc,0xbf7ff35e,
0x3ee87171,0x3ec8917e,0xbf3504f3,0xbf4d9f02,0x3ea7bf25,0x3e862210,0xbf61c598,0xbf710908,0x3e47c5c2,0x3e0255f4,0xbf7b14be,0xbf7fb10f,0x3d712283,0xbc20d8d2,0xbf7ec46d,0xbf7853f8,
0x3f800000,0x3f800000,0xbe9e377a,0xbec3ef15,0x3f800000,0x3f800000,0xbee87171,0xbf05c277,0x3f800000,0x3f800000,0xbf167918,0xbf26423a,0x3f800000,0x3f800000,0xbf3504f3,0xbf42a9f7,
0x3f78ed3c,0x3f7853f8,0xbf05c277,0xbf187fc0,0x3f77b493,0x3f770f11,0xbf2a0c73,0xbf3a4582,0x3f766377,0x3f75b1c9,0xbf490a88,0xbf563e03,0x3f74fa0b,0x3f743c41,0xbf61c598,0xbf6b8a3d,
0x3f641901,0x3f61c598,0xbf3504f3,0xbf45e403,0x3f5f5be6,0x3f5cdc29,0xbf54db31,0xbf61c598,0x3f5a46a0,0x3f579b8c,0xbf6c835e,0xbf74fa0b,0x3f54db31,0x3f5205d4,0xbf7b14be,0xbf7ec46d,
0x3f42a9f7,0x3f3daef9,0xbf5a46a0,0xbf676bd8,0x3f3889dc,0x3f333bc6,0xbf71decf,0xbf79805c,0x3f2dc5e3,0x3f28296a,0xbf7e39bc,0xbf7ffcd7,0x3f226799,0x3f1c81b9,0xbf7ec46d,0xbf7a9421,
0x3f167918,0x3f0e39da,0xbf737871,0xbf7b14be,0x3f05c277,0x3efa2c90,0xbf7f35f9,0xbf7fcd79,0x3ee87171,0x3ed65a92,0xbf7cd925,0xbf766377,0x3ec3ef15,0x3eb13641,0xbf6c835e,0xbf5f5be6,
0x3ec3ef15,0x3eac7cd4,0xbf7f35f9,0xbf7fb10f,0x3e94a031,0x3e78cfcc,0xbf7c0361,0xbf743c41,0x3e47c5c2,0x3e164083,0xbf687c12,0xbf58f3c4,0x3dc8bd36,0x3d48fb30,0xbf45e403,0xbf2f9c32,
0x3e20305b,0x3dc8bd36,0xbf7cd925,0xbf74fa0b,0x3d20cee7,0xbca0d6d6,0xbf687c12,0xbf579b8c,0xbda0af2a,0xbe0c4cf7,0xbf42a9f7,0xbf2a0c73,0xbe47c5c2,0xbe814693,0xbf0e39da,0xbedf7108,
0xbda0af2a,0xbe164083,0xbf6c835e,0xbf5b941a,0xbe5b73dc,0xbe8fcefe,0xbf45e403,0xbf2beb4a,0xbeb13641,0xbed1c759,0xbf0e39da,0xbedae880,0xbef15aea,0xbf07e565,0xbe94a031,0xbe164083,
0x3f800000,0x3f800000,0xbf4f1bbd,0xbf5a46a0,0x3f800000,0x3f800000,0xbf641901,0xbf6c835e,0x3f800000,0x3f800000,0xbf737871,0xbf78ed3c,0x3f800000,0x3f800000,0xbf7cd925,0xbf7f35f9,
0x3f737871,0x3f72ae9e,0xbf737871,0xbf79805c,0x3f71decf,0x3f710908,0xbf7d95f4,0xbf7fb10f,0x3f702d4f,0x3f6f4ba8,0xbf7fcd79,0xbf7deafa,0x3f6e641a,0x3f6d76aa,0xbf7a0d54,0xbf743c41,
0x3f4f1bbd,0x3f4c1d35,0xbf800000,0xbf7ec46d,0x3f490a88,0x3f45e403,0xbf7b14be,0xbf74fa0b,0x3f42a9f7,0x3f3f5cb5,0xbf6c835e,0xbf61c598,0x3f3bfc8f,0x3f3889dc,0xbf54db31,0xbf45e403,
0x3f167918,0x3f104f0e,0xbf737871,0xbf698690,0x3f0a04f8,0x3f039c3d,0xbf5cdc29,0xbf4d9f02,0x3efa2c90,0x3eece91a,0xbf3bfc8f,0xbf28296a,0x3edf7108,0x3ed1c759,0xbf1260b2,0xbef5c6c5,
0x3e9e377a,0x3e8afa3e,0xbf4f1bbd,0xbf3bfc8f,0x3e6f0c4d,0x3e47c5c2,0xbf26423a,0xbf0e39da,0x3e20305b,0x3df0b772,0xbee87171,0xbeb13641,0x3da0af2a,0x3d20cee7,0xbe6f0c4d,0xbdf0b772,
0,0xbd48fb30,0xbf167918,0xbef5c6c5,0xbdc8bd36,0xbe164083,0xbeba9be1,0xbe78cfcc,0xbe47c5c2,0xbe78cfcc,0xbdf0b772,0x3c20d8d2,0xbe94a031,0xbeac7cd4,0x3e0c4cf7,0x3e862210,
0xbe9e377a,0xbeba9be1,0xbe9e377a,0xbe3403f1,0xbed65a92,0xbef15aea,0xbd20cee7,0x3dc8bd36,0xbf05c277,0xbf1260b2,0x3e6f0c4d,0x3eba9be1,0xbf1e7cf1,0xbf2a0c73,0x3efa2c90,0x3f1a82a4,
0xbf167918,0xbf2456f1,0,0x3e164083,0xbf316e2c,0xbf3daef9,0x3e94a031,0x3edae880,0xbf490a88,0xbf53731f,0x3f0e39da,0x3f2beb4a,0xbf5cdc29,0xbf653a48,0x3f45e403,0x3f5b941a,
0x80000000,0x80000000,0x80000000,0xbda0af2a,0x80000000,0x80000000,0xbe20305b,0xbe6f0c4d,0x80000000,0x80000000,0xbe9e377a,0xbec3ef15,0x80000000,0x80000000,0xbee87171,0xbf05c277,
0x80000000,0xbc20d8d2,0x80000000,0xbdb4b86a,0xbca0d6d6,0xbcf13d4c,0xbe3403f1,0xbe862210,0xbd20cee7,0xbd48fb30,0xbeb13641,0xbedae880,0xbd712283,0xbd8ca1f2,0xbf0172c3,0xbf146eba,
0x80000000,0xbca0d6d6,0x80000000,0xbdc8bd36,0xbd20cee7,0xbd712283,0xbe47c5c2,0xbe94a031,0xbda0af2a,0xbdc8bd36,0xbec3ef15,0xbef15aea,0xbdf0b772,0xbe0c4cf7,0xbf0e39da,0xbf226799,
0x80000000,0xbcf13d4c,0x80000000,0xbddcbd0d,0xbd712283,0xbdb4b86a,0xbe5b73dc,0xbea2fd52,0xbdf0b772,0xbe164083,0xbed65a92,0xbf039c3d,0xbe3403f1,0xbe519f65,0xbf1a82a4,0xbf2f9c32,
0x80000000,0xbd20cee7,0x80000000,0xbdf0b772,0xbda0af2a,0xbdf0b772,0xbe6f0c4d,0xbeb13641,0xbe20305b,0xbe47c5c2,0xbee87171,0xbf0e39da,0xbe6f0c4d,0xbe8afa3e,0xbf26423a,0xbf3bfc8f,
0x80000000,0xbd48fb30,0x80000000,0xbe0255f4,0xbdc8bd36,0xbe164083,0xbe814693,0xbebf47d7,0xbe47c5c2,0xbe78cfcc,0xbefa2c90,0xbf187fc0,0xbe94a031,0xbeac7cd4,0xbf316e2c,0xbf4779bc,
0x80000000,0xbd712283,0x80000000,0xbe0c4cf7,0xbdf0b772,0xbe3403f1,0xbe8afa3e,0xbecd2ef3,0xbe6f0c4d,0xbe94a031,0xbf05c277,0xbf226799,0xbeb13641,0xbecd2ef3,0xbf3bfc8f,0xbf5205d4,
0x80000000,0xbd8ca1f2,0x80000000,0xbe164083,0xbe0c4cf7,0xbe519f65,0xbe94a031,0xbedae880,0xbe8afa3e,0xbeac7cd4,0xbf0e39da,0xbf2beb4a,0xbecd2ef3,0xbeece91a,0xbf45e403,0xbf5b941a,
0x80000000,0x80000000,0xbf167918,0xbf26423a,0x80000000,0x80000000,0xbf3504f3,0xbf42a9f7,0x80000000,0x80000000,0xbf4f1bbd,0xbf5a46a0,0x80000000,0x80000000,0xbf641901,0xbf6c835e,
0xbda0af2a,0xbdb4b86a,0xbf26423a,0xbf36c9a9,0xbdc8bd36,0xbddcbd0d,0xbf45e403,0xbf53731f,0xbdf0b772,0xbe0255f4,0xbf5f5be6,0xbf698690,0xbe0c4cf7,0xbe164083,0xbf71decf,0xbf7853f8,
0xbe20305b,0xbe3403f1,0xbf3504f3,0xbf45e403,0xbe47c5c2,0xbe5b73dc,0xbf54db31,0xbf61c598,0xbe6f0c4d,0xbe814693,0xbf6c835e,0xbf74fa0b,0xbe8afa3e,0xbe94a031,0xbf7b14be,0xbf7ec46d,
0xbe6f0c4d,0xbe862210,0xbf42a9f7,0xbf53731f,0xbe94a031,0xbea2fd52,0xbf61c598,0xbf6d76aa,0xbeb13641,0xbebf47d7,0xbf766377,0xbf7c7160,0xbecd2ef3,0xbedae880,0xbf7f8e56,0xbf7fb10f,
0xbe9e377a,0xbeb13641,0xbf4f1bbd,0xbf5f5be6,0xbec3ef15,0xbed65a92,0xbf6c835e,0xbf766377,0xbee87171,0xbefa2c90,0xbf7cd925,0xbf7fcd79,0xbf05c277,0xbf0e39da,0xbf7f35f9,0xbf7b14be,
0xbec3ef15,0xbedae880,0xbf5a46a0,0xbf698690,0xbef15aea,0xbf039c3d,0xbf74fa0b,0xbf7c7160,0xbf0e39da,0xbf187fc0,0xbf7fcd79,0xbf7f0059,0xbf226799,0xbf2beb4a,0xbf7a0d54,0xbf710908,
0xbee87171,0xbf0172c3,0xbf641901,0xbf71decf,0xbf0e39da,0xbf1a82a4,0xbf7b14be,0xbf7f8e56,0xbf26423a,0xbf316e2c,0xbf7f35f9,0xbf7a0d54,0xbf3bfc8f,0xbf45e403,0xbf702d4f,0xbf61c598,
0xbf05c277,0xbf146eba,0xbf6c835e,0xbf7853f8,0xbf226799,0xbf2f9c32,0xbf7ec46d,0xbf7fb10f,0xbf3bfc8f,0xbf4779bc,0xbf7b14be,0xbf710908,0xbf5205d4,0xbf5b941a,0xbf61c598,0xbf4d9f02,
0x80000000,0x80000000,0xbf737871,0xbf78ed3c,0x80000000,0x80000000,0xbf7cd925,0xbf7f35f9,0x80000000,0x80000000,0xbf800000,0xbf7f35f9,0x80000000,0x80000000,0xbf7cd925,0xbf78ed3c,
0xbe20305b,0xbe2a1c3f,0xbf7cd925,0xbf7f654e,0xbe3403f1,0xbe3de731,0xbf7ff35e,0xbf7e8238,0xbe47c5c2,0xbe519f65,0xbf7b14be,0xbf75b1c9,0xbe5b73dc,0xbe6542e9,0xbf6e641a,0xbf653a48,
0xbe9e377a,0xbea7bf25,0xbf800000,0xbf7ec46d,0xbeb13641,0xbeba9be1,0xbf7b14be,0xbf74fa0b,0xbec3ef15,0xbecd2ef3,0xbf6c835e,0xbf61c598,0xbed65a92,0xbedf7108,0xbf54db31,0xbf45e403,
0xbee87171,0xbef5c6c5,0xbf7cd925,0xbf770f11,0xbf0172c3,0xbf07e565,0xbf6e641a,0xbf62f219,0xbf0e39da,0xbf146eba,0xbf54db31,0xbf444969,0xbf1a82a4,0xbf207440,0xbf316e2c,0xbf1c81b9,
0xbf167918,0xbf1e7cf1,0xbf737871,0xbf687c12,0xbf26423a,0xbf2dc5e3,0xbf5a46a0,0xbf490a88,0xbf3504f3,0xbf3bfc8f,0xbf3504f3,0xbf1e7cf1,0xbf42a9f7,0xbf490a88,0xbf05c277,0xbed65a92,
0xbf3504f3,0xbf3daef9,0xbf641901,0xbf53731f,0xbf45e403,0xbf4d9f02,0xbf3f5cb5,0xbf28296a,0xbf54db31,0xbf5b941a,0xbf0e39da,0xbee3f40d,0xbf61c598,0xbf676bd8,0xbea7bf25,0xbe519f65,
0xbf4f1bbd,0xbf579b8c,0xbf4f1bbd,0xbf3889dc,0xbf5f5be6,0xbf6655e7,0xbf1e7cf1,0xbf0172c3,0xbf6c835e,0xbf71decf,0xbec3ef15,0xbe814693,0xbf766377,0xbf7a0d54,0xbdf0b772,0x3ca0d6d6,
0xbf641901,0xbf6b8a3d,0xbf3504f3,0xbf187fc0,0xbf71decf,0xbf770f11,0xbef15aea,0xbeac7cd4,0xbf7b14be,0xbf7deafa,0xbe47c5c2,0xbd48fb30,0xbf7f8e56,0xbf7ffcd7,0x3dc8bd36,0x3e78cfcc,
0x80000000,0x80000000,0xbf737871,0xbf6c835e,0x80000000,0x80000000,0xbf641901,0xbf5a46a0,0x80000000,0x80000000,0xbf4f1bbd,0xbf42a9f7,0x80000000,0x80000000,0xbf3504f3,0xbf26423a,
0xbe6f0c4d,0xbe78cfcc,0xbf5a46a0,0xbf4d9f02,0xbe814693,0xbe862210,0xbf3f5cb5,0xbf2f9c32,0xbe8afa3e,0xbe8fcefe,0xbf1e7cf1,0xbf0c2124,0xbe94a031,0xbe996dba,0xbef15aea,0xbec8917e,
0xbee87171,0xbef15aea,0xbf3504f3,0xbf226799,0xbefa2c90,0xbf0172c3,0xbf0e39da,0xbef15aea,0xbf05c277,0xbf0a04f8,0xbec3ef15,0xbe94a031,0xbf0e39da,0xbf1260b2,0xbe47c5c2,0xbdc8bd36,
0xbf26423a,0xbf2beb4a,0xbf05c277,0xbedae880,0xbf316e2c,0xbf36c9a9,0xbea7bf25,0xbe6542e9,0xbf3bfc8f,0xbf4105b8,0xbdf0b772,0xbc20d8d2,0xbf45e403,0xbf4a965e,0x3dc8bd36,0x3e519f65,
0xbf4f1bbd,0xbf54db31,0xbe9e377a,0xbe47c5c2,0xbf5a46a0,0xbf5f5be6,0xbda0af2a,0x3d20cee7,0xbf641901,0xbf687c12,0x3e20305b,0x3e8afa3e,0xbf6c835e,0xbf702d4f,0x3ec3ef15,0x3efa2c90,
0xbf6c835e,0xbf710908,0xbda0af2a,0x3d48fb30,0xbf74fa0b,0xbf7853f8,0x3e3403f1,0x3e996dba,0xbf7b14be,0xbf7d3aac,0x3ed65a92,0x3f07e565,0xbf7ec46d,0xbf7fb10f,0x3f226799,0x3f3a4582,
0xbf7cd925,0xbf7ec46d,0x3e20305b,0x3e94a031,0xbf7fcd79,0xbf7ff35e,0x3ed65a92,0x3f0a04f8,0xbf7f35f9,0xbf7d95f4,0x3f26423a,0x3f3f5cb5,0xbf7b14be,0xbf77b493,0x3f54db31,0x3f6655e7,
0xbf7f35f9,0xbf7d3aac,0x3ec3ef15,0x3f039c3d,0xbf7a0d54,0xbf75b1c9,0x3f226799,0x3f3daef9,0xbf702d4f,0xbf698690,0x3f54db31,0x3f676bd8,0xbf61c598,0xbf58f3c4,0x3f74fa0b,0x3f7d3aac,
0x80000000,0x80000000,0xbf167918,0xbf05c277,0x80000000,0x80000000,0xbee87171,0xbec3ef15,0x80000000,0x80000000,0xbe9e377a,0xbe6f0c4d,0x80000000,0x80000000,0xbe20305b,0xbda0af2a,
0xbe9e377a,0xbea2fd52,0xbe9e377a,0xbe6542e9,0xbea7bf25,0xbeac7cd4,0xbe0c4cf7,0xbd48fb30,0xbeb13641,0xbeb5eb4f,0x3d20cee7,0x3e0255f4,0xbeba9be1,0xbebf47d7,0x3e5b73dc,0x3e996dba,
0xbf167918,0xbf1a82a4,0x80000000,0x3dc8bd36,0xbf1e7cf1,0xbf226799,0x3e47c5c2,0x3e94a031,0xbf26423a,0xbf2a0c73,0x3ec3ef15,0x3ef15aea,0xbf2dc5e3,0xbf316e2c,0x3f0e39da,0x3f226799,
0xbf4f1bbd,0xbf53731f,0x3e9e377a,0x3ed1c759,0xbf579b8c,0xbf5b941a,0x3f0172c3,0x3f187fc0,0xbf5f5be6,0xbf62f219,0x3f2dc5e3,0x3f4105b8,0xbf6655e7,0xbf698690,0x3f5205d4,0x3f609384,
0xbf737871,0xbf766377,0x3f167918,0x3f2dc5e3,0xbf78ed3c,0xbf7b14be,0x3f42a9f7,0x3f54db31,0xbf7cd925,0xbf7e39bc,0x3f641901,0x3f702d4f,0xbf7f35f9,0xbf7fcd79,0x3f78ed3c,0x3f7e39bc,
0xbf800000,0xbf7fb10f,0x3f4f1bbd,0x3f609384,0xbf7ec46d,0xbf7d3aac,0x3f6e641a,0x3f7853f8,0xbf7b14be,0xbf7853f8,0x3f7e39bc,0x3f7ffcd7,0xbf74fa0b,0xbf710908,0x3f7d95f4,0x3f770f11,
0xbf737871,0xbf6e641a,0x3f737871,0x3f7c0361,0xbf687c12,0xbf61c598,0x3f7fcd79,0x3f7ec46d,0xbf5a46a0,0xbf5205d4,0x3f78ed3c,0x3f6e641a,0xbf490a88,0xbf3f5cb5,0x3f5f5be6,0x3f4c1d35,
0xbf4f1bbd,0xbf444969,0x3f800000,0x3f7d3aac,0xbf3889dc,0xbf2beb4a,0x3f74fa0b,0x3f676bd8,0xbf1e7cf1,0xbf104f0e,0x3f54db31,0x3f3daef9,0xbf0172c3,0xbee3f40d,0x3f226799,0x3f039c3d,
0x3f803f80,0,0x3f803f80,0,0x3f803f80,0,0x3f803f80,0,0x3f7d3f80,0x3e200000,0x3f643f73,0x3ee83e9e,0x3f353f4f,0x3f353f16,0x3ee83f16,0x3f643f4f,
0x3f733f80,0x3e9e0000,0x3f163f4f,0x3f4f3f16,0x3e9e,0x3f803f73,0xbf16be9e,0x3f4f3f73,0x3f643f80,0x3ee80000,0x3e203f16,0x3f7d3f4f,0xbf35be9e,0x3f353f73,0xbf7dbf73,0xbe203e9e,
0x3f4f3f80,0x3f160000,0xbe9e3e9e,0x3f733f73,0xbf80bf4f,0x3f16,0xbe9ebf4f,0xbf73bf16,0x3f353f80,0x3f350000,0xbf350000,0x3f353f80,0xbf35bf80,0xbf350000,0x3f350000,0xbf35bf80,
0x3f163f80,0x3f4f0000,0xbf73be9e,0x3e9e3f73,0xbf4f,0xbf80bf16,0x3f733f4f,0x3e9ebf16,0x3ee83f80,0x3f640000,0xbf7dbf16,0xbe203f4f,0x3f35be9e,0xbf35bf73,0x3e203f73,0x3f7d3e9e,
0x3e9e3f80,0x3f730000,0xbf4fbf4f,0xbf163f16,0x3f803e9e,0xbf73,0xbf4f3e9e,0x3f163f73,0x3e203f80,0x3f7d0000,0xbee8bf73,0xbf643e9e,0x3f353f4f,0x3f35bf16,0xbf64bf16,0xbee83f4f,
0x3f80,0x3f800000,0xbf80,0xbf800000,0x3f80,0x3f800000,0xbf80,0xbf800000,0xbe203f80,0x3f7d0000,0x3ee8bf73,0xbf64be9e,0xbf353f4f,0x3f353f16,0x3f64bf16,0xbee8bf4f,
0xbe9e3f80,0x3f730000,0x3f4fbf4f,0xbf16bf16,0xbf803e9e,0x3f73,0x3f4f3e9e,0x3f16bf73,0xbee83f80,0x3f640000,0x3f7dbf16,0xbe20bf4f,0xbf35be9e,0xbf353f73,0xbe203f73,0x3f7dbe9e,
0xbf163f80,0x3f4f0000,0x3f73be9e,0x3e9ebf73,0xbf4f,0xbf803f16,0xbf733f4f,0x3e9e3f16,0xbf353f80,0x3f350000,0x3f350000,0x3f35bf80,0x3f35bf80,0xbf350000,0xbf350000,0xbf353f80,
0xbf4f3f80,0x3f160000,0x3e9e3e9e,0x3f73bf73,0x3f80bf4f,0xbf16,0x3e9ebf4f,0xbf733f16,0xbf643f80,0x3ee80000,0xbe203f16,0x3f7dbf4f,0x3f35be9e,0x3f35bf73,0x3f7dbf73,0xbe20be9e,
0xbf733f80,0x3e9e0000,0xbf163f4f,0x3f4fbf16,0x3e9e,0x3f80bf73,0x3f16be9e,0x3f4fbf73,0xbf7d3f80,0x3e200000,0xbf643f73,0x3ee8be9e,0xbf353f4f,0x3f35bf16,0xbee83f16,0x3f64bf4f,
0xbf803f80,0,0xbf803f80,0,0xbf803f80,0,0xbf803f80,0,0xbf7d3f80,0xbe200000,0xbf643f73,0xbee83e9e,0xbf353f4f,0xbf353f16,0xbee83f16,0xbf643f4f,
0xbf733f80,0xbe9e0000,0xbf163f4f,0xbf4f3f16,0x3e9e,0xbf803f73,0x3f16be9e,0xbf4f3f73,0xbf643f80,0xbee80000,0xbe203f16,0xbf7d3f4f,0x3f35be9e,0xbf353f73,0x3f7dbf73,0x3e203e9e,
0xbf4f3f80,0xbf160000,0x3e9e3e9e,0xbf733f73,0x3f80bf4f,0x3f16,0x3e9ebf4f,0x3f73bf16,0xbf353f80,0xbf350000,0x3f350000,0xbf353f80,0x3f35bf80,0x3f350000,0xbf350000,0x3f35bf80,
0xbf163f80,0xbf4f0000,0x3f73be9e,0xbe9e3f73,0xbf4f,0x3f80bf16,0xbf733f4f,0xbe9ebf16,0xbee83f80,0xbf640000,0x3f7dbf16,0x3e203f4f,0xbf35be9e,0x3f35bf73,0xbe203f73,0xbf7d3e9e,
0xbe9e3f80,0xbf730000,0x3f4fbf4f,0x3f163f16,0xbf803e9e,0xbf73,0x3f4f3e9e,0xbf163f73,0xbe203f80,0xbf7d0000,0x3ee8bf73,0x3f643e9e,0xbf353f4f,0xbf35bf16,0x3f64bf16,0x3ee83f4f,
0x3f80,0xbf800000,0xbf80,0x3f800000,0x3f80,0xbf800000,0xbf80,0x3f800000,0x3e203f80,0xbf7d0000,0xbee8bf73,0x3f64be9e,0x3f353f4f,0xbf353f16,0xbf64bf16,0x3ee8bf4f,
0x3e9e3f80,0xbf730000,0xbf4fbf4f,0x3f16bf16,0x3f803e9e,0x3f73,0xbf4f3e9e,0xbf16bf73,0x3ee83f80,0xbf640000,0xbf7dbf16,0x3e20bf4f,0x3f35be9e,0x3f353f73,0x3e203f73,0xbf7dbe9e,
0x3f163f80,0xbf4f0000,0xbf73be9e,0xbe9ebf73,0xbf4f,0x3f803f16,0x3f733f4f,0xbe9e3f16,0x3f353f80,0xbf350000,0xbf350000,0xbf35bf80,0xbf35bf80,0x3f350000,0x3f350000,0x3f353f80,
0x3f4f3f80,0xbf160000,0xbe9e3e9e,0xbf73bf73,0xbf80bf4f,0xbf16,0xbe9ebf4f,0x3f733f16,0x3f643f80,0xbee80000,0x3e203f16,0xbf7dbf4f,0xbf35be9e,0xbf35bf73,0xbf7dbf73,0x3e20be9e,
0x3f733f80,0xbe9e0000,0x3f163f4f,0xbf4fbf16,0x3e9e,0xbf80bf73,0xbf16be9e,0xbf4fbf73,0x3f7d3f80,0xbe200000,0x3f643f73,0xbee8be9e,0x3f353f4f,0xbf35bf16,0x3ee83f16,0xbf64bf4f,
0x3f803f80,0,0x3f803f80,0,0x3f803f80,0,0x3f803f80,0,0x3e203e9e,0x3f7d3f73,0xbe200000,0x3f7d3f80,0xbee8be9e,0x3f643f73,0xbf35bf16,0x3f353f4f,
0xbf73bf4f,0x3e9e3f16,0xbf73bf80,0xbe9e0000,0xbf16bf4f,0xbf4fbf16,0xbe9e,0xbf80bf73,0xbee8bf4f,0xbf64bf16,0x3ee80000,0xbf64bf80,0x3f7d3f4f,0xbe20bf16,0x3f353f73,0x3f353e9e,
0x3f4f3e9e,0xbf16bf73,0x3f4f3f80,0x3f160000,0xbe9e3e9e,0x3f733f73,0xbf80bf4f,0x3f16,0x3f353f80,0x3f350000,0xbf350000,0x3f353f80,0xbf35bf80,0xbf350000,0x3f350000,0xbf35bf80,
0xbf163e9e,0x3f4f3f73,0xbf16bf80,0xbf4f0000,0x3f733e9e,0xbe9ebf73,0x3f4f,0x3f803f16,0xbf64bf4f,0xbee83f16,0x3f640000,0xbee8bf80,0xbe203f4f,0x3f7d3f16,0xbf35bf73,0xbf353e9e,
0x3e9ebf4f,0xbf73bf16,0x3e9e3f80,0x3f730000,0xbf4fbf4f,0xbf163f16,0x3f803e9e,0xbf73,0x3f7d3e9e,0x3e20bf73,0xbf7d0000,0x3e203f80,0x3f64be9e,0xbee8bf73,0xbf353f16,0x3f353f4f,
0x3f80,0x3f800000,0xbf80,0xbf800000,0x3f80,0x3f800000,0xbf80,0xbf800000,0xbf7d3e9e,0x3e203f73,0x3f7d0000,0x3e20bf80,0xbf64be9e,0xbee83f73,0x3f353f16,0x3f35bf4f,
0xbe9ebf4f,0xbf733f16,0xbe9e3f80,0x3f730000,0x3f4fbf4f,0xbf16bf16,0xbf803e9e,0x3f73,0x3f64bf4f,0xbee8bf16,0xbf640000,0xbee83f80,0x3e203f4f,0x3f7dbf16,0x3f35bf73,0xbf35be9e,
0x3f163e9e,0x3f4fbf73,0x3f16bf80,0xbf4f0000,0xbf733e9e,0xbe9e3f73,0x3f4f,0x3f80bf16,0xbf353f80,0x3f350000,0x3f350000,0x3f35bf80,0x3f35bf80,0xbf350000,0xbf350000,0xbf353f80,
0xbf4f3e9e,0xbf163f73,0xbf4f3f80,0x3f160000,0x3e9e3e9e,0x3f73bf73,0x3f80bf4f,0xbf16,0x3ee8bf4f,0xbf643f16,0xbee80000,0xbf643f80,0xbf7d3f4f,0xbe203f16,0xbf353f73,0x3f35be9e,
0x3f73bf4f,0x3e9ebf16,0x3f73bf80,0xbe9e0000,0x3f16bf4f,0xbf4f3f16,0xbe9e,0xbf803f73,0xbe203e9e,0x3f7dbf73,0x3e200000,0x3f7dbf80,0x3ee8be9e,0x3f64bf73,0x3f35bf16,0x3f35bf4f,
0xbf803f80,0,0xbf803f80,0,0xbf803f80,0,0xbf803f80,0,0xbe203e9e,0xbf7d3f73,0x3e200000,0xbf7d3f80,0x3ee8be9e,0xbf643f73,0x3f35bf16,0xbf353f4f,
0x3f73bf4f,0xbe9e3f16,0x3f73bf80,0x3e9e0000,0x3f16bf4f,0x3f4fbf16,0xbe9e,0x3f80bf73,0x3ee8bf4f,0x3f64bf16,0xbee80000,0x3f64bf80,0xbf7d3f4f,0x3e20bf16,0xbf353f73,0xbf353e9e,
0xbf4f3e9e,0x3f16bf73,0xbf4f3f80,0xbf160000,0x3e9e3e9e,0xbf733f73,0x3f80bf4f,0x3f16,0xbf353f80,0xbf350000,0x3f350000,0xbf353f80,0x3f35bf80,0x3f350000,0xbf350000,0x3f35bf80,
0x3f163e9e,0xbf4f3f73,0x3f16bf80,0x3f4f0000,0xbf733e9e,0x3e9ebf73,0x3f4f,0xbf803f16,0x3f64bf4f,0x3ee83f16,0xbf640000,0x3ee8bf80,0x3e203f4f,0xbf7d3f16,0x3f35bf73,0x3f353e9e,
0xbe9ebf4f,0x3f73bf16,0xbe9e3f80,0xbf730000,0x3f4fbf4f,0x3f163f16,0xbf803e9e,0xbf73,0xbf7d3e9e,0xbe20bf73,0x3f7d0000,0xbe203f80,0xbf64be9e,0x3ee8bf73,0x3f353f16,0xbf353f4f,
0x3f80,0xbf800000,0xbf80,0x3f800000,0x3f80,0xbf800000,0xbf80,0x3f800000,0x3f7d3e9e,0xbe203f73,0xbf7d0000,0xbe20bf80,0x3f64be9e,0x3ee83f73,0xbf353f16,0xbf35bf4f,
0x3e9ebf4f,0x3f733f16,0x3e9e3f80,0xbf730000,0xbf4fbf4f,0x3f16bf16,0x3f803e9e,0x3f73,0xbf64bf4f,0x3ee8bf16,0x3f640000,0x3ee83f80,0xbe203f4f,0xbf7dbf16,0xbf35bf73,0x3f35be9e,
0xbf163e9e,0xbf4fbf73,0xbf16bf80,0x3f4f0000,0x3f733e9e,0x3e9e3f73,0x3f4f,0xbf80bf16,0x3f353f80,0xbf350000,0xbf350000,0xbf35bf80,0xbf35bf80,0x3f350000,0x3f350000,0x3f353f80,
0x3f4f3e9e,0x3f163f73,0x3f4f3f80,0xbf160000,0xbe9e3e9e,0xbf73bf73,0xbf80bf4f,0xbf16,0xbee8bf4f,0x3f643f16,0x3ee80000,0x3f643f80,0x3f7d3f4f,0x3e203f16,0x3f353f73,0xbf35be9e,
0xbf73bf4f,0xbe9ebf16,0xbf73bf80,0x3e9e0000,0xbf16bf4f,0x3f4f3f16,0xbe9e,0x3f803f73,0x3e203e9e,0xbf7dbf73,0xbe200000,0xbf7dbf80,0xbee8be9e,0xbf64bf73,0xbf35bf16,0xbf35bf4f,
0x3f803f80,0,0x3f803f80,0,0x3f803f80,0,0x3f803f80,0,0xbf64bf4f,0x3ee83f16,0xbf7dbf73,0x3e203e9e,0xbf7dbf80,0xbe200000,0xbf64bf73,0xbee8be9e,
0x3f163e9e,0xbf4fbf73,0x3f733f4f,0xbe9ebf16,0x3f733f80,0x3e9e0000,0x3f163f4f,0x3f4f3f16,0xbe203e9e,0x3f7d3f73,0xbf64bf16,0x3ee83f4f,0xbf64bf80,0xbee80000,0xbe20bf16,0xbf7dbf4f,
0xbe9ebf4f,0xbf73bf16,0x3f4f3e9e,0xbf16bf73,0x3f4f3f80,0x3f160000,0xbe9e3e9e,0x3f733f73,0x3f353f80,0x3f350000,0xbf350000,0x3f353f80,0xbf35bf80,0xbf350000,0x3f350000,0xbf35bf80,
0xbf73bf4f,0xbe9e3f16,0x3f16be9e,0xbf4fbf73,0x3f163f80,0x3f4f0000,0xbf73be9e,0x3e9e3f73,0x3f7d3e9e,0xbe20bf73,0xbee83f16,0x3f643f4f,0xbee8bf80,0xbf640000,0x3f7d3f16,0x3e20bf4f,
0xbf4f3e9e,0x3f163f73,0x3e9ebf4f,0xbf73bf16,0x3e9e3f80,0x3f730000,0xbf4fbf4f,0xbf163f16,0x3ee8bf4f,0xbf64bf16,0xbe203f73,0x3f7d3e9e,0xbe20bf80,0xbf7d0000,0x3ee83f73,0x3f64be9e,
0x3f80,0x3f800000,0xbf80,0xbf800000,0x3f80,0x3f800000,0xbf80,0xbf800000,0xbee8bf4f,0xbf643f16,0x3e203f73,0x3f7dbe9e,0x3e20bf80,0xbf7d0000,0xbee83f73,0x3f643e9e,
0x3f4f3e9e,0x3f16bf73,0xbe9ebf4f,0xbf733f16,0xbe9e3f80,0x3f730000,0x3f4fbf4f,0xbf16bf16,0xbf7d3e9e,0xbe203f73,0x3ee83f16,0x3f64bf4f,0x3ee8bf80,0xbf640000,0xbf7d3f16,0x3e203f4f,
0x3f73bf4f,0xbe9ebf16,0xbf16be9e,0xbf4f3f73,0xbf163f80,0x3f4f0000,0x3f73be9e,0x3e9ebf73,0xbf353f80,0x3f350000,0x3f350000,0x3f35bf80,0x3f35bf80,0xbf350000,0xbf350000,0xbf353f80,
0x3e9ebf4f,0xbf733f16,0xbf4f3e9e,0xbf163f73,0xbf4f3f80,0x3f160000,0x3e9e3e9e,0x3f73bf73,0x3e203e9e,0x3f7dbf73,0x3f64bf16,0x3ee8bf4f,0x3f64bf80,0xbee80000,0x3e20bf16,0xbf7d3f4f,
0xbf163e9e,0xbf4f3f73,0xbf733f4f,0xbe9e3f16,0xbf733f80,0x3e9e0000,0xbf163f4f,0x3f4fbf16,0x3f64bf4f,0x3ee8bf16,0x3f7dbf73,0x3e20be9e,0x3f7dbf80,0xbe200000,0x3f64bf73,0xbee83e9e,
0xbf803f80,0,0xbf803f80,0,0xbf803f80,0,0xbf803f80,0,0x3f64bf4f,0xbee83f16,0x3f7dbf73,0xbe203e9e,0x3f7dbf80,0x3e200000,0x3f64bf73,0x3ee8be9e,
0xbf163e9e,0x3f4fbf73,0xbf733f4f,0x3e9ebf16,0xbf733f80,0xbe9e0000,0xbf163f4f,0xbf4f3f16,0x3e203e9e,0xbf7d3f73,0x3f64bf16,0xbee83f4f,0x3f64bf80,0x3ee80000,0x3e20bf16,0x3f7dbf4f,
0x3e9ebf4f,0x3f73bf16,0xbf4f3e9e,0x3f16bf73,0xbf4f3f80,0xbf160000,0x3e9e3e9e,0xbf733f73,0xbf353f80,0xbf350000,0x3f350000,0xbf353f80,0x3f35bf80,0x3f350000,0xbf350000,0x3f35bf80,
0x3f73bf4f,0x3e9e3f16,0xbf16be9e,0x3f4fbf73,0xbf163f80,0xbf4f0000,0x3f73be9e,0xbe9e3f73,0xbf7d3e9e,0x3e20bf73,0x3ee83f16,0xbf643f4f,0x3ee8bf80,0x3f640000,0xbf7d3f16,0xbe20bf4f,
0x3f4f3e9e,0xbf163f73,0xbe9ebf4f,0x3f73bf16,0xbe9e3f80,0xbf730000,0x3f4fbf4f,0x3f163f16,0xbee8bf4f,0x3f64bf16,0x3e203f73,0xbf7d3e9e,0x3e20bf80,0x3f7d0000,0xbee83f73,0xbf64be9e,
0x3f80,0xbf800000,0xbf80,0x3f800000,0x3f80,0xbf800000,0xbf80,0x3f800000,0x3ee8bf4f,0x3f643f16,0xbe203f73,0xbf7dbe9e,0xbe20bf80,0x3f7d0000,0x3ee83f73,0xbf643e9e,
0xbf4f3e9e,0xbf16bf73,0x3e9ebf4f,0x3f733f16,0x3e9e3f80,0xbf730000,0xbf4fbf4f,0x3f16bf16,0x3f7d3e9e,0x3e203f73,0xbee83f16,0xbf64bf4f,0xbee8bf80,0x3f640000,0x3f7d3f16,0xbe203f4f,
0xbf73bf4f,0x3e9ebf16,0x3f16be9e,0x3f4f3f73,0x3f163f80,0xbf4f0000,0xbf73be9e,0xbe9ebf73,0x3f353f80,0xbf350000,0xbf350000,0xbf35bf80,0xbf35bf80,0x3f350000,0x3f350000,0x3f353f80,
0xbe9ebf4f,0x3f733f16,0x3f4f3e9e,0x3f163f73,0x3f4f3f80,0xbf160000,0xbe9e3e9e,0xbf73bf73,0xbe203e9e,0xbf7dbf73,0xbf64bf16,0xbee8bf4f,0xbf64bf80,0x3ee80000,0xbe20bf16,0x3f7d3f4f,
0x3f163e9e,0x3f4f3f73,0x3f733f4f,0x3e9e3f16,0x3f733f80,0xbe9e0000,0x3f163f4f,0xbf4fbf16,0xbf64bf4f,0xbee8bf16,0xbf7dbf73,0xbe20be9e,0xbf7dbf80,0x3e200000,0xbf64bf73,0x3ee83e9e,
0x3f803f80,0,0x3f803f80,0,0x3f803f80,0,0x3f803f80,0,0xbf35bf4f,0xbf35bf16,0xbee8bf16,0xbf64bf4f,0xbe20be9e,0xbf7dbf73,0x3e200000,0xbf7dbf80,
0x3e9e,0x3f803f73,0xbf16be9e,0x3f4f3f73,0xbf73bf4f,0x3e9e3f16,0xbf73bf80,0xbe9e0000,0x3f353e9e,0xbf35bf73,0x3f7d3f73,0x3e20be9e,0x3ee83f4f,0x3f643f16,0xbee80000,0x3f643f80,
0xbf80bf4f,0x3f16,0xbe9ebf4f,0xbf73bf16,0x3f4f3e9e,0xbf16bf73,0x3f4f3f80,0x3f160000,0x3f353f80,0x3f350000,0xbf350000,0x3f353f80,0xbf35bf80,0xbf350000,0x3f350000,0xbf35bf80,
0xbf4f,0xbf80bf16,0x3f733f4f,0x3e9ebf16,0xbf163e9e,0x3f4f3f73,0xbf16bf80,0xbf4f0000,0xbf353e9e,0x3f353f73,0xbe20bf73,0xbf7dbe9e,0x3f643f4f,0x3ee8bf16,0xbf640000,0x3ee83f80,
0x3f803e9e,0xbf73,0xbf4f3e9e,0x3f163f73,0x3e9ebf4f,0xbf73bf16,0x3e9e3f80,0x3f730000,0xbf35bf4f,0xbf353f16,0x3f643f16,0x3ee8bf4f,0xbf7dbe9e,0xbe203f73,0x3f7d0000,0xbe20bf80,
0x3f80,0x3f800000,0xbf80,0xbf800000,0x3f80,0x3f800000,0xbf80,0xbf800000,0x3f35bf4f,0xbf35bf16,0xbf643f16,0x3ee83f4f,0x3f7dbe9e,0xbe20bf73,0xbf7d0000,0xbe203f80,
0xbf803e9e,0x3f73,0x3f4f3e9e,0x3f16bf73,0xbe9ebf4f,0xbf733f16,0xbe9e3f80,0x3f730000,0x3f353e9e,0x3f35bf73,0x3e20bf73,0xbf7d3e9e,0xbf643f4f,0x3ee83f16,0x3f640000,0x3ee8bf80,
0xbf4f,0xbf803f16,0xbf733f4f,0x3e9e3f16,0x3f163e9e,0x3f4fbf73,0x3f16bf80,0xbf4f0000,0xbf353f80,0x3f350000,0x3f350000,0x3f35bf80,0x3f35bf80,0xbf350000,0xbf350000,0xbf353f80,
0x3f80bf4f,0xbf16,0x3e9ebf4f,0xbf733f16,0xbf4f3e9e,0xbf163f73,0xbf4f3f80,0x3f160000,0xbf353e9e,0xbf353f73,0xbf7d3f73,0x3e203e9e,0xbee83f4f,0x3f64bf16,0x3ee80000,0x3f64bf80,
0x3e9e,0x3f80bf73,0x3f16be9e,0x3f4fbf73,0x3f73bf4f,0x3e9ebf16,0x3f73bf80,0xbe9e0000,0x3f35bf4f,0xbf353f16,0x3ee8bf16,0xbf643f4f,0x3e20be9e,0xbf7d3f73,0xbe200000,0xbf7d3f80,
0xbf803f80,0,0xbf803f80,0,0xbf803f80,0,0xbf803f80,0,0x3f35bf4f,0x3f35bf16,0x3ee8bf16,0x3f64bf4f,0x3e20be9e,0x3f7dbf73,0xbe200000,0x3f7dbf80,
0x3e9e,0xbf803f73,0x3f16be9e,0xbf4f3f73,0x3f73bf4f,0xbe9e3f16,0x3f73bf80,0x3e9e0000,0xbf353e9e,0x3f35bf73,0xbf7d3f73,0xbe20be9e,0xbee83f4f,0xbf643f16,0x3ee80000,0xbf643f80,
0x3f80bf4f,0x3f16,0x3e9ebf4f,0x3f73bf16,0xbf4f3e9e,0x3f16bf73,0xbf4f3f80,0xbf160000,0xbf353f80,0xbf350000,0x3f350000,0xbf353f80,0x3f35bf80,0x3f350000,0xbf350000,0x3f35bf80,
0xbf4f,0x3f80bf16,0xbf733f4f,0xbe9ebf16,0x3f163e9e,0xbf4f3f73,0x3f16bf80,0x3f4f0000,0x3f353e9e,0xbf353f73,0x3e20bf73,0x3f7dbe9e,0xbf643f4f,0xbee8bf16,0x3f640000,0xbee83f80,
0xbf803e9e,0xbf73,0x3f4f3e9e,0xbf163f73,0xbe9ebf4f,0x3f73bf16,0xbe9e3f80,0xbf730000,0x3f35bf4f,0x3f353f16,0xbf643f16,0xbee8bf4f,0x3f7dbe9e,0x3e203f73,0xbf7d0000,0x3e20bf80,
0x3f80,0xbf800000,0xbf80,0x3f800000,0x3f80,0xbf800000,0xbf80,0x3f800000,0xbf35bf4f,0x3f35bf16,0x3f643f16,0xbee83f4f,0xbf7dbe9e,0x3e20bf73,0x3f7d0000,0x3e203f80,
0x3f803e9e,0x3f73,0xbf4f3e9e,0xbf16bf73,0x3e9ebf4f,0x3f733f16,0x3e9e3f80,0xbf730000,0xbf353e9e,0xbf35bf73,0xbe20bf73,0x3f7d3e9e,0x3f643f4f,0xbee83f16,0xbf640000,0xbee8bf80,
0xbf4f,0x3f803f16,0x3f733f4f,0xbe9e3f16,0xbf163e9e,0xbf4fbf73,0xbf16bf80,0x3f4f0000,0x3f353f80,0xbf350000,0xbf350000,0xbf35bf80,0xbf35bf80,0x3f350000,0x3f350000,0x3f353f80,
0xbf80bf4f,0xbf16,0xbe9ebf4f,0x3f733f16,0x3f4f3e9e,0x3f163f73,0x3f4f3f80,0xbf160000,0x3f353e9e,0x3f353f73,0x3f7d3f73,0xbe203e9e,0x3ee83f4f,0xbf64bf16,0xbee80000,0xbf64bf80,
0x3e9e,0xbf80bf73,0xbf16be9e,0xbf4fbf73,0xbf73bf4f,0xbe9ebf16,0xbf73bf80,0x3e9e0000,0xbf35bf4f,0x3f353f16,0xbee8bf16,0x3f643f4f,0xbe20be9e,0x3f7d3f73,0x3e200000,0x3f7d3f80,
0x3f803f80,0,0x3f803f80,0,0x3f803f80,0,0x3f803f80,0,0x3ee83e9e,0xbf64bf73,0x3f353f16,0xbf35bf4f,0x3f643f4f,0xbee8bf16,0x3f7d3f73,0xbe20be9e,
0xbf16bf4f,0xbf4fbf16,0xbe9e,0xbf80bf73,0x3f163e9e,0xbf4fbf73,0x3f733f4f,0xbe9ebf16,0xbf7dbf4f,0x3e203f16,0xbf35bf73,0xbf35be9e,0x3e20be9e,0xbf7dbf73,0x3f643f16,0xbee8bf4f,
0xbe9e3e9e,0x3f733f73,0xbf80bf4f,0x3f16,0xbe9ebf4f,0xbf73bf16,0x3f4f3e9e,0xbf16bf73,0x3f353f80,0x3f350000,0xbf350000,0x3f353f80,0xbf35bf80,0xbf350000,0x3f350000,0xbf35bf80,
0x3f733e9e,0xbe9ebf73,0x3f4f,0x3f803f16,0xbf73bf4f,0xbe9e3f16,0x3f16be9e,0xbf4fbf73,0x3e20bf4f,0xbf7dbf16,0x3f353f73,0x3f35be9e,0xbf7dbe9e,0x3e203f73,0x3ee8bf16,0xbf64bf4f,
0xbf4fbf4f,0xbf163f16,0x3f803e9e,0xbf73,0xbf4f3e9e,0x3f163f73,0x3e9ebf4f,0xbf73bf16,0xbf643e9e,0x3ee83f73,0x3f35bf16,0xbf35bf4f,0xbee83f4f,0x3f643f16,0x3e20bf73,0xbf7dbe9e,
0x3f80,0x3f800000,0xbf80,0xbf800000,0x3f80,0x3f800000,0xbf80,0xbf800000,0x3f643e9e,0x3ee8bf73,0xbf35bf16,0xbf353f4f,0x3ee83f4f,0x3f64bf16,0xbe20bf73,0xbf7d3e9e,
0x3f4fbf4f,0xbf16bf16,0xbf803e9e,0x3f73,0x3f4f3e9e,0x3f16bf73,0xbe9ebf4f,0xbf733f16,0xbe20bf4f,0xbf7d3f16,0xbf353f73,0x3f353e9e,0x3f7dbe9e,0x3e20bf73,0xbee8bf16,0xbf643f4f,
0xbf733e9e,0xbe9e3f73,0x3f4f,0x3f80bf16,0x3f73bf4f,0xbe9ebf16,0xbf16be9e,0xbf4f3f73,0xbf353f80,0x3f350000,0x3f350000,0x3f35bf80,0x3f35bf80,0xbf350000,0xbf350000,0xbf353f80,
0x3e9e3e9e,0x3f73bf73,0x3f80bf4f,0xbf16,0x3e9ebf4f,0xbf733f16,0xbf4f3e9e,0xbf163f73,0x3f7dbf4f,0x3e20bf16,0x3f35bf73,0xbf353e9e,0xbe20be9e,0xbf7d3f73,0xbf643f16,0xbee83f4f,
0x3f16bf4f,0xbf4f3f16,0xbe9e,0xbf803f73,0xbf163e9e,0xbf4f3f73,0xbf733f4f,0xbe9e3f16,0xbee83e9e,0xbf643f73,0xbf353f16,0xbf353f4f,0xbf643f4f,0xbee83f16,0xbf7d3f73,0xbe203e9e,
0xbf803f80,0,0xbf803f80,0,0xbf803f80,0,0xbf803f80,0,0xbee83e9e,0x3f64bf73,0xbf353f16,0x3f35bf4f,0xbf643f4f,0x3ee8bf16,0xbf7d3f73,0x3e20be9e,
0x3f16bf4f,0x3f4fbf16,0xbe9e,0x3f80bf73,0xbf163e9e,0x3f4fbf73,0xbf733f4f,0x3e9ebf16,0x3f7dbf4f,0xbe203f16,0x3f35bf73,0x3f35be9e,0xbe20be9e,0x3f7dbf73,0xbf643f16,0x3ee8bf4f,
0x3e9e3e9e,0xbf733f73,0x3f80bf4f,0x3f16,0x3e9ebf4f,0x3f73bf16,0xbf4f3e9e,0x3f16bf73,0xbf353f80,0xbf350000,0x3f350000,0xbf353f80,0x3f35bf80,0x3f350000,0xbf350000,0x3f35bf80,
0xbf733e9e,0x3e9ebf73,0x3f4f,0xbf803f16,0x3f73bf4f,0x3e9e3f16,0xbf16be9e,0x3f4fbf73,0xbe20bf4f,0x3f7dbf16,0xbf353f73,0xbf35be9e,0x3f7dbe9e,0xbe203f73,0xbee8bf16,0x3f64bf4f,
0x3f4fbf4f,0x3f163f16,0xbf803e9e,0xbf73,0x3f4f3e9e,0xbf163f73,0xbe9ebf4f,0x3f73bf16,0x3f643e9e,0xbee83f73,0xbf35bf16,0x3f35bf4f,0x3ee83f4f,0xbf643f16,0xbe20bf73,0x3f7dbe9e,
0x3f80,0xbf800000,0xbf80,0x3f800000,0x3f80,0xbf800000,0xbf80,0x3f800000,0xbf643e9e,0xbee8bf73,0x3f35bf16,0x3f353f4f,0xbee83f4f,0xbf64bf16,0x3e20bf73,0x3f7d3e9e,
0xbf4fbf4f,0x3f16bf16,0x3f803e9e,0x3f73,0xbf4f3e9e,0xbf16bf73,0x3e9ebf4f,0x3f733f16,0x3e20bf4f,0x3f7d3f16,0x3f353f73,0xbf353e9e,0xbf7dbe9e,0xbe20bf73,0x3ee8bf16,0x3f643f4f,
0x3f733e9e,0x3e9e3f73,0x3f4f,0xbf80bf16,0xbf73bf4f,0x3e9ebf16,0x3f16be9e,0x3f4f3f73,0x3f353f80,0xbf350000,0xbf350000,0xbf35bf80,0xbf35bf80,0x3f350000,0x3f350000,0x3f353f80,
0xbe9e3e9e,0xbf73bf73,0xbf80bf4f,0xbf16,0xbe9ebf4f,0x3f733f16,0x3f4f3e9e,0x3f163f73,0xbf7dbf4f,0xbe20bf16,0xbf35bf73,0x3f353e9e,0x3e20be9e,0x3f7d3f73,0x3f643f16,0x3ee83f4f,
0xbf16bf4f,0x3f4f3f16,0xbe9e,0x3f803f73,0x3f163e9e,0x3f4f3f73,0x3f733f4f,0x3e9e3f16,0x3ee83e9e,0x3f643f73,0x3f353f16,0x3f353f4f,0x3f643f4f,0x3ee83f16,0x3f7d3f73,0x3e203e9e,
0x3f803f80,0x3f80,0xbf803f80,0x3f80,0x3f803f80,0xbf80,0xbf803f80,0xbf80,0x3f803f80,0x3f80,0xbf803f80,0x3f80,0x3f803f80,0xbf80,0xbf803f80,0xbf80,
0x3f7b3f80,0xbe483f80,0xbf7b3f80,0x3e483f80,0x3f553f6d,0x3f0ebf6d,0xbf553f6d,0xbf0ebf6d,0x3f0e3f35,0xbf553f35,0xbf0e3f35,0x3f553f35,0x3e483ec4,0x3f7bbec4,0xbe483ec4,0xbf7bbec4,
0x3f6d3f80,0xbec43f80,0xbf6d3f80,0x3ec43f80,0x3ec43f35,0x3f6dbf35,0xbec43f35,0xbf6dbf35,0xbec40000,0xbf6d0000,0x3ec40000,0x3f6d0000,0xbf6dbf35,0x3ec43f35,0x3f6dbf35,0xbec43f35,
0x3f553f80,0xbf0e3f80,0xbf553f80,0x3f0e3f80,0xbe483ec4,0x3f7bbec4,0x3e483ec4,0xbf7bbec4,0xbf7bbf35,0xbe48bf35,0x3f7bbf35,0x3e48bf35,0xbf0ebf6d,0xbf553f6d,0x3f0ebf6d,0x3f553f6d,
0x3f353f80,0xbf353f80,0xbf353f80,0x3f353f80,0xbf350000,0x3f350000,0x3f350000,0xbf350000,0xbf35bf80,0x3f35bf80,0x3f35bf80,0xbf35bf80,0x3f350000,0xbf350000,0xbf350000,0x3f350000,
0x3f0e3f80,0xbf553f80,0xbf0e3f80,0x3f553f80,0xbf7bbec4,0x3e483ec4,0x3f7bbec4,0xbe483ec4,0x3e48bf35,0x3f7bbf35,0xbe48bf35,0xbf7bbf35,0x3f553f6d,0x3f0ebf6d,0xbf553f6d,0xbf0ebf6d,
0x3ec43f80,0xbf6d3f80,0xbec43f80,0x3f6d3f80,0xbf6dbf35,0xbec43f35,0x3f6dbf35,0x3ec43f35,0x3f6d0000,0x3ec40000,0xbf6d0000,0xbec40000,0xbec43f35,0x3f6dbf35,0x3ec43f35,0xbf6dbf35,
0x3e483f80,0xbf7b3f80,0xbe483f80,0x3f7b3f80,0xbf0ebf6d,0xbf553f6d,0x3f0ebf6d,0x3f553f6d,0x3f553f35,0xbf0e3f35,0xbf553f35,0x3f0e3f35,0xbf7bbec4,0xbe483ec4,0x3f7bbec4,0x3e483ec4,
0x3f803f80,0x3f80,0xbf803f80,0x3f80,0x3f803f80,0xbf80,0xbf803f80,0xbf80,0x3f803f80,0x3f80,0xbf803f80,0x3f80,0x3f803f80,0xbf80,0xbf803f80,0xbf80,
0xbe480000,0xbf7b0000,0x3e480000,0x3f7b0000,0xbf0ebec4,0x3f553ec4,0x3f0ebec4,0xbf553ec4,0xbf55bf35,0xbf0ebf35,0x3f55bf35,0x3f0ebf35,0xbf7bbf6d,0x3e483f6d,0x3f7bbf6d,0xbe483f6d,
0xbf6dbf80,0x3ec4bf80,0x3f6dbf80,0xbec4bf80,0xbec4bf35,0xbf6d3f35,0x3ec4bf35,0x3f6d3f35,0x3ec40000,0x3f6d0000,0xbec40000,0xbf6d0000,0x3f6d3f35,0xbec4bf35,0xbf6d3f35,0x3ec4bf35,
0x3f0e0000,0x3f550000,0xbf0e0000,0xbf550000,0x3f7b3f6d,0x3e48bf6d,0xbf7b3f6d,0xbe48bf6d,0x3e483f35,0xbf7b3f35,0xbe483f35,0x3f7b3f35,0xbf55bec4,0x3f0e3ec4,0x3f55bec4,0xbf0e3ec4,
0x3f353f80,0xbf353f80,0xbf353f80,0x3f353f80,0xbf350000,0x3f350000,0x3f350000,0xbf350000,0xbf35bf80,0x3f35bf80,0x3f35bf80,0xbf35bf80,0x3f350000,0xbf350000,0xbf350000,0x3f350000,
0xbf550000,0xbf0e0000,0x3f550000,0x3f0e0000,0xbe48bf6d,0xbf7b3f6d,0x3e48bf6d,0x3f7b3f6d,0x3f7b3f35,0xbe483f35,0xbf7b3f35,0x3e483f35,0xbf0e3ec4,0x3f55bec4,0x3f0e3ec4,0xbf55bec4,
0xbec4bf80,0x3f6dbf80,0x3ec4bf80,0xbf6dbf80,0x3f6d3f35,0x3ec4bf35,0xbf6d3f35,0xbec4bf35,0xbf6d0000,0xbec40000,0x3f6d0000,0x3ec40000,0x3ec4bf35,0xbf6d3f35,0xbec4bf35,0x3f6d3f35,
0x3f7b0000,0x3e480000,0xbf7b0000,0xbe480000,0xbf553ec4,0x3f0ebec4,0x3f553ec4,0xbf0ebec4,0x3f0ebf35,0x3f55bf35,0xbf0ebf35,0xbf55bf35,0xbe483f6d,0x3f7bbf6d,0x3e483f6d,0xbf7bbf6d,
0x3f803f80,0x3f80,0xbf803f80,0x3f80,0x3f803f80,0xbf80,0xbf803f80,0xbf80,0x3f803f80,0x3f80,0xbf803f80,0x3f80,0x3f803f80,0xbf80,0xbf803f80,0xbf80,
0xbf7bbf80,0x3e48bf80,0x3f7bbf80,0xbe48bf80,0xbf55bf6d,0xbf0e3f6d,0x3f55bf6d,0x3f0e3f6d,0xbf0ebf35,0x3f55bf35,0x3f0ebf35,0xbf55bf35,0xbe48bec4,0xbf7b3ec4,0x3e48bec4,0x3f7b3ec4,
0x3f6d3f80,0xbec43f80,0xbf6d3f80,0x3ec43f80,0x3ec43f35,0x3f6dbf35,0xbec43f35,0xbf6dbf35,0xbec40000,0xbf6d0000,0x3ec40000,0x3f6d0000,0xbf6dbf35,0x3ec43f35,0x3f6dbf35,0xbec43f35,
0xbf55bf80,0x3f0ebf80,0x3f55bf80,0xbf0ebf80,0x3e48bec4,0xbf7b3ec4,0xbe48bec4,0x3f7b3ec4,0x3f7b3f35,0x3e483f35,0xbf7b3f35,0xbe483f35,0x3f0e3f6d,0x3f55bf6d,0xbf0e3f6d,0xbf55bf6d,
0x3f353f80,0xbf353f80,0xbf353f80,0x3f353f80,0xbf350000,0x3f350000,0x3f350000,0xbf350000,0xbf35bf80,0x3f35bf80,0x3f35bf80,0xbf35bf80,0x3f350000,0xbf350000,0xbf350000,0x3f350000,
0xbf0ebf80,0x3f55bf80,0x3f0ebf80,0xbf55bf80,0x3f7b3ec4,0xbe48bec4,0xbf7b3ec4,0x3e48bec4,0xbe483f35,0xbf7b3f35,0x3e483f35,0x3f7b3f35,0xbf55bf6d,0xbf0e3f6d,0x3f55bf6d,0x3f0e3f6d,
0x3ec43f80,0xbf6d3f80,0xbec43f80,0x3f6d3f80,0xbf6dbf35,0xbec43f35,0x3f6dbf35,0x3ec43f35,0x3f6d0000,0x3ec40000,0xbf6d0000,0xbec40000,0xbec43f35,0x3f6dbf35,0x3ec43f35,0xbf6dbf35,
0xbe48bf80,0x3f7bbf80,0x3e48bf80,0xbf7bbf80,0x3f0e3f6d,0x3f55bf6d,0xbf0e3f6d,0xbf55bf6d,0xbf55bf35,0x3f0ebf35,0x3f55bf35,0xbf0ebf35,0x3f7b3ec4,0x3e48bec4,0xbf7b3ec4,0xbe48bec4,
0x3f803f80,0x3f80,0xbf803f80,0x3f80,0x3f803f80,0xbf80,0xbf803f80,0xbf80,0x3f803f80,0x3f80,0xbf803f80,0x3f80,0x3f803f80,0xbf80,0xbf803f80,0xbf80,
0x3e480000,0x3f7b0000,0xbe480000,0xbf7b0000,0x3f0e3ec4,0xbf55bec4,0xbf0e3ec4,0x3f55bec4,0x3f553f35,0x3f0e3f35,0xbf553f35,0xbf0e3f35,0x3f7b3f6d,0xbe48bf6d,0xbf7b3f6d,0x3e48bf6d,
0xbf6dbf80,0x3ec4bf80,0x3f6dbf80,0xbec4bf80,0xbec4bf35,0xbf6d3f35,0x3ec4bf35,0x3f6d3f35,0x3ec40000,0x3f6d0000,0xbec40000,0xbf6d0000,0x3f6d3f35,0xbec4bf35,0xbf6d3f35,0x3ec4bf35,
0xbf0e0000,0xbf550000,0x3f0e0000,0x3f550000,0xbf7bbf6d,0xbe483f6d,0x3f7bbf6d,0x3e483f6d,0xbe48bf35,0x3f7bbf35,0x3e48bf35,0xbf7bbf35,0x3f553ec4,0xbf0ebec4,0xbf553ec4,0x3f0ebec4,
0x3f353f80,0xbf353f80,0xbf353f80,0x3f353f80,0xbf350000,0x3f350000,0x3f350000,0xbf350000,0xbf35bf80,0x3f35bf80,0x3f35bf80,0xbf35bf80,0x3f350000,0xbf350000,0xbf350000,0x3f350000,
0x3f550000,0x3f0e0000,0xbf550000,0xbf0e0000,0x3e483f6d,0x3f7bbf6d,0xbe483f6d,0xbf7bbf6d,0xbf7bbf35,0x3e48bf35,0x3f7bbf35,0xbe48bf35,0x3f0ebec4,0xbf553ec4,0xbf0ebec4,0x3f553ec4,
0xbec4bf80,0x3f6dbf80,0x3ec4bf80,0xbf6dbf80,0x3f6d3f35,0x3ec4bf35,0xbf6d3f35,0xbec4bf35,0xbf6d0000,0xbec40000,0x3f6d0000,0x3ec40000,0x3ec4bf35,0xbf6d3f35,0xbec4bf35,0x3f6d3f35,
0xbf7b0000,0xbe480000,0x3f7b0000,0x3e480000,0x3f55bec4,0xbf0e3ec4,0xbf55bec4,0x3f0e3ec4,0xbf0e3f35,0xbf553f35,0x3f0e3f35,0x3f553f35,0x3e48bf6d,0xbf7b3f6d,0xbe48bf6d,0x3f7b3f6d,
0,0x3f800000,0,0xbf800000,0,0xbf800000,0,0x3f800000,0,0x3f800000,0,0xbf800000,0,0xbf800000,0,0x3f800000,
0x3e480000,0x3f7b0000,0xbe480000,0xbf7b0000,0x3f0e3ec4,0xbf55bec4,0xbf0e3ec4,0x3f55bec4,0x3f553f35,0x3f0e3f35,0xbf553f35,0xbf0e3f35,0x3f7b3f6d,0xbe48bf6d,0xbf7b3f6d,0x3e48bf6d,
0x3ec40000,0x3f6d0000,0xbec40000,0xbf6d0000,0x3f6d3f35,0xbec4bf35,0xbf6d3f35,0x3ec4bf35,0x3f6d3f80,0xbec43f80,0xbf6d3f80,0x3ec43f80,0x3ec43f35,0x3f6dbf35,0xbec43f35,0xbf6dbf35,
0x3f0e0000,0x3f550000,0xbf0e0000,0xbf550000,0x3f7b3f6d,0x3e48bf6d,0xbf7b3f6d,0xbe48bf6d,0x3e483f35,0xbf7b3f35,0xbe483f35,0x3f7b3f35,0xbf55bec4,0x3f0e3ec4,0x3f55bec4,0xbf0e3ec4,
0x3f350000,0x3f350000,0xbf350000,0xbf350000,0x3f353f80,0x3f35bf80,0xbf353f80,0xbf35bf80,0xbf350000,0xbf350000,0x3f350000,0x3f350000,0xbf35bf80,0xbf353f80,0x3f35bf80,0x3f353f80,
0x3f550000,0x3f0e0000,0xbf550000,0xbf0e0000,0x3e483f6d,0x3f7bbf6d,0xbe483f6d,0xbf7bbf6d,0xbf7bbf35,0x3e48bf35,0x3f7bbf35,0xbe48bf35,0x3f0ebec4,0xbf553ec4,0xbf0ebec4,0x3f553ec4,
0x3f6d0000,0x3ec40000,0xbf6d0000,0xbec40000,0xbec43f35,0x3f6dbf35,0x3ec43f35,0xbf6dbf35,0xbec4bf80,0x3f6dbf80,0x3ec4bf80,0xbf6dbf80,0x3f6d3f35,0x3ec4bf35,0xbf6d3f35,0xbec4bf35,
0x3f7b0000,0x3e480000,0xbf7b0000,0xbe480000,0xbf553ec4,0x3f0ebec4,0x3f553ec4,0xbf0ebec4,0x3f0ebf35,0x3f55bf35,0xbf0ebf35,0xbf55bf35,0xbe483f6d,0x3f7bbf6d,0x3e483f6d,0xbf7bbf6d,
0,0x3f800000,0,0xbf800000,0,0xbf800000,0,0x3f800000,0,0x3f800000,0,0xbf800000,0,0xbf800000,0,0x3f800000,
0x3f7b3f80,0xbe483f80,0xbf7b3f80,0x3e483f80,0x3f553f6d,0x3f0ebf6d,0xbf553f6d,0xbf0ebf6d,0x3f0e3f35,0xbf553f35,0xbf0e3f35,0x3f553f35,0x3e483ec4,0x3f7bbec4,0xbe483ec4,0xbf7bbec4,
0xbec40000,0xbf6d0000,0x3ec40000,0x3f6d0000,0xbf6dbf35,0x3ec43f35,0x3f6dbf35,0xbec43f35,0xbf6dbf80,0x3ec4bf80,0x3f6dbf80,0xbec4bf80,0xbec4bf35,0xbf6d3f35,0x3ec4bf35,0x3f6d3f35,
0xbf55bf80,0x3f0ebf80,0x3f55bf80,0xbf0ebf80,0x3e48bec4,0xbf7b3ec4,0xbe48bec4,0x3f7b3ec4,0x3f7b3f35,0x3e483f35,0xbf7b3f35,0xbe483f35,0x3f0e3f6d,0x3f55bf6d,0xbf0e3f6d,0xbf55bf6d,
0x3f350000,0x3f350000,0xbf350000,0xbf350000,0x3f353f80,0x3f35bf80,0xbf353f80,0xbf35bf80,0xbf350000,0xbf350000,0x3f350000,0x3f350000,0xbf35bf80,0xbf353f80,0x3f35bf80,0x3f353f80,
0x3f0e3f80,0xbf553f80,0xbf0e3f80,0x3f553f80,0xbf7bbec4,0x3e483ec4,0x3f7bbec4,0xbe483ec4,0x3e48bf35,0x3f7bbf35,0xbe48bf35,0xbf7bbf35,0x3f553f6d,0x3f0ebf6d,0xbf553f6d,0xbf0ebf6d,
0xbf6d0000,0xbec40000,0x3f6d0000,0x3ec40000,0x3ec4bf35,0xbf6d3f35,0xbec4bf35,0x3f6d3f35,0x3ec43f80,0xbf6d3f80,0xbec43f80,0x3f6d3f80,0xbf6dbf35,0xbec43f35,0x3f6dbf35,0x3ec43f35,
0xbe48bf80,0x3f7bbf80,0x3e48bf80,0xbf7bbf80,0x3f0e3f6d,0x3f55bf6d,0xbf0e3f6d,0xbf55bf6d,0xbf55bf35,0x3f0ebf35,0x3f55bf35,0xbf0ebf35,0x3f7b3ec4,0x3e48bec4,0xbf7b3ec4,0xbe48bec4,
0,0x3f800000,0,0xbf800000,0,0xbf800000,0,0x3f800000,0,0x3f800000,0,0xbf800000,0,0xbf800000,0,0x3f800000,
0xbe480000,0xbf7b0000,0x3e480000,0x3f7b0000,0xbf0ebec4,0x3f553ec4,0x3f0ebec4,0xbf553ec4,0xbf55bf35,0xbf0ebf35,0x3f55bf35,0x3f0ebf35,0xbf7bbf6d,0x3e483f6d,0x3f7bbf6d,0xbe483f6d,
0x3ec40000,0x3f6d0000,0xbec40000,0xbf6d0000,0x3f6d3f35,0xbec4bf35,0xbf6d3f35,0x3ec4bf35,0x3f6d3f80,0xbec43f80,0xbf6d3f80,0x3ec43f80,0x3ec43f35,0x3f6dbf35,0xbec43f35,0xbf6dbf35,
0xbf0e0000,0xbf550000,0x3f0e0000,0x3f550000,0xbf7bbf6d,0xbe483f6d,0x3f7bbf6d,0x3e483f6d,0xbe48bf35,0x3f7bbf35,0x3e48bf35,0xbf7bbf35,0x3f553ec4,0xbf0ebec4,0xbf553ec4,0x3f0ebec4,
0x3f350000,0x3f350000,0xbf350000,0xbf350000,0x3f353f80,0x3f35bf80,0xbf353f80,0xbf35bf80,0xbf350000,0xbf350000,0x3f350000,0x3f350000,0xbf35bf80,0xbf353f80,0x3f35bf80,0x3f353f80,
0xbf550000,0xbf0e0000,0x3f550000,0x3f0e0000,0xbe48bf6d,0xbf7b3f6d,0x3e48bf6d,0x3f7b3f6d,0x3f7b3f35,0xbe483f35,0xbf7b3f35,0x3e483f35,0xbf0e3ec4,0x3f55bec4,0x3f0e3ec4,0xbf55bec4,
0x3f6d0000,0x3ec40000,0xbf6d0000,0xbec40000,0xbec43f35,0x3f6dbf35,0x3ec43f35,0xbf6dbf35,0xbec4bf80,0x3f6dbf80,0x3ec4bf80,0xbf6dbf80,0x3f6d3f35,0x3ec4bf35,0xbf6d3f35,0xbec4bf35,
0xbf7b0000,0xbe480000,0x3f7b0000,0x3e480000,0x3f55bec4,0xbf0e3ec4,0xbf55bec4,0x3f0e3ec4,0xbf0e3f35,0xbf553f35,0x3f0e3f35,0x3f553f35,0x3e48bf6d,0xbf7b3f6d,0xbe48bf6d,0x3f7b3f6d,
0,0x3f800000,0,0xbf800000,0,0xbf800000,0,0x3f800000,0,0x3f800000,0,0xbf800000,0,0xbf800000,0,0x3f800000,
0xbf7bbf80,0x3e48bf80,0x3f7bbf80,0xbe48bf80,0xbf55bf6d,0xbf0e3f6d,0x3f55bf6d,0x3f0e3f6d,0xbf0ebf35,0x3f55bf35,0x3f0ebf35,0xbf55bf35,0xbe48bec4,0xbf7b3ec4,0x3e48bec4,0x3f7b3ec4,
0xbec40000,0xbf6d0000,0x3ec40000,0x3f6d0000,0xbf6dbf35,0x3ec43f35,0x3f6dbf35,0xbec43f35,0xbf6dbf80,0x3ec4bf80,0x3f6dbf80,0xbec4bf80,0xbec4bf35,0xbf6d3f35,0x3ec4bf35,0x3f6d3f35,
0x3f553f80,0xbf0e3f80,0xbf553f80,0x3f0e3f80,0xbe483ec4,0x3f7bbec4,0x3e483ec4,0xbf7bbec4,0xbf7bbf35,0xbe48bf35,0x3f7bbf35,0x3e48bf35,0xbf0ebf6d,0xbf553f6d,0x3f0ebf6d,0x3f553f6d,
0x3f350000,0x3f350000,0xbf350000,0xbf350000,0x3f353f80,0x3f35bf80,0xbf353f80,0xbf35bf80,0xbf350000,0xbf350000,0x3f350000,0x3f350000,0xbf35bf80,0xbf353f80,0x3f35bf80,0x3f353f80,
0xbf0ebf80,0x3f55bf80,0x3f0ebf80,0xbf55bf80,0x3f7b3ec4,0xbe48bec4,0xbf7b3ec4,0x3e48bec4,0xbe483f35,0xbf7b3f35,0x3e483f35,0x3f7b3f35,0xbf55bf6d,0xbf0e3f6d,0x3f55bf6d,0x3f0e3f6d,
0xbf6d0000,0xbec40000,0x3f6d0000,0x3ec40000,0x3ec4bf35,0xbf6d3f35,0xbec4bf35,0x3f6d3f35,0x3ec43f80,0xbf6d3f80,0xbec43f80,0x3f6d3f80,0xbf6dbf35,0xbec43f35,0x3f6dbf35,0x3ec43f35,
0x3e483f80,0xbf7b3f80,0xbe483f80,0x3f7b3f80,0xbf0ebf6d,0xbf553f6d,0x3f0ebf6d,0x3f553f6d,0x3f553f35,0xbf0e3f35,0xbf553f35,0x3f0e3f35,0xbf7bbec4,0xbe483ec4,0x3f7bbec4,0x3e483ec4,
0x3f800000,0x3f800000,0x3f800000,0x3f7ec46d,0x3f800000,0x3f800000,0x3f7b14be,0x3f74fa0b,0x3f800000,0x3f800000,0x3f6c835e,0x3f61c598,0x3f800000,0x3f800000,0x3f54db31,0x3f45e403,
0x3f800000,0x3f7ffb11,0x3f800000,0x3f7e70b0,0x3f7fec43,0x3f7fd397,0x3f79c79d,0x3f721352,0x3f7fb10f,0x3f7f84ab,0x3f676bd8,0x3f59f26a,0x3f7f4e6d,0x3f7f0e58,0x3f49d112,0x3f373a23,
0x3f800000,0x3f7fec43,0x3f800000,0x3f7e1324,0x3f7fb10f,0x3f7f4e6d,0x3f7853f8,0x3f6ed89e,0x3f7ec46d,0x3f7e1324,0x3f61c598,0x3f514d3d,0x3f7d3aac,0x3f7c3b28,0x3f3daef9,0x3f273656,
0x3f800000,0x3f7fd397,0x3f800000,0x3f7dabcc,0x3f7f4e6d,0x3f7e70b0,0x3f76ba07,0x3f6b4b0c,0x3f7d3aac,0x3f7baccd,0x3f5b941a,0x3f47de65,0x3f79c79d,0x3f778bc5,0x3f3085bb,0x3f15f6d9,
0x3f800000,0x3f7fb10f,0x3f800000,0x3f7d3aac,0x3f7ec46d,0x3f7d3aac,0x3f74fa0b,0x3f676bd8,0x3f7b14be,0x3f7853f8,0x3f54db31,0x3f3daef9,0x3f74fa0b,0x3f710908,0x3f226799,0x3f039c3d,
0x3f800000,0x3f7f84ab,0x3f800000,0x3f7cbfc9,0x3f7e1324,0x3f7baccd,0x3f731447,0x3f633c5a,0x3f7853f8,0x3f740bdd,0x3f4d9f02,0x3f32c8c9,0x3f6ed89e,0x3f68bf3c,0x3f13682a,0x3ee0924f,
0x3f800000,0x3f7f4e6d,0x3f800000,0x3f7c3b28,0x3f7d3aac,0x3f79c79d,0x3f710908,0x3f5ebe05,0x3f74fa0b,0x3f6ed89e,0x3f45e403,0x3f273656,0x3f676bd8,0x3f5ebe05,0x3f039c3d,0x3eb8442a,
0x3f800000,0x3f7f0e58,0x3f800000,0x3f7baccd,0x3f7c3b28,0x3f778bc5,0x3f6ed89e,0x3f59f26a,0x3f710908,0x3f68bf3c,0x3f3daef9,0x3f1b02c6,0x3f5ebe05,0x3f531849,0x3ee63375,0x3e8e9a22,
0x3f800000,0x3f800000,0x3f3504f3,0x3f226799,0x3f800000,0x3f800000,0x3f0e39da,0x3ef15aea,0x3f800000,0x3f800000,0x3ec3ef15,0x3e94a031,0x3f800000,0x3f800000,0x3e47c5c2,0x3dc8bd36,
0x3f7ec46d,0x3f7e70b0,0x3f226799,0x3f0b9a6b,0x3f7e1324,0x3f7dabcc,0x3ee63375,0x3eb263ef,0x3f7d3aac,0x3f7cbfc9,0x3e78cfcc,0x3e09cf86,0x3f7c3b28,0x3f7baccd,0x3cc90ab0,0xbdafb680,
0x3f7b14be,0x3f79c79d,0x3f0e39da,0x3ee63375,0x3f7853f8,0x3f76ba07,0x3eac7cd4,0x3e605c13,0x3f74fa0b,0x3f731447,0x3dc8bd36,0xbcc90ab0,0x3f710908,0x3f6ed89e,0xbe164083,0xbe888e93,
0x3f74fa0b,0x3f721352,0x3ef15aea,0x3eb263ef,0x3f6ed89e,0x3f6b4b0c,0x3e605c13,0x3dafb680,0x3f676bd8,0x3f633c5a,0xbd48fb30,0xbe3b6ecf,0x3f5ebe05,0x3f59f26a,0xbea09ae5,0xbee0924f,
0x3f6c835e,0x3f676bd8,0x3ec3ef15,0x3e78cfcc,0x3f61c598,0x3f5b941a,0x3dc8bd36,0xbd48fb30,0x3f54db31,0x3f4d9f02,0xbe47c5c2,0xbeac7cd4,0x3f45e403,0x3f3daef9,0xbef15aea,0xbf187fc0,
0x3f61c598,0x3f59f26a,0x3e94a031,0x3e09cf86,0x3f514d3d,0x3f47de65,0xbcc90ab0,0xbe3b6ecf,0x3f3daef9,0x3f32c8c9,0xbeac7cd4,0xbef6e0cb,0x3f273656,0x3f1b02c6,0xbf1d7fd1,0xbf3b8f3b,
0x3f54db31,0x3f49d112,0x3e47c5c2,0x3cc90ab0,0x3f3daef9,0x3f3085bb,0xbe164083,0xbea09ae5,0x3f226799,0x3f13682a,0xbef15aea,0xbf1d7fd1,0x3f039c3d,0x3ee63375,0xbf3daef9,0xbf584853,
0x3f45e403,0x3f373a23,0x3dc8bd36,0xbdafb680,0x3f273656,0x3f15f6d9,0xbe888e93,0xbee0924f,0x3f039c3d,0x3ee0924f,0xbf187fc0,0xbf3b8f3b,0x3eb8442a,0x3e8e9a22,0xbf584853,0xbf6db293,
0x3f800000,0x3f800000,0,0xbdc8bd36,0x3f800000,0x3f800000,0xbe47c5c2,0xbe94a031,0x3f800000,0x3f800000,0xbec3ef15,0xbef15aea,0x3f800000,0x3f800000,0xbf0e39da,0xbf226799,
0x3f7b14be,0x3f7a7302,0xbe47c5c2,0xbe9aa086,0x3f79c79d,0x3f791298,0xbecf7bca,0xbf00e7e4,0x3f7853f8,0x3f778bc5,0xbf187fc0,0xbf2e3bde,0x3f76ba07,0x3f75dec6,0xbf41d870,0xbf531849,
0x3f6c835e,0x3f6a09a7,0xbec3ef15,0xbefc5d27,0x3f676bd8,0x3f64aa59,0xbf187fc0,0xbf3085bb,0x3f61c598,0x3f5ebe05,0xbf45e403,0xbf584853,0x3f5b941a,0x3f584853,0xbf676bd8,0xbf731447,
0x3f54db31,0x3f4f7a1f,0xbf0e39da,0xbf299415,0x3f49d112,0x3f43e200,0xbf41d870,0xbf5695e5,0x3f3daef9,0x3f373a23,0xbf676bd8,0xbf740bdd,0x3f3085bb,0x3f299415,0xbf7c3b28,0xbf7fd397,
0x3f3504f3,0x3f2beb4a,0xbf3504f3,0xbf4d9f02,0x3f226799,0x3f187fc0,0xbf61c598,0xbf710908,0x3f0e39da,0x3f039c3d,0xbf7b14be,0xbf7fb10f,0x3ef15aea,0x3edae880,0xbf7ec46d,0xbf7853f8,
0x3f0e39da,0x3f00e7e4,0xbf54db31,0xbf68bf3c,0x3ee63375,0x3ec9b953,0xbf76ba07,0xbf7e70b0,0x3eac7cd4,0x3e8e9a22,0xbf7fb10f,0xbf7a7302,0x3e605c13,0x3e22abb6,0xbf6ed89e,0xbf5d2d53,
0x3ec3ef15,0x3ea09ae5,0xbf6c835e,0xbf79c79d,0x3e78cfcc,0x3e2f10a2,0xbf7fb10f,0xbf7e1324,0x3dc8bd36,0x3cc90ab0,0xbf74fa0b,0xbf64aa59,0xbd48fb30,0xbdfab273,0xbf4d9f02,0xbf3085bb,
0x3e47c5c2,0x3de1bc2e,0xbf7b14be,0xbf7ffb11,0x3cc90ab0,0xbd7b2b74,0xbf7c3b28,0xbf6ff573,0xbe164083,0xbe6c9a7f,0xbf5b941a,0xbf3fc767,0xbea09ae5,0xbec9b953,0xbf1d7fd1,0xbeebcbbb,
0x3f800000,0x3f800000,0xbf3504f3,0xbf45e403,0x3f800000,0x3f800000,0xbf54db31,0xbf61c598,0x3f800000,0x3f800000,0xbf6c835e,0xbf74fa0b,0x3f800000,0x3f800000,0xbf7b14be,0xbf7ec46d,
0x3f74fa0b,0x3f740bdd,0xbf61c598,0xbf6db293,0x3f731447,0x3f721352,0xbf76ba07,0xbf7cbfc9,0x3f710908,0x3f6ff573,0xbf7fb10f,0xbf7f84ab,0x3f6ed89e,0x3f6db293,0xbf7c3b28,0xbf75dec6,
0x3f54db31,0x3f514d3d,0xbf7b14be,0xbf7f4e6d,0x3f4d9f02,0x3f49d112,0xbf7fb10f,0xbf7c3b28,0x3f45e403,0x3f41d870,0xbf74fa0b,0xbf6a09a7,0x3f3daef9,0x3f396842,0xbf5b941a,0xbf49d112,
0x3f226799,0x3f1b02c6,0xbf7ec46d,0xbf791298,0x3f13682a,0x3f0b9a6b,0xbf6ed89e,0xbf604621,0x3f039c3d,0x3ef6e0cb,0xbf4d9f02,0xbf373a23,0x3ee63375,0x3ed53641,0xbf1d7fd1,0xbf00e7e4,
0x3ec3ef15,0x3eac7cd4,0xbf6c835e,0xbf5b941a,0x3e94a031,0x3e78cfcc,0xbf45e403,0xbf2beb4a,0x3e47c5c2,0x3e164083,0xbf0e39da,0xbedae880,0x3dc8bd36,0x3d48fb30,0xbe94a031,0xbe164083,
0x3dc8bd36,0x3d16c32c,0xbf45e403,0xbf299415,0xbcc90ab0,0xbdafb680,0xbf08f59b,0xbec9b953,0xbe164083,0xbe541501,0xbe78cfcc,0xbdafb680,0xbe888e93,0xbea68f12,0x3d96a905,0x3e6c9a7f,
0xbe47c5c2,0xbe888e93,0xbf0e39da,0xbecf7bca,0xbeac7cd4,0xbecf7bca,0xbe78cfcc,0xbd96a905,0xbef15aea,0xbf08f59b,0x3dc8bd36,0x3e888e93,0xbf187fc0,0xbf273656,0x3edae880,0x3f13682a,
0xbef15aea,0xbf0b9a6b,0xbe94a031,0xbde1bc2e,0xbf1d7fd1,0xbf2e3bde,0x3d96a905,0x3e827dc0,0xbf3daef9,0xbf4bbbf8,0x3edae880,0x3f15f6d9,0xbf584853,0xbf633c5a,0x3f396842,0x3f5695e5,
0,0,0,0x3dc8bd36,0,0,0x3e47c5c2,0x3e94a031,0,0,0x3ec3ef15,0x3ef15aea,0,0,0x3f0e39da,0x3f226799,
0,0x3c490e90,0,0x3de1bc2e,0x3cc90ab0,0x3d16c32c,0x3e605c13,0x3ea68f12,0x3d48fb30,0x3d7b2b74,0x3edae880,0x3f064b82,0x3d96a905,0x3dafb680,0x3f1d7fd1,0x3f32c8c9,
0,0x3cc90ab0,0,0x3dfab273,0x3d48fb30,0x3d96a905,0x3e78cfcc,0x3eb8442a,0x3dc8bd36,0x3dfab273,0x3ef15aea,0x3f13682a,0x3e164083,0x3e2f10a2,0x3f2beb4a,0x3f41d870,
0,0x3d16c32c,0,0x3e09cf86,0x3d96a905,0x3de1bc2e,0x3e888e93,0x3ec9b953,0x3e164083,0x3e3b6ecf,0x3f039c3d,0x3f1ff6cb,0x3e605c13,0x3e827dc0,0x3f396842,0x3f4f7a1f,
0,0x3d48fb30,0,0x3e164083,0x3dc8bd36,0x3e164083,0x3e94a031,0x3edae880,0x3e47c5c2,0x3e78cfcc,0x3f0e39da,0x3f2beb4a,0x3e94a031,0x3eac7cd4,0x3f45e403,0x3f5b941a,
0,0x3d7b2b74,0,0x3e22abb6,0x3dfab273,0x3e3b6ecf,0x3ea09ae5,0x3eebcbbb,0x3e78cfcc,0x3e9aa086,0x3f187fc0,0x3f373a23,0x3eb8442a,0x3ed53641,0x3f514d3d,0x3f660f88,
0,0x3d96a905,0,0x3e2f10a2,0x3e164083,0x3e605c13,0x3eac7cd4,0x3efc5d27,0x3e94a031,0x3eb8442a,0x3f226799,0x3f41d870,0x3edae880,0x3efc5d27,0x3f5b941a,0x3f6ed89e,
0,0x3dafb680,0,0x3e3b6ecf,0x3e2f10a2,0x3e827dc0,0x3eb8442a,0x3f064b82,0x3eac7cd4,0x3ed53641,0x3f2beb4a,0x3f4bbbf8,0x3efc5d27,0x3f10d3cd,0x3f64aa59,0x3f75dec6,
0,0,0x3f3504f3,0x3f45e403,0,0,0x3f54db31,0x3f61c598,0,0,0x3f6c835e,0x3f74fa0b,0,0,0x3f7b14be,0x3f7ec46d,
0x3dc8bd36,0x3de1bc2e,0x3f45e403,0x3f5695e5,0x3dfab273,0x3e09cf86,0x3f64aa59,0x3f6ff573,0x3e164083,0x3e22abb6,0x3f7853f8,0x3f7dabcc,0x3e2f10a2,0x3e3b6ecf,0x3f7fec43,0x3f7f0e58,
0x3e47c5c2,0x3e605c13,0x3f54db31,0x3f64aa59,0x3e78cfcc,0x3e888e93,0x3f710908,0x3f79c79d,0x3e94a031,0x3ea09ae5,0x3f7ec46d,0x3f7fec43,0x3eac7cd4,0x3eb8442a,0x3f7d3aac,0x3f76ba07,
0x3e94a031,0x3ea68f12,0x3f61c598,0x3f6ff573,0x3eb8442a,0x3ec9b953,0x3f79c79d,0x3f7f0e58,0x3edae880,0x3eebcbbb,0x3f7fb10f,0x3f7baccd,0x3efc5d27,0x3f064b82,0x3f731447,0x3f660f88,
0x3ec3ef15,0x3edae880,0x3f6c835e,0x3f7853f8,0x3ef15aea,0x3f039c3d,0x3f7ec46d,0x3f7fb10f,0x3f0e39da,0x3f187fc0,0x3f7b14be,0x3f710908,0x3f226799,0x3f2beb4a,0x3f61c598,0x3f4d9f02,
0x3ef15aea,0x3f064b82,0x3f74fa0b,0x3f7dabcc,0x3f13682a,0x3f1ff6cb,0x3f7fec43,0x3f7baccd,0x3f2beb4a,0x3f373a23,0x3f710908,0x3f604621,0x3f41d870,0x3f4bbbf8,0x3f49d112,0x3f2e3bde,
0x3f0e39da,0x3f1d7fd1,0x3f7b14be,0x3f7fec43,0x3f2beb4a,0x3f396842,0x3f7d3aac,0x3f731447,0x3f45e403,0x3f514d3d,0x3f61c598,0x3f49d112,0x3f5b941a,0x3f64aa59,0x3f2beb4a,0x3f08f59b,
0x3f226799,0x3f32c8c9,0x3f7ec46d,0x3f7f0e58,0x3f41d870,0x3f4f7a1f,0x3f76ba07,0x3f660f88,0x3f5b941a,0x3f660f88,0x3f4d9f02,0x3f2e3bde,0x3f6ed89e,0x3f75dec6,0x3f08f59b,0x3ebe1d4a,
0,0,0x3f800000,0x3f7ec46d,0,0,0x3f7b14be,0x3f74fa0b,0,0,0x3f6c835e,0x3f61c598,0,0,0x3f54db31,0x3f45e403,
0x3e47c5c2,0x3e541501,0x3f7b14be,0x3f740bdd,0x3e605c13,0x3e6c9a7f,0x3f6a09a7,0x3f5d2d53,0x3e78cfcc,0x3e827dc0,0x3f4d9f02,0x3f3b8f3b,0x3e888e93,0x3e8e9a22,0x3f273656,0x3f10d3cd,
0x3ec3ef15,0x3ecf7bca,0x3f6c835e,0x3f5ebe05,0x3edae880,0x3ee63375,0x3f4d9f02,0x3f396842,0x3ef15aea,0x3efc5d27,0x3f226799,0x3f08f59b,0x3f039c3d,0x3f08f59b,0x3edae880,0x3ea09ae5,
0x3f0e39da,0x3f15f6d9,0x3f54db31,0x3f3fc767,0x3f1d7fd1,0x3f24d225,0x3f273656,0x3f0b9a6b,0x3f2beb4a,0x3f32c8c9,0x3edae880,0x3e9aa086,0x3f396842,0x3f3fc767,0x3e2f10a2,0x3d16c32c,
0x3f3504f3,0x3f3daef9,0x3f3504f3,0x3f187fc0,0x3f45e403,0x3f4d9f02,0x3ef15aea,0x3eac7cd4,0x3f54db31,0x3f5b941a,0x3e47c5c2,0x3d48fb30,0x3f61c598,0x3f676bd8,0xbdc8bd36,0xbe78cfcc,
0x3f54db31,0x3f5d2d53,0x3f0e39da,0x3ed53641,0x3f64aa59,0x3f6b4b0c,0x3e888e93,0x3de1bc2e,0x3f710908,0x3f75dec6,0xbd48fb30,0xbe541501,0x3f79c79d,0x3f7cbfc9,0xbeb8442a,0xbf00e7e4,
0x3f6c835e,0x3f731447,0x3ec3ef15,0x3e605c13,0x3f7853f8,0x3f7c3b28,0x3d48fb30,0xbdfab273,0x3f7ec46d,0x3f7fec43,0xbe94a031,0xbee63375,0x3f7fb10f,0x3f7e1324,0xbf187fc0,0xbf396842,
0x3f7b14be,0x3f7e70b0,0x3e47c5c2,0x3c490e90,0x3f7fec43,0x3f7f84ab,0xbe2f10a2,0xbeb263ef,0x3f7d3aac,0x3f791298,0xbf039c3d,0xbf299415,0x3f731447,0x3f6b4b0c,0xbf49d112,0xbf633c5a,
0,0,0x3f3504f3,0x3f226799,0,0,0x3f0e39da,0x3ef15aea,0,0,0x3ec3ef15,0x3e94a031,0,0,0x3e47c5c2,0x3dc8bd36,
0x3e94a031,0x3e9aa086,0x3ef15aea,0x3ebe1d4a,0x3ea09ae5,0x3ea68f12,0x3e888e93,0x3e22abb6,0x3eac7cd4,0x3eb263ef,0x3d48fb30,0xbd7b2b74,0x3eb8442a,0x3ebe1d4a,0xbe2f10a2,0xbe8e9a22,
0x3f0e39da,0x3f13682a,0x3e47c5c2,0x3d96a905,0x3f187fc0,0x3f1d7fd1,0xbd48fb30,0xbe2f10a2,0x3f226799,0x3f273656,0xbe94a031,0xbecf7bca,0x3f2beb4a,0x3f3085bb,0xbf039c3d,0xbf1d7fd1,
0x3f45e403,0x3f4bbbf8,0xbdc8bd36,0xbe6c9a7f,0x3f514d3d,0x3f5695e5,0xbeb8442a,0xbef6e0cb,0x3f5b941a,0x3f604621,0xbf187fc0,0xbf32c8c9,0x3f64aa59,0x3f68bf3c,0xbf49d112,0xbf5d2d53,
0x3f6c835e,0x3f710908,0xbec3ef15,0xbf039c3d,0x3f74fa0b,0x3f7853f8,0xbf226799,0xbf3daef9,0x3f7b14be,0x3f7d3aac,0xbf54db31,0xbf676bd8,0x3f7ec46d,0x3f7fb10f,0xbf74fa0b,0xbf7d3aac,
0x3f7ec46d,0x3f7fd397,0xbf226799,0xbf3fc767,0x3f7fec43,0x3f7f0e58,0xbf584853,0xbf6b4b0c,0x3f7d3aac,0x3f7a7302,0xbf7853f8,0xbf7f0e58,0x3f76ba07,0x3f721352,0xbf7f4e6d,0xbf791298,
0x3f7b14be,0x3f76ba07,0xbf54db31,0xbf6a09a7,0x3f710908,0x3f6a09a7,0xbf7853f8,0xbf7f4e6d,0x3f61c598,0x3f584853,0xbf7ec46d,0xbf76ba07,0x3f4d9f02,0x3f41d870,0xbf676bd8,0xbf514d3d,
0x3f61c598,0x3f5695e5,0xbf74fa0b,0xbf7e70b0,0x3f49d112,0x3f3b8f3b,0xbf7f4e6d,0xbf778bc5,0x3f2beb4a,0x3f1b02c6,0xbf676bd8,0xbf4f7a1f,0x3f08f59b,0x3eebcbbb,0xbf3085bb,0xbf0b9a6b,
0x3f800000,0x3f7fffb1,0x3f7ffec4,0x3f7ffd39,0x3f7ffb11,0x3f7ff84a,0x3f7ff4e6,0x3f7ff0e3,0x3f7fec43,0x3f7fe705,0x3f7fe129,0x3f7fdaaf,0x3f7fd397,0x3f7fcbe2,0x3f7fc38f,0x3f7fba9e,
0x3f7fb10f,0x3f7fa6e3,0x3f7f9c18,0x3f7f90b1,0x3f7f84ab,0x3f7f7808,0x3f7f6ac7,0x3f7f5ce9,0x3f7f4e6d,0x3f7f3f54,0x3f7f2f9d,0x3f7f1f49,0x3f7f0e58,0x3f7efcc9,0x3f7eea9d,0x3f7ed7d4,
0x3f7ec46d,0x3f7eb069,0x3f7e9bc9,0x3f7e868b,0x3f7e70b0,0x3f7e5a38,0x3f7e4323,0x3f7e2b72,0x3f7e1324,0x3f7dfa38,0x3f7de0b1,0x3f7dc68c,0x3f7dabcc,0x3f7d906e,0x3f7d7474,0x3f7d57de,
0x3f7d3aac,0x3f7d1cdd,0x3f7cfe73,0x3f7cdf6c,0x3f7cbfc9,0x3f7c9f8a,0x3f7c7eb0,0x3f7c5d3a,0x3f7c3b28,0x3f7c187a,0x3f7bf531,0x3f7bd14d,0x3f7baccd,0x3f7b87b2,0x3f7b61fc,0x3f7b3bab,
0x3f7b14be,0x3f7aed37,0x3f7ac516,0x3f7a9c59,0x3f7a7302,0x3f7a4910,0x3f7a1e84,0x3f79f35e,0x3f79c79d,0x3f799b43,0x3f796e4e,0x3f7940c0,0x3f791298,0x3f78e3d6,0x3f78b47b,0x3f788486,
0x3f7853f8,0x3f7822d1,0x3f77f110,0x3f77beb7,0x3f778bc5,0x3f77583a,0x3f772417,0x3f76ef5b,0x3f76ba07,0x3f76841b,0x3f764d97,0x3f76167a,0x3f75dec6,0x3f75a67b,0x3f756d97,0x3f75341d,
0x3f74fa0b,0x3f74bf62,0x3f748422,0x3f74484b,0x3f740bdd,0x3f73ced9,0x3f73913f,0x3f73530e,0x3f731447,0x3f72d4eb,0x3f7294f8,0x3f725470,0x3f721352,0x3f71d19f,0x3f718f57,0x3f714c7a,
0x3f710908,0x3f70c501,0x3f708066,0x3f703b37,0x3f6ff573,0x3f6faf1b,0x3f6f6830,0x3f6f20b0,0x3f6ed89e,0x3f6e8ff8,0x3f6e46be,0x3f6dfcf2,0x3f6db293,0x3f6d67a1,0x3f6d1c1d,0x3f6cd007,
0x3f6c835e,0x3f6c3624,0x3f6be858,0x3f6b99fb,0x3f6b4b0c,0x3f6afb8c,0x3f6aab7b,0x3f6a5ad9,0x3f6a09a7,0x3f69b7e4,0x3f696591,0x3f6912ae,0x3f68bf3c,0x3f686b39,0x3f6816a8,0x3f67c187,
0x3f676bd8,0x3f671599,0x3f66becc,0x3f666771,0x3f660f88,0x3f65b710,0x3f655e0b,0x3f650479,0x3f64aa59,0x3f644fac,0x3f63f473,0x3f6398ac,0x3f633c5a,0x3f62df7b,0x3f628210,0x3f62241a,
0x3f61c598,0x3f61668a,0x3f6106f2,0x3f60a6cf,0x3f604621,0x3f5fe4e9,0x3f5f8327,0x3f5f20db,0x3f5ebe05,0x3f5e5aa6,0x3f5df6be,0x3f5d924d,0x3f5d2d53,0x3f5cc7d1,0x3f5c61c7,0x3f5bfb34,
0x3f5b941a,0x3f5b2c79,0x3f5ac450,0x3f5a5ba0,0x3f59f26a,0x3f5988ad,0x3f591e6a,0x3f58b3a1,0x3f584853,0x3f57dc7f,0x3f577026,0x3f570348,0x3f5695e5,0x3f5627fe,0x3f55b993,0x3f554aa4,
0x3f54db31,0x3f546b3b,0x3f53fac3,0x3f5389c7,0x3f531849,0x3f52a649,0x3f5233c6,0x3f51c0c2,0x3f514d3d,0x3f50d937,0x3f5064af,0x3f4fefa8,0x3f4f7a1f,0x3f4f0417,0x3f4e8d90,0x3f4e1689,
0x3f4d9f02,0x3f4d26fd,0x3f4cae79,0x3f4c3578,0x3f4bbbf8,0x3f4b41fa,0x3f4ac77f,0x3f4a4c87,0x3f49d112,0x3f495521,0x3f48d8b3,0x3f485bca,0x3f47de65,0x3f476085,0x3f46e22a,0x3f466354,
0x3f45e403,0x3f456439,0x3f44e3f5,0x3f446337,0x3f43e200,0x3f436051,0x3f42de29,0x3f425b89,0x3f41d870,0x3f4154e1,0x3f40d0da,0x3f404c5c,0x3f3fc767,0x3f3f41fc,0x3f3ebc1b,0x3f3e35c5,
0x3f3daef9,0x3f3d27b8,0x3f3ca003,0x3f3c17d9,0x3f3b8f3b,0x3f3b0629,0x3f3a7ca4,0x3f39f2ac,0x3f396842,0x3f38dd65,0x3f385216,0x3f37c655,0x3f373a23,0x3f36ad7f,0x3f36206c,0x3f3592e7,
0x3f3504f3,0x3f34768f,0x3f33e7bc,0x3f33587a,0x3f32c8c9,0x3f3238aa,0x3f31a81d,0x3f311722,0x3f3085bb,0x3f2ff3e6,0x3f2f61a5,0x3f2ecef7,0x3f2e3bde,0x3f2da859,0x3f2d1469,0x3f2c800f,
0x3f2beb4a,0x3f2b561b,0x3f2ac082,0x3f2a2a80,0x3f299415,0x3f28fd41,0x3f286605,0x3f27ce61,0x3f273656,0x3f269de3,0x3f26050a,0x3f256bcb,0x3f24d225,0x3f24381a,0x3f239da9,0x3f2302d3,
0x3f226799,0x3f21cbfb,0x3f212ff9,0x3f209393,0x3f1ff6cb,0x3f1f599f,0x3f1ebc12,0x3f1e1e22,0x3f1d7fd1,0x3f1ce11f,0x3f1c420c,0x3f1ba299,0x3f1b02c6,0x3f1a6293,0x3f19c200,0x3f19210f,
0x3f187fc0,0x3f17de12,0x3f173c07,0x3f16999f,0x3f15f6d9,0x3f1553b7,0x3f14b039,0x3f140c5f,0x3f13682a,0x3f12c39a,0x3f121eb0,0x3f11796b,0x3f10d3cd,0x3f102dd5,0x3f0f8784,0x3f0ee0db,
0x3f0e39da,0x3f0d9281,0x3f0cead0,0x3f0c42c9,0x3f0b9a6b,0x3f0af1b7,0x3f0a48ad,0x3f099f4e,0x3f08f59b,0x3f084b92,0x3f07a136,0x3f06f686,0x3f064b82,0x3f05a02c,0x3f04f484,0x3f044889,
0x3f039c3d,0x3f02ef9f,0x3f0242b1,0x3f019573,0x3f00e7e4,0x3f003a06,0x3eff17b2,0x3efdbabb,0x3efc5d27,0x3efafef7,0x3ef9a02d,0x3ef840c8,0x3ef6e0cb,0x3ef58035,0x3ef41f07,0x3ef2bd43,
0x3ef15aea,0x3eeff7fb,0x3eee9479,0x3eed3063,0x3eebcbbb,0x3eea6681,0x3ee900b7,0x3ee79a5d,0x3ee63375,0x3ee4cbfe,0x3ee363fa,0x3ee1fb6a,0x3ee0924f,0x3edf28a9,0x3eddbe79,0x3edc53c1,
0x3edae880,0x3ed97cb9,0x3ed8106b,0x3ed6a399,0x3ed53641,0x3ed3c867,0x3ed25a09,0x3ed0eb2a,0x3ecf7bca,0x3ece0bea,0x3ecc9b8b,0x3ecb2aae,0x3ec9b953,0x3ec8477c,0x3ec6d529,0x3ec5625c,
0x3ec3ef15,0x3ec27b55,0x3ec1071e,0x3ebf926f,0x3ebe1d4a,0x3ebca7af,0x3ebb31a0,0x3eb9bb1e,0x3eb8442a,0x3eb6ccc3,0x3eb554ec,0x3eb3dca5,0x3eb263ef,0x3eb0eacb,0x3eaf713a,0x3eadf73c,
0x3eac7cd4,0x3eab0201,0x3ea986c4,0x3ea80b1f,0x3ea68f12,0x3ea5129f,0x3ea395c5,0x3ea21887,0x3ea09ae5,0x3e9f1cdf,0x3e9d9e78,0x3e9c1faf,0x3e9aa086,0x3e9920fe,0x3e97a117,0x3e9620d2,
0x3e94a031,0x3e931f35,0x3e919ddd,0x3e901c2c,0x3e8e9a22,0x3e8d17c0,0x3e8b9507,0x3e8a11f7,0x3e888e93,0x3e870ada,0x3e8586ce,0x3e840270,0x3e827dc0,0x3e80f8c0,0x3e7ee6e1,0x3e7bdba4,
0x3e78cfcc,0x3e75c35a,0x3e72b651,0x3e6fa8b2,0x3e6c9a7f,0x3e698bba,0x3e667c66,0x3e636c83,0x3e605c13,0x3e5d4b1a,0x3e5a3997,0x3e57278f,0x3e541501,0x3e5101f1,0x3e4dee60,0x3e4ada4f,
0x3e47c5c2,0x3e44b0b9,0x3e419b37,0x3e3e853e,0x3e3b6ecf,0x3e3857ec,0x3e354098,0x3e3228d4,0x3e2f10a2,0x3e2bf804,0x3e28defc,0x3e25c58c,0x3e22abb6,0x3e1f917b,0x3e1c76de,0x3e195be0,
0x3e164083,0x3e1324ca,0x3e1008b7,0x3e0cec4a,0x3e09cf86,0x3e06b26e,0x3e039502,0x3e007745,0x3dfab273,0x3df475c0,0x3dee3876,0x3de7fa9a,0x3de1bc2e,0x3ddb7d37,0x3dd53db9,0x3dcefdb7,
0x3dc8bd36,0x3dc27c39,0x3dbc3ac3,0x3db5f8da,0x3dafb680,0x3da973ba,0x3da3308c,0x3d9cecf9,0x3d96a905,0x3d9064b4,0x3d8a200a,0x3d83db0a,0x3d7b2b74,0x3d6ea038,0x3d621469,0x3d55880e,
0x3d48fb30,0x3d3c6dd5,0x3d2fe007,0x3d2351cb,0x3d16c32c,0x3d0a342f,0x3cfb49ba,0x3ce22a7a,0x3cc90ab0,0x3cafea69,0x3c96c9b6,0x3c7b514b,0x3c490e90,0x3c16cb58,0x3bc90f88,0x3b490fc6,
0,0x3b490fc6,0x3bc90f88,0x3c16cb58,0x3c490e90,0x3c7b514b,0x3c96c9b6,0x3cafea69,0x3cc90ab0,0x3ce22a7a,0x3cfb49ba,0x3d0a342f,0x3d16c32c,0x3d2351cb,0x3d2fe007,0x3d3c6dd5,
0x3d48fb30,0x3d55880e,0x3d621469,0x3d6ea038,0x3d7b2b74,0x3d83db0a,0x3d8a200a,0x3d9064b4,0x3d96a905,0x3d9cecf9,0x3da3308c,0x3da973ba,0x3dafb680,0x3db5f8da,0x3dbc3ac3,0x3dc27c39,
0x3dc8bd36,0x3dcefdb7,0x3dd53db9,0x3ddb7d37,0x3de1bc2e,0x3de7fa9a,0x3dee3876,0x3df475c0,0x3dfab273,0x3e007745,0x3e039502,0x3e06b26e,0x3e09cf86,0x3e0cec4a,0x3e1008b7,0x3e1324ca,
0x3e164083,0x3e195be0,0x3e1c76de,0x3e1f917b,0x3e22abb6,0x3e25c58c,0x3e28defc,0x3e2bf804,0x3e2f10a2,0x3e3228d4,0x3e354098,0x3e3857ec,0x3e3b6ecf,0x3e3e853e,0x3e419b37,0x3e44b0b9,
0x3e47c5c2,0x3e4ada4f,0x3e4dee60,0x3e5101f1,0x3e541501,0x3e57278f,0x3e5a3997,0x3e5d4b1a,0x3e605c13,0x3e636c83,0x3e667c66,0x3e698bba,0x3e6c9a7f,0x3e6fa8b2,0x3e72b651,0x3e75c35a,
0x3e78cfcc,0x3e7bdba4,0x3e7ee6e1,0x3e80f8c0,0x3e827dc0,0x3e840270,0x3e8586ce,0x3e870ada,0x3e888e93,0x3e8a11f7,0x3e8b9507,0x3e8d17c0,0x3e8e9a22,0x3e901c2c,0x3e919ddd,0x3e931f35,
0x3e94a031,0x3e9620d2,0x3e97a117,0x3e9920fe,0x3e9aa086,0x3e9c1faf,0x3e9d9e78,0x3e9f1cdf,0x3ea09ae5,0x3ea21887,0x3ea395c5,0x3ea5129f,0x3ea68f12,0x3ea80b1f,0x3ea986c4,0x3eab0201,
0x3eac7cd4,0x3eadf73c,0x3eaf713a,0x3eb0eacb,0x3eb263ef,0x3eb3dca5,0x3eb554ec,0x3eb6ccc3,0x3eb8442a,0x3eb9bb1e,0x3ebb31a0,0x3ebca7af,0x3ebe1d4a,0x3ebf926f,0x3ec1071e,0x3ec27b55,
0x3ec3ef15,0x3ec5625c,0x3ec6d529,0x3ec8477c,0x3ec9b953,0x3ecb2aae,0x3ecc9b8b,0x3ece0bea,0x3ecf7bca,0x3ed0eb2a,0x3ed25a09,0x3ed3c867,0x3ed53641,0x3ed6a399,0x3ed8106b,0x3ed97cb9,
0x3edae880,0x3edc53c1,0x3eddbe79,0x3edf28a9,0x3ee0924f,0x3ee1fb6a,0x3ee363fa,0x3ee4cbfe,0x3ee63375,0x3ee79a5d,0x3ee900b7,0x3eea6681,0x3eebcbbb,0x3eed3063,0x3eee9479,0x3eeff7fb,
0x3ef15aea,0x3ef2bd43,0x3ef41f07,0x3ef58035,0x3ef6e0cb,0x3ef840c8,0x3ef9a02d,0x3efafef7,0x3efc5d27,0x3efdbabb,0x3eff17b2,0x3f003a06,0x3f00e7e4,0x3f019573,0x3f0242b1,0x3f02ef9f,
0x3f039c3d,0x3f044889,0x3f04f484,0x3f05a02c,0x3f064b82,0x3f06f686,0x3f07a136,0x3f084b92,0x3f08f59b,0x3f099f4e,0x3f0a48ad,0x3f0af1b7,0x3f0b9a6b,0x3f0c42c9,0x3f0cead0,0x3f0d9281,
0x3f0e39da,0x3f0ee0db,0x3f0f8784,0x3f102dd5,0x3f10d3cd,0x3f11796b,0x3f121eb0,0x3f12c39a,0x3f13682a,0x3f140c5f,0x3f14b039,0x3f1553b7,0x3f15f6d9,0x3f16999f,0x3f173c07,0x3f17de12,
0x3f187fc0,0x3f19210f,0x3f19c200,0x3f1a6293,0x3f1b02c6,0x3f1ba299,0x3f1c420c,0x3f1ce11f,0x3f1d7fd1,0x3f1e1e22,0x3f1ebc12,0x3f1f599f,0x3f1ff6cb,0x3f209393,0x3f212ff9,0x3f21cbfb,
0x3f226799,0x3f2302d3,0x3f239da9,0x3f24381a,0x3f24d225,0x3f256bcb,0x3f26050a,0x3f269de3,0x3f273656,0x3f27ce61,0x3f286605,0x3f28fd41,0x3f299415,0x3f2a2a80,0x3f2ac082,0x3f2b561b,
0x3f2beb4a,0x3f2c800f,0x3f2d1469,0x3f2da859,0x3f2e3bde,0x3f2ecef7,0x3f2f61a5,0x3f2ff3e6,0x3f3085bb,0x3f311722,0x3f31a81d,0x3f3238aa,0x3f32c8c9,0x3f33587a,0x3f33e7bc,0x3f34768f,
0x3f3504f3,0x3f3592e7,0x3f36206c,0x3f36ad7f,0x3f373a23,0x3f37c655,0x3f385216,0x3f38dd65,0x3f396842,0x3f39f2ac,0x3f3a7ca4,0x3f3b0629,0x3f3b8f3b,0x3f3c17d9,0x3f3ca003,0x3f3d27b8,
0x3f3daef9,0x3f3e35c5,0x3f3ebc1b,0x3f3f41fc,0x3f3fc767,0x3f404c5c,0x3f40d0da,0x3f4154e1,0x3f41d870,0x3f425b89,0x3f42de29,0x3f436051,0x3f43e200,0x3f446337,0x3f44e3f5,0x3f456439,
0x3f45e403,0x3f466354,0x3f46e22a,0x3f476085,0x3f47de65,0x3f485bca,0x3f48d8b3,0x3f495521,0x3f49d112,0x3f4a4c87,0x3f4ac77f,0x3f4b41fa,0x3f4bbbf8,0x3f4c3578,0x3f4cae79,0x3f4d26fd,
0x3f4d9f02,0x3f4e1689,0x3f4e8d90,0x3f4f0417,0x3f4f7a1f,0x3f4fefa8,0x3f5064af,0x3f50d937,0x3f514d3d,0x3f51c0c2,0x3f5233c6,0x3f52a649,0x3f531849,0x3f5389c7,0x3f53fac3,0x3f546b3b,
0x3f54db31,0x3f554aa4,0x3f55b993,0x3f5627fe,0x3f5695e5,0x3f570348,0x3f577026,0x3f57dc7f,0x3f584853,0x3f58b3a1,0x3f591e6a,0x3f5988ad,0x3f59f26a,0x3f5a5ba0,0x3f5ac450,0x3f5b2c79,
0x3f5b941a,0x3f5bfb34,0x3f5c61c7,0x3f5cc7d1,0x3f5d2d53,0x3f5d924d,0x3f5df6be,0x3f5e5aa6,0x3f5ebe05,0x3f5f20db,0x3f5f8327,0x3f5fe4e9,0x3f604621,0x3f60a6cf,0x3f6106f2,0x3f61668a,
0x3f61c598,0x3f62241a,0x3f628210,0x3f62df7b,0x3f633c5a,0x3f6398ac,0x3f63f473,0x3f644fac,0x3f64aa59,0x3f650479,0x3f655e0b,0x3f65b710,0x3f660f88,0x3f666771,0x3f66becc,0x3f671599,
0x3f676bd8,0x3f67c187,0x3f6816a8,0x3f686b39,0x3f68bf3c,0x3f6912ae,0x3f696591,0x3f69b7e4,0x3f6a09a7,0x3f6a5ad9,0x3f6aab7b,0x3f6afb8c,0x3f6b4b0c,0x3f6b99fb,0x3f6be858,0x3f6c3624,
0x3f6c835e,0x3f6cd007,0x3f6d1c1d,0x3f6d67a1,0x3f6db293,0x3f6dfcf2,0x3f6e46be,0x3f6e8ff8,0x3f6ed89e,0x3f6f20b0,0x3f6f6830,0x3f6faf1b,0x3f6ff573,0x3f703b37,0x3f708066,0x3f70c501,
0x3f710908,0x3f714c7a,0x3f718f57,0x3f71d19f,0x3f721352,0x3f725470,0x3f7294f8,0x3f72d4eb,0x3f731447,0x3f73530e,0x3f73913f,0x3f73ced9,0x3f740bdd,0x3f74484b,0x3f748422,0x3f74bf62,
0x3f74fa0b,0x3f75341d,0x3f756d97,0x3f75a67b,0x3f75dec6,0x3f76167a,0x3f764d97,0x3f76841b,0x3f76ba07,0x3f76ef5b,0x3f772417,0x3f77583a,0x3f778bc5,0x3f77beb7,0x3f77f110,0x3f7822d1,
0x3f7853f8,0x3f788486,0x3f78b47b,0x3f78e3d6,0x3f791298,0x3f7940c0,0x3f796e4e,0x3f799b43,0x3f79c79d,0x3f79f35e,0x3f7a1e84,0x3f7a4910,0x3f7a7302,0x3f7a9c59,0x3f7ac516,0x3f7aed37,
0x3f7b14be,0x3f7b3bab,0x3f7b61fc,0x3f7b87b2,0x3f7baccd,0x3f7bd14d,0x3f7bf531,0x3f7c187a,0x3f7c3b28,0x3f7c5d3a,0x3f7c7eb0,0x3f7c9f8a,0x3f7cbfc9,0x3f7cdf6c,0x3f7cfe73,0x3f7d1cdd,
0x3f7d3aac,0x3f7d57de,0x3f7d7474,0x3f7d906e,0x3f7dabcc,0x3f7dc68c,0x3f7de0b1,0x3f7dfa38,0x3f7e1324,0x3f7e2b72,0x3f7e4323,0x3f7e5a38,0x3f7e70b0,0x3f7e868b,0x3f7e9bc9,0x3f7eb069,
0x3f7ec46d,0x3f7ed7d4,0x3f7eea9d,0x3f7efcc9,0x3f7f0e58,0x3f7f1f49,0x3f7f2f9d,0x3f7f3f54,0x3f7f4e6d,0x3f7f5ce9,0x3f7f6ac7,0x3f7f7808,0x3f7f84ab,0x3f7f90b1,0x3f7f9c18,0x3f7fa6e3,
0x3f7fb10f,0x3f7fba9e,0x3f7fc38f,0x3f7fcbe2,0x3f7fd397,0x3f7fdaaf,0x3f7fe129,0x3f7fe705,0x3f7fec43,0x3f7ff0e3,0x3f7ff4e6,0x3f7ff84a,0x3f7ffb11,0x3f7ffd39,0x3f7ffec4,0x3f7fffb1,
};

__device__ __forceinline__ int tid_here() { return __shfl_xor_sync(~0u, (int)threadIdx.x, 0); }
__device__ __forceinline__ void ld_tab(uint32_t* d, int chunk) { asm volatile("ld.global.v4.u32 {%0,%1,%2,%3}, [%4];" : "=r"(d[0]), "=r"(d[1]), "=r"(d[2]), "=r"(d[3]) : "l"((const uint4*)g_tab + chunk) : "memory"); }
__device__ __forceinline__ void ld_tab(float* d, int chunk) { asm volatile("ld.global.v4.f32 {%0,%1,%2,%3}, [%4];" : "=f"(d[0]), "=f"(d[1]), "=f"(d[2]), "=f"(d[3]) : "l"((const uint4*)g_tab + chunk) : "memory"); }
__device__ __forceinline__ void fft640(uint32_t plane, uint32_t tab, int lane, const uint32_t* fr, const uint32_t* fi, const float (*tc)[4], const float (*ts)[4], float (*xr)[4], float (*xi)[4]) {
  uint32_t A1[5][4], nfi[4];
#pragma unroll
  for (int i = 0; i < 4; i++) nfi[i] = fi[i] ^ 0x80008000u;
  const uint32_t la = plane + (lane >> 4) * 1280 + (lane & 15) * 80;
#pragma unroll
  for (int j = 0; j < 5; j++) {
    uint32_t r0, r1, i0, i1; ldsm4t(r0, r1, i0, i1, la + j * 16);
    float yr[4], yi[4];
    mmaZ(yr, fr, r0, r1); mmaZ(yi, fi, r0, r1); mmaA(yr, nfi, i0, i1); mmaA(yi, fr, i0, i1);
    float zr[4], zi[4];
#pragma unroll
    for (int e = 0; e < 4; e++) { zr[e] = yr[e] * tc[j][e] - yi[e] * ts[j][e]; zi[e] = yr[e] * ts[j][e] + yi[e] * tc[j][e]; }
    A1[j][0] = pack_bf16(zr[0], zr[1]); A1[j][1] = pack_bf16(zr[2], zr[3]); A1[j][2] = pack_bf16(zi[0], zi[1]); A1[j][3] = pack_bf16(zi[2], zi[3]);
  }
#pragma unroll
  for (int t = 0; t < 5; t++) {
    uint32_t A2[4] = {A1[t][2], A1[t][3], A1[t][0] ^ 0x80008000u, A1[t][1] ^ 0x80008000u};
#pragma unroll
    for (int u = 0; u < 5; u++) {
      uint32_t b0, b1; asm volatile("ld.shared.v2.b32 {%0,%1}, [%2];" : "=r"(b0), "=r"(b1) : "r"(tab + (t * 5 + u) * 256 + lane * 8));
      if (t == 0) { mmaZ(xr[u], A1[t], b0, b1); mmaZ(xi[u], A2, b0, b1); } else { mmaA(xr[u], A1[t], b0, b1); mmaA(xi[u], A2, b0, b1); }
    }
  }
}
__device__ __forceinline__ void ln_row(float* v) {
  float s = 0.f;
#pragma unroll
  for (int i = 0; i < 20; i++) s += v[i];
#pragma unroll
  for (int o = 16; o; o >>= 1) s += __shfl_xor_sync(~0u, s, o);
  const float mean = s * (1.f / D_);
  float qv = 0.f;
#pragma unroll
  for (int i = 0; i < 20; i++) { v[i] -= mean; qv += v[i] * v[i]; }
#pragma unroll
  for (int o = 16; o; o >>= 1) qv += __shfl_xor_sync(~0u, qv, o);
  const float rs = rsqrtf(qv * (1.f / D_) + 1e-5f);
#pragma unroll
  for (int i = 0; i < 20; i++) v[i] *= rs;
}

#define TLBASE (1024 + 896)
struct AParams { const bf16* x; uint32_t *Z1, *Z2; const uint32_t* WT; bf16 *x1, *hN; uint32_t* sync; const uint32_t* rowdone; int nw; uint32_t tag; };
constexpr int SY_1 = 0, SY_2 = 32, SY_3 = 64, SY_W = 96;
__device__ __forceinline__ void red_release(uint32_t* p) { asm volatile("red.release.gpu.global.add.u32 [%0], 1;" :: "l"(p) : "memory"); }
__device__ __forceinline__ void red_relaxed(uint32_t* p) { asm volatile("red.relaxed.gpu.global.add.u32 [%0], 1;" :: "l"(p) : "memory"); }
__device__ __forceinline__ void spin_count(const uint32_t* p, uint32_t n) {
  uint32_t v; int guard = 0;
#pragma unroll 1
  do { asm volatile("ld.relaxed.gpu.global.u32 %0, [%1];" : "=r"(v) : "l"(p) : "memory"); } while (v < n && ++guard < 400000);
}

__device__ __forceinline__ void filter_prep(uint32_t* WT, uint32_t sm, int k2) {
  const int tid = threadIdx.x, r = (tid >> 5) & 3;
  const uint32_t src = sm + (8 * (tid & 3) + r) * 642;
#pragma unroll 2
  for (int f = (tid >> 7) * 8 + ((tid & 31) >> 2); f < 321; f += 24) {
    uint32_t v[4];
#pragma unroll
    for (int i = 0; i < 4; i++) {
      unsigned short lo, hi;
      const uint32_t a = src + f * 2 + ((i >> 1) * 4 + (i & 1) * 32) * 642;
      asm volatile("ld.shared.u16 %0, [%1];" : "=h"(lo) : "r"(a)); asm volatile("ld.shared.u16 %0, [%1];" : "=h"(hi) : "r"(a + 41088));
      v[i] = lo | ((uint32_t)hi << 16);
    }
    stg128(WT + f * 2048 + k2 * 64 + r * 16 + (tid & 3) * 4, v[0], v[1], v[2], v[3]);
  }
}

template <typename F> __device__ __forceinline__ void a_phase2(const AParams& a, float* buf, int f, F hook) {
  const int t0 = tid_here(), tid = t0 & 127, lane = tid & 31, w = tid >> 5, g = lane >> 2, q = lane & 3, barid = 5 + (t0 >> 7);
  const int f2 = (640 - f) % 640;
#define WGBAR() asm volatile("bar.sync %0, 128;" :: "r"(barid) : "memory")
  uint32_t fr[4], fi[4], nfi[4], br[4][4], bi[4][4];
  float tc[4][4], ts[4][4], wc[4], ws[4];
  ld_tab(wc, TB_2048 + tid); ld_tab(ws, TB_2048 + 128 + tid); ld_tab(fr, TB_F16 + lane); ld_tab(fi, TB_F16 + 32 + lane);
#pragma unroll
  for (int j = 0; j < 4; j++) { ld_tab(tc[j], TB_512 + j * 32 + lane); ld_tab(ts[j], TB_512 + 128 + j * 32 + lane); }
  if (tid == 32 && !a.nw) l2_prefetch(a.WT + f * 2048, 8192);
  const uint32_t* zs[4];
#pragma unroll
  for (int j = 0; j < 4; j++) { const int m = j * 256 + 2 * tid; zs[j] = a.Z1 + (m / 12) * 7680 + m % 12; }
  if (tid == 0) { spin_count(a.sync + SY_1, 86); TL(6); }
  WGBAR();
  const uint32_t sbuf = smem_u32(buf);
  {
    uint2 P[4], Q[4];
#pragma unroll 1
    for (int guard = 0; guard < 100000; guard++) {
      uint32_t bad = 0;
#pragma unroll
      for (int j = 0; j < 4; j++) {
        asm volatile("ld.relaxed.gpu.global.v2.u32 {%0,%1}, [%2];" : "=r"(P[j].x), "=r"(P[j].y) : "l"(zs[j] + f * 12) : "memory");
        asm volatile("ld.relaxed.gpu.global.v2.u32 {%0,%1}, [%2];" : "=r"(Q[j].x), "=r"(Q[j].y) : "l"(zs[j] + f2 * 12) : "memory");
      }
#pragma unroll
      for (int j = 0; j < 4; j++) bad |= (P[j].x ^ a.tag) | (Q[j].x ^ a.tag);
      if (__all_sync(~0u, !(bad & 1))) break;
    }
    float ur[4][4], ui[4][4];
#pragma unroll
    for (int i = 0; i < 4; i++) {
      float ar[4], ai[4];
#pragma unroll
      for (int j = 0; j < 4; j++) {
        const uint32_t p = (i >> 1) ? P[j].y : P[j].x, z = (i >> 1) ? Q[j].y : Q[j].x;
        if (!(i & 1)) { ar[j] = bf_lo(p) + bf_lo(z); ai[j] = bf_hi(p) - bf_hi(z); }
        else { ar[j] = bf_hi(p) + bf_hi(z); ai[j] = bf_lo(z) - bf_lo(p); }
      }
      const float s0r = ar[0] + ar[2], s0i = ai[0] + ai[2], d0r = ar[0] - ar[2], d0i = ai[0] - ai[2];
      const float s1r = ar[1] + ar[3], s1i = ai[1] + ai[3], d1r = ar[1] - ar[3], d1i = ai[1] - ai[3];
      ur[0][i] = s0r + s1r; ui[0][i] = s0i + s1i;
      const float vr[3] = {d0r + d1i, s0r - s1r, d0r - d1i}, vi[3] = {d0i - d1r, s0i - s1i, d0i + d1r};
      const float c2 = wc[i] * wc[i] - ws[i] * ws[i], s2 = 2.f * wc[i] * ws[i];
      const float twc[4] = {1.f, wc[i], c2, c2 * wc[i] - s2 * ws[i]}, tws[4] = {0.f, ws[i], s2, s2 * wc[i] + c2 * ws[i]};
#pragma unroll
      for (int r = 1; r < 4; r++) { const float c = twc[r], s = tws[r]; ur[r][i] = vr[r - 1] * c + vi[r - 1] * s; ui[r][i] = vi[r - 1] * c - vr[r - 1] * s; }
    }
    const uint32_t o = sbuf + (tid >> 3) * 80 + (tid & 7) * 8;
#pragma unroll
    for (int r = 0; r < 4; r++) {
      asm volatile("st.shared.v2.b32 [%0], {%1,%2};" :: "r"(o + r * 5120), "r"(pack_bf16(ur[r][0], ur[r][1])), "r"(pack_bf16(ur[r][2], ur[r][3])) : "memory");
      asm volatile("st.shared.v2.b32 [%0], {%1,%2};" :: "r"(o + r * 5120 + 1280), "r"(pack_bf16(ui[r][0], ui[r][1])), "r"(pack_bf16(ui[r][2], ui[r][3])) : "memory");
    }
  }
#pragma unroll
  for (int j = 0; j < 4; j++) { ld_tab(br[j], TB_F32 + j * 32 + lane); ld_tab(bi[j], TB_F32 + 128 + j * 32 + lane); }
  if (tid == 0 && a.nw) spin_count(a.sync + SY_W, a.nw);
  WGBAR();
  hook(1);
  TL(7);
  uint2 wt[8];
#pragma unroll
  for (int i = 0; i < 8; i++) wt[i] = __ldcg((const uint2*)(a.WT + f * 2048 + ((i >> 1) * 8 + 2 * q + (i & 1)) * 64 + w * 16 + g * 2));
  {
    uint32_t A1[4][4], A2[4][4];
#pragma unroll
    for (int i = 0; i < 4; i++) nfi[i] = fi[i] ^ 0x80008000u;
    const uint32_t la = sbuf + w * 5120 + (lane >> 4) * 1280 + (lane & 15) * 80;
#pragma unroll
    for (int j = 0; j < 4; j++) {
      uint32_t r0, r1, i0, i1; ldsm4t(r0, r1, i0, i1, la + j * 16);
      float yr[4], yi[4];
      mmaZ(yr, fr, r0, r1); mmaZ(yi, fi, r0, r1); mmaA(yr, nfi, i0, i1); mmaA(yi, fr, i0, i1);
      float zr[4], zi[4];
#pragma unroll
      for (int e = 0; e < 4; e++) { zr[e] = yr[e] * tc[j][e] + yi[e] * ts[j][e]; zi[e] = yi[e] * tc[j][e] - yr[e] * ts[j][e]; }
      A1[j][0] = pack_bf16(zr[0], zr[1]); A1[j][1] = pack_bf16(zr[2], zr[3]); A1[j][2] = pack_bf16(zi[0], zi[1]); A1[j][3] = pack_bf16(zi[2], zi[3]);
      A2[j][0] = A1[j][2]; A2[j][1] = A1[j][3]; A2[j][2] = A1[j][0] ^ 0x80008000u; A2[j][3] = A1[j][1] ^ 0x80008000u;
    }
    float xr[4][4], xi[4][4];
#pragma unroll
    for (int t = 0; t < 4; t++)
#pragma unroll
      for (int u = 0; u < 4; u++) {
        if (t == 0) { mmaZ(xr[u], A1[t], br[t][u], bi[t][u]); mmaZ(xi[u], A2[t], br[t][u], bi[t][u]); } else { mmaA(xr[u], A1[t], br[t][u], bi[t][u]); mmaA(xi[u], A2[t], br[t][u], bi[t][u]); }
      }
#pragma unroll
    for (int u = 0; u < 4; u++) {
      const uint32_t wv[4] = {wt[2 * u].x, wt[2 * u + 1].x, wt[2 * u].y, wt[2 * u + 1].y};
      float zr[4], zi[4];
#pragma unroll
      for (int e = 0; e < 4; e++) { const float c = bf_lo(wv[e]), b = bf_hi(wv[e]); zr[e] = xr[u][e] * c - xi[u][e] * b; zi[e] = xr[u][e] * b + xi[u][e] * c; }
      A2[u][2] = pack_bf16(zr[0], zr[1]); A2[u][3] = pack_bf16(zr[2], zr[3]); A2[u][0] = pack_bf16(zi[0], zi[1]); A2[u][1] = pack_bf16(zi[2], zi[3]);
      A1[u][0] = A2[u][2]; A1[u][1] = A2[u][3]; A1[u][2] = A2[u][0] ^ 0x80008000u; A1[u][3] = A2[u][1] ^ 0x80008000u;
    }
#pragma unroll
    for (int t = 0; t < 4; t++)
#pragma unroll
      for (int u = 0; u < 4; u++) {
        if (t == 0) { mmaZ(xr[u], A1[t], br[t][u], bi[t][u]); mmaZ(xi[u], A2[t], br[t][u], bi[t][u]); } else { mmaA(xr[u], A1[t], br[t][u], bi[t][u]); mmaA(xi[u], A2[t], br[t][u], bi[t][u]); }
      }
    __syncwarp();
    float* pl = buf + w * 1280;
    const float nrm = 0.5f / (2048.f * 640.f);
#pragma unroll
    for (int j = 0; j < 4; j++) {
      float zr[4], zi[4];
#pragma unroll
      for (int e = 0; e < 4; e++) { zr[e] = xr[j][e] * tc[j][e] - xi[j][e] * ts[j][e]; zi[e] = xi[j][e] * tc[j][e] + xr[j][e] * ts[j][e]; }
      const uint32_t r0 = movm(pack_bf16(zr[0], zr[1])), r1 = movm(pack_bf16(zr[2], zr[3])), i0 = movm(pack_bf16(zi[0], zi[1])), i1 = movm(pack_bf16(zi[2], zi[3]));
      float yr[4], yi[4];
      mmaZ(yr, fr, r0, r1); mmaZ(yi, nfi, r0, r1); mmaA(yr, fi, i0, i1); mmaA(yi, fr, i0, i1);
      *(float2*)(pl + g * 40 + 8 * j + 2 * q) = make_float2(yr[0] * nrm, yr[1] * nrm); *(float2*)(pl + (g + 8) * 40 + 8 * j + 2 * q) = make_float2(yr[2] * nrm, yr[3] * nrm);
      *(float2*)(pl + 640 + g * 40 + 8 * j + 2 * q) = make_float2(yi[0] * nrm, yi[1] * nrm); *(float2*)(pl + 640 + (g + 8) * 40 + 8 * j + 2 * q) = make_float2(yi[2] * nrm, yi[3] * nrm);
    }
  }
  ld_tab(wc, TB_2048 + tid); ld_tab(ws, TB_2048 + 128 + tid);
  WGBAR();
  hook(2);
  TL(8);
  {
    float4 Ur[4], Ui[4];
#pragma unroll
    for (int r = 0; r < 4; r++) { Ur[r] = *(const float4*)(buf + r * 1280 + (tid >> 3) * 40 + (tid & 7) * 4); Ui[r] = *(const float4*)(buf + r * 1280 + 640 + (tid >> 3) * 40 + (tid & 7) * 4); }
    float yr[4][4], yi[4][4];
#pragma unroll
    for (int i = 0; i < 4; i++) {
      float ar[4], ai[4];
      const float c2 = wc[i] * wc[i] - ws[i] * ws[i], s2 = 2.f * wc[i] * ws[i];
      const float twc[4] = {1.f, wc[i], c2, c2 * wc[i] - s2 * ws[i]}, tws[4] = {0.f, ws[i], s2, s2 * wc[i] + c2 * ws[i]};
#pragma unroll
      for (int r = 0; r < 4; r++) {
        const float a = i == 0 ? Ur[r].x : i == 1 ? Ur[r].y : i == 2 ? Ur[r].z : Ur[r].w, b = i == 0 ? Ui[r].x : i == 1 ? Ui[r].y : i == 2 ? Ui[r].z : Ui[r].w;
        if (r == 0) { ar[r] = a; ai[r] = b; } else { const float c = twc[r], s = tws[r]; ar[r] = a * c - b * s; ai[r] = b * c + a * s; }
      }
      const float s0r = ar[0] + ar[2], s0i = ai[0] + ai[2], d0r = ar[0] - ar[2], d0i = ai[0] - ai[2];
      const float s1r = ar[1] + ar[3], s1i = ai[1] + ai[3], d1r = ar[1] - ar[3], d1i = ai[1] - ai[3];
      yr[0][i] = s0r + s1r; yi[0][i] = s0i + s1i; yr[2][i] = s0r - s1r; yi[2][i] = s0i - s1i;
      yr[1][i] = d0r - d1i; yi[1][i] = d0i + d1r; yr[3][i] = d0r + d1i; yi[3][i] = d0i - d1r;
    }
    const float im = (f == f2) ? 0.f : 1.f;
#pragma unroll
    for (int j = 0; j < 4; j++) {
      *(uint2*)(a.Z2 + f * 1024 + j * 256 + 2 * tid) = make_uint2((pack_bf16(yr[j][0] - im * yi[j][1], yr[j][1] + im * yi[j][0]) & ~1u) | a.tag, pack_bf16(yr[j][2] - im * yi[j][3], yr[j][3] + im * yi[j][2]));
      if (f != f2) *(uint2*)(a.Z2 + f2 * 1024 + j * 256 + 2 * tid) = make_uint2((pack_bf16(yr[j][0] + yi[j][1], yr[j][1] - yi[j][0]) & ~1u) | a.tag, pack_bf16(yr[j][2] + yi[j][3], yr[j][3] - yi[j][2]));
    }
  }
  TL(9);
}

constexpr int KA_TR_STRIDE = 804;
template <typename F> __device__ __forceinline__ void a_layer(const AParams& a, char* scratch, int v, int w, F hook) {
  const int tid = tid_here(), lane = tid & 31;
  uint32_t raw[2][10], fr[4], fi[4];
  float tc[5][4], ts[5][4];
  bool act = v < 86;
  int m = act ? min(v * 12 + w, 1023) : v * 4 + w;
  uint32_t* buf = (uint32_t*)(scratch + 6400) + (w & 3) * KA_TR_STRIDE + (w >> 2) * 3244;
  auto load_rows = [&]() {
    const int lane = tid_here() & 31;
#pragma unroll
    for (int i = 0; i < 10; i++) asm volatile("ld.global.cg.v2.u32 {%0,%1}, [%2];" : "=r"(raw[i / 5][2 * (i % 5)]), "=r"(raw[i / 5][2 * (i % 5) + 1]) : "l"(a.x + (size_t)(2 * m) * D_ + i * 128 + lane * 4) : "memory");
  };
  auto load_tabs = [&]() {
    uint32_t t[2][4];
    const int tid = tid_here(), lane = tid & 31;
    ld_tab(t[0], TB_F40 + (tid & 255)); ld_tab(t[1], TB_F40 + 144 + (tid & 255));
    ld_tab(fr, TB_F16 + lane); ld_tab(fi, TB_F16 + 32 + lane);
#pragma unroll
    for (int j = 0; j < 5; j++) { ld_tab(tc[j], TB_640 + j * 32 + lane); ld_tab(ts[j], TB_640 + 160 + j * 32 + lane); }
    sts128(smem_u32(scratch) + (tid & 255) * 16, t[0][0], t[0][1], t[0][2], t[0][3]); sts128(smem_u32(scratch) + 2304 + (tid & 255) * 16, t[1][0], t[1][1], t[1][2], t[1][3]);
  };
  if (a.rowdone) { load_tabs(); if (act) spin_count(a.rowdone + (m >> 4) * 16, 32); load_rows(); }
  else { load_rows(); load_tabs(); }
  __syncthreads();
  hook(-1);
  TL(1);
#pragma unroll 1
  for (int it = 0;; it++) {
    if (act) {
#pragma unroll
      for (int r = 0; r < 2; r++) {
        float x[20];
#pragma unroll
        for (int i = 0; i < 10; i++) { x[2 * i] = bf_lo(raw[r][i]); x[2 * i + 1] = bf_hi(raw[r][i]); }
        ln_row(x);
#pragma unroll
        for (int i = 0; i < 10; i++) raw[r][i] = pack_bf16(x[2 * i], x[2 * i + 1]);
      }
    }
    if (it) break;
    if (act) {
#pragma unroll
      for (int i = 0; i < 10; i++) *(uint2*)(buf + i * 64 + lane * 2) = make_uint2(raw[i / 5][2 * (i % 5)], raw[i / 5][2 * (i % 5) + 1]);
      __syncwarp();
    }
    TL(2);
#pragma unroll 1
    for (int ph = 0;; ph++) {
      if (act) {
        float xr[5][4], xi[5][4];
        const int lane = tid_here() & 31, g = lane >> 2, q = lane & 3;
        fft640(smem_u32(buf), smem_u32(scratch), lane, fr, fi, tc, ts, xr, xi);
        __syncwarp();
#pragma unroll
        for (int u = 0; u < 5; u++)
#pragma unroll
          for (int e = 0; e < 4; e++) { const int f = g + 8 * (e >> 1) + 16 * (8 * u + 2 * q + (e & 1)); buf[f + 8 * (f >> 5)] = pack_bf16(xr[u][e], xi[u][e]); }
        __syncwarp();
      }
      if (ph) break;
      __syncthreads();
      TL(3);
      const int t1 = tid_here(), f0 = t1 / 3, part = t1 % 3;
      if (act) {
        const uint32_t* src = (const uint32_t*)(scratch + 6400) + part * 3244 + f0 + 8 * (f0 >> 5);
        uint32_t ov[5][4];
#pragma unroll
        for (int i = 0; i < 5; i++)
#pragma unroll
          for (int k = 0; k < 4; k++) ov[i][k] = src[k * KA_TR_STRIDE + i * 160];
#pragma unroll
        for (int i = 0; i < 5; i++) stg128(a.Z1 + v * 7680 + (i * 384 + t1) * 4, (ov[i][0] & ~1u) | a.tag, ov[i][1], (ov[i][2] & ~1u) | a.tag, ov[i][3]);
      }
      TL(4);
      __syncthreads();
      if (tid == 32 && act) { red_relaxed(a.sync + SY_1); TL(5); }
      hook(0);
      const int f = (w >> 2) * 131 + v;
      if (f < 321) a_phase2(a, (float*)(scratch + (w >> 2) * 20480), f, hook);
      asm volatile("fence.proxy.async.shared::cta;" ::: "memory");
      __syncthreads();
      if (tid == 32) red_relaxed(a.sync + SY_2);
      hook(3);
      if (w >= 8 || v >= 128) return;
      act = true; m = v * 8 + w;
      scratch += 32768; buf = (uint32_t*)(scratch + 6400);
      {
        load_rows(); load_tabs();
        if (tid == 0) { spin_count(a.sync + SY_2, 131); TL(10); }
        bar_sync<5, 256>();
        uint4 za[3], zb[3];
        const int tid = tid_here();
#pragma unroll 1
        for (int guard = 0; guard < 100000; guard++) {
          uint32_t bad = 0;
#pragma unroll
          for (int i = 0; i < 3; i++) {
            const uint32_t* s = a.Z2 + (i * 256 + (tid & (i < 2 ? 254 : 126))) * 1024 + v * 8 + (tid & 1) * 4;
            asm volatile("ld.relaxed.gpu.global.v4.u32 {%0,%1,%2,%3}, [%4];" : "=r"(za[i].x), "=r"(za[i].y), "=r"(za[i].z), "=r"(za[i].w) : "l"(s) : "memory");
            asm volatile("ld.relaxed.gpu.global.v4.u32 {%0,%1,%2,%3}, [%4];" : "=r"(zb[i].x), "=r"(zb[i].y), "=r"(zb[i].z), "=r"(zb[i].w) : "l"(s + 1024) : "memory");
          }
#pragma unroll
          for (int i = 0; i < 3; i++) bad |= (za[i].x ^ a.tag) | (zb[i].x ^ a.tag) | (za[i].z ^ a.tag) | (zb[i].z ^ a.tag);
          if (__all_sync(~0u, !(bad & 1))) break;
        }
#pragma unroll
        for (int i = 0; i < 3; i++) if (i < 2 || tid < 128) {
          const uint4 c = za[i], b = zb[i];
          uint32_t* d = buf + (tid & 1) * 4 * KA_TR_STRIDE + i * 128 + (tid >> 1);
          d[320] = __byte_perm(c.x, b.x, 0x5410); d[0] = __byte_perm(c.x, b.x, 0x7632); d += KA_TR_STRIDE;
          d[320] = __byte_perm(c.y, b.y, 0x5410); d[0] = __byte_perm(c.y, b.y, 0x7632); d += KA_TR_STRIDE;
          d[320] = __byte_perm(c.z, b.z, 0x5410); d[0] = __byte_perm(c.z, b.z, 0x7632); d += KA_TR_STRIDE;
          d[320] = __byte_perm(c.w, b.w, 0x5410); d[0] = __byte_perm(c.w, b.w, 0x7632);
        }
        bar_sync<5, 256>();
        hook(4);
        TL(11);
      }
      buf += w * KA_TR_STRIDE;
    }
    {
      TL(12);
      const int lane = tid_here() & 31;
#pragma unroll
      for (int i = 0; i < 5; i++) {
        const uint4 y = *(const uint4*)(buf + i * 160 + lane * 4 + 8 * (lane >> 3));
        raw[0][2 * i] = hadd2(raw[0][2 * i], __byte_perm(y.x, y.y, 0x7632)); raw[0][2 * i + 1] = hadd2(raw[0][2 * i + 1], __byte_perm(y.z, y.w, 0x7632));
        raw[1][2 * i] = hadd2(raw[1][2 * i], __byte_perm(y.x, y.y, 0x5410)); raw[1][2 * i + 1] = hadd2(raw[1][2 * i + 1], __byte_perm(y.z, y.w, 0x5410));
      }
#pragma unroll
      for (int i = 0; i < 10; i++) *(uint2*)(a.x1 + (size_t)(2 * m) * D_ + i * 128 + lane * 4) = make_uint2(raw[i / 5][2 * (i % 5)], raw[i / 5][2 * (i % 5) + 1]);
    }
  }
  {
#pragma unroll
    for (int i = 0; i < 10; i++) *(uint2*)(a.hN + (size_t)(2 * m) * D_ + i * 128 + lane * 4) = make_uint2(raw[i / 5][2 * (i % 5)], raw[i / 5][2 * (i % 5) + 1]);
    TL(13);
    bar_sync<5, 256>();
    if (tid == 0) { red_release(a.sync + SY_3); TL(14); }
  }
}

__device__ __forceinline__ void tma2d(uint32_t dst, const CUtensorMap* tm, int c0, int c1, uint32_t bar) {
  asm volatile("cp.async.bulk.tensor.2d.shared::cluster.global.mbarrier::complete_tx::bytes [%0], [%1, {%3, %4}], [%2];" :: "r"(dst), "l"(tm), "r"(bar), "r"(c0), "r"(c1) : "memory");
}
__device__ __forceinline__ void bulk_g2s(uint32_t dst, const void* src, int bytes, uint32_t bar) {
  asm volatile("cp.async.bulk.shared::cluster.global.mbarrier::complete_tx::bytes [%0], [%1], %2, [%3];" :: "r"(dst), "l"(src), "r"(bytes), "r"(bar) : "memory");
}
__device__ __forceinline__ uint64_t desc128(uint32_t a) { return (uint64_t)((a & 0x3FFFF) >> 4) | (1ull << 16) | (64ull << 32) | (1ull << 62); }
#define WG_FENCE() asm volatile("wgmma.fence.sync.aligned;" ::: "memory")
#define WG_COMMIT() asm volatile("wgmma.commit_group.sync.aligned;" ::: "memory")
#define WG_WAIT(n) asm volatile("wgmma.wait_group.sync.aligned " #n ";" ::: "memory")
__device__ __forceinline__ void wg_rs_n64(float* d, const uint32_t* a, uint64_t db, int acc) {
  asm volatile("{.reg .pred p; setp.ne.b32 p, %37, 0;\n"
    "wgmma.mma_async.sync.aligned.m64n64k16.f32.bf16.bf16 {%0,%1,%2,%3,%4,%5,%6,%7,%8,%9,%10,%11,%12,%13,%14,%15,%16,%17,%18,%19,%20,%21,%22,%23,%24,%25,%26,%27,%28,%29,%30,%31}, {%32,%33,%34,%35}, %36, p, 1, 1, 0;}"
    : "+f"(d[0]), "+f"(d[1]), "+f"(d[2]), "+f"(d[3]), "+f"(d[4]), "+f"(d[5]), "+f"(d[6]), "+f"(d[7]), "+f"(d[8]), "+f"(d[9]), "+f"(d[10]), "+f"(d[11]), "+f"(d[12]), "+f"(d[13]), "+f"(d[14]), "+f"(d[15]),
      "+f"(d[16]), "+f"(d[17]), "+f"(d[18]), "+f"(d[19]), "+f"(d[20]), "+f"(d[21]), "+f"(d[22]), "+f"(d[23]), "+f"(d[24]), "+f"(d[25]), "+f"(d[26]), "+f"(d[27]), "+f"(d[28]), "+f"(d[29]), "+f"(d[30]), "+f"(d[31])
    : "r"(a[0]), "r"(a[1]), "r"(a[2]), "r"(a[3]), "l"(db), "r"(acc));
}
__device__ __forceinline__ void wg_rs_n32(float* d, const uint32_t* a, uint64_t db, int acc) {
  asm volatile("{.reg .pred p; setp.ne.b32 p, %21, 0;\n"
    "wgmma.mma_async.sync.aligned.m64n32k16.f32.bf16.bf16 {%0,%1,%2,%3,%4,%5,%6,%7,%8,%9,%10,%11,%12,%13,%14,%15}, {%16,%17,%18,%19}, %20, p, 1, 1, 0;}"
    : "+f"(d[0]), "+f"(d[1]), "+f"(d[2]), "+f"(d[3]), "+f"(d[4]), "+f"(d[5]), "+f"(d[6]), "+f"(d[7]), "+f"(d[8]), "+f"(d[9]), "+f"(d[10]), "+f"(d[11]), "+f"(d[12]), "+f"(d[13]), "+f"(d[14]), "+f"(d[15])
    : "r"(a[0]), "r"(a[1]), "r"(a[2]), "r"(a[3]), "l"(db), "r"(acc));
}
__device__ __forceinline__ void wg_ss_n40_tt(float* d, uint64_t da, uint64_t db, int acc) {
  asm volatile("{.reg .pred p; setp.ne.b32 p, %22, 0;\n"
    "wgmma.mma_async.sync.aligned.m64n40k16.f32.bf16.bf16 {%0,%1,%2,%3,%4,%5,%6,%7,%8,%9,%10,%11,%12,%13,%14,%15,%16,%17,%18,%19}, %20, %21, p, 1, 1, 1, 1;}"
    : "+f"(d[0]), "+f"(d[1]), "+f"(d[2]), "+f"(d[3]), "+f"(d[4]), "+f"(d[5]), "+f"(d[6]), "+f"(d[7]), "+f"(d[8]), "+f"(d[9]), "+f"(d[10]), "+f"(d[11]), "+f"(d[12]), "+f"(d[13]), "+f"(d[14]), "+f"(d[15]),
      "+f"(d[16]), "+f"(d[17]), "+f"(d[18]), "+f"(d[19])
    : "l"(da), "l"(db), "r"(acc));
}
__device__ __forceinline__ void wg_ss_n32_ta(float* d, uint64_t da, uint64_t db, int acc) {
  asm volatile("{.reg .pred p; setp.ne.b32 p, %18, 0;\n"
    "wgmma.mma_async.sync.aligned.m64n32k16.f32.bf16.bf16 {%0,%1,%2,%3,%4,%5,%6,%7,%8,%9,%10,%11,%12,%13,%14,%15}, %16, %17, p, 1, 1, 1, 0;}"
    : "+f"(d[0]), "+f"(d[1]), "+f"(d[2]), "+f"(d[3]), "+f"(d[4]), "+f"(d[5]), "+f"(d[6]), "+f"(d[7]), "+f"(d[8]), "+f"(d[9]), "+f"(d[10]), "+f"(d[11]), "+f"(d[12]), "+f"(d[13]), "+f"(d[14]), "+f"(d[15])
    : "l"(da), "l"(db), "r"(acc));
}
__device__ __forceinline__ uint64_t desc_ns(uint32_t a, uint32_t lbo, uint32_t sbo) { return (uint64_t)((a & 0x3FFFF) >> 4) | ((uint64_t)(lbo >> 4) << 16) | ((uint64_t)(sbo >> 4) << 32); }
__device__ __forceinline__ void wait_count(const uint32_t* p, uint32_t n) {
  uint32_t v; int guard = 0;
#pragma unroll 1
  while (true) { asm volatile("ld.relaxed.gpu.global.u32 %0, [%1];" : "=r"(v) : "l"(p) : "memory"); if (__all_sync(~0u, v >= n) || ++guard > 200000) break; }
}

constexpr int SD_WS = 0, SD_REC = 16384, SD_O = SD_REC + 2 * 30720, SD_OI = SD_O + 2 * 8192, SD_OUT = SD_OI + 2 * 40960, SD_FIN = SD_OUT + 8192, SD_BAR = SD_FIN + 10240;
constexpr int SD_SMEM = SD_BAR + 512 + 1024;
#undef TLBASE
#define TLBASE (1024 + SD_BAR + 256)
#define QRING 4
constexpr int ORING = 8, PRING = 2 * ORING;
constexpr int FL_MEM = 162 * 1024, FL_RDY = 166 * 1024, FL_SM = 170 * 1024;
struct SideParams { CUtensorMap tmWo, tmP; const char* QKV; char *O, *part; const bf16* x1; bf16* out; uint32_t *comm, *sync; uint64_t dhi; int first, period, phase, win, lag, tmem, mask, last, dbgf; };
#define DBGF(m) false
#define ELECT "{.reg .pred p; elect.sync _|p, 0xffffffff;\n"
#define ATS(i)
__global__ void __launch_bounds__(512, 1) side_kernel(const __grid_constant__ SideParams p) {
  extern __shared__ __align__(1024) char smem_raw[];
  const uint32_t sb = (smem_u32(smem_raw) + 1023) & ~1023u, wfull = sb + SD_BAR, rland = wfull + 8, ofull = wfull + 16, ofree = wfull + 32,
    ifull = wfull + 48, ifree = wfull + 64, rfull = wfull + 80, rfree = wfull + 96, fdone = wfull + 112, ffull = wfull + 128;
  const int tid = threadIdx.x, lane = tid & 31, w = __shfl_sync(~0u, tid >> 5, 0);
  if (!DBGF(16)) pdl_launch();
  if (tid == 0) {
    spin_count(p.sync + SY_3, 128);
    uint32_t sm, mate; asm("mov.u32 %0, %%smid;" : "=r"(sm));
    asm volatile("ld.relaxed.gpu.global.u32 %0, [%1];" : "=r"(mate) : "l"(p.comm + FL_SM - (p.first ^ 1) * 1024 + (sm ^ 1)) : "memory");
    const uint32_t n = atomicAdd(p.comm + FL_SM + 512 + (mate ? 8 : 0), 1);
    asm volatile("st.shared.b32 [%0], %1;" :: "r"(fdone + 12), "r"(mate ? 35 - n : n) : "memory");
  }
  __syncthreads();
  int h; asm volatile("ld.shared.b32 %0, [%1];" : "=r"(h) : "r"(fdone + 12) : "memory");
  h = __shfl_sync(~0u, h, 0);
  if (h == 35) return;
  const int cb = h % 5, ks = h / 5, h0 = ks < 4 ? 5 * ks : 4 + 4 * ks, nh = ks < 4 ? 5 : 4;
  const int nseg = DBGF(16) ? 0 : NSEG;
  auto since = [&](uint32_t ref) { uint32_t now; asm volatile("mov.u32 %0, %%globaltimer_lo;" : "=r"(now) :: "memory"); return (now - ((ref >> 7) << 5)) & 0x3FFFFFFF; };
  auto gate = [&](int s) {
#pragma unroll 1
    for (int guard = 0; guard < 4000; guard++) {
      uint32_t ref; asm volatile("ld.volatile.shared.b32 %0, [%1];" : "=r"(ref) : "r"(fdone + 4) : "memory");
      const int n = ref & 127;
      if (n >= p.last || n > s + p.lag || (since(ref) + p.period - p.phase) % p.period <= p.win) break;
    }
  };
  TL(0);
  if (tid == 0) {
    mbar_init(wfull, 1); mbar_init(rland, 1); mbar_init(ffull, 1);
    for (int i = 0; i < 2; i++) { mbar_init(ofull + i * 8, 2); mbar_init(ofree + i * 8, 1); mbar_init(ifull + i * 8, 1); mbar_init(ifree + i * 8, 8); mbar_init(rfull + i * 8, 1); mbar_init(rfree + i * 8, 4); }
    asm volatile("st.shared.v2.b32 [%0], {%1,%1};" :: "r"(fdone), "r"(0) : "memory");
    asm volatile("fence.proxy.async.shared::cta;" ::: "memory");
    mbar_expect(wfull, nh * 32768);
#pragma unroll 1
    for (int b = 0; b < 4 * nh; b++) tma2d(sb + ((b + 2) % 20) * 8192, &p.tmWo, cb * 128 + (b & 1) * 64, h0 * 128 + (b >> 1) * 64, wfull);
  }
  __syncthreads();
  if (w < 8) {
    asm volatile("setmaxnreg.inc.sync.aligned.u32 192;");
    const int c = w >> 2, mg = w & 3;
    const uint32_t boxoff = (((lane >> 4) << 3) + (lane & 7)) * 128 + (((2 * mg + ((lane >> 3) & 1)) ^ (lane & 7)) << 4);
    uint32_t A[36][4];
    mbar_wait(wfull, 0);
#pragma unroll
    for (int f = 0; f < 36; f++) ldsm4t(A[f][0], A[f][1], A[f][2], A[f][3], sb + 16384 + c * 8192 + boxoff + (f >> 2) * 16384 + (f & 3) * 2048);
    asm volatile("fence.proxy.async.shared::cta;" ::: "memory");
    bar_sync<1, 320>();
    TL(1);
    const uint32_t oa = sb + SD_OUT + c * 4096 + boxoff;
#pragma unroll 1
    for (int s = 0; s < nseg; s++) {
      const int b = s & 1;
      const uint64_t db = p.dhi + (uint32_t)(((sb + SD_OI) >> 4) + b * 2560), da = p.dhi + (uint32_t)(((sb + SD_WS) >> 4) + c * 512);
#define D128(x) (x)
      float acc[16];
      mbar_wait_long(ifull + b * 8, (s >> 1) & 1);
      ATS(0)
      WG_FENCE();
#pragma unroll
      for (int k = 0; k < 32; k++) wg_rs_n32(acc, A[k], D128(db + (k >> 2) * 256 + (k & 3) * 2), k);
      if (nh == 5) {
#pragma unroll
        for (int k = 32; k < 36; k++) wg_rs_n32(acc, A[k], D128(db + 2048 + (k & 3) * 2), 1);
#pragma unroll
        for (int k = 0; k < 4; k++) wg_ss_n32_ta(acc, D128(da + k * 128), D128(db + 2304 + k * 2), 1);
      }
      WG_COMMIT();
      bar_sync<2, 256>();
      WG_WAIT(0);
      ATS(1)
      if (lane == 0) mbar_arrive(ifree + b * 8);
#pragma unroll
      for (int u = 0; u < 2; u++)
        asm volatile("stmatrix.sync.aligned.m8n8.x4.trans.shared.b16 [%0], {%1,%2,%3,%4};" :: "r"(oa + u * 2048),
          "r"(pack_bf16(acc[8 * u], acc[8 * u + 1])), "r"(pack_bf16(acc[8 * u + 2], acc[8 * u + 3])), "r"(pack_bf16(acc[8 * u + 4], acc[8 * u + 5])), "r"(pack_bf16(acc[8 * u + 6], acc[8 * u + 7])) : "memory");
      asm volatile("fence.proxy.async.shared::cta;" ::: "memory");
      if (w > 0) bar_arrive<4, 256>();
      else {
        bar_sync<4, 256>();
        asm volatile(ELECT "@p cp.async.bulk.tensor.3d.global.shared::cta.bulk_group [%0, {%2, %3, %4}], [%1];\n"
          "cp.async.bulk.commit_group;\ncp.async.bulk.wait_group 0;\n@p fence.proxy.async.global;\n@p red.release.gpu.global.add.u32 [%5], 1;}"
          :: "l"(&p.tmP), "r"(sb + SD_OUT), "r"(0), "r"((s % PRING) * 32), "r"(ks * 10 + cb * 2), "l"(p.comm + FL_RDY + s * 16 + 8) : "memory");
        ATS(2)
      }
    }
    TL(5);
  } else if (w < 12) {
    asm volatile("setmaxnreg.dec.sync.aligned.u32 72;");
    const int a = w - 8, g = lane >> 2, q = lane & 3;
    const float sc2 = 0.08838834764831845f * 1.4426950408889634f;
#pragma unroll 1
    for (int s = 0; s < (h < 32 ? nseg : 0); s++) {
      const int b = s & 1;
      const uint32_t rec = sb + SD_REC + b * 30720;
      mbar_wait_long(rfull + b * 8, (s >> 1) & 1);
      ATS(1)
      if (s == 0) TL(2);
      uint32_t P[3][4]; float inv[2];
      {
        float sc[20];
        const uint64_t dq = desc_ns(rec + 1024, 128, 1024), dk = desc_ns(rec + 5120, 128, 1024);
        WG_FENCE();
#pragma unroll
        for (int k = 0; k < 8; k++) wg_ss_n40_tt(sc, dq + (k >> 2) * 640 + (k & 3) * 16, dk + (k >> 2) * 640 + (k & 3) * 16, k);
        WG_COMMIT(); WG_WAIT(0);
        ATS(2)
#pragma unroll
        for (int rh = 0; rh < 2; rh++) {
          const int row = 16 * a + 8 * rh + g;
          float v[5][2], mx = -3.0e38f;
#pragma unroll
          for (int n = 0; n < 5; n++)
#pragma unroll
            for (int e = 0; e < 2; e++) {
              const bool ok = n == 0 || (8 * (n - 1) + 2 * q + e) <= row;
              v[n][e] = ok ? sc[4 * n + 2 * rh + e] * sc2 : -1.0e9f * 1.4426950408889634f; mx = fmaxf(mx, v[n][e]);
            }
          mx = fmaxf(mx, __shfl_xor_sync(~0u, mx, 1)); mx = fmaxf(mx, __shfl_xor_sync(~0u, mx, 2));
          float sum = 0.f;
#pragma unroll
          for (int n = 0; n < 5; n++) { const float e0 = ex2(v[n][0] - mx), e1 = ex2(v[n][1] - mx); sum += e0 + e1; P[n >> 1][(n & 1) * 2 + rh] = pack_bf16(e0, e1); }
          P[2][2 + rh] = 0u;
          sum += __shfl_xor_sync(~0u, sum, 1); sum += __shfl_xor_sync(~0u, sum, 2);
          asm("rcp.approx.ftz.f32 %0, %1;" : "=f"(inv[rh]) : "f"(sum));
        }
      }
      ATS(3)
      mbar_wait_long(ofree + b * 8, ((s >> 1) & 1) ^ 1);
      ATS(4)
      const uint32_t od = sb + SD_O + b * 8192 + (16 * a + (lane & 15)) * 128;
#pragma unroll 1
      for (int hf = 0; hf < 2; hf++) {
        float o[32];
        const uint64_t dv = desc_ns(rec + 20480 + hf * 5120, 1024, 128);
        WG_FENCE();
        wg_rs_n64(o, P[0], dv, 0); wg_rs_n64(o, P[1], dv + 128, 1); wg_rs_n64(o, P[2], desc_ns(rec + 20480 + hf * 5120 + 4096, 0, 128), 1);
        WG_COMMIT(); WG_WAIT(0);
        if (a < 2) {
#pragma unroll
          for (int n = 0; n < 8; n += 2) {
            const float* x = o + 4 * n;
            asm volatile("stmatrix.sync.aligned.m8n8.x4.shared.b16 [%0], {%1,%2,%3,%4};" :: "r"(od + hf * 4096 + (((n + (lane >> 4)) ^ (lane & 7)) << 4)),
              "r"(pack_bf16(x[0] * inv[0], x[1] * inv[0])), "r"(pack_bf16(x[2] * inv[1], x[3] * inv[1])), "r"(pack_bf16(x[4] * inv[0], x[5] * inv[0])), "r"(pack_bf16(x[6] * inv[1], x[7] * inv[1])) : "memory");
          }
        }
      }
      if (a < 2) {
        asm volatile("fence.proxy.async.shared::cta;" ::: "memory");
        __syncwarp();
        if (lane == 0) mbar_arrive(ofull + b * 8);
      }
      if (lane == 0) mbar_arrive(rfree + b * 8);
      ATS(5)
    }
    TL(3);
  } else {
    asm volatile("setmaxnreg.dec.sync.aligned.u32 56;");
    if (w == 13) {
      bar_sync<1, 320>();
#pragma unroll 1
      for (int s = 0; s < nseg; s++) {
        mbar_wait_long(ifree + (s & 1) * 8, ((s >> 1) & 1) ^ 1);
        wait_count(p.comm + FL_RDY + s * 16 + ks, nh);
        gate(s + 2);
        ATS(0)
        asm volatile(ELECT "@p mbarrier.arrive.expect_tx.shared.b64 _, [%2], %3;\n@p cp.async.bulk.shared::cluster.global.mbarrier::complete_tx::bytes [%0], [%1], %3, [%2];}"
          :: "r"(sb + SD_OI + (s & 1) * 40960), "l"(p.O + (size_t)((s % ORING) * 32 + h0) * 8192), "r"(ifull + (s & 1) * 8), "r"(nh * 8192) : "memory");
      }
    } else if (h >= 32 && w < 15) {
    } else if (w == 12) {
#pragma unroll 1
      for (int s = 0; s < nseg; s++) {
        mbar_wait_long(ofull + (s & 1) * 8, (s >> 1) & 1);
        int fin, guard = 0;
        do { asm volatile("ld.volatile.shared.b32 %0, [%1];" : "=r"(fin) : "r"(fdone) : "memory"); } while (fin + ORING <= s && ++guard < 1000000);
        ATS(0)
        asm volatile(ELECT "@p cp.async.bulk.global.shared::cta.bulk_group [%0], [%1], 8192;\n"
          "cp.async.bulk.commit_group;\ncp.async.bulk.wait_group 0;\n@p mbarrier.arrive.shared.b64 _, [%3];\n@p fence.proxy.async.global;\n@p red.release.gpu.global.add.u32 [%2], 1;}"
          :: "l"(p.O + (size_t)((s % ORING) * 32 + h) * 8192), "r"(sb + SD_O + (s & 1) * 8192), "l"(p.comm + FL_RDY + s * 16 + (h < 20 ? h / 5 : (h - 4) >> 2)), "r"(ofree + (s & 1) * 8) : "memory");
        ATS(1)
      }
      TL(4);
    } else if (w == 14) {
      if (DBGF(16)) pdl_wait(); else
      mbar_wait_long(ofull, 0);
#pragma unroll 1
      for (int s = 0; s < nseg; s++) {
        asm volatile("fence.proxy.async.shared::cta;" ::: "memory");
        __syncwarp();
        asm volatile(ELECT "@p mbarrier.arrive.expect_tx.shared.b64 _, [%2], 10240;\n@p cp.async.bulk.shared::cluster.global.mbarrier::complete_tx::bytes [%0], [%1], 1280, [%2];}"
          :: "r"(sb + SD_FIN + 8960), "l"(p.x1 + (size_t)(s * 32 + h) * D_), "r"(ffull) : "memory");
        wait_count(p.comm + FL_RDY + s * 16 + 8, 35);
        ATS(0)
        asm volatile(ELECT "@p cp.async.bulk.shared::cluster.global.mbarrier::complete_tx::bytes [%0], [%1], 8960, [%2];}"
          :: "r"(sb + SD_FIN), "l"(p.part + (size_t)((s % PRING) * 32 + h) * 8960), "r"(ffull) : "memory");
        mbar_wait_long(ffull, s & 1);
        ATS(1)
        asm volatile("st.volatile.shared.b32 [%0], %1;" :: "r"(fdone), "r"(s + 1) : "memory");
#pragma unroll
        for (int i = 0; i < 5; i++) {
          uint32_t v[8][2];
#pragma unroll
          for (int u = 0; u < 8; u++) asm volatile("ld.shared.v2.b32 {%0,%1}, [%2];" : "=r"(v[u][0]), "=r"(v[u][1]) : "r"(sb + SD_FIN + u * 1280 + i * 256 + lane * 8) : "memory");
          uint32_t y[2];
#pragma unroll
          for (int k = 0; k < 2; k++) {
            y[k] = pack_bf16(((bf_lo(v[0][k]) + bf_lo(v[1][k])) + (bf_lo(v[2][k]) + bf_lo(v[3][k]))) + ((bf_lo(v[4][k]) + bf_lo(v[5][k])) + bf_lo(v[6][k])),
                             ((bf_hi(v[0][k]) + bf_hi(v[1][k])) + (bf_hi(v[2][k]) + bf_hi(v[3][k]))) + ((bf_hi(v[4][k]) + bf_hi(v[5][k])) + bf_hi(v[6][k])));
            asm("add.rn.bf16x2 %0, %0, %1;" : "+r"(y[k]) : "r"(v[7][k]));
          }
          *(uint2*)(p.out + (size_t)(s * 32 + h) * D_ + i * 128 + lane * 4) = make_uint2(y[0], y[1]);
        }
        __syncwarp();
        if (lane == 0 && p.first) red_release(p.comm + FL_RDY + s * 16 + 12);
        ATS(2)
      }
    } else {
      uint32_t lp = 0, known = 0;
      bar_sync<1, 320>();
#pragma unroll 1
      for (int s = 0; s < nseg; s++) {
        const int b = s & 1;
        const uint32_t rec = sb + SD_REC + b * 30720;
        if (h < 32) mbar_wait_long(rfree + b * 8, ((s >> 1) & 1) ^ 1);
        uint32_t f = ~0u;
#pragma unroll 1
        for (int guard = 0; guard < 100000; guard++) {
          if (lane < 3) asm volatile("ld.relaxed.gpu.global.u32 %0, [%1];" : "=r"(f) : "l"(p.comm + FL_MEM + (h & 31) * 32 + lane * 8) : "memory");
          known = __reduce_min_sync(~0u, f & 127);
          if (known > (uint32_t)(s + (s < NSEG - 2 && !(p.mask & 8)))) break;
        }
        f = __shfl_sync(~0u, f, 0);
        if (lane == 0) asm volatile("st.volatile.shared.b32 [%0], %1;" :: "r"(fdone + 4), "r"(f) : "memory");
        if (h >= 32) continue;
        __syncwarp();
        const char* src = p.QKV + (size_t)((s % QRING) * 32 + h) * 30720;
#pragma unroll 1
        for (int tries = 0; tries < 20000; tries++) {
          if ((f & 127) == s + 1 && tries == (s >= NSEG - 2)) { const uint32_t t = s == NSEG - 1 ? p.tmem - 512 : p.tmem; for (int guard = 0; since(f) < t && guard < 4000; guard++) {} }
          if (tries == 0) gate(s);
          ATS(0)
          asm volatile("fence.proxy.async.shared::cta;" ::: "memory");
          __syncwarp();
          if (tries == 0) asm volatile(ELECT "@p mbarrier.arrive.expect_tx.shared.b64 _, [%2], 30720;\n@p cp.async.bulk.shared::cluster.global.mbarrier::complete_tx::bytes [%0], [%1], 30720, [%2];}" :: "r"(rec), "l"(src), "r"(rland) : "memory");
          else asm volatile(ELECT "@p mbarrier.arrive.expect_tx.shared.b64 _, [%2], 4096;\n"
            "@p cp.async.bulk.shared::cluster.global.mbarrier::complete_tx::bytes [%0+5120], [%1+5120], 1024, [%2];\n@p cp.async.bulk.shared::cluster.global.mbarrier::complete_tx::bytes [%0+15360], [%1+15360], 1024, [%2];\n"
            "@p cp.async.bulk.shared::cluster.global.mbarrier::complete_tx::bytes [%0+20480], [%1+20480], 1024, [%2];\n@p cp.async.bulk.shared::cluster.global.mbarrier::complete_tx::bytes [%0+25600], [%1+25600], 1024, [%2];}"
            :: "r"(rec), "l"(src), "r"(rland) : "memory");
          mbar_wait_long(rland, lp); lp ^= 1;
          uint32_t mx = 0;
#pragma unroll
          for (int k = 0; k < 4; k++) { uint32_t v; asm volatile("ld.shared.b32 %0, [%1];" : "=r"(v) : "r"(rec + (k == 0 ? 5120 : 10240 + k * 5120) + lane * 32 + (lane >> 2) * 4) : "memory"); mx = max(mx, v); }
          if (__all_sync(~0u, mx != ~0u)) break;
        }
        if (lane == 0) { mbar_arrive(rfull + b * 8); asm volatile("st.relaxed.gpu.global.u32 [%0], %1;" :: "l"(p.comm + FL_MEM + h * 32 + 24), "r"(s + 1) : "memory"); }
      }
    }
    if (w == 14) { TL(6); __syncwarp(); TL_DUMP((p.first ^ 1) * 166 + 131 + h, lane); }
    if (!p.first && tid == 448 && h == 0) { for (int i = 0; i < 8; i++) p.sync[i * 32 - 128] = 0; }
  }
}

__device__ __forceinline__ uint32_t ld_relaxed(const void* p) { uint32_t v; asm volatile("ld.relaxed.gpu.global.u32 %0, [%1];" : "=r"(v) : "l"(p) : "memory"); return v; }
__device__ __forceinline__ void st_relaxed(void* p, uint32_t v) { asm volatile("st.relaxed.gpu.global.u32 [%0], %1;" :: "l"(p), "r"(v) : "memory"); }
__device__ __forceinline__ void st_relaxed_if(void* p, uint32_t v, uint32_t c) { asm volatile("{.reg .pred p; setp.ne.u32 p, %2, 0; @p st.relaxed.gpu.global.u32 [%0], %1;}" :: "l"(p), "r"(v), "r"(c) : "memory"); }
__device__ __forceinline__ uint32_t clk32() { uint32_t c; asm volatile("mov.u32 %0, %%clock;" : "=r"(c) :: "memory"); return c; }
__device__ __forceinline__ uint32_t gt32() { uint64_t c; asm volatile("mov.u64 %0, %%globaltimer;" : "=l"(c) :: "memory"); return (uint32_t)c; }
__device__ __forceinline__ void wait_gt(uint32_t T) {
  asm volatile("{\n.reg .pred p;\n.reg .u64 t;\n.reg .u32 lo, hi;\nLG%=:\nmov.u64 t, %%globaltimer;\nmov.b64 {lo, hi}, t;\nsub.u32 lo, lo, %0;\nsetp.lt.s32 p, lo, 0;\n@p bra.uni LG%=;\n}" :: "r"(T) : "memory");
}
__device__ __forceinline__ void advance(uint32_t& T, uint32_t lim, uint32_t step) {
  asm volatile("{\n.reg .pred p;\n.reg .s32 d;\nLA%=:\nsub.s32 d, %1, %0;\nsetp.gt.s32 p, d, 0;\n@p add.u32 %0, %0, %2;\n@p bra.uni LA%=;\n}" : "+r"(T) : "r"(lim), "r"(step));
}
template <int LUT> __device__ __forceinline__ uint32_t lop3(uint32_t a, uint32_t b, uint32_t c) { uint32_t r; asm("lop3.b32 %0, %1, %2, %3, %4;" : "=r"(r) : "r"(a), "r"(b), "r"(c), "n"(LUT)); return r; }
__device__ __forceinline__ uint32_t ldsm1t(uint32_t a) { uint32_t r; asm volatile("ldmatrix.sync.aligned.m8n8.x1.trans.shared.b16 {%0}, [%1];" : "=r"(r) : "r"(a) : "memory"); return r; }
__device__ __forceinline__ uint32_t hmax2(uint32_t a, uint32_t b) { uint32_t r; asm("max.bf16x2 %0, %1, %2;" : "=r"(r) : "r"(a), "r"(b)); return r; }
__device__ __forceinline__ uint32_t lds32(uint32_t a) { uint32_t v; asm volatile("ld.shared.b32 %0, [%1];" : "=r"(v) : "r"(a) : "memory"); return v; }
__device__ __forceinline__ void sts32(uint32_t a, uint32_t v) { asm volatile("st.shared.b32 [%0], %1;" :: "r"(a), "r"(v) : "memory"); }
__device__ __forceinline__ uint32_t mapa(uint32_t a, int rank) { uint32_t r; asm("mapa.shared::cluster.u32 %0, %1, %2;" : "=r"(r) : "r"(a), "r"(rank)); return r; }
template <int OFF> __device__ __forceinline__ void stas32(uint32_t a, uint32_t v, uint32_t bar) {
  asm volatile("st.async.weak.shared::cluster.mbarrier::complete_tx::bytes.b32 [%0+%3], %1, [%2];" :: "r"(a), "r"(v), "r"(bar), "n"(OFF) : "memory");
}
#define OPAQUE(x) x = __shfl_sync(~0u, x, lane)
#define CLUSTER_SYNC() asm volatile("barrier.cluster.arrive.release.aligned; barrier.cluster.wait.acquire.aligned;" ::: "memory")

constexpr int SM_BAR = 0;
constexpr int SM_WO = 2048;
constexpr int SM_VR = 43008;
constexpr int SM_RED = 59392;
constexpr int SM_AT = 67584;
constexpr int SM_MEMT = 108672;
constexpr int SM_QK = 119040;
constexpr int SM_SC = 123136;
constexpr int SM_OX = 125184;
constexpr int SM_VM = 127744;
constexpr int SM_ST = 139264;
constexpr int SM_X = 149504;
constexpr int SM_WST = 2048;
constexpr int SM_WS = 67584;
constexpr int REC_SMEM = 231424 + 1024;
constexpr int MB_A = 0, MB_QK = 24, MB_R = 32, MB_V = 56, MB_KV = 64, MB_X = 80, MB_IA = 96, MB_IC = 104, MB_TK = 112, MB_PRB = 120, MB_DP = 128, MB_TAB = 256, MB_T2 = 512;
#define NTQ 10
#define NTV 4
#define NB0 4
#define PINK 14
#define NB1 7
#define PINT 5
#define WPLAN 0x5542110
#define OPF 3
#define XPOS 1
#define W0K 4
#define NLATE 1
#define VPOS 0
#define XK 2
#define IMM 0
#define DLY2 0
#define DLY3 0
#define GATEK 3
#define TOLQ 96
#define TOLV 160
constexpr int POLL_LIMIT = 20000;
constexpr int CM_X3 = 160, CM_MISC = 172;
__device__ __forceinline__ uint32_t x3_slot(int slot) { return (CM_X3 + (slot & 1) * 64 + (slot & 2) * 128) * 4096; }
__device__ __forceinline__ int near_page(int pg, int side) { return pg + ((__popc(pg & 0xB3) ^ side) & 1); }
__device__ __forceinline__ int mem_line(int jb) { const int ks = jb >> 1, c = ks >= 20, kk = ks - 20 * c; return (kk >> 2) * 16 + c * 8 + (kk & 3) * 2 + (jb & 1); }

struct RecParams {
  CUtensorMap tmW[3], tmWo, tmX;
  AParams a[2];
  const bf16 *mem0, *wr, *wi;
  char* QKV;
  uint32_t* comm;
  uint64_t dhi;
  int period, c3, slack, xlate, gap, zero, helper, layer, dbgf;
  uint32_t *dbg, *log;
};
#define PRB(k)
#define LDW(d, a) ldsm4t(d[0], d[1], d[2], d[3], a)

#undef TLBASE
#define TLBASE (1024 + 896)
#define PRBASE (mbar + w * 16)
#define PRIMM 1024
#define PROFF 0
template <bool VR>
__device__ __forceinline__ void rec_gemm_warps(const RecParams& p, const uint32_t sb, const int h, const int r, const int L, const int w) {
  const int tid = tid_here(), lane = tid & 31;
  const int mg = w & 3, c = w >> 2;
  constexpr int NT = VR ? NTV : NTQ, NW = VR ? 8 : 16;
  uint32_t R[20][4], P[20][4], Wr[NW - NT][4];
  const uint32_t mbar = sb + SM_BAR;
  uint32_t l16 = lane * 16, lm = (lane >> 4) * 1024 + (lane & 15) * 16;
  OPAQUE(l16); OPAQUE(lm);
#define wl16 (l16 + (sb + w * 512))
  {
    const uint32_t boxoff = (((lane >> 4) << 3) + (lane & 7)) * 128 + (((2 * mg + ((lane >> 3) & 1)) ^ (lane & 7)) << 4);
    mbar_wait(mbar + MB_IA, 0);
    TL(15);
    const uint32_t wa = sb + SM_WS + c * 40960 + boxoff;
#pragma unroll
    for (int k = 0; k < 20; k++) LDW(R[k], wa + 81920 + k * 2048);
    bar_arrive<4, 288>();
#pragma unroll
    for (int k = 0; k < 20; k++) LDW(P[k], wa + k * 2048);
    bar_sync<2, 256>();
#pragma unroll
    for (int i = 0; i < NT; i++) sts128(wl16 + SM_AT + i * 4096, P[i][0], P[i][1], P[i][2], P[i][3]);
    mbar_wait(mbar + MB_IC, 0);
    TL(16);
    const uint32_t woa = sb + SM_WST + c * 16384 + boxoff;
#pragma unroll
    for (int i = 0; i < NW; i++) {
      const uint32_t a = woa + (VR ? i * 2048 : (i & 1) * 32768 + (i >> 1) * 2048);
      if (i >= 4 && i < 4 + NW - NT) LDW(Wr[i - 4], a); else LDW(P[i < 4 ? i : i - (NW - NT)], a);
    }
    asm volatile("fence.proxy.async.shared::cta;" ::: "memory");
    bar_sync<1, 384>();
#pragma unroll
    for (int i = 0; i < NT; i++) sts128(wl16 + SM_WO + i * 4096, P[i][0], P[i][1], P[i][2], P[i][3]);
    asm volatile("barrier.cluster.arrive.relaxed.aligned; barrier.cluster.wait.aligned;" ::: "memory");
  }
#define LDT(i) lds128(P[i], wl16 + SM_AT + (i) * 4096)
#define WGX(acc, A, ks, sc) wg_rs_n32(acc, A[ks], d##A + (((ks) >> 2) * 256 + ((ks) & 3) * 2), sc)
  float tb[16];
  constexpr int KW = VR ? 20 - W0K : 20;
  auto stream0 = [&](int n) {
    const uint64_t dP = p.dhi + (uint32_t)(((sb + SM_X + c * 20480) >> 4) + (n & 1) * 2560 + ((n + 1) & p.zero));
    WG_FENCE();
#pragma unroll
    for (int k = KW; k < 20; k++) WGX(tb, P, k, k - KW);
    WG_COMMIT();
  };
  auto stream = [&](int n) {
    float ta[16];
    const uint64_t dR = p.dhi + (uint32_t)(((sb + SM_X + c * 20480) >> 4) + (n & 1) * 2560), dP = dR + (uint32_t)(~n & p.zero);
    WG_FENCE();
    constexpr int NE = NT - (VR ? NLATE : 4);
#pragma unroll
    for (int k = 0; k < 20; k++) { WGX(ta, R, k, k); if ((k & 1) && k / 2 < NE) LDT(k / 2); }
    WG_COMMIT();
#define GATE(i) if (VR && (i) == GATEK) { if (GATEK) WG_COMMIT(); asm volatile("bar.sync 12, %0;" :: "r"((h & 1) ? 320 : 352) : "memory"); WG_FENCE(); }
    constexpr int K2 = VR ? NT + XK : 16;
#pragma unroll
    for (int k = K2; k < KW; k++) { GATE(k - K2); WGX(tb, P, k, KW < 20 || k > K2); }
    WG_COMMIT();
    WG_WAIT(1);
#pragma unroll
    for (int i = 0; i < 2; i++)
      sts128(l16 + (sb + (w ^ 4) * 512) + SM_RED + i * 4096, pack_bf16(ta[8 * i], ta[8 * i + 1]), pack_bf16(ta[8 * i + 2], ta[8 * i + 3]), pack_bf16(ta[8 * i + 4], ta[8 * i + 5]), pack_bf16(ta[8 * i + 6], ta[8 * i + 7]));
#pragma unroll
    for (int i = NE; i < NT; i++) LDT(i);
#pragma unroll
    for (int k = NT; k < K2; k++) { GATE(KW - K2 + k - NT); WGX(tb, P, k, 1); }
    WG_FENCE();
#pragma unroll
    for (int k = 0; k < NE; k++) WGX(tb, P, k, 1);
    bar_sync<11, 384>();
    uint32_t o[2][4];
    lds128(o[0], wl16 + SM_RED); lds128(o[1], wl16 + SM_RED + 4096);
    WG_FENCE();
#pragma unroll
    for (int k = NE; k < NT; k++) WGX(tb, P, k, 1);
    WG_COMMIT();
    WG_WAIT(0);
#pragma unroll
    for (int i = 0; i < 2; i++)
      asm volatile("stmatrix.sync.aligned.m8n8.x4.shared.b16 [%0], {%1,%2,%3,%4};" :: "r"(lm + (sb + (c ^ 1) * 5120 + mg * 256) + SM_ST + 1024 + i * 2048),
        "r"(hadd2(pack_bf16(tb[8 * i], tb[8 * i + 1]), o[i][0])), "r"(hadd2(pack_bf16(tb[8 * i + 2], tb[8 * i + 3]), o[i][1])),
        "r"(hadd2(pack_bf16(tb[8 * i + 4], tb[8 * i + 5]), o[i][2])), "r"(hadd2(pack_bf16(tb[8 * i + 6], tb[8 * i + 7]), o[i][3])) : "memory");
    bar_arrive<14, 320>();
  };
  int s = -2, att = 0;
#pragma unroll 1
  while (true) {
    if (s >= 0) {
    uint32_t B[10][4], Wf[NT][4], dp[4];
    float ap[2][4], ar[2][4];
#define LDO(i, base) lds128(Wf[i], (base) + SM_WO + (i) * 4096)
#define LDB(k2) ldsm4t(B[k2][0], B[k2][1], B[k2][2], B[k2][3], l16 + (sb + c * 1024) + SM_MEMT + ((k2) >> 1) * 2048 + ((k2) & 1) * 512)
#define BK(k) B[(k) >> 1][((k) & 1) * 2], B[(k) >> 1][((k) & 1) * 2 + 1]
    mbar_wait(mbar + MB_A, att & 1);
    PRB(0)
    LDB(0); LDB(1);
#pragma unroll
    for (int k = 0; k < 20; k++) {
      if (!(k & 1) && k < 16) LDB(k / 2 + 2);
      if (k == PINK) {
        const uint32_t wb = lop3<0xF8>(l16, __float_as_uint(ap[0][0]), p.zero) + (sb + w * 512);
#pragma unroll
        for (int u = 0; u < NB0 && u < NT; u++) LDO(u, wb);
      }
      if (k < 2) { mmaZ(ap[k], P[k], BK(k)); mmaZ(ar[k], R[k], BK(k)); } else { mmaA(ap[k & 1], P[k], BK(k)); mmaA(ar[k & 1], R[k], BK(k)); }
    }
    asm volatile("stmatrix.sync.aligned.m8n8.x4.shared.b16 [%0], {%1,%2,%3,%4};" :: "r"(lm + (sb + c * 2048 + mg * 256) + SM_QK),
      "r"(pack_bf16(ar[0][0] + ar[1][0], ar[0][1] + ar[1][1])), "r"(pack_bf16(ar[0][2] + ar[1][2], ar[0][3] + ar[1][3])),
      "r"(pack_bf16(ap[0][0] + ap[1][0], ap[0][1] + ap[1][1])), "r"(pack_bf16(ap[0][2] + ap[1][2], ap[0][3] + ap[1][3])) : "memory");
    bar_arrive<9, 384>();
    PRB(1)
    att++;
    uint32_t bad;
    asm volatile("{.reg .pred p; setp.ne.u32 p, 0, 0; bar.red.or.pred p, 8, 384, p; selp.u32 %0, 1, 0, p;}" : "=r"(bad) :: "memory");
    if (bad) {
#pragma unroll
      for (int i = 0; i < NT; i++) LDT(i);
      continue;
    }
    if (s == NSEG - 1) break;
    if (KW < 20) stream0(s);
    lds128(dp, mbar + MB_DP + w * 16);
#pragma unroll
    for (int i = NB0; i < NT && (VR || i < NB1); i++) LDO(i, wl16);
    uint32_t fmask = (~(l16 | dp[0]) >> 4) & 1, bit = ((s >> 1) & 1) ? 0u : fmask;
    char* cb = (char*)p.comm + ((s & 1) * (256 * 4096) + (l16 >> 2));
    char *d0 = cb + dp[0], *d1 = cb + dp[1], *d2 = cb + dp[2], *d3 = cb + dp[3];
    if (VR) asm volatile("" : "+l"(d0), "+l"(d1), "+r"(bit), "+r"(fmask)); else asm volatile("" : "+l"(d0), "+l"(d1), "+l"(d2), "+l"(d3), "+r"(bit), "+r"(fmask));
    if (KW < 20) WG_WAIT(0);
    sched_fence();
    if (VR) bar_arrive<2, 384>();
    else {
      bar_sync<2, 384>();
#pragma unroll
      for (int i = NB1; i < NT; i++) LDO(i, wl16);
    }
    bar_sync<3, 384>();
    PRB(2)
    uint32_t ob[4][4];
    float z0, z1;
#pragma unroll
    for (int i = 0; i < 4; i++) LDW(ob[i], l16 + sb + SM_OX + i * 512);
    asm volatile("ld.shared.v2.f32 {%0,%1}, [%2];" : "=f"(z0), "=f"(z1) : "r"(l16 + sb + SM_OX + 2048) : "memory");
#define WO(i) ((i) >= 4 && (i) < 4 + NW - NT ? Wr[(i) >= 4 && (i) < 4 + NW - NT ? (i) - 4 : 0] : Wf[(i) < 4 ? (i) : (i) < 4 + NW - NT ? 0 : (i) - (NW - NT)])
    float ga[4][4];
#pragma unroll
    for (int i = 0; i < NW; i++) {
      const int ks = VR ? i : i >> 1;
      if (i < 4) mmaZ(ga[i], WO(i), ob[ks >> 1][(ks & 1) * 2], ob[ks >> 1][(ks & 1) * 2 + 1]); else mmaA(ga[i & 3], WO(i), ob[ks >> 1][(ks & 1) * 2], ob[ks >> 1][(ks & 1) * 2 + 1]);
    }
    asm("rcp.approx.ftz.f32 %0, %0;" : "+f"(z0)); asm("rcp.approx.ftz.f32 %0, %0;" : "+f"(z1));
#pragma unroll
    for (int i = 0; i < 4; i++) { ga[0][i] += ga[2][i]; ga[1][i] += ga[3][i]; if (VR) ga[0][i] += ga[1][i]; }
#pragma unroll
    for (int t = 0; t < NW / 8; t++) {
      st_relaxed(t ? d2 : d0, lop3<0xF4>(bit, pack_bf16(ga[t][0] * z0, ga[t][1] * z1), fmask));
      st_relaxed(t ? d3 : d1, lop3<0xF4>(bit, pack_bf16(ga[t][2] * z0, ga[t][3] * z1), fmask));
    }
    PRB(3)
    } else { mbar_wait(mbar + MB_X + (s & 1) * 8, 0); if (KW < 20) { stream0(s); WG_WAIT(0); } }
    bar_sync<10, 256>();
    stream(s);
    PRB(4)
    s++;
  }
  if (__all_sync(~0u, lds32(mbar + MB_TAB + 4) == 0)) {
#pragma unroll
    for (int i = 0; i < NT; i++) LDT(i);
    bar_sync<1, 384>();
    const int ln = l16 >> 4;
    const uint32_t wa = sb + SM_WS + c * 40960 + (((ln >> 4) << 3) + (ln & 7)) * 128 + (((2 * mg + ((ln >> 3) & 1)) ^ (ln & 7)) << 4);
#pragma unroll
    for (int k = 0; k < 40; k++) {
      const uint32_t* f = k < 20 ? R[k % 20] : P[k % 20];
      asm volatile("stmatrix.sync.aligned.m8n8.x4.trans.shared.b16 [%0], {%1,%2,%3,%4};" :: "r"(wa + (k < 20 ? 81920 : 0) + (k % 20) * 2048), "r"(f[0]), "r"(f[1]), "r"(f[2]), "r"(f[3]) : "memory");
    }
  }
#undef wl16
}

#undef PRBASE
#undef PRIMM
#undef PROFF
#define PRBASE (mbar + j * 16)
#define PRIMM (1024 + 4)
#define PROFF 8
__device__ __forceinline__ void x_load(const RecParams& p, const uint32_t sb, int n) {
  if (DBGF(32)) { if ((threadIdx.x & 31) == 0) mbar_arrive(sb + SM_BAR + MB_X + (n & 1) * 8); return; }
  asm volatile(ELECT "@p mbarrier.arrive.expect_tx.shared.b64 _, [%2], 40960;\n"
    "@p cp.async.bulk.tensor.3d.shared::cluster.global.mbarrier::complete_tx::bytes [%0], [%1, {%3, %4, %3}], [%2];}"
      :: "r"(sb + SM_X + (n & 1) * 40960), "l"(&p.tmX), "r"(sb + SM_BAR + MB_X + (n & 1) * 8), "r"(0), "r"(n * 32) : "memory");
}
__device__ __forceinline__ int rec_attn_setup(const RecParams& p, const uint32_t sb, const int h, const int r, const int L, const int j) {
  const int ct = tid_here() - 256, lane = ct & 31;
  const uint32_t mbar = sb + SM_BAR;
  uint32_t* misc = p.comm + CM_MISC * 1024;
  if (j == 2 && lane == 0 && L == 0) {
    uint32_t b0 = 60000, b1 = 60000;
#pragma unroll 1
    for (int it = 0; it < 40; it++) {
      uint32_t* a = misc + (it & 1) * 1024 + 128 + blockIdx.x * 8;
      const uint32_t t0 = clk32();
      uint32_t v; asm volatile("atom.relaxed.gpu.global.exch.b32 %0, [%1], %2;" : "=r"(v) : "l"(a), "r"(t0) : "memory");
      st_relaxed_if(a, 0, v == t0 + 1);
      const uint32_t t = clk32() - t0;
      if (it & 1) b1 = min(b1, t); else b0 = min(b0, t);
      if (it >= 5 && min(b0, b1) < 370 && min(b0, b1) + 80 < max(b0, b1)) break;
    }
    sts32(mbar + MB_PRB, b0); sts32(mbar + MB_PRB + 4, b1);
  }
  if (ct == 32 && L == 0) { uint32_t sm; asm volatile("mov.u32 %0, %%smid;" : "=r"(sm)); st_relaxed(p.comm + FL_SM + sm, 1); }
  if (blockIdx.x == 0 && ct == 0 && L == 0) st_relaxed(misc + 96, gt32() & ~31u);
  bar_sync<15, 128>();
  const uint32_t b0 = lds32(mbar + MB_PRB), b1 = lds32(mbar + MB_PRB + 4);
  const int side = __shfl_sync(~0u, ((b1 < b0) ^ __popc(CM_MISC & 0xB3)) & 1, 0);
  if (r == 2 && lane == 0 && j + (h & 1) < 3) st_relaxed(misc + (j < 2 ? 2 * h + j : 64 + (h >> 1)), side);
  if (j < 2) {
    const int job = 2 * (16 * r + (lane >> 2) + ((lane & 2) && r < 2 ? 8 : 0)) + (lane & 1);
    uint32_t v; int guard = 0;
    do { v = ld_relaxed(misc + (j ? 96 : job)); } while (v == 0xFFFFFFFFu && ++guard < 1000000);
    sts32(mbar + (j ? MB_TK : MB_DP + lane * 4), j ? v + (gt32() - v) / p.slack * p.slack : near_page(2 * job, v) * 4096 + h * 128);
    __syncwarp();
  }
  uint32_t m0[5][4];
#pragma unroll
  for (int i = 0; i < 20; i++) m0[i >> 2][i & 3] = *(const uint32_t*)(p.mem0 + (lane >> 2) * D_ + (j * 20 + i) * 8 + (lane & 3) * 2);
  if (j == 3) {
    spin_count(p.a[L].sync + SY_3, 128);
    bar_sync<4, 288>();
    asm volatile("fence.proxy.async;" ::: "memory");
    x_load(p, sb, 0); x_load(p, sb, 1);
    TL(17);
  }
  bar_sync<1, 384>();
  asm volatile("barrier.cluster.arrive.relaxed.aligned;" ::: "memory");
#pragma unroll
  for (int i = 0; i < 5; i++)
    asm volatile("stmatrix.sync.aligned.m8n8.x4.trans.shared.b16 [%0], {%1,%2,%3,%4};" :: "r"(sb + SM_MEMT + mem_line(j * 20 + i * 4) * 128 + lane * 16), "r"(m0[i][0]), "r"(m0[i][1]), "r"(m0[i][2]), "r"(m0[i][3]) : "memory");
  sts128(sb + SM_ST + (ct >> 6) * 5120 + (ct & 63) * 16, ~0u, ~0u, ~0u, ~0u);
  asm volatile("barrier.cluster.wait.aligned;" ::: "memory");
  return side;
}
__device__ __forceinline__ void rec_attn_warps(const RecParams& p, const uint32_t sb, char* smem, const int h, const int r, const int side, const int L, const int j) {
  const int lane = tid_here() & 31, mi = lane >> 3;
  const uint32_t mbar = sb + SM_BAR;
#define VR (r == 2)
#define is_red (j + (h & 1) < 3 * r - 3)
  uint32_t l16 = sb + lane * 16;
#define wr16 (l16 + j * 512)
#define L0 ((l16 & 511) == 0)
  uint32_t ka = VR ? (mi != (lane & 3) ? 0u : (lane & 4) ? 0x3F800000u : 0x00003F80u)
    : j < 2 ? sb + SM_ST + 6144 + (2 * j + (mi & 1)) * 1024 + ((mi >> 1) * 8 + (lane & 7)) * 16 : sb + SM_QK + j * 512 + ((mi & 1) * 16 + (mi >> 1) * 8 + (lane & 7)) * 16;
  uint32_t own = VR ? sb + SM_AT + 28672 + j * 4096 + lane * 32 + (lane & 12) * 2 : sb + SM_SC + r * 1024 + (j < 2 ? j * 256 : 256 + j * 128) + lane * 4;
  uint32_t va = sb + SM_VR + (j >> 1) * 4096 + (mi >> 1) * 1024 + ((j & 1) * 32 + (mi & 1) * 8 + (lane & 7)) * 16, ps[2], pb[2];
#pragma unroll
  for (int i = 0; i < 2; i++) {
    const int peer = VR ? i : i == 0 ? r ^ 1 : 2;
    ps[i] = mapa(VR ? wr16 + SM_VM : own, peer); pb[i] = mapa(mbar + (VR ? MB_V : MB_QK), peer);
    OPAQUE(ps[i]); OPAQUE(pb[i]);
  }
  OPAQUE(ka); OPAQUE(own); OPAQUE(va); OPAQUE(l16);
  const char* comm = (const char*)p.comm;
  const uint32_t ones = 0x3F803F80u;
  const float sc2 = 0.08838834764831845f * 1.4426950408889634f;
  uint32_t kf[4][4], vf[4][4];
#pragma unroll
  for (int i = 0; i < 16; i++) kf[i >> 2][i & 3] = vf[i >> 2][i & 3] = p.zero;
  char* const rec0 = p.QKV + (h * 3 + r) * 10240;
  uint32_t* const fl = p.comm + FL_MEM + (L * 32 + h) * 32;
#define REC(n) (rec0 + ((n) & (QRING - 1)) * (96 * 10240))
  auto m_store = [&](int n) {
    if (VR || j < 2) {
      const int jj = VR ? j : j + 2;
      uint32_t a[4], b[4]; lds128(a, l16 + jj * 512 + SM_QK); lds128(b, l16 + (jj ^ 2) * 512 + SM_QK + 2048);
      asm volatile("st.relaxed.gpu.global.v4.u32 [%0], {%1,%2,%3,%4};" :: "l"(REC(n) + ((jj >> 1) * 5120 + (j & 1) * 512) + (l16 & 511)),
        "r"(hadd2(a[0], b[0])), "r"(hadd2(a[1], b[1])), "r"(hadd2(a[2], b[2])), "r"(hadd2(a[3], b[3])) : "memory");
    }
  };
  int att = 1, rph = 0;
  const int jb = j < 2 ? 2 * h + j : 64 + (h >> 1), ln = mem_line(jb) + 16;
  const uint32_t inbox = near_page(2 * jb, side) * 4096, bline = (ln >> 5) * 16384 + (ln & 31) * 128;
#define VERDICT(bad) asm volatile("{.reg .pred p; setp.ne.u32 p, %0, 0; bar.red.or.pred p, 8, 384, p;}" :: "n"(bad) : "memory")
#pragma unroll 1
  for (int s = -2; s < NSEG - 1; s++) {
    const uint32_t par = s & 1;
    auto v_load = [&]() {
      asm volatile("cp.async.bulk.wait_group 0;" ::: "memory");
      if (VR) asm volatile(ELECT
        "@p cp.async.bulk.shared::cluster.global.mbarrier::complete_tx::bytes.multicast::cluster [%0], [%1+1024], 4096, [%2], %3;\n"
        "@p cp.async.bulk.shared::cluster.global.mbarrier::complete_tx::bytes.multicast::cluster [%0+4096], [%1+6144], 4096, [%2], %3;}"
          :: "r"(sb + SM_VR + (par ^ 1) * 8192), "l"(REC(s + 1)), "r"(mbar + MB_KV + (par ^ 1) * 8), "h"((unsigned short)7) : "memory");
    };
    auto load_v = [&]() {
      if (s >= -1) mbar_wait(mbar + MB_KV + (par ^ 1) * 8, ((s + 1) >> 1) & 1);
#pragma unroll
      for (int i = 0; i < 4; i++) ldsm4(vf[i][0], vf[i][1], vf[i][2], vf[i][3], va + (par ^ 1) * 8192 + (i >> 1) * 2048 + (i & 1) * 256);
    };
    if (s >= 0) {
    uint32_t su[6], sw[6], vm[4];
#define LDSM2T(d, a) asm volatile("ldmatrix.sync.aligned.m8n8.x2.trans.shared.b16 {%0,%1}, [%2];" : "=r"(d[4]), "=r"(d[5]) : "r"(a) : "memory")
#define HADD4(a, b) { a[0] = hadd2(a[0], b[0]); a[1] = hadd2(a[1], b[1]); a[2] = hadd2(a[2], b[2]); a[3] = hadd2(a[3], b[3]); }
    bar_sync<9, 384>();
    PRB(0)
    {
      uint32_t qf[2][4], qg[2][4];
      float sa[4][4];
      if (j + (r & 2) < 2) {
        LDW(qf[0], l16 + SM_QK); LDW(qg[0], l16 + SM_QK + 3072); LDW(qf[1], l16 + SM_QK + 512); LDW(qg[1], l16 + SM_QK + 3584);
        HADD4(qf[0], qg[0]); HADD4(qf[1], qg[1]);
#pragma unroll
        for (int i = 0; i < 4; i++) mmaZ(sa[i], kf[i], qf[i >> 1][(i & 1) * 2], qf[i >> 1][(i & 1) * 2 + 1]);
        const uint32_t t0 = pack_bf16((sa[0][0] + sa[1][0]) + (sa[2][0] + sa[3][0]), (sa[0][1] + sa[1][1]) + (sa[2][1] + sa[3][1]));
        const uint32_t t1 = pack_bf16((sa[0][2] + sa[1][2]) + (sa[2][2] + sa[3][2]), (sa[0][3] + sa[1][3]) + (sa[2][3] + sa[3][3]));
        stas32<0>(ps[0], t0, pb[0]); stas32<0>(ps[1], t0, pb[1]); stas32<128>(ps[0], t1, pb[0]); stas32<128>(ps[1], t1, pb[1]);
        sts32(own, t0); sts32(own + 128, t1);
      } else if (!VR) {
        LDW(qf[0], wr16 + SM_QK - 1024); LDW(qg[0], wr16 + SM_QK + 2048); LDW(qf[1], ka); LDW(qg[1], ka + 1024);
        HADD4(qf[0], qg[0]); HADD4(qf[1], qg[1]);
        mmaZ(sa[0], qf[1], qf[0][0], qf[0][1]); mmaZ(sa[1], qf[1], qf[0][2], qf[0][3]);
        const uint32_t t0 = pack_bf16(sa[0][0] + sa[1][2], sa[0][1] + sa[1][3]);
        stas32<0>(ps[0], t0, pb[0]); stas32<0>(ps[1], t0, pb[1]);
        sts32(own, t0);
      } else {
        ldsm4(qf[0][0], qf[0][1], qf[0][2], qf[0][3], wr16 + SM_QK); ldsm4(qg[0][0], qg[0][1], qg[0][2], qg[0][3], l16 + (j ^ 2) * 512 + SM_QK + 2048);
        HADD4(qf[0], qg[0]);
        sts128(wr16 + SM_VM, qf[0][0], qf[0][1], qf[0][2], qf[0][3]);
#pragma unroll
        for (int i = 0; i < 2; i++)
          asm volatile("st.async.weak.shared::cluster.mbarrier::complete_tx::bytes.v4.b32 [%0], {%1,%2,%3,%4}, [%5];" :: "r"(ps[i]), "r"(qf[0][0]), "r"(qf[0][1]), "r"(qf[0][2]), "r"(qf[0][3]), "r"(pb[i]) : "memory");
      }
      PRB(1)
      VERDICT(0);
      if (VR) { if (VPOS == 1 && j == 2) v_load(); mbar_wait(mbar + MB_QK, par); }
      LDW(su, l16 + SM_SC + (r & 1) * 1024); LDSM2T(su, l16 + SM_SC + 512 + (r & 1) * 1024);
      if (!VR) mbar_wait(mbar + MB_QK, par);
      PRB(2)
      LDW(sw, l16 + SM_SC + 1024 - (r & 1) * 1024); LDSM2T(sw, l16 + SM_SC + 1536 - (r & 1) * 1024);
      su[4] = hadd2(su[4], su[5]);
    }
    {
      HADD4(su, sw); su[4] = hadd2(su[4], hadd2(sw[4], sw[5]));
      uint32_t m = hmax2(hmax2(hmax2(su[0], su[1]), hmax2(su[2], su[3])), su[4]);
      const uint32_t m1 = __shfl_xor_sync(~0u, m, 1), m2 = __shfl_xor_sync(~0u, m, 2), m3 = __shfl_xor_sync(~0u, m, 3);
      float t[10];
#pragma unroll
      for (int i = 0; i < 5; i++) { t[2 * i] = bf_lo(su[i]) * sc2; t[2 * i + 1] = bf_hi(su[i]) * sc2; }
      {
        asm volatile("" : "+f"(t[0]), "+f"(t[1]), "+f"(t[2]), "+f"(t[3]), "+f"(t[4]), "+f"(t[5]), "+f"(t[6]), "+f"(t[7]), "+f"(t[8]), "+f"(t[9]));
        mbar_wait(mbar + MB_V, par | (r >> 1)); bar_arrive<2, 384>(); lds128(vm, wr16 + SM_VM);
      }
      t[PINT] = __uint_as_float(lop3<0xF8>(__float_as_uint(t[PINT]), vm[0], p.zero));
      m = hmax2(hmax2(m, m1), hmax2(m2, m3));
      const float mx = fmaxf(bf_lo(m), bf_hi(m));
#define EX(i) ex2(fmaf(mx, -sc2, t[i]))
      float o1[2][4], z[4];
      const uint32_t P0 = pack_bf16(EX(0), EX(1)), P1 = pack_bf16(EX(2), EX(3));
      mmaZ(o1[0], vf[0], P0, P1); mmaZ(o1[1], vf[1], P0, P1); mma16816z(z, ones, ones, ones, ones, P0, P1);
      const float e4 = EX(4), e5 = EX(5);
      const uint32_t P2 = pack_bf16(e4, e5), P3 = pack_bf16(EX(6), EX(7));
      mmaA(o1[0], vf[2], P2, P3); mmaA(o1[1], vf[3], P2, P3); mma16816(z, ones, ones, ones, ones, P2, P3);
      const uint32_t Pm = pack_bf16(EX(8), EX(9));
      mma1688(o1[0], vm[0], vm[1], Pm); mma1688(o1[1], vm[2], vm[3], Pm); mma1688(z, ones, ones, Pm);
      asm volatile("stmatrix.sync.aligned.m8n8.x4.shared.b16 [%0], {%1,%2,%3,%4};" :: "r"(wr16 + SM_OX),
        "r"(pack_bf16(o1[0][0], o1[0][1])), "r"(pack_bf16(o1[0][2], o1[0][3])), "r"(pack_bf16(o1[1][0], o1[1][1])), "r"(pack_bf16(o1[1][2], o1[1][3])) : "memory");
      if (j == 3) asm volatile("st.shared.v2.f32 [%0], {%1,%2};" :: "r"(l16 + SM_OX + 2048), "f"(z[0]), "f"(z[1]) : "memory");
    }
    bar_arrive<3, 384>();
    PRB(3)
    if (j == 3) asm volatile(ELECT "@p mbarrier.arrive.expect_tx.shared.b64 _, [%0+%4], %2;\n@p mbarrier.arrive.expect_tx.shared.b64 _, [%1], 8192;\n"
      "@p mbarrier.arrive.expect_tx.shared.b64 _, [%0+%5], 10368;\nsetp.ne.and.u32 p, %3, 2, p;\n@p mbarrier.arrive.expect_tx.shared.b64 _, [%0+%6], 2048;}"
        :: "r"(mbar), "r"(mbar + MB_KV + par * 8), "r"(VR ? 1536 : 768), "r"(r), "n"(MB_QK), "n"(MB_A), "n"(MB_V) : "memory");
    }
    uint32_t T3 = lds32(mbar + MB_TK) + p.period;
    {
      const uint32_t now = gt32(), lim = now + p.c3 + p.gap;
      if ((int)(T3 - now) > 20000) T3 = now;
      advance(T3, lim, p.slack);
    }
    if (s >= 0) m_store(s);
    if (j + (r & 2) < 2) {
#pragma unroll
      for (int i = 0; i < 4; i++) LDW(kf[i], ka + i * 256);
    } else {
#pragma unroll
      for (int i = 0; i < 16; i++) kf[i >> 2][i & 3] = 0;
    }
    int used = 0;
    if (j == 2 && s >= -1) { if (VPOS != 1 || !VR || s < 0) v_load(); used = ld_relaxed(fl + 24); }
    if (VPOS == 1) load_v();
    bar_arrive<11, 384>();
    if (is_red) {
      const uint32_t expect = ((s >> 1) & 1) ^ 1, rb = mbar + MB_R + j * 8, stg = SM_AT + 28672 + j * 4096, s1 = ka | (s & p.zero);
      char* w0 = (char*)comm + (x3_slot(s + 1) + bline + (l16 & 511) / 4);
      asm volatile("" : "+l"(w0));
      uint32_t T2 = T3 - p.c3;
      if (s < 0) asm volatile("bar.arrive 12, %0;" :: "r"((h & 1) ? 320 : 352) : "memory");
      else {
#pragma unroll 1
        for (int nth = 0;; nth++) {
          wait_gt(T2);
          if (DLY2) wait_gt(T2);
          PRB(4)
          asm volatile(ELECT "@p cp.async.bulk.shared::cluster.global.mbarrier::complete_tx::bytes [%0], [%1], 4096, [%2];\n@p mbarrier.arrive.expect_tx.shared.b64 _, [%2], 4096;}"
            :: "r"(sb + stg), "l"(comm + (inbox + par * (256 * 4096))), "r"(rb) : "memory");
          mbar_wait(rb, rph & 1); rph++;
          uint32_t x[8][4], f[4];
          float ra[4][4];
#pragma unroll
          for (int i = 0; i < 8; i++) ldsm4(x[i][0], x[i][1], x[i][2], x[i][3], l16 + stg + i * 512);
#pragma unroll
          for (int i = 0; i < 4; i++) f[i] = lds32(own + i * 1024);
#pragma unroll
          for (int i = 0; i < 8; i++) { if (i < 4) mmaZ(ra[i], x[i], ka, s1); else mmaA(ra[i & 3], x[i], ka, s1); }
          const uint32_t ok = __all_sync(~0u, lop3<0xA8>(lop3<0x7E>(f[0], f[1], expect), lop3<0x7E>(f[2], f[3], expect), 1) == 0) || nth == POLL_LIMIT;
          const uint32_t v = pack_bf16(((ra[0][0] + ra[0][2]) + (ra[1][0] + ra[1][2])) + ((ra[2][0] + ra[2][2]) + (ra[3][0] + ra[3][2])), ((ra[0][1] + ra[0][3]) + (ra[1][1] + ra[1][3])) + ((ra[2][1] + ra[2][3]) + (ra[3][1] + ra[3][3])));
          asm volatile("{.reg .pred p, q; setp.ne.u32 p, %2, 0; setp.eq.u32 q, %4, 0; @q bar.arrive 12, %3; @p st.relaxed.gpu.global.u32 [%0], %1; @p st.relaxed.gpu.global.u32 [%0+4096], %1; @p bar.arrive 15, %5;}"
            :: "l"(w0), "r"(v), "r"(ok), "r"(lop3<0xF8>((h & 1) ? 320 : 352, __float_as_uint(ra[3][0]), p.zero)), "r"(nth), "r"((h & 1) ? 96 : 128) : "memory");
          if (ok) break;
          if (nth == 0) {
            char* c = (char*)comm + (x3_slot(s + 1) + 1920);
            asm volatile(ELECT "@p red.relaxed.gpu.global.max.s32 [%0], %1;\n@p red.relaxed.gpu.global.max.s32 [%0+4096], %1;}" :: "l"(c), "r"(lds32(mbar + MB_TAB + 8) + 1) : "memory");
          }
          if (!IMM || nth) { T2 += p.slack; advance(T2, gt32() - TOLQ, p.slack); }
        }
        PRB(5)
        w0 = (char*)((uint64_t)w0 ^ (1 << 20));
        st_relaxed(w0, 0xFFFFFFFFu); st_relaxed(w0 + 4096, 0xFFFFFFFFu);
      }
#pragma unroll
      for (int i = 0; i < 16; i++) kf[i >> 2][i & 3] = 0;
    }
#pragma unroll 1
    for (int guard = 0;; guard++) {
      if (j == 3 && s >= 0) {
        if (VR && guard == 0) { asm volatile("bar.sync 15, %0;" :: "r"((h & 1) ? 96 : 128) : "memory"); sts32(mbar + MB_TAB, 0); }
        advance(T3, gt32() - (VR ? TOLV : TOLQ), p.slack);
        wait_gt(T3);
        if (DLY3) wait_gt(T3);
        asm volatile(ELECT
          "@p cp.async.bulk.shared::cluster.global.mbarrier::complete_tx::bytes [%0+-128], [%2+1920], 2176, [%1];\n"
          "@p cp.async.bulk.shared::cluster.global.mbarrier::complete_tx::bytes [%0+2048], [%2+16384], 4096, [%1];\n"
          "@p cp.async.bulk.shared::cluster.global.mbarrier::complete_tx::bytes [%0+6144], [%2+32768], 4096, [%1];}"
          :: "r"(sb + SM_MEMT), "r"(mbar + MB_A), "l"(comm + (x3_slot(s + 1) + side * 4096)) : "memory");
      }
      PRB(6)
      if (VPOS == 0) load_v();
      uint32_t m = 0, ok;
      if (j < 2) {
        if (s + 3 < NSEG) mbar_wait(mbar + MB_X + (par ^ 1) * 8, ((s + 3) >> 1) & 1);
        if (s >= 0) {
          mbar_wait(mbar + MB_A, att & 1);
#pragma unroll
          for (int i = 0; i < 5; i++) m = max(m, lds32(l16 + (l16 & 511) + (l16 & 448) / 16 + (j * 1024 + SM_MEMT + i * 2048)));
        }
      } else if (guard == 0) {
        bar_sync<14, 320>();
        if (j == 2) {
#pragma unroll 1
          for (int g2 = 0; __any_sync(~0u, used + QRING < s + 3) && g2 < POLL_LIMIT && !DBGF(16); g2++) used = ld_relaxed(fl + 24);
          asm volatile("fence.proxy.async.shared::cta;" ::: "memory");
          if (s + 2 < NSEG && !DBGF(64)) asm volatile(ELECT "@p cp.async.bulk.global.shared::cta.bulk_group [%0], [%1], 10240;\ncp.async.bulk.commit_group;}" :: "l"(REC(s + 2)), "r"(sb + SM_ST) : "memory");
        } else if (XPOS == 0 && s + 4 < NSEG) { if (s >= 0) wait_gt(T3 + 192); x_load(p, sb, s + 4); }
      }
      if (VPOS == 2) load_v();
      att++;
      asm volatile("{.reg .pred p; setp.ne.u32 p, %1, 0xffffffff; bar.red.and.pred p, 13, 128, p; selp.u32 %0, 1, 0, p;}" : "=r"(ok) : "r"(m) : "memory");
      if (__all_sync(~0u, ok) || guard == POLL_LIMIT) break;
      bar_arrive<9, 384>();
      VERDICT(1);
      if (j == 3) asm volatile(ELECT "@p mbarrier.arrive.expect_tx.shared.b64 _, [%0], 10368;}" :: "r"(mbar + MB_A) : "memory");
      T3 += p.slack;
    }
    PRB(7)
    if (j == 3) {
      if (XPOS == 1 && s + 4 < NSEG) x_load(p, sb, s + 4);
      if (s >= 0) {
        const int seen = lds32(sb + SM_MEMT - 128), had = lds32(mbar + MB_TAB + 8), cnt = max(seen, had);
        sts32(mbar + MB_TAB + 8, cnt); sts32(mbar + MB_TK, T3 + (cnt - had) * p.xlate);
      }
      st_relaxed(fl + r * 8, ((T3 >> 5) << 7) | (s + 2));
      if (s == -2) asm volatile(ELECT "@p mbarrier.arrive.shared.b64 _, [%0];}" :: "r"(mbar + MB_A) : "memory");
      if (s < 0) TL(18);
    }
  }
  bar_sync<9, 384>();
  m_store(NSEG - 1);
  VERDICT(0);
  TL(19);
  if (__all_sync(~0u, lds32(mbar + MB_TAB + 4) == 0)) bar_arrive<1, 384>();
  if (is_red) {
    uint32_t* wpoi = (uint32_t*)(comm + (x3_slot(2) + bline + (l16 & 511) / 4));
    st_relaxed(wpoi, 0xFFFFFFFFu); st_relaxed(wpoi + 1024, 0xFFFFFFFFu);
#pragma unroll 1
    for (int i = 0; i < 8; i++) stg128((char*)comm + (inbox + 256 * 4096 + i * 512 + (l16 & 511)), 0, 0, 0, 0);
    __threadfence();
  }
#undef VR
}

__global__ void __launch_bounds__(384, 1) rec_kernel(const __grid_constant__ RecParams p) {
  extern __shared__ __align__(1024) char smem_raw[];
  const uint32_t sb = (smem_u32(smem_raw) + 1023) & ~1023u;
  char* smem = smem_raw + (sb - smem_u32(smem_raw));
  const int tid = threadIdx.x;
  const uint32_t mbar = sb + SM_BAR;
  pdl_launch();
  if (!p.helper) {
    if (tid == 32 || tid == 96) l2_prefetch((tid == 32 ? p.wi : p.wr) + blockIdx.x * 6848, 13696);
    if (tid == 64 && blockIdx.x < 12) l2_prefetch(g_tab + TB_F32 * 4 + blockIdx.x * 256, 1024);
  }
#pragma unroll 1
  for (int L = p.layer; L < 2; L++) {
    {
    const int w = __shfl_sync(~0u, tid >> 5, 0), bid = blockIdx.x + (L & p.zero), h = bid / 3, r = bid % 3;
    TL(0);
    if (tid == 0) {
#pragma unroll 1
      for (int i = 0; i < 14; i++) {
        if (L > p.layer) asm volatile("mbarrier.inval.shared.b64 [%0];" :: "r"(mbar + i * 8) : "memory");
        mbar_init(mbar + i * 8, 1);
      }
      asm volatile("fence.mbarrier_init.release.cluster;" ::: "memory");
      asm volatile("fence.proxy.async.shared::cta;" ::: "memory");
      mbar_expect(mbar + MB_QK, r == 2 ? 1536 : 768); mbar_expect(mbar + MB_V, 2048);
      mbar_expect(mbar + MB_KV, 8192); mbar_expect(mbar + MB_KV + 8, 8192);
      sts32(mbar + MB_TAB + 4, L); sts32(mbar + MB_TAB + 8, L * 1000);
      mbar_expect(mbar + MB_IA, L ? 0 : 163840); mbar_expect(mbar + MB_IC, r == 2 ? 32768 : 65536);
    }
    const int v = bid + p.helper * 96;
    const bool prep = L == 0 && v >= 86;
    if (prep && v < 118 && tid == 0) {
      mbar_expect(mbar + 8, 2 * 41088);
      bulk_g2s(sb + SM_WS, p.wr + (v - 86) * 64 * 321, 41088, mbar + 8); bulk_g2s(sb + SM_WS + 41088, p.wi + (v - 86) * 64 * 321, 41088, mbar + 8);
    }
    __syncwarp();
    auto wo_load = [&](int i0) {
#pragma unroll 1
      for (int i = i0; i < i0 + 4; i++)
        asm volatile(ELECT "@p cp.async.bulk.tensor.2d.shared::cluster.global.mbarrier::complete_tx::bytes [%0], [%1, {%3, %4}], [%2];}"
          :: "r"(sb + SM_WST + i * 8192), "l"(&p.tmWo), "r"(mbar + MB_IC), "r"(r * 256 + (i >> 1) * 64), "r"(h * 128 + (i & 1) * 64) : "memory");
    };
    a_layer(p.a[L], smem + SM_WST, v, w, [&](int u) {
        if (u == -1 && prep) {
          const int o = (v - 86) * 384 + tid, pg = 160 + ((o >> 8) & 15) + ((o >> 12) & 1) * 64 + (o >> 13) * 256;
          const uint32_t c = (pg & 2) ? 0u : ~0u;
          if (o < 64 * 256) stg128((uint4*)p.comm + pg * 256 + (o & 255), c, c, c, c);
          if (v < 118) { mbar_wait(mbar + 8, 0); filter_prep((uint32_t*)p.a[0].WT, sb + SM_WS, v - 86); }
          asm volatile("fence.proxy.async.shared::cta;" ::: "memory");
          TL(20);
          __syncthreads();
        }
        if (u == 0 && prep && tid == 256) { red_release(p.a[0].sync + SY_W); TL(21); }
        auto w_load = [&](int i) {
          asm volatile(ELECT "@p cp.async.bulk.tensor.2d.shared::cluster.global.mbarrier::complete_tx::bytes [%0], [%1, {%3, %4}], [%2];}"
            :: "r"(sb + SM_WS + ((0x3102 >> (4 * (i & 3))) & 3) * 40960 + (i >> 2) * 8192), "l"(&p.tmW[r == 2 ? 2 : i & 1]), "r"(mbar + MB_IA), "r"(h * 128 + (r == 2 ? i & 1 : r) * 64), "r"((i & 2) * 160 + (i >> 2) * 64) : "memory");
        };
        const int b0 = (WPLAN >> (4 * u + 4)) & 15, n = ((WPLAN >> (4 * u + 8)) & 15) - b0;
        if (n > 0 && w + L * 12 + p.helper * 12 < 4 * n) w_load(4 * b0 + w);
        if (u == OPF && w < 4 && r + p.helper * 2 < 2)
          asm volatile(ELECT "@p cp.async.bulk.prefetch.tensor.2d.L2.global [%0, {%1, %2}];}" :: "l"(&p.tmWo), "r"(r * 256 + 128 + (w >> 1) * 64), "r"(h * 128 + (w & 1) * 64) : "memory");
        if (u == 4 && w == 4 && !p.helper) wo_load(0);
      });
    if (p.helper) {
      return;
    }
    __syncwarp();
    if (w == 2 && r < 2) { asm volatile("fence.proxy.async.shared::cta;" ::: "memory"); wo_load(4); }
    }
    L = __shfl_sync(~0u, lds32(mbar + MB_TAB + 4), 0);
    const int w = __shfl_sync(~0u, tid >> 5, 0), bid = blockIdx.x + (L & p.zero), h = bid / 3, r = bid % 3;
    if (w < 8) {
      asm volatile("setmaxnreg.inc.sync.aligned.u32 216;");
      if (r < 2) rec_gemm_warps<false>(p, sb, h, r, L, w); else rec_gemm_warps<true>(p, sb, h, r, L, w);
      asm volatile("setmaxnreg.dec.sync.aligned.u32 168;");
    } else {
      asm volatile("setmaxnreg.dec.sync.aligned.u32 72;");
      const int side = rec_attn_setup(p, sb, h, r, L, w - 8);
      rec_attn_warps(p, sb, smem, h, r, side, L, w - 8);
      asm volatile("setmaxnreg.inc.sync.aligned.u32 168;");
    }
    asm volatile("barrier.cluster.arrive.relaxed.aligned; barrier.cluster.wait.aligned;" ::: "memory");
    L = __shfl_sync(~0u, lds32(mbar + MB_TAB + 4), 0);
    if (tid < 32) TL_DUMP(L * 166 + blockIdx.x, tid);
    __syncthreads();
  }
}

constexpr int PERIOD = 1984, C3 = 480, SLACK = 704, XLATE = 128, GAP = 128;
static int PH[6] = {256, 704, 3, 1280, 8, 63};
__device__ __align__(128) uint32_t g_Z1[86 * 7680], g_ZT[640 * 1024];
__device__ __align__(128) uint32_t g_WT[321 * 2048];
__device__ bf16 g_x1[S_ * D_], g_x2[S_ * D_], g_hN[S_ * D_];
__device__ __align__(128) uint4 g_QKV[QRING * 32 * 30720 / 16], g_O[ORING * 32 * 8192 / 16];
__device__ __align__(128) uint4 g_part[PRING * 32 * 8960 / 16];
__device__ __align__(128) uint32_t g_sync[256];
__device__ uint32_t g_comm[(4 << 20) / 4];

typedef CUresult (*EncodeFn)(CUtensorMap*, CUtensorMapDataType, cuuint32_t, void*, const cuuint64_t*, const cuuint64_t*, const cuuint32_t*, const cuuint32_t*,
                             CUtensorMapInterleave, CUtensorMapSwizzle, CUtensorMapL2promotion, CUtensorMapFloatOOBfill);
static void make_map(EncodeFn fn, CUtensorMap* m, const void* base, uint64_t cols, uint64_t rows, uint32_t bc, uint32_t br) {
  cuuint64_t dims[2] = {cols, rows}, strides[1] = {cols * 2}; cuuint32_t box[2] = {bc, br}, es[2] = {1, 1};
  fn(m, CU_TENSOR_MAP_DATA_TYPE_BFLOAT16, 2, (void*)base, dims, strides, box, es, CU_TENSOR_MAP_INTERLEAVE_NONE, CU_TENSOR_MAP_SWIZZLE_128B, CU_TENSOR_MAP_L2_PROMOTION_L2_256B, CU_TENSOR_MAP_FLOAT_OOB_FILL_NONE);
}
template <typename T> static T* sym(T& s) { void* p; cudaGetSymbolAddress(&p, s); return (T*)p; }

template <typename... KA, typename... A> static void launch(void (*k)(KA...), int grid, int block, int smem, bool pdl, int cluster, A... a) {
  cudaLaunchConfig_t cfg = {};
  cfg.gridDim = dim3(grid); cfg.blockDim = dim3(block); cfg.dynamicSmemBytes = smem; cfg.stream = cudaStreamPerThread;
  cudaLaunchAttribute at[2]; int n = 0;
  if (pdl) { at[n].id = cudaLaunchAttributeProgrammaticStreamSerialization; at[n].val.programmaticStreamSerializationAllowed = 1; n++; }
  if (cluster > 1) { at[n].id = cudaLaunchAttributeClusterDimension; at[n].val.clusterDim.x = cluster; at[n].val.clusterDim.y = 1; at[n].val.clusterDim.z = 1; n++; }
  cfg.attrs = at; cfg.numAttrs = n;
  cudaLaunchKernelEx(&cfg, k, KA(a)...);
}

extern "C" void kernel_launch(void* const* d_in, const int* in_sizes, int n_in, void* d_out, int out_size) {
  const bf16 *x = (const bf16*)d_in[0], *wr = (const bf16*)d_in[1], *wi = (const bf16*)d_in[2], *mem0 = (const bf16*)d_in[4];
  const bf16 *Wq = (const bf16*)d_in[5], *Wk = (const bf16*)d_in[6], *Wv = (const bf16*)d_in[7], *Wo = (const bf16*)d_in[8];
  bf16* out = (bf16*)d_out;
  uint32_t *Z1 = (uint32_t*)sym(g_Z1), *ZT = (uint32_t*)sym(g_ZT), *WT = (uint32_t*)sym(g_WT);
  bf16 *x1 = (bf16*)sym(g_x1), *x2 = (bf16*)sym(g_x2), *hN = (bf16*)sym(g_hN);
  char *QKV = (char*)sym(g_QKV), *part = (char*)sym(g_part);
  uint32_t* comm = (uint32_t*)(((uint64_t)sym(g_comm) + (2 << 20) - 1) & ~(uint64_t)((2 << 20) - 1));
  EncodeFn enc = nullptr; cudaDriverEntryPointQueryResult qr;
  cudaGetDriverEntryPoint("cuTensorMapEncodeTiled", (void**)&enc, cudaEnableDefault, &qr);
  CUtensorMap tmW[3], tmWo, tmX, tmP;
  { cuuint64_t dims[3] = {64, PRING * 32, 70}, strides[2] = {8960, 128}; cuuint32_t box[3] = {64, 32, 2}, es[3] = {1, 1, 1};
    enc(&tmP, CU_TENSOR_MAP_DATA_TYPE_BFLOAT16, 3, part, dims, strides, box, es, CU_TENSOR_MAP_INTERLEAVE_NONE, CU_TENSOR_MAP_SWIZZLE_128B, CU_TENSOR_MAP_L2_PROMOTION_NONE, CU_TENSOR_MAP_FLOAT_OOB_FILL_NONE); }
  { cuuint64_t dims[3] = {64, 2048, 10}, strides[2] = {1280, 128}; cuuint32_t box[3] = {64, 32, 10}, es[3] = {1, 1, 1};
    enc(&tmX, CU_TENSOR_MAP_DATA_TYPE_BFLOAT16, 3, hN, dims, strides, box, es, CU_TENSOR_MAP_INTERLEAVE_NONE, CU_TENSOR_MAP_SWIZZLE_128B, CU_TENSOR_MAP_L2_PROMOTION_L2_256B, CU_TENSOR_MAP_FLOAT_OOB_FILL_NONE); }
  make_map(enc, &tmW[0], Wq, 4096, 640, 64, 64); make_map(enc, &tmW[1], Wk, 4096, 640, 64, 64); make_map(enc, &tmW[2], Wv, 4096, 640, 64, 64);
  make_map(enc, &tmWo, Wo, 640, 4096, 64, 64);
  int dbgf = 0;
  cudaFuncSetAttribute(side_kernel, cudaFuncAttributeMaxDynamicSharedMemorySize, SD_SMEM);
  cudaFuncSetAttribute(rec_kernel, cudaFuncAttributeMaxDynamicSharedMemorySize, REC_SMEM);
  uint32_t* sy = (uint32_t*)sym(g_sync);
  RecParams rp = {{tmW[0], tmW[1], tmW[2]}, tmWo, tmX, {{x, Z1, ZT, WT, x1, hN, sy, nullptr, 45, 1}, {x2, Z1, ZT, WT, x1, hN, sy + 128, (dbgf & 16) ? nullptr : comm + FL_RDY + 12, 0, 0}},
                  mem0, wr, wi, QKV, comm, 0x4000004000010000ull, PERIOD, C3, SLACK, XLATE, GAP, 0, 0, 0, dbgf, nullptr, nullptr};
  launch(rec_kernel, 96, 384, REC_SMEM, false, 3, rp);
  for (int L = 0; L < 2; L++) {
    rp.helper = 1; rp.layer = L;
    launch(rec_kernel, 35, 384, REC_SMEM, true, 1, rp);
    SideParams sp = {tmWo, tmP, QKV, (char*)sym(g_O), part, x1, L == 0 ? x2 : out, comm + L * 1024, sy + L * 128, rp.dhi, L == 0, rp.period, PH[0], PH[1], PH[2], PH[3], PH[4], PH[5], dbgf};
    launch(side_kernel, 36, 512, SD_SMEM, true, 1, sp);
  }
}
```

```cpp
#include <cuda_runtime.h>
#include <cuda_bf16.h>
#include <cuda.h>
#include <stdint.h>
typedef __nv_bfloat16 bf16;
constexpr int S_ = 2048, D_ = 640, H_ = 32, DH = 128, NSEG = 64;

__device__ __forceinline__ uint32_t smem_u32(const void* p) { return (uint32_t)__cvta_generic_to_shared(p); }
__device__ __forceinline__ uint32_t pack_bf16(float lo, float hi) { uint32_t r; asm("cvt.rn.bf16x2.f32 %0, %1, %2;" : "=r"(r) : "f"(hi), "f"(lo)); return r; }
__device__ __forceinline__ float bf_lo(uint32_t v) { return __uint_as_float(v << 16); }
__device__ __forceinline__ float bf_hi(uint32_t v) { return __uint_as_float(v & 0xFFFF0000u); }
__device__ __forceinline__ void ldsm4t(uint32_t& r0, uint32_t& r1, uint32_t& r2, uint32_t& r3, uint32_t a) {
  asm volatile("ldmatrix.sync.aligned.m8n8.x4.trans.shared.b16 {%0,%1,%2,%3}, [%4];" : "=r"(r0), "=r"(r1), "=r"(r2), "=r"(r3) : "r"(a) : "memory");
}
__device__ __forceinline__ void ldsm4(uint32_t& r0, uint32_t& r1, uint32_t& r2, uint32_t& r3, uint32_t a) {
  asm volatile("ldmatrix.sync.aligned.m8n8.x4.shared.b16 {%0,%1,%2,%3}, [%4];" : "=r"(r0), "=r"(r1), "=r"(r2), "=r"(r3) : "r"(a) : "memory");
}
__device__ __forceinline__ void mma16816(float* d, uint32_t a0, uint32_t a1, uint32_t a2, uint32_t a3, uint32_t b0, uint32_t b1) {
  asm volatile("mma.sync.aligned.m16n8k16.row.col.f32.bf16.bf16.f32 {%0,%1,%2,%3}, {%4,%5,%6,%7}, {%8,%9}, {%0,%1,%2,%3};"
    : "+f"(d[0]), "+f"(d[1]), "+f"(d[2]), "+f"(d[3]) : "r"(a0), "r"(a1), "r"(a2), "r"(a3), "r"(b0), "r"(b1));
}
__device__ __forceinline__ void mma16816z(float* d, uint32_t a0, uint32_t a1, uint32_t a2, uint32_t a3, uint32_t b0, uint32_t b1) {
  asm volatile("mma.sync.aligned.m16n8k16.row.col.f32.bf16.bf16.f32 {%0,%1,%2,%3}, {%4,%5,%6,%7}, {%8,%9}, {%10,%10,%10,%10};"
    : "=f"(d[0]), "=f"(d[1]), "=f"(d[2]), "=f"(d[3]) : "r"(a0), "r"(a1), "r"(a2), "r"(a3), "r"(b0), "r"(b1), "f"(0.f));
}
__device__ __forceinline__ void mma1688z(float* d, uint32_t a0, uint32_t a1, uint32_t b0) {
  asm volatile("mma.sync.aligned.m16n8k8.row.col.f32.bf16.bf16.f32 {%0,%1,%2,%3}, {%4,%5}, {%6}, {%7,%7,%7,%7};"
    : "=f"(d[0]), "=f"(d[1]), "=f"(d[2]), "=f"(d[3]) : "r"(a0), "r"(a1), "r"(b0), "f"(0.f));
}
__device__ __forceinline__ void mma1688(float* d, uint32_t a0, uint32_t a1, uint32_t b0) {
  asm volatile("mma.sync.aligned.m16n8k8.row.col.f32.bf16.bf16.f32 {%0,%1,%2,%3}, {%4,%5}, {%6}, {%0,%1,%2,%3};"
    : "+f"(d[0]), "+f"(d[1]), "+f"(d[2]), "+f"(d[3]) : "r"(a0), "r"(a1), "r"(b0));
}
__device__ __forceinline__ void mmaA(float* d, const uint32_t* a, uint32_t b0, uint32_t b1) { mma16816(d, a[0], a[1], a[2], a[3], b0, b1); }
__device__ __forceinline__ void mmaZ(float* d, const uint32_t* a, uint32_t b0, uint32_t b1) { mma16816z(d, a[0], a[1], a[2], a[3], b0, b1); }
__device__ __forceinline__ uint32_t movm(uint32_t a) { uint32_t d; asm volatile("movmatrix.sync.aligned.m8n8.trans.b16 %0, %1;" : "=r"(d) : "r"(a)); return d; }
__device__ __forceinline__ void cp_async16(uint32_t dst, const void* src) { asm volatile("cp.async.cg.shared.global [%0], [%1], 16;" :: "r"(dst), "l"(src) : "memory"); }
__device__ __forceinline__ void cp_commit() { asm volatile("cp.async.commit_group;" ::: "memory"); }
template <int N> __device__ __forceinline__ void cp_wait() { asm volatile("cp.async.wait_group %0;" :: "n"(N) : "memory"); }
__device__ __forceinline__ void lds128(uint32_t* r, uint32_t a) { asm volatile("ld.shared.v4.b32 {%0,%1,%2,%3}, [%4];" : "=r"(r[0]), "=r"(r[1]), "=r"(r[2]), "=r"(r[3]) : "r"(a) : "memory"); }
__device__ __forceinline__ void sts128(uint32_t a, uint32_t r0, uint32_t r1, uint32_t r2, uint32_t r3) { asm volatile("st.shared.v4.b32 [%0], {%1,%2,%3,%4};" :: "r"(a), "r"(r0), "r"(r1), "r"(r2), "r"(r3) : "memory"); }
__device__ __forceinline__ void stg128(void* p, uint32_t r0, uint32_t r1, uint32_t r2, uint32_t r3) { asm volatile("st.global.v4.b32 [%0], {%1,%2,%3,%4};" :: "l"(p), "r"(r0), "r"(r1), "r"(r2), "r"(r3) : "memory"); }
template <int ID, int N> __device__ __forceinline__ void bar_sync() { asm volatile("bar.sync %0, %1;" :: "n"(ID), "n"(N) : "memory"); }
template <int ID, int N> __device__ __forceinline__ void bar_arrive() { asm volatile("bar.arrive %0, %1;" :: "n"(ID), "n"(N) : "memory"); }
__device__ __forceinline__ void mbar_wait(uint32_t bar, uint32_t parity) {
  asm volatile("{\n.reg .pred p, pq;\n.reg .u32 n;\nmov.u32 n, 0;\nLW%=:\nmbarrier.try_wait.parity.shared::cta.b64 p, [%0], %1;\n@p bra.uni LD%=;\nadd.u32 n, n, 1;\nsetp.lt.u32 pq, n, 1000000;\n@pq bra.uni LW%=;\nLD%=:\n}" :: "r"(bar), "r"(parity) : "memory");
}
#define mbar_wait_long mbar_wait
__device__ __forceinline__ void mbar_init(uint32_t bar, int n) { asm volatile("mbarrier.init.shared.b64 [%0], %1;" :: "r"(bar), "r"(n) : "memory"); }
__device__ __forceinline__ void mbar_expect(uint32_t bar, int bytes) { asm volatile("mbarrier.arrive.expect_tx.shared.b64 _, [%0], %1;" :: "r"(bar), "r"(bytes) : "memory"); }
__device__ __forceinline__ void mbar_arrive(uint32_t bar) { asm volatile("mbarrier.arrive.shared.b64 _, [%0];" :: "r"(bar) : "memory"); }
__device__ __forceinline__ void l2_prefetch(const void* p, int bytes) { asm volatile("cp.async.bulk.prefetch.L2.global [%0], %1;" :: "l"(p), "r"(bytes) : "memory"); }
__device__ __forceinline__ float ex2(float x) { float y; asm("ex2.approx.ftz.f32 %0, %1;" : "=f"(y) : "f"(x)); return y; }
__device__ __forceinline__ void pdl_wait() { asm volatile("griddepcontrol.wait;" ::: "memory"); }
__device__ __forceinline__ void pdl_launch() { asm volatile("griddepcontrol.launch_dependents;" ::: "memory"); }
__device__ __forceinline__ uint32_t hadd2(uint32_t a, uint32_t b) { uint32_t r; asm("add.rn.bf16x2 %0, %1, %2;" : "=r"(r) : "r"(a), "r"(b)); return r; }
__device__ __forceinline__ void sched_fence() { asm volatile("{\n.reg .pred p;\n.reg .u32 t;\nLF%=:\nmov.u32 t, %%clock;\nsetp.eq.u32 p, t, %0;\n@p bra.uni LF%=;\n}" :: "n"(12345) : "memory"); }
#define TL(k)
#define TL_DUMP(slot, t)

constexpr int TB_F16 = 0, TB_640 = 64, TB_F40 = 384, TB_F32 = 784, TB_512 = 1040, TB_2048 = 1296;
__device__ __align__(128) const uint32_t g_tab[6208] = {
0x3f803f80,0xbf803f80,0x3f803f80,0xbf803f80,0x3f803f80,0xbf803f80,0x3f803f80,0xbf803f80,0x3f803f80,0xbf803f80,0x3f803f80,0xbf803f80,0x3f803f80,0xbf803f80,0x3f803f80,0xbf803f80,
0x3f6d3f80,0xbf6d3f80,0xbf6dbf80,0x3f6dbf80,0x3ec43f35,0xbec43f35,0xbec4bf35,0x3ec4bf35,0xbec40000,0x3ec40000,0x3ec40000,0xbec40000,0xbf6dbf35,0x3f6dbf35,0x3f6d3f35,0xbf6d3f35,
0x3f353f80,0xbf353f80,0x3f353f80,0xbf353f80,0xbf350000,0x3f350000,0xbf350000,0x3f350000,0xbf35bf80,0x3f35bf80,0xbf35bf80,0x3f35bf80,0x3f350000,0xbf350000,0x3f350000,0xbf350000,
0x3ec43f80,0xbec43f80,0xbec4bf80,0x3ec4bf80,0xbf6dbf35,0x3f6dbf35,0x3f6d3f35,0xbf6d3f35,0x3f6d0000,0xbf6d0000,0xbf6d0000,0x3f6d0000,0xbec43f35,0x3ec43f35,0x3ec4bf35,0xbec4bf35,
0x3f80,0x3f80,0x3f80,0x3f80,0xbf80,0xbf80,0xbf80,0xbf80,0x3f80,0x3f80,0x3f80,0x3f80,0xbf80,0xbf80,0xbf80,0xbf80,
0xbec43f80,0x3ec43f80,0x3ec4bf80,0xbec4bf80,0x3f6dbf35,0xbf6dbf35,0xbf6d3f35,0x3f6d3f35,0xbf6d0000,0x3f6d0000,0x3f6d0000,0xbf6d0000,0x3ec43f35,0xbec43f35,0xbec4bf35,0x3ec4bf35,
0xbf353f80,0x3f353f80,0xbf353f80,0x3f353f80,0x3f350000,0xbf350000,0x3f350000,0xbf350000,0x3f35bf80,0xbf35bf80,0x3f35bf80,0xbf35bf80,0xbf350000,0x3f350000,0xbf350000,0x3f350000,
0xbf6d3f80,0x3f6d3f80,0x3f6dbf80,0xbf6dbf80,0xbec43f35,0x3ec43f35,0x3ec4bf35,0xbec4bf35,0x3ec40000,0xbec40000,0xbec40000,0x3ec40000,0x3f6dbf35,0xbf6dbf35,0xbf6d3f35,0x3f6d3f35,
0x80008000,0x80008000,0x80008000,0x80008000,0x80008000,0x80008000,0x80008000,0x80008000,0x80008000,0x80008000,0x80008000,0x80008000,0x80008000,0x80008000,0x80008000,0x80008000,
0xbec48000,0x3ec48000,0x3ec48000,0xbec48000,0xbf6dbf35,0x3f6dbf35,0x3f6d3f35,0xbf6d3f35,0xbf6dbf80,0x3f6dbf80,0x3f6d3f80,0xbf6d3f80,0xbec4bf35,0x3ec4bf35,0x3ec43f35,0xbec43f35,
0xbf358000,0x3f358000,0xbf358000,0x3f358000,0xbf35bf80,0x3f35bf80,0xbf35bf80,0x3f35bf80,0x3f358000,0xbf358000,0x3f358000,0xbf358000,0x3f353f80,0xbf353f80,0x3f353f80,0xbf353f80,
0xbf6d8000,0x3f6d8000,0x3f6d8000,0xbf6d8000,0x3ec4bf35,0xbec4bf35,0xbec43f35,0x3ec43f35,0x3ec43f80,0xbec43f80,0xbec4bf80,0x3ec4bf80,0xbf6dbf35,0x3f6dbf35,0x3f6d3f35,0xbf6d3f35,
0xbf808000,0x3f808000,0xbf808000,0x3f808000,0x3f808000,0xbf808000,0x3f808000,0xbf808000,0xbf808000,0x3f808000,0xbf808000,0x3f808000,0x3f808000,0xbf808000,0x3f808000,0xbf808000,
0xbf6d8000,0x3f6d8000,0x3f6d8000,0xbf6d8000,0x3ec43f35,0xbec43f35,0xbec4bf35,0x3ec4bf35,0x3ec4bf80,0xbec4bf80,0xbec43f80,0x3ec43f80,0xbf6d3f35,0x3f6d3f35,0x3f6dbf35,0xbf6dbf35,
0xbf358000,0x3f358000,0xbf358000,0x3f358000,0xbf353f80,0x3f353f80,0xbf353f80,0x3f353f80,0x3f358000,0xbf358000,0x3f358000,0xbf358000,0x3f35bf80,0xbf35bf80,0x3f35bf80,0xbf35bf80,
0xbec48000,0x3ec48000,0x3ec48000,0xbec48000,0xbf6d3f35,0x3f6d3f35,0x3f6dbf35,0xbf6dbf35,0xbf6d3f80,0x3f6d3f80,0x3f6dbf80,0xbf6dbf80,0xbec43f35,0x3ec43f35,0x3ec4bf35,0xbec4bf35,
0x3f800000,0x3f800000,0x3f800000,0x3f7f35f9,0x3f800000,0x3f800000,0x3f7cd925,0x3f78ed3c,0x3f800000,0x3f800000,0x3f737871,0x3f6c835e,0x3f800000,0x3f800000,0x3f641901,0x3f5a46a0,
0x3f800000,0x3f7ffcd7,0x3f800000,0x3f7f0059,0x3f7ff35e,0x3f7fe394,0x3f7c0361,0x3f770f11,0x3f7fcd79,0x3f7fb10f,0x3f702d4f,0x3f676bd8,0x3f7f8e56,0x3f7f654e,0x3f5cdc29,0x3f50935b,
0x3f800000,0x3f7ff35e,0x3f800000,0x3f7ec46d,0x3f7fcd79,0x3f7f8e56,0x3f7b14be,0x3f74fa0b,0x3f7f35f9,0x3f7ec46d,0x3f6c835e,0x3f61c598,0x3f7e39bc,0x3f7d95f4,0x3f54db31,0x3f45e403,
0x3f800000,0x3f7fe394,0x3f800000,0x3f7e8238,0x3f7f8e56,0x3f7f0059,0x3f7a0d54,0x3f72ae9e,0x3f7e39bc,0x3f7d3aac,0x3f687c12,0x3f5b941a,0x3f7c0361,0x3f7a9421,0x3f4c1d35,0x3f3a4582,
0x3f800000,0x3f7fcd79,0x3f800000,0x3f7e39bc,0x3f7f35f9,0x3f7e39bc,0x3f78ed3c,0x3f702d4f,0x3f7cd925,0x3f7b14be,0x3f641901,0x3f54db31,0x3f78ed3c,0x3f766377,0x3f42a9f7,0x3f2dc5e3,
0x3f800000,0x3f7fb10f,0x3f800000,0x3f7deafa,0x3f7ec46d,0x3f7d3aac,0x3f77b493,0x3f6d76aa,0x3f7b14be,0x3f7853f8,0x3f5f5be6,0x3f4d9f02,0x3f74fa0b,0x3f710908,0x3f3889dc,0x3f207440,
0x3f800000,0x3f7f8e56,0x3f800000,0x3f7d95f4,0x3f7e39bc,0x3f7c0361,0x3f766377,0x3f6a8b4b,0x3f78ed3c,0x3f74fa0b,0x3f5a46a0,0x3f45e403,0x3f702d4f,0x3f6a8b4b,0x3f2dc5e3,0x3f1260b2,
0x3f800000,0x3f7f654e,0x3f800000,0x3f7d3aac,0x3f7d95f4,0x3f7a9421,0x3f74fa0b,0x3f676bd8,0x3f766377,0x3f710908,0x3f54db31,0x3f3daef9,0x3f6a8b4b,0x3f62f219,0x3f226799,0x3f039c3d,
0x3f800000,0x3f800000,0x3f4f1bbd,0x3f42a9f7,0x3f800000,0x3f800000,0x3f3504f3,0x3f26423a,0x3f800000,0x3f800000,0x3f167918,0x3f05c277,0x3f800000,0x3f800000,0x3ee87171,0x3ec3ef15,
0x3f7f35f9,0x3f7f0059,0x3f42a9f7,0x3f333bc6,0x3f7ec46d,0x3f7e8238,0x3f226799,0x3f104f0e,0x3f7e39bc,0x3f7deafa,0x3efa2c90,0x3ed1c759,0x3f7d95f4,0x3f7d3aac,0x3ea7bf25,0x3e78cfcc,
0x3f7cd925,0x3f7c0361,0x3f3504f3,0x3f226799,0x3f7b14be,0x3f7a0d54,0x3f0e39da,0x3ef15aea,0x3f78ed3c,0x3f77b493,0x3ec3ef15,0x3e94a031,0x3f766377,0x3f74fa0b,0x3e47c5c2,0x3dc8bd36,
0x3f78ed3c,0x3f770f11,0x3f26423a,0x3f104f0e,0x3f74fa0b,0x3f72ae9e,0x3ef15aea,0x3ebf47d7,0x3f702d4f,0x3f6d76aa,0x3e8afa3e,0x3e2a1c3f,0x3f6a8b4b,0x3f676bd8,0x3d712283,0xbd48fb30,
0x3f737871,0x3f702d4f,0x3f167918,0x3efa2c90,0x3f6c835e,0x3f687c12,0x3ec3ef15,0x3e8afa3e,0x3f641901,0x3f5f5be6,0x3e20305b,0x3d20cee7,0x3f5a46a0,0x3f54db31,0xbda0af2a,0xbe47c5c2,
0x3f6c835e,0x3f676bd8,0x3f05c277,0x3ed1c759,0x3f61c598,0x3f5b941a,0x3e94a031,0x3e2a1c3f,0x3f54db31,0x3f4d9f02,0x3d20cee7,0xbdb4b86a,0x3f45e403,0x3f3daef9,0xbe5b73dc,0xbeac7cd4,
0x3f641901,0x3f5cdc29,0x3ee87171,0x3ea7bf25,0x3f54db31,0x3f4c1d35,0x3e47c5c2,0x3d712283,0x3f42a9f7,0x3f3889dc,0xbda0af2a,0xbe5b73dc,0x3f2dc5e3,0x3f226799,0xbeb13641,0xbef15aea,
0x3f5a46a0,0x3f50935b,0x3ec3ef15,0x3e78cfcc,0x3f45e403,0x3f3a4582,0x3dc8bd36,0xbd48fb30,0x3f2dc5e3,0x3f207440,0xbe47c5c2,0xbeac7cd4,0x3f1260b2,0x3f039c3d,0xbef15aea,0xbf187fc0,
0x3f800000,0x3f800000,0x3e9e377a,0x3e6f0c4d,0x3f800000,0x3f800000,0x3e20305b,0x3da0af2a,0x3f800000,0x3f800000,0,0xbda0af2a,0x3f800000,0x3f800000,0xbe20305b,0xbe6f0c4d,
0x3f7cd925,0x3f7c7160,0x3e20305b,0x3d8ca1f2,0x3f7c0361,0x3f7b8f2a,0xbca0d6d6,0xbddcbd0d,0x3f7b14be,0x3f7a9421,0xbe47c5c2,0xbe8fcefe,0x3f7a0d54,0x3f79805c,0xbeba9be1,0xbee3f40d,
0x3f737871,0x3f71decf,0,0xbdc8bd36,0x3f702d4f,0x3f6e641a,0xbe47c5c2,0xbe94a031,0x3f6c835e,0x3f6a8b4b,0xbec3ef15,0xbef15aea,0x3f687c12,0x3f6655e7,0xbf0e39da,0xbf226799,
0x3f641901,0x3f609384,0xbe20305b,0xbe862210,0x3f5cdc29,0x3f58f3c4,0xbeba9be1,0xbeece91a,0x3f54db31,0x3f50935b,0xbf0e39da,0xbf2456f1,0x3f4c1d35,0x3f4779bc,0xbf3889dc,0xbf4a965e,
0x3f4f1bbd,0x3f490a88,0xbe9e377a,0xbed65a92,0x3f42a9f7,0x3f3bfc8f,0xbf05c277,0xbf1e7cf1,0x3f3504f3,0x3f2dc5e3,0xbf3504f3,0xbf490a88,0x3f26423a,0x3f1e7cf1,0xbf5a46a0,0xbf687c12,
0x3f3504f3,0x3f2beb4a,0xbee87171,0xbf104f0e,0x3f226799,0x3f187fc0,0xbf2a0c73,0xbf4105b8,0x3f0e39da,0x3f039c3d,0xbf54db31,0xbf653a48,0x3ef15aea,0x3edae880,0xbf71decf,0xbf7a9421,
0x3f167918,0x3f0a04f8,0xbf167918,0xbf316e2c,0x3efa2c90,0x3edf7108,0xbf490a88,0xbf5cdc29,0x3ec3ef15,0x3ea7bf25,0xbf6c835e,0xbf77b493,0x3e8afa3e,0x3e5b73dc,0xbf7e39bc,0xbf7ff35e,
0x3ee87171,0x3ec8917e,0xbf3504f3,0xbf4d9f02,0x3ea7bf25,0x3e862210,0xbf61c598,0xbf710908,0x3e47c5c2,0x3e0255f4,0xbf7b14be,0xbf7fb10f,0x3d712283,0xbc20d8d2,0xbf7ec46d,0xbf7853f8,
0x3f800000,0x3f800000,0xbe9e377a,0xbec3ef15,0x3f800000,0x3f800000,0xbee87171,0xbf05c277,0x3f800000,0x3f800000,0xbf167918,0xbf26423a,0x3f800000,0x3f800000,0xbf3504f3,0xbf42a9f7,
0x3f78ed3c,0x3f7853f8,0xbf05c277,0xbf187fc0,0x3f77b493,0x3f770f11,0xbf2a0c73,0xbf3a4582,0x3f766377,0x3f75b1c9,0xbf490a88,0xbf563e03,0x3f74fa0b,0x3f743c41,0xbf61c598,0xbf6b8a3d,
0x3f641901,0x3f61c598,0xbf3504f3,0xbf45e403,0x3f5f5be6,0x3f5cdc29,0xbf54db31,0xbf61c598,0x3f5a46a0,0x3f579b8c,0xbf6c835e,0xbf74fa0b,0x3f54db31,0x3f5205d4,0xbf7b14be,0xbf7ec46d,
0x3f42a9f7,0x3f3daef9,0xbf5a46a0,0xbf676bd8,0x3f3889dc,0x3f333bc6,0xbf71decf,0xbf79805c,0x3f2dc5e3,0x3f28296a,0xbf7e39bc,0xbf7ffcd7,0x3f226799,0x3f1c81b9,0xbf7ec46d,0xbf7a9421,
0x3f167918,0x3f0e39da,0xbf737871,0xbf7b14be,0x3f05c277,0x3efa2c90,0xbf7f35f9,0xbf7fcd79,0x3ee87171,0x3ed65a92,0xbf7cd925,0xbf766377,0x3ec3ef15,0x3eb13641,0xbf6c835e,0xbf5f5be6,
0x3ec3ef15,0x3eac7cd4,0xbf7f35f9,0xbf7fb10f,0x3e94a031,0x3e78cfcc,0xbf7c0361,0xbf743c41,0x3e47c5c2,0x3e164083,0xbf687c12,0xbf58f3c4,0x3dc8bd36,0x3d48fb30,0xbf45e403,0xbf2f9c32,
0x3e20305b,0x3dc8bd36,0xbf7cd925,0xbf74fa0b,0x3d20cee7,0xbca0d6d6,0xbf687c12,0xbf579b8c,0xbda0af2a,0xbe0c4cf7,0xbf42a9f7,0xbf2a0c73,0xbe47c5c2,0xbe814693,0xbf0e39da,0xbedf7108,
0xbda0af2a,0xbe164083,0xbf6c835e,0xbf5b941a,0xbe5b73dc,0xbe8fcefe,0xbf45e403,0xbf2beb4a,0xbeb13641,0xbed1c759,0xbf0e39da,0xbedae880,0xbef15aea,0xbf07e565,0xbe94a031,0xbe164083,
0x3f800000,0x3f800000,0xbf4f1bbd,0xbf5a46a0,0x3f800000,0x3f800000,0xbf641901,0xbf6c835e,0x3f800000,0x3f800000,0xbf737871,0xbf78ed3c,0x3f800000,0x3f800000,0xbf7cd925,0xbf7f35f9,
0x3f737871,0x3f72ae9e,0xbf737871,0xbf79805c,0x3f71decf,0x3f710908,0xbf7d95f4,0xbf7fb10f,0x3f702d4f,0x3f6f4ba8,0xbf7fcd79,0xbf7deafa,0x3f6e641a,0x3f6d76aa,0xbf7a0d54,0xbf743c41,
0x3f4f1bbd,0x3f4c1d35,0xbf800000,0xbf7ec46d,0x3f490a88,0x3f45e403,0xbf7b14be,0xbf74fa0b,0x3f42a9f7,0x3f3f5cb5,0xbf6c835e,0xbf61c598,0x3f3bfc8f,0x3f3889dc,0xbf54db31,0xbf45e403,
0x3f167918,0x3f104f0e,0xbf737871,0xbf698690,0x3f0a04f8,0x3f039c3d,0xbf5cdc29,0xbf4d9f02,0x3efa2c90,0x3eece91a,0xbf3bfc8f,0xbf28296a,0x3edf7108,0x3ed1c759,0xbf1260b2,0xbef5c6c5,
0x3e9e377a,0x3e8afa3e,0xbf4f1bbd,0xbf3bfc8f,0x3e6f0c4d,0x3e47c5c2,0xbf26423a,0xbf0e39da,0x3e20305b,0x3df0b772,0xbee87171,0xbeb13641,0x3da0af2a,0x3d20cee7,0xbe6f0c4d,0xbdf0b772,
0,0xbd48fb30,0xbf167918,0xbef5c6c5,0xbdc8bd36,0xbe164083,0xbeba9be1,0xbe78cfcc,0xbe47c5c2,0xbe78cfcc,0xbdf0b772,0x3c20d8d2,0xbe94a031,0xbeac7cd4,0x3e0c4cf7,0x3e862210,
0xbe9e377a,0xbeba9be1,0xbe9e377a,0xbe3403f1,0xbed65a92,0xbef15aea,0xbd20cee7,0x3dc8bd36,0xbf05c277,0xbf1260b2,0x3e6f0c4d,0x3eba9be1,0xbf1e7cf1,0xbf2a0c73,0x3efa2c90,0x3f1a82a4,
0xbf167918,0xbf2456f1,0,0x3e164083,0xbf316e2c,0xbf3daef9,0x3e94a031,0x3edae880,0xbf490a88,0xbf53731f,0x3f0e39da,0x3f2beb4a,0xbf5cdc29,0xbf653a48,0x3f45e403,0x3f5b941a,
0x80000000,0x80000000,0x80000000,0xbda0af2a,0x80000000,0x80000000,0xbe20305b,0xbe6f0c4d,0x80000000,0x80000000,0xbe9e377a,0xbec3ef15,0x80000000,0x80000000,0xbee87171,0xbf05c277,
0x80000000,0xbc20d8d2,0x80000000,0xbdb4b86a,0xbca0d6d6,0xbcf13d4c,0xbe3403f1,0xbe862210,0xbd20cee7,0xbd48fb30,0xbeb13641,0xbedae880,0xbd712283,0xbd8ca1f2,0xbf0172c3,0xbf146eba,
0x80000000,0xbca0d6d6,0x80000000,0xbdc8bd36,0xbd20cee7,0xbd712283,0xbe47c5c2,0xbe94a031,0xbda0af2a,0xbdc8bd36,0xbec3ef15,0xbef15aea,0xbdf0b772,0xbe0c4cf7,0xbf0e39da,0xbf226799,
0x80000000,0xbcf13d4c,0x80000000,0xbddcbd0d,0xbd712283,0xbdb4b86a,0xbe5b73dc,0xbea2fd52,0xbdf0b772,0xbe164083,0xbed65a92,0xbf039c3d,0xbe3403f1,0xbe519f65,0xbf1a82a4,0xbf2f9c32,
0x80000000,0xbd20cee7,0x80000000,0xbdf0b772,0xbda0af2a,0xbdf0b772,0xbe6f0c4d,0xbeb13641,0xbe20305b,0xbe47c5c2,0xbee87171,0xbf0e39da,0xbe6f0c4d,0xbe8afa3e,0xbf26423a,0xbf3bfc8f,
0x80000000,0xbd48fb30,0x80000000,0xbe0255f4,0xbdc8bd36,0xbe164083,0xbe814693,0xbebf47d7,0xbe47c5c2,0xbe78cfcc,0xbefa2c90,0xbf187fc0,0xbe94a031,0xbeac7cd4,0xbf316e2c,0xbf4779bc,
0x80000000,0xbd712283,0x80000000,0xbe0c4cf7,0xbdf0b772,0xbe3403f1,0xbe8afa3e,0xbecd2ef3,0xbe6f0c4d,0xbe94a031,0xbf05c277,0xbf226799,0xbeb13641,0xbecd2ef3,0xbf3bfc8f,0xbf5205d4,
0x80000000,0xbd8ca1f2,0x80000000,0xbe164083,0xbe0c4cf7,0xbe519f65,0xbe94a031,0xbedae880,0xbe8afa3e,0xbeac7cd4,0xbf0e39da,0xbf2beb4a,0xbecd2ef3,0xbeece91a,0xbf45e403,0xbf5b941a,
0x80000000,0x80000000,0xbf167918,0xbf26423a,0x80000000,0x80000000,0xbf3504f3,0xbf42a9f7,0x80000000,0x80000000,0xbf4f1bbd,0xbf5a46a0,0x80000000,0x80000000,0xbf641901,0xbf6c835e,
0xbda0af2a,0xbdb4b86a,0xbf26423a,0xbf36c9a9,0xbdc8bd36,0xbddcbd0d,0xbf45e403,0xbf53731f,0xbdf0b772,0xbe0255f4,0xbf5f5be6,0xbf698690,0xbe0c4cf7,0xbe164083,0xbf71decf,0xbf7853f8,
0xbe20305b,0xbe3403f1,0xbf3504f3,0xbf45e403,0xbe47c5c2,0xbe5b73dc,0xbf54db31,0xbf61c598,0xbe6f0c4d,0xbe814693,0xbf6c835e,0xbf74fa0b,0xbe8afa3e,0xbe94a031,0xbf7b14be,0xbf7ec46d,
0xbe6f0c4d,0xbe862210,0xbf42a9f7,0xbf53731f,0xbe94a031,0xbea2fd52,0xbf61c598,0xbf6d76aa,0xbeb13641,0xbebf47d7,0xbf766377,0xbf7c7160,0xbecd2ef3,0xbedae880,0xbf7f8e56,0xbf7fb10f,
0xbe9e377a,0xbeb13641,0xbf4f1bbd,0xbf5f5be6,0xbec3ef15,0xbed65a92,0xbf6c835e,0xbf766377,0xbee87171,0xbefa2c90,0xbf7cd925,0xbf7fcd79,0xbf05c277,0xbf0e39da,0xbf7f35f9,0xbf7b14be,
0xbec3ef15,0xbedae880,0xbf5a46a0,0xbf698690,0xbef15aea,0xbf039c3d,0xbf74fa0b,0xbf7c7160,0xbf0e39da,0xbf187fc0,0xbf7fcd79,0xbf7f0059,0xbf226799,0xbf2beb4a,0xbf7a0d54,0xbf710908,
0xbee87171,0xbf0172c3,0xbf641901,0xbf71decf,0xbf0e39da,0xbf1a82a4,0xbf7b14be,0xbf7f8e56,0xbf26423a,0xbf316e2c,0xbf7f35f9,0xbf7a0d54,0xbf3bfc8f,0xbf45e403,0xbf702d4f,0xbf61c598,
0xbf05c277,0xbf146eba,0xbf6c835e,0xbf7853f8,0xbf226799,0xbf2f9c32,0xbf7ec46d,0xbf7fb10f,0xbf3bfc8f,0xbf4779bc,0xbf7b14be,0xbf710908,0xbf5205d4,0xbf5b941a,0xbf61c598,0xbf4d9f02,
0x80000000,0x80000000,0xbf737871,0xbf78ed3c,0x80000000,0x80000000,0xbf7cd925,0xbf7f35f9,0x80000000,0x80000000,0xbf800000,0xbf7f35f9,0x80000000,0x80000000,0xbf7cd925,0xbf78ed3c,
0xbe20305b,0xbe2a1c3f,0xbf7cd925,0xbf7f654e,0xbe3403f1,0xbe3de731,0xbf7ff35e,0xbf7e8238,0xbe47c5c2,0xbe519f65,0xbf7b14be,0xbf75b1c9,0xbe5b73dc,0xbe6542e9,0xbf6e641a,0xbf653a48,
0xbe9e377a,0xbea7bf25,0xbf800000,0xbf7ec46d,0xbeb13641,0xbeba9be1,0xbf7b14be,0xbf74fa0b,0xbec3ef15,0xbecd2ef3,0xbf6c835e,0xbf61c598,0xbed65a92,0xbedf7108,0xbf54db31,0xbf45e403,
0xbee87171,0xbef5c6c5,0xbf7cd925,0xbf770f11,0xbf0172c3,0xbf07e565,0xbf6e641a,0xbf62f219,0xbf0e39da,0xbf146eba,0xbf54db31,0xbf444969,0xbf1a82a4,0xbf207440,0xbf316e2c,0xbf1c81b9,
0xbf167918,0xbf1e7cf1,0xbf737871,0xbf687c12,0xbf26423a,0xbf2dc5e3,0xbf5a46a0,0xbf490a88,0xbf3504f3,0xbf3bfc8f,0xbf3504f3,0xbf1e7cf1,0xbf42a9f7,0xbf490a88,0xbf05c277,0xbed65a92,
0xbf3504f3,0xbf3daef9,0xbf641901,0xbf53731f,0xbf45e403,0xbf4d9f02,0xbf3f5cb5,0xbf28296a,0xbf54db31,0xbf5b941a,0xbf0e39da,0xbee3f40d,0xbf61c598,0xbf676bd8,0xbea7bf25,0xbe519f65,
0xbf4f1bbd,0xbf579b8c,0xbf4f1bbd,0xbf3889dc,0xbf5f5be6,0xbf6655e7,0xbf1e7cf1,0xbf0172c3,0xbf6c835e,0xbf71decf,0xbec3ef15,0xbe814693,0xbf766377,0xbf7a0d54,0xbdf0b772,0x3ca0d6d6,
0xbf641901,0xbf6b8a3d,0xbf3504f3,0xbf187fc0,0xbf71decf,0xbf770f11,0xbef15aea,0xbeac7cd4,0xbf7b14be,0xbf7deafa,0xbe47c5c2,0xbd48fb30,0xbf7f8e56,0xbf7ffcd7,0x3dc8bd36,0x3e78cfcc,
0x80000000,0x80000000,0xbf737871,0xbf6c835e,0x80000000,0x80000000,0xbf641901,0xbf5a46a0,0x80000000,0x80000000,0xbf4f1bbd,0xbf42a9f7,0x80000000,0x80000000,0xbf3504f3,0xbf26423a,
0xbe6f0c4d,0xbe78cfcc,0xbf5a46a0,0xbf4d9f02,0xbe814693,0xbe862210,0xbf3f5cb5,0xbf2f9c32,0xbe8afa3e,0xbe8fcefe,0xbf1e7cf1,0xbf0c2124,0xbe94a031,0xbe996dba,0xbef15aea,0xbec8917e,
0xbee87171,0xbef15aea,0xbf3504f3,0xbf226799,0xbefa2c90,0xbf0172c3,0xbf0e39da,0xbef15aea,0xbf05c277,0xbf0a04f8,0xbec3ef15,0xbe94a031,0xbf0e39da,0xbf1260b2,0xbe47c5c2,0xbdc8bd36,
0xbf26423a,0xbf2beb4a,0xbf05c277,0xbedae880,0xbf316e2c,0xbf36c9a9,0xbea7bf25,0xbe6542e9,0xbf3bfc8f,0xbf4105b8,0xbdf0b772,0xbc20d8d2,0xbf45e403,0xbf4a965e,0x3dc8bd36,0x3e519f65,
0xbf4f1bbd,0xbf54db31,0xbe9e377a,0xbe47c5c2,0xbf5a46a0,0xbf5f5be6,0xbda0af2a,0x3d20cee7,0xbf641901,0xbf687c12,0x3e20305b,0x3e8afa3e,0xbf6c835e,0xbf702d4f,0x3ec3ef15,0x3efa2c90,
0xbf6c835e,0xbf710908,0xbda0af2a,0x3d48fb30,0xbf74fa0b,0xbf7853f8,0x3e3403f1,0x3e996dba,0xbf7b14be,0xbf7d3aac,0x3ed65a92,0x3f07e565,0xbf7ec46d,0xbf7fb10f,0x3f226799,0x3f3a4582,
0xbf7cd925,0xbf7ec46d,0x3e20305b,0x3e94a031,0xbf7fcd79,0xbf7ff35e,0x3ed65a92,0x3f0a04f8,0xbf7f35f9,0xbf7d95f4,0x3f26423a,0x3f3f5cb5,0xbf7b14be,0xbf77b493,0x3f54db31,0x3f6655e7,
0xbf7f35f9,0xbf7d3aac,0x3ec3ef15,0x3f039c3d,0xbf7a0d54,0xbf75b1c9,0x3f226799,0x3f3daef9,0xbf702d4f,0xbf698690,0x3f54db31,0x3f676bd8,0xbf61c598,0xbf58f3c4,0x3f74fa0b,0x3f7d3aac,
0x80000000,0x80000000,0xbf167918,0xbf05c277,0x80000000,0x80000000,0xbee87171,0xbec3ef15,0x80000000,0x80000000,0xbe9e377a,0xbe6f0c4d,0x80000000,0x80000000,0xbe20305b,0xbda0af2a,
0xbe9e377a,0xbea2fd52,0xbe9e377a,0xbe6542e9,0xbea7bf25,0xbeac7cd4,0xbe0c4cf7,0xbd48fb30,0xbeb13641,0xbeb5eb4f,0x3d20cee7,0x3e0255f4,0xbeba9be1,0xbebf47d7,0x3e5b73dc,0x3e996dba,
0xbf167918,0xbf1a82a4,0x80000000,0x3dc8bd36,0xbf1e7cf1,0xbf226799,0x3e47c5c2,0x3e94a031,0xbf26423a,0xbf2a0c73,0x3ec3ef15,0x3ef15aea,0xbf2dc5e3,0xbf316e2c,0x3f0e39da,0x3f226799,
0xbf4f1bbd,0xbf53731f,0x3e9e377a,0x3ed1c759,0xbf579b8c,0xbf5b941a,0x3f0172c3,0x3f187fc0,0xbf5f5be6,0xbf62f219,0x3f2dc5e3,0x3f4105b8,0xbf6655e7,0xbf698690,0x3f5205d4,0x3f609384,
0xbf737871,0xbf766377,0x3f167918,0x3f2dc5e3,0xbf78ed3c,0xbf7b14be,0x3f42a9f7,0x3f54db31,0xbf7cd925,0xbf7e39bc,0x3f641901,0x3f702d4f,0xbf7f35f9,0xbf7fcd79,0x3f78ed3c,0x3f7e39bc,
0xbf800000,0xbf7fb10f,0x3f4f1bbd,0x3f609384,0xbf7ec46d,0xbf7d3aac,0x3f6e641a,0x3f7853f8,0xbf7b14be,0xbf7853f8,0x3f7e39bc,0x3f7ffcd7,0xbf74fa0b,0xbf710908,0x3f7d95f4,0x3f770f11,
0xbf737871,0xbf6e641a,0x3f737871,0x3f7c0361,0xbf687c12,0xbf61c598,0x3f7fcd79,0x3f7ec46d,0xbf5a46a0,0xbf5205d4,0x3f78ed3c,0x3f6e641a,0xbf490a88,0xbf3f5cb5,0x3f5f5be6,0x3f4c1d35,
0xbf4f1bbd,0xbf444969,0x3f800000,0x3f7d3aac,0xbf3889dc,0xbf2beb4a,0x3f74fa0b,0x3f676bd8,0xbf1e7cf1,0xbf104f0e,0x3f54db31,0x3f3daef9,0xbf0172c3,0xbee3f40d,0x3f226799,0x3f039c3d,
0x3f803f80,0,0x3f803f80,0,0x3f803f80,0,0x3f803f80,0,0x3f7d3f80,0x3e200000,0x3f643f73,0x3ee83e9e,0x3f353f4f,0x3f353f16,0x3ee83f16,0x3f643f4f,
0x3f733f80,0x3e9e0000,0x3f163f4f,0x3f4f3f16,0x3e9e,0x3f803f73,0xbf16be9e,0x3f4f3f73,0x3f643f80,0x3ee80000,0x3e203f16,0x3f7d3f4f,0xbf35be9e,0x3f353f73,0xbf7dbf73,0xbe203e9e,
0x3f4f3f80,0x3f160000,0xbe9e3e9e,0x3f733f73,0xbf80bf4f,0x3f16,0xbe9ebf4f,0xbf73bf16,0x3f353f80,0x3f350000,0xbf350000,0x3f353f80,0xbf35bf80,0xbf350000,0x3f350000,0xbf35bf80,
0x3f163f80,0x3f4f0000,0xbf73be9e,0x3e9e3f73,0xbf4f,0xbf80bf16,0x3f733f4f,0x3e9ebf16,0x3ee83f80,0x3f640000,0xbf7dbf16,0xbe203f4f,0x3f35be9e,0xbf35bf73,0x3e203f73,0x3f7d3e9e,
0x3e9e3f80,0x3f730000,0xbf4fbf4f,0xbf163f16,0x3f803e9e,0xbf73,0xbf4f3e9e,0x3f163f73,0x3e203f80,0x3f7d0000,0xbee8bf73,0xbf643e9e,0x3f353f4f,0x3f35bf16,0xbf64bf16,0xbee83f4f,
0x3f80,0x3f800000,0xbf80,0xbf800000,0x3f80,0x3f800000,0xbf80,0xbf800000,0xbe203f80,0x3f7d0000,0x3ee8bf73,0xbf64be9e,0xbf353f4f,0x3f353f16,0x3f64bf16,0xbee8bf4f,
0xbe9e3f80,0x3f730000,0x3f4fbf4f,0xbf16bf16,0xbf803e9e,0x3f73,0x3f4f3e9e,0x3f16bf73,0xbee83f80,0x3f640000,0x3f7dbf16,0xbe20bf4f,0xbf35be9e,0xbf353f73,0xbe203f73,0x3f7dbe9e,
0xbf163f80,0x3f4f0000,0x3f73be9e,0x3e9ebf73,0xbf4f,0xbf803f16,0xbf733f4f,0x3e9e3f16,0xbf353f80,0x3f350000,0x3f350000,0x3f35bf80,0x3f35bf80,0xbf350000,0xbf350000,0xbf353f80,
0xbf4f3f80,0x3f160000,0x3e9e3e9e,0x3f73bf73,0x3f80bf4f,0xbf16,0x3e9ebf4f,0xbf733f16,0xbf643f80,0x3ee80000,0xbe203f16,0x3f7dbf4f,0x3f35be9e,0x3f35bf73,0x3f7dbf73,0xbe20be9e,
0xbf733f80,0x3e9e0000,0xbf163f4f,0x3f4fbf16,0x3e9e,0x3f80bf73,0x3f16be9e,0x3f4fbf73,0xbf7d3f80,0x3e200000,0xbf643f73,0x3ee8be9e,0xbf353f4f,0x3f35bf16,0xbee83f16,0x3f64bf4f,
0xbf803f80,0,0xbf803f80,0,0xbf803f80,0,0xbf803f80,0,0xbf7d3f80,0xbe200000,0xbf643f73,0xbee83e9e,0xbf353f4f,0xbf353f16,0xbee83f16,0xbf643f4f,
0xbf733f80,0xbe9e0000,0xbf163f4f,0xbf4f3f16,0x3e9e,0xbf803f73,0x3f16be9e,0xbf4f3f73,0xbf643f80,0xbee80000,0xbe203f16,0xbf7d3f4f,0x3f35be9e,0xbf353f73,0x3f7dbf73,0x3e203e9e,
0xbf4f3f80,0xbf160000,0x3e9e3e9e,0xbf733f73,0x3f80bf4f,0x3f16,0x3e9ebf4f,0x3f73bf16,0xbf353f80,0xbf350000,0x3f350000,0xbf353f80,0x3f35bf80,0x3f350000,0xbf350000,0x3f35bf80,
0xbf163f80,0xbf4f0000,0x3f73be9e,0xbe9e3f73,0xbf4f,0x3f80bf16,0xbf733f4f,0xbe9ebf16,0xbee83f80,0xbf640000,0x3f7dbf16,0x3e203f4f,0xbf35be9e,0x3f35bf73,0xbe203f73,0xbf7d3e9e,
0xbe9e3f80,0xbf730000,0x3f4fbf4f,0x3f163f16,0xbf803e9e,0xbf73,0x3f4f3e9e,0xbf163f73,0xbe203f80,0xbf7d0000,0x3ee8bf73,0x3f643e9e,0xbf353f4f,0xbf35bf16,0x3f64bf16,0x3ee83f4f,
0x3f80,0xbf800000,0xbf80,0x3f800000,0x3f80,0xbf800000,0xbf80,0x3f800000,0x3e203f80,0xbf7d0000,0xbee8bf73,0x3f64be9e,0x3f353f4f,0xbf353f16,0xbf64bf16,0x3ee8bf4f,
0x3e9e3f80,0xbf730000,0xbf4fbf4f,0x3f16bf16,0x3f803e9e,0x3f73,0xbf4f3e9e,0xbf16bf73,0x3ee83f80,0xbf640000,0xbf7dbf16,0x3e20bf4f,0x3f35be9e,0x3f353f73,0x3e203f73,0xbf7dbe9e,
0x3f163f80,0xbf4f0000,0xbf73be9e,0xbe9ebf73,0xbf4f,0x3f803f16,0x3f733f4f,0xbe9e3f16,0x3f353f80,0xbf350000,0xbf350000,0xbf35bf80,0xbf35bf80,0x3f350000,0x3f350000,0x3f353f80,
0x3f4f3f80,0xbf160000,0xbe9e3e9e,0xbf73bf73,0xbf80bf4f,0xbf16,0xbe9ebf4f,0x3f733f16,0x3f643f80,0xbee80000,0x3e203f16,0xbf7dbf4f,0xbf35be9e,0xbf35bf73,0xbf7dbf73,0x3e20be9e,
0x3f733f80,0xbe9e0000,0x3f163f4f,0xbf4fbf16,0x3e9e,0xbf80bf73,0xbf16be9e,0xbf4fbf73,0x3f7d3f80,0xbe200000,0x3f643f73,0xbee8be9e,0x3f353f4f,0xbf35bf16,0x3ee83f16,0xbf64bf4f,
0x3f803f80,0,0x3f803f80,0,0x3f803f80,0,0x3f803f80,0,0x3e203e9e,0x3f7d3f73,0xbe200000,0x3f7d3f80,0xbee8be9e,0x3f643f73,0xbf35bf16,0x3f353f4f,
0xbf73bf4f,0x3e9e3f16,0xbf73bf80,0xbe9e0000,0xbf16bf4f,0xbf4fbf16,0xbe9e,0xbf80bf73,0xbee8bf4f,0xbf64bf16,0x3ee80000,0xbf64bf80,0x3f7d3f4f,0xbe20bf16,0x3f353f73,0x3f353e9e,
0x3f4f3e9e,0xbf16bf73,0x3f4f3f80,0x3f160000,0xbe9e3e9e,0x3f733f73,0xbf80bf4f,0x3f16,0x3f353f80,0x3f350000,0xbf350000,0x3f353f80,0xbf35bf80,0xbf350000,0x3f350000,0xbf35bf80,
0xbf163e9e,0x3f4f3f73,0xbf16bf80,0xbf4f0000,0x3f733e9e,0xbe9ebf73,0x3f4f,0x3f803f16,0xbf64bf4f,0xbee83f16,0x3f640000,0xbee8bf80,0xbe203f4f,0x3f7d3f16,0xbf35bf73,0xbf353e9e,
0x3e9ebf4f,0xbf73bf16,0x3e9e3f80,0x3f730000,0xbf4fbf4f,0xbf163f16,0x3f803e9e,0xbf73,0x3f7d3e9e,0x3e20bf73,0xbf7d0000,0x3e203f80,0x3f64be9e,0xbee8bf73,0xbf353f16,0x3f353f4f,
0x3f80,0x3f800000,0xbf80,0xbf800000,0x3f80,0x3f800000,0xbf80,0xbf800000,0xbf7d3e9e,0x3e203f73,0x3f7d0000,0x3e20bf80,0xbf64be9e,0xbee83f73,0x3f353f16,0x3f35bf4f,
0xbe9ebf4f,0xbf733f16,0xbe9e3f80,0x3f730000,0x3f4fbf4f,0xbf16bf16,0xbf803e9e,0x3f73,0x3f64bf4f,0xbee8bf16,0xbf640000,0xbee83f80,0x3e203f4f,0x3f7dbf16,0x3f35bf73,0xbf35be9e,
0x3f163e9e,0x3f4fbf73,0x3f16bf80,0xbf4f0000,0xbf733e9e,0xbe9e3f73,0x3f4f,0x3f80bf16,0xbf353f80,0x3f350000,0x3f350000,0x3f35bf80,0x3f35bf80,0xbf350000,0xbf350000,0xbf353f80,
0xbf4f3e9e,0xbf163f73,0xbf4f3f80,0x3f160000,0x3e9e3e9e,0x3f73bf73,0x3f80bf4f,0xbf16,0x3ee8bf4f,0xbf643f16,0xbee80000,0xbf643f80,0xbf7d3f4f,0xbe203f16,0xbf353f73,0x3f35be9e,
0x3f73bf4f,0x3e9ebf16,0x3f73bf80,0xbe9e0000,0x3f16bf4f,0xbf4f3f16,0xbe9e,0xbf803f73,0xbe203e9e,0x3f7dbf73,0x3e200000,0x3f7dbf80,0x3ee8be9e,0x3f64bf73,0x3f35bf16,0x3f35bf4f,
0xbf803f80,0,0xbf803f80,0,0xbf803f80,0,0xbf803f80,0,0xbe203e9e,0xbf7d3f73,0x3e200000,0xbf7d3f80,0x3ee8be9e,0xbf643f73,0x3f35bf16,0xbf353f4f,
0x3f73bf4f,0xbe9e3f16,0x3f73bf80,0x3e9e0000,0x3f16bf4f,0x3f4fbf16,0xbe9e,0x3f80bf73,0x3ee8bf4f,0x3f64bf16,0xbee80000,0x3f64bf80,0xbf7d3f4f,0x3e20bf16,0xbf353f73,0xbf353e9e,
0xbf4f3e9e,0x3f16bf73,0xbf4f3f80,0xbf160000,0x3e9e3e9e,0xbf733f73,0x3f80bf4f,0x3f16,0xbf353f80,0xbf350000,0x3f350000,0xbf353f80,0x3f35bf80,0x3f350000,0xbf350000,0x3f35bf80,
0x3f163e9e,0xbf4f3f73,0x3f16bf80,0x3f4f0000,0xbf733e9e,0x3e9ebf73,0x3f4f,0xbf803f16,0x3f64bf4f,0x3ee83f16,0xbf640000,0x3ee8bf80,0x3e203f4f,0xbf7d3f16,0x3f35bf73,0x3f353e9e,
0xbe9ebf4f,0x3f73bf16,0xbe9e3f80,0xbf730000,0x3f4fbf4f,0x3f163f16,0xbf803e9e,0xbf73,0xbf7d3e9e,0xbe20bf73,0x3f7d0000,0xbe203f80,0xbf64be9e,0x3ee8bf73,0x3f353f16,0xbf353f4f,
0x3f80,0xbf800000,0xbf80,0x3f800000,0x3f80,0xbf800000,0xbf80,0x3f800000,0x3f7d3e9e,0xbe203f73,0xbf7d0000,0xbe20bf80,0x3f64be9e,0x3ee83f73,0xbf353f16,0xbf35bf4f,
0x3e9ebf4f,0x3f733f16,0x3e9e3f80,0xbf730000,0xbf4fbf4f,0x3f16bf16,0x3f803e9e,0x3f73,0xbf64bf4f,0x3ee8bf16,0x3f640000,0x3ee83f80,0xbe203f4f,0xbf7dbf16,0xbf35bf73,0x3f35be9e,
0xbf163e9e,0xbf4fbf73,0xbf16bf80,0x3f4f0000,0x3f733e9e,0x3e9e3f73,0x3f4f,0xbf80bf16,0x3f353f80,0xbf350000,0xbf350000,0xbf35bf80,0xbf35bf80,0x3f350000,0x3f350000,0x3f353f80,
0x3f4f3e9e,0x3f163f73,0x3f4f3f80,0xbf160000,0xbe9e3e9e,0xbf73bf73,0xbf80bf4f,0xbf16,0xbee8bf4f,0x3f643f16,0x3ee80000,0x3f643f80,0x3f7d3f4f,0x3e203f16,0x3f353f73,0xbf35be9e,
0xbf73bf4f,0xbe9ebf16,0xbf73bf80,0x3e9e0000,0xbf16bf4f,0x3f4f3f16,0xbe9e,0x3f803f73,0x3e203e9e,0xbf7dbf73,0xbe200000,0xbf7dbf80,0xbee8be9e,0xbf64bf73,0xbf35bf16,0xbf35bf4f,
0x3f803f80,0,0x3f803f80,0,0x3f803f80,0,0x3f803f80,0,0xbf64bf4f,0x3ee83f16,0xbf7dbf73,0x3e203e9e,0xbf7dbf80,0xbe200000,0xbf64bf73,0xbee8be9e,
0x3f163e9e,0xbf4fbf73,0x3f733f4f,0xbe9ebf16,0x3f733f80,0x3e9e0000,0x3f163f4f,0x3f4f3f16,0xbe203e9e,0x3f7d3f73,0xbf64bf16,0x3ee83f4f,0xbf64bf80,0xbee80000,0xbe20bf16,0xbf7dbf4f,
0xbe9ebf4f,0xbf73bf16,0x3f4f3e9e,0xbf16bf73,0x3f4f3f80,0x3f160000,0xbe9e3e9e,0x3f733f73,0x3f353f80,0x3f350000,0xbf350000,0x3f353f80,0xbf35bf80,0xbf350000,0x3f350000,0xbf35bf80,
0xbf73bf4f,0xbe9e3f16,0x3f16be9e,0xbf4fbf73,0x3f163f80,0x3f4f0000,0xbf73be9e,0x3e9e3f73,0x3f7d3e9e,0xbe20bf73,0xbee83f16,0x3f643f4f,0xbee8bf80,0xbf640000,0x3f7d3f16,0x3e20bf4f,
0xbf4f3e9e,0x3f163f73,0x3e9ebf4f,0xbf73bf16,0x3e9e3f80,0x3f730000,0xbf4fbf4f,0xbf163f16,0x3ee8bf4f,0xbf64bf16,0xbe203f73,0x3f7d3e9e,0xbe20bf80,0xbf7d0000,0x3ee83f73,0x3f64be9e,
0x3f80,0x3f800000,0xbf80,0xbf800000,0x3f80,0x3f800000,0xbf80,0xbf800000,0xbee8bf4f,0xbf643f16,0x3e203f73,0x3f7dbe9e,0x3e20bf80,0xbf7d0000,0xbee83f73,0x3f643e9e,
0x3f4f3e9e,0x3f16bf73,0xbe9ebf4f,0xbf733f16,0xbe9e3f80,0x3f730000,0x3f4fbf4f,0xbf16bf16,0xbf7d3e9e,0xbe203f73,0x3ee83f16,0x3f64bf4f,0x3ee8bf80,0xbf640000,0xbf7d3f16,0x3e203f4f,
0x3f73bf4f,0xbe9ebf16,0xbf16be9e,0xbf4f3f73,0xbf163f80,0x3f4f0000,0x3f73be9e,0x3e9ebf73,0xbf353f80,0x3f350000,0x3f350000,0x3f35bf80,0x3f35bf80,0xbf350000,0xbf350000,0xbf353f80,
0x3e9ebf4f,0xbf733f16,0xbf4f3e9e,0xbf163f73,0xbf4f3f80,0x3f160000,0x3e9e3e9e,0x3f73bf73,0x3e203e9e,0x3f7dbf73,0x3f64bf16,0x3ee8bf4f,0x3f64bf80,0xbee80000,0x3e20bf16,0xbf7d3f4f,
0xbf163e9e,0xbf4f3f73,0xbf733f4f,0xbe9e3f16,0xbf733f80,0x3e9e0000,0xbf163f4f,0x3f4fbf16,0x3f64bf4f,0x3ee8bf16,0x3f7dbf73,0x3e20be9e,0x3f7dbf80,0xbe200000,0x3f64bf73,0xbee83e9e,
0xbf803f80,0,0xbf803f80,0,0xbf803f80,0,0xbf803f80,0,0x3f64bf4f,0xbee83f16,0x3f7dbf73,0xbe203e9e,0x3f7dbf80,0x3e200000,0x3f64bf73,0x3ee8be9e,
0xbf163e9e,0x3f4fbf73,0xbf733f4f,0x3e9ebf16,0xbf733f80,0xbe9e0000,0xbf163f4f,0xbf4f3f16,0x3e203e9e,0xbf7d3f73,0x3f64bf16,0xbee83f4f,0x3f64bf80,0x3ee80000,0x3e20bf16,0x3f7dbf4f,
0x3e9ebf4f,0x3f73bf16,0xbf4f3e9e,0x3f16bf73,0xbf4f3f80,0xbf160000,0x3e9e3e9e,0xbf733f73,0xbf353f80,0xbf350000,0x3f350000,0xbf353f80,0x3f35bf80,0x3f350000,0xbf350000,0x3f35bf80,
0x3f73bf4f,0x3e9e3f16,0xbf16be9e,0x3f4fbf73,0xbf163f80,0xbf4f0000,0x3f73be9e,0xbe9e3f73,0xbf7d3e9e,0x3e20bf73,0x3ee83f16,0xbf643f4f,0x3ee8bf80,0x3f640000,0xbf7d3f16,0xbe20bf4f,
0x3f4f3e9e,0xbf163f73,0xbe9ebf4f,0x3f73bf16,0xbe9e3f80,0xbf730000,0x3f4fbf4f,0x3f163f16,0xbee8bf4f,0x3f64bf16,0x3e203f73,0xbf7d3e9e,0x3e20bf80,0x3f7d0000,0xbee83f73,0xbf64be9e,
0x3f80,0xbf800000,0xbf80,0x3f800000,0x3f80,0xbf800000,0xbf80,0x3f800000,0x3ee8bf4f,0x3f643f16,0xbe203f73,0xbf7dbe9e,0xbe20bf80,0x3f7d0000,0x3ee83f73,0xbf643e9e,
0xbf4f3e9e,0xbf16bf73,0x3e9ebf4f,0x3f733f16,0x3e9e3f80,0xbf730000,0xbf4fbf4f,0x3f16bf16,0x3f7d3e9e,0x3e203f73,0xbee83f16,0xbf64bf4f,0xbee8bf80,0x3f640000,0x3f7d3f16,0xbe203f4f,
0xbf73bf4f,0x3e9ebf16,0x3f16be9e,0x3f4f3f73,0x3f163f80,0xbf4f0000,0xbf73be9e,0xbe9ebf73,0x3f353f80,0xbf350000,0xbf350000,0xbf35bf80,0xbf35bf80,0x3f350000,0x3f350000,0x3f353f80,
0xbe9ebf4f,0x3f733f16,0x3f4f3e9e,0x3f163f73,0x3f4f3f80,0xbf160000,0xbe9e3e9e,0xbf73bf73,0xbe203e9e,0xbf7dbf73,0xbf64bf16,0xbee8bf4f,0xbf64bf80,0x3ee80000,0xbe20bf16,0x3f7d3f4f,
0x3f163e9e,0x3f4f3f73,0x3f733f4f,0x3e9e3f16,0x3f733f80,0xbe9e0000,0x3f163f4f,0xbf4fbf16,0xbf64bf4f,0xbee8bf16,0xbf7dbf73,0xbe20be9e,0xbf7dbf80,0x3e200000,0xbf64bf73,0x3ee83e9e,
0x3f803f80,0,0x3f803f80,0,0x3f803f80,0,0x3f803f80,0,0xbf35bf4f,0xbf35bf16,0xbee8bf16,0xbf64bf4f,0xbe20be9e,0xbf7dbf73,0x3e200000,0xbf7dbf80,
0x3e9e,0x3f803f73,0xbf16be9e,0x3f4f3f73,0xbf73bf4f,0x3e9e3f16,0xbf73bf80,0xbe9e0000,0x3f353e9e,0xbf35bf73,0x3f7d3f73,0x3e20be9e,0x3ee83f4f,0x3f643f16,0xbee80000,0x3f643f80,
0xbf80bf4f,0x3f16,0xbe9ebf4f,0xbf73bf16,0x3f4f3e9e,0xbf16bf73,0x3f4f3f80,0x3f160000,0x3f353f80,0x3f350000,0xbf350000,0x3f353f80,0xbf35bf80,0xbf350000,0x3f350000,0xbf35bf80,
0xbf4f,0xbf80bf16,0x3f733f4f,0x3e9ebf16,0xbf163e9e,0x3f4f3f73,0xbf16bf80,0xbf4f0000,0xbf353e9e,0x3f353f73,0xbe20bf73,0xbf7dbe9e,0x3f643f4f,0x3ee8bf16,0xbf640000,0x3ee83f80,
0x3f803e9e,0xbf73,0xbf4f3e9e,0x3f163f73,0x3e9ebf4f,0xbf73bf16,0x3e9e3f80,0x3f730000,0xbf35bf4f,0xbf353f16,0x3f643f16,0x3ee8bf4f,0xbf7dbe9e,0xbe203f73,0x3f7d0000,0xbe20bf80,
0x3f80,0x3f800000,0xbf80,0xbf800000,0x3f80,0x3f800000,0xbf80,0xbf800000,0x3f35bf4f,0xbf35bf16,0xbf643f16,0x3ee83f4f,0x3f7dbe9e,0xbe20bf73,0xbf7d0000,0xbe203f80,
0xbf803e9e,0x3f73,0x3f4f3e9e,0x3f16bf73,0xbe9ebf4f,0xbf733f16,0xbe9e3f80,0x3f730000,0x3f353e9e,0x3f35bf73,0x3e20bf73,0xbf7d3e9e,0xbf643f4f,0x3ee83f16,0x3f640000,0x3ee8bf80,
0xbf4f,0xbf803f16,0xbf733f4f,0x3e9e3f16,0x3f163e9e,0x3f4fbf73,0x3f16bf80,0xbf4f0000,0xbf353f80,0x3f350000,0x3f350000,0x3f35bf80,0x3f35bf80,0xbf350000,0xbf350000,0xbf353f80,
0x3f80bf4f,0xbf16,0x3e9ebf4f,0xbf733f16,0xbf4f3e9e,0xbf163f73,0xbf4f3f80,0x3f160000,0xbf353e9e,0xbf353f73,0xbf7d3f73,0x3e203e9e,0xbee83f4f,0x3f64bf16,0x3ee80000,0x3f64bf80,
0x3e9e,0x3f80bf73,0x3f16be9e,0x3f4fbf73,0x3f73bf4f,0x3e9ebf16,0x3f73bf80,0xbe9e0000,0x3f35bf4f,0xbf353f16,0x3ee8bf16,0xbf643f4f,0x3e20be9e,0xbf7d3f73,0xbe200000,0xbf7d3f80,
0xbf803f80,0,0xbf803f80,0,0xbf803f80,0,0xbf803f80,0,0x3f35bf4f,0x3f35bf16,0x3ee8bf16,0x3f64bf4f,0x3e20be9e,0x3f7dbf73,0xbe200000,0x3f7dbf80,
0x3e9e,0xbf803f73,0x3f16be9e,0xbf4f3f73,0x3f73bf4f,0xbe9e3f16,0x3f73bf80,0x3e9e0000,0xbf353e9e,0x3f35bf73,0xbf7d3f73,0xbe20be9e,0xbee83f4f,0xbf643f16,0x3ee80000,0xbf643f80,
0x3f80bf4f,0x3f16,0x3e9ebf4f,0x3f73bf16,0xbf4f3e9e,0x3f16bf73,0xbf4f3f80,0xbf160000,0xbf353f80,0xbf350000,0x3f350000,0xbf353f80,0x3f35bf80,0x3f350000,0xbf350000,0x3f35bf80,
0xbf4f,0x3f80bf16,0xbf733f4f,0xbe9ebf16,0x3f163e9e,0xbf4f3f73,0x3f16bf80,0x3f4f0000,0x3f353e9e,0xbf353f73,0x3e20bf73,0x3f7dbe9e,0xbf643f4f,0xbee8bf16,0x3f640000,0xbee83f80,
0xbf803e9e,0xbf73,0x3f4f3e9e,0xbf163f73,0xbe9ebf4f,0x3f73bf16,0xbe9e3f80,0xbf730000,0x3f35bf4f,0x3f353f16,0xbf643f16,0xbee8bf4f,0x3f7dbe9e,0x3e203f73,0xbf7d0000,0x3e20bf80,
0x3f80,0xbf800000,0xbf80,0x3f800000,0x3f80,0xbf800000,0xbf80,0x3f800000,0xbf35bf4f,0x3f35bf16,0x3f643f16,0xbee83f4f,0xbf7dbe9e,0x3e20bf73,0x3f7d0000,0x3e203f80,
0x3f803e9e,0x3f73,0xbf4f3e9e,0xbf16bf73,0x3e9ebf4f,0x3f733f16,0x3e9e3f80,0xbf730000,0xbf353e9e,0xbf35bf73,0xbe20bf73,0x3f7d3e9e,0x3f643f4f,0xbee83f16,0xbf640000,0xbee8bf80,
0xbf4f,0x3f803f16,0x3f733f4f,0xbe9e3f16,0xbf163e9e,0xbf4fbf73,0xbf16bf80,0x3f4f0000,0x3f353f80,0xbf350000,0xbf350000,0xbf35bf80,0xbf35bf80,0x3f350000,0x3f350000,0x3f353f80,
0xbf80bf4f,0xbf16,0xbe9ebf4f,0x3f733f16,0x3f4f3e9e,0x3f163f73,0x3f4f3f80,0xbf160000,0x3f353e9e,0x3f353f73,0x3f7d3f73,0xbe203e9e,0x3ee83f4f,0xbf64bf16,0xbee80000,0xbf64bf80,
0x3e9e,0xbf80bf73,0xbf16be9e,0xbf4fbf73,0xbf73bf4f,0xbe9ebf16,0xbf73bf80,0x3e9e0000,0xbf35bf4f,0x3f353f16,0xbee8bf16,0x3f643f4f,0xbe20be9e,0x3f7d3f73,0x3e200000,0x3f7d3f80,
0x3f803f80,0,0x3f803f80,0,0x3f803f80,0,0x3f803f80,0,0x3ee83e9e,0xbf64bf73,0x3f353f16,0xbf35bf4f,0x3f643f4f,0xbee8bf16,0x3f7d3f73,0xbe20be9e,
0xbf16bf4f,0xbf4fbf16,0xbe9e,0xbf80bf73,0x3f163e9e,0xbf4fbf73,0x3f733f4f,0xbe9ebf16,0xbf7dbf4f,0x3e203f16,0xbf35bf73,0xbf35be9e,0x3e20be9e,0xbf7dbf73,0x3f643f16,0xbee8bf4f,
0xbe9e3e9e,0x3f733f73,0xbf80bf4f,0x3f16,0xbe9ebf4f,0xbf73bf16,0x3f4f3e9e,0xbf16bf73,0x3f353f80,0x3f350000,0xbf350000,0x3f353f80,0xbf35bf80,0xbf350000,0x3f350000,0xbf35bf80,
0x3f733e9e,0xbe9ebf73,0x3f4f,0x3f803f16,0xbf73bf4f,0xbe9e3f16,0x3f16be9e,0xbf4fbf73,0x3e20bf4f,0xbf7dbf16,0x3f353f73,0x3f35be9e,0xbf7dbe9e,0x3e203f73,0x3ee8bf16,0xbf64bf4f,
0xbf4fbf4f,0xbf163f16,0x3f803e9e,0xbf73,0xbf4f3e9e,0x3f163f73,0x3e9ebf4f,0xbf73bf16,0xbf643e9e,0x3ee83f73,0x3f35bf16,0xbf35bf4f,0xbee83f4f,0x3f643f16,0x3e20bf73,0xbf7dbe9e,
0x3f80,0x3f800000,0xbf80,0xbf800000,0x3f80,0x3f800000,0xbf80,0xbf800000,0x3f643e9e,0x3ee8bf73,0xbf35bf16,0xbf353f4f,0x3ee83f4f,0x3f64bf16,0xbe20bf73,0xbf7d3e9e,
0x3f4fbf4f,0xbf16bf16,0xbf803e9e,0x3f73,0x3f4f3e9e,0x3f16bf73,0xbe9ebf4f,0xbf733f16,0xbe20bf4f,0xbf7d3f16,0xbf353f73,0x3f353e9e,0x3f7dbe9e,0x3e20bf73,0xbee8bf16,0xbf643f4f,
0xbf733e9e,0xbe9e3f73,0x3f4f,0x3f80bf16,0x3f73bf4f,0xbe9ebf16,0xbf16be9e,0xbf4f3f73,0xbf353f80,0x3f350000,0x3f350000,0x3f35bf80,0x3f35bf80,0xbf350000,0xbf350000,0xbf353f80,
0x3e9e3e9e,0x3f73bf73,0x3f80bf4f,0xbf16,0x3e9ebf4f,0xbf733f16,0xbf4f3e9e,0xbf163f73,0x3f7dbf4f,0x3e20bf16,0x3f35bf73,0xbf353e9e,0xbe20be9e,0xbf7d3f73,0xbf643f16,0xbee83f4f,
0x3f16bf4f,0xbf4f3f16,0xbe9e,0xbf803f73,0xbf163e9e,0xbf4f3f73,0xbf733f4f,0xbe9e3f16,0xbee83e9e,0xbf643f73,0xbf353f16,0xbf353f4f,0xbf643f4f,0xbee83f16,0xbf7d3f73,0xbe203e9e,
0xbf803f80,0,0xbf803f80,0,0xbf803f80,0,0xbf803f80,0,0xbee83e9e,0x3f64bf73,0xbf353f16,0x3f35bf4f,0xbf643f4f,0x3ee8bf16,0xbf7d3f73,0x3e20be9e,
0x3f16bf4f,0x3f4fbf16,0xbe9e,0x3f80bf73,0xbf163e9e,0x3f4fbf73,0xbf733f4f,0x3e9ebf16,0x3f7dbf4f,0xbe203f16,0x3f35bf73,0x3f35be9e,0xbe20be9e,0x3f7dbf73,0xbf643f16,0x3ee8bf4f,
0x3e9e3e9e,0xbf733f73,0x3f80bf4f,0x3f16,0x3e9ebf4f,0x3f73bf16,0xbf4f3e9e,0x3f16bf73,0xbf353f80,0xbf350000,0x3f350000,0xbf353f80,0x3f35bf80,0x3f350000,0xbf350000,0x3f35bf80,
0xbf733e9e,0x3e9ebf73,0x3f4f,0xbf803f16,0x3f73bf4f,0x3e9e3f16,0xbf16be9e,0x3f4fbf73,0xbe20bf4f,0x3f7dbf16,0xbf353f73,0xbf35be9e,0x3f7dbe9e,0xbe203f73,0xbee8bf16,0x3f64bf4f,
0x3f4fbf4f,0x3f163f16,0xbf803e9e,0xbf73,0x3f4f3e9e,0xbf163f73,0xbe9ebf4f,0x3f73bf16,0x3f643e9e,0xbee83f73,0xbf35bf16,0x3f35bf4f,0x3ee83f4f,0xbf643f16,0xbe20bf73,0x3f7dbe9e,
0x3f80,0xbf800000,0xbf80,0x3f800000,0x3f80,0xbf800000,0xbf80,0x3f800000,0xbf643e9e,0xbee8bf73,0x3f35bf16,0x3f353f4f,0xbee83f4f,0xbf64bf16,0x3e20bf73,0x3f7d3e9e,
0xbf4fbf4f,0x3f16bf16,0x3f803e9e,0x3f73,0xbf4f3e9e,0xbf16bf73,0x3e9ebf4f,0x3f733f16,0x3e20bf4f,0x3f7d3f16,0x3f353f73,0xbf353e9e,0xbf7dbe9e,0xbe20bf73,0x3ee8bf16,0x3f643f4f,
0x3f733e9e,0x3e9e3f73,0x3f4f,0xbf80bf16,0xbf73bf4f,0x3e9ebf16,0x3f16be9e,0x3f4f3f73,0x3f353f80,0xbf350000,0xbf350000,0xbf35bf80,0xbf35bf80,0x3f350000,0x3f350000,0x3f353f80,
0xbe9e3e9e,0xbf73bf73,0xbf80bf4f,0xbf16,0xbe9ebf4f,0x3f733f16,0x3f4f3e9e,0x3f163f73,0xbf7dbf4f,0xbe20bf16,0xbf35bf73,0x3f353e9e,0x3e20be9e,0x3f7d3f73,0x3f643f16,0x3ee83f4f,
0xbf16bf4f,0x3f4f3f16,0xbe9e,0x3f803f73,0x3f163e9e,0x3f4f3f73,0x3f733f4f,0x3e9e3f16,0x3ee83e9e,0x3f643f73,0x3f353f16,0x3f353f4f,0x3f643f4f,0x3ee83f16,0x3f7d3f73,0x3e203e9e,
0x3f803f80,0x3f80,0xbf803f80,0x3f80,0x3f803f80,0xbf80,0xbf803f80,0xbf80,0x3f803f80,0x3f80,0xbf803f80,0x3f80,0x3f803f80,0xbf80,0xbf803f80,0xbf80,
0x3f7b3f80,0xbe483f80,0xbf7b3f80,0x3e483f80,0x3f553f6d,0x3f0ebf6d,0xbf553f6d,0xbf0ebf6d,0x3f0e3f35,0xbf553f35,0xbf0e3f35,0x3f553f35,0x3e483ec4,0x3f7bbec4,0xbe483ec4,0xbf7bbec4,
0x3f6d3f80,0xbec43f80,0xbf6d3f80,0x3ec43f80,0x3ec43f35,0x3f6dbf35,0xbec43f35,0xbf6dbf35,0xbec40000,0xbf6d0000,0x3ec40000,0x3f6d0000,0xbf6dbf35,0x3ec43f35,0x3f6dbf35,0xbec43f35,
0x3f553f80,0xbf0e3f80,0xbf553f80,0x3f0e3f80,0xbe483ec4,0x3f7bbec4,0x3e483ec4,0xbf7bbec4,0xbf7bbf35,0xbe48bf35,0x3f7bbf35,0x3e48bf35,0xbf0ebf6d,0xbf553f6d,0x3f0ebf6d,0x3f553f6d,
0x3f353f80,0xbf353f80,0xbf353f80,0x3f353f80,0xbf350000,0x3f350000,0x3f350000,0xbf350000,0xbf35bf80,0x3f35bf80,0x3f35bf80,0xbf35bf80,0x3f350000,0xbf350000,0xbf350000,0x3f350000,
0x3f0e3f80,0xbf553f80,0xbf0e3f80,0x3f553f80,0xbf7bbec4,0x3e483ec4,0x3f7bbec4,0xbe483ec4,0x3e48bf35,0x3f7bbf35,0xbe48bf35,0xbf7bbf35,0x3f553f6d,0x3f0ebf6d,0xbf553f6d,0xbf0ebf6d,
0x3ec43f80,0xbf6d3f80,0xbec43f80,0x3f6d3f80,0xbf6dbf35,0xbec43f35,0x3f6dbf35,0x3ec43f35,0x3f6d0000,0x3ec40000,0xbf6d0000,0xbec40000,0xbec43f35,0x3f6dbf35,0x3ec43f35,0xbf6dbf35,
0x3e483f80,0xbf7b3f80,0xbe483f80,0x3f7b3f80,0xbf0ebf6d,0xbf553f6d,0x3f0ebf6d,0x3f553f6d,0x3f553f35,0xbf0e3f35,0xbf553f35,0x3f0e3f35,0xbf7bbec4,0xbe483ec4,0x3f7bbec4,0x3e483ec4,
0x3f803f80,0x3f80,0xbf803f80,0x3f80,0x3f803f80,0xbf80,0xbf803f80,0xbf80,0x3f803f80,0x3f80,0xbf803f80,0x3f80,0x3f803f80,0xbf80,0xbf803f80,0xbf80,
0xbe480000,0xbf7b0000,0x3e480000,0x3f7b0000,0xbf0ebec4,0x3f553ec4,0x3f0ebec4,0xbf553ec4,0xbf55bf35,0xbf0ebf35,0x3f55bf35,0x3f0ebf35,0xbf7bbf6d,0x3e483f6d,0x3f7bbf6d,0xbe483f6d,
0xbf6dbf80,0x3ec4bf80,0x3f6dbf80,0xbec4bf80,0xbec4bf35,0xbf6d3f35,0x3ec4bf35,0x3f6d3f35,0x3ec40000,0x3f6d0000,0xbec40000,0xbf6d0000,0x3f6d3f35,0xbec4bf35,0xbf6d3f35,0x3ec4bf35,
0x3f0e0000,0x3f550000,0xbf0e0000,0xbf550000,0x3f7b3f6d,0x3e48bf6d,0xbf7b3f6d,0xbe48bf6d,0x3e483f35,0xbf7b3f35,0xbe483f35,0x3f7b3f35,0xbf55bec4,0x3f0e3ec4,0x3f55bec4,0xbf0e3ec4,
0x3f353f80,0xbf353f80,0xbf353f80,0x3f353f80,0xbf350000,0x3f350000,0x3f350000,0xbf350000,0xbf35bf80,0x3f35bf80,0x3f35bf80,0xbf35bf80,0x3f350000,0xbf350000,0xbf350000,0x3f350000,
0xbf550000,0xbf0e0000,0x3f550000,0x3f0e0000,0xbe48bf6d,0xbf7b3f6d,0x3e48bf6d,0x3f7b3f6d,0x3f7b3f35,0xbe483f35,0xbf7b3f35,0x3e483f35,0xbf0e3ec4,0x3f55bec4,0x3f0e3ec4,0xbf55bec4,
0xbec4bf80,0x3f6dbf80,0x3ec4bf80,0xbf6dbf80,0x3f6d3f35,0x3ec4bf35,0xbf6d3f35,0xbec4bf35,0xbf6d0000,0xbec40000,0x3f6d0000,0x3ec40000,0x3ec4bf35,0xbf6d3f35,0xbec4bf35,0x3f6d3f35,
0x3f7b0000,0x3e480000,0xbf7b0000,0xbe480000,0xbf553ec4,0x3f0ebec4,0x3f553ec4,0xbf0ebec4,0x3f0ebf35,0x3f55bf35,0xbf0ebf35,0xbf55bf35,0xbe483f6d,0x3f7bbf6d,0x3e483f6d,0xbf7bbf6d,
0x3f803f80,0x3f80,0xbf803f80,0x3f80,0x3f803f80,0xbf80,0xbf803f80,0xbf80,0x3f803f80,0x3f80,0xbf803f80,0x3f80,0x3f803f80,0xbf80,0xbf803f80,0xbf80,
0xbf7bbf80,0x3e48bf80,0x3f7bbf80,0xbe48bf80,0xbf55bf6d,0xbf0e3f6d,0x3f55bf6d,0x3f0e3f6d,0xbf0ebf35,0x3f55bf35,0x3f0ebf35,0xbf55bf35,0xbe48bec4,0xbf7b3ec4,0x3e48bec4,0x3f7b3ec4,
0x3f6d3f80,0xbec43f80,0xbf6d3f80,0x3ec43f80,0x3ec43f35,0x3f6dbf35,0xbec43f35,0xbf6dbf35,0xbec40000,0xbf6d0000,0x3ec40000,0x3f6d0000,0xbf6dbf35,0x3ec43f35,0x3f6dbf35,0xbec43f35,
0xbf55bf80,0x3f0ebf80,0x3f55bf80,0xbf0ebf80,0x3e48bec4,0xbf7b3ec4,0xbe48bec4,0x3f7b3ec4,0x3f7b3f35,0x3e483f35,0xbf7b3f35,0xbe483f35,0x3f0e3f6d,0x3f55bf6d,0xbf0e3f6d,0xbf55bf6d,
0x3f353f80,0xbf353f80,0xbf353f80,0x3f353f80,0xbf350000,0x3f350000,0x3f350000,0xbf350000,0xbf35bf80,0x3f35bf80,0x3f35bf80,0xbf35bf80,0x3f350000,0xbf350000,0xbf350000,0x3f350000,
0xbf0ebf80,0x3f55bf80,0x3f0ebf80,0xbf55bf80,0x3f7b3ec4,0xbe48bec4,0xbf7b3ec4,0x3e48bec4,0xbe483f35,0xbf7b3f35,0x3e483f35,0x3f7b3f35,0xbf55bf6d,0xbf0e3f6d,0x3f55bf6d,0x3f0e3f6d,
0x3ec43f80,0xbf6d3f80,0xbec43f80,0x3f6d3f80,0xbf6dbf35,0xbec43f35,0x3f6dbf35,0x3ec43f35,0x3f6d0000,0x3ec40000,0xbf6d0000,0xbec40000,0xbec43f35,0x3f6dbf35,0x3ec43f35,0xbf6dbf35,
0xbe48bf80,0x3f7bbf80,0x3e48bf80,0xbf7bbf80,0x3f0e3f6d,0x3f55bf6d,0xbf0e3f6d,0xbf55bf6d,0xbf55bf35,0x3f0ebf35,0x3f55bf35,0xbf0ebf35,0x3f7b3ec4,0x3e48bec4,0xbf7b3ec4,0xbe48bec4,
0x3f803f80,0x3f80,0xbf803f80,0x3f80,0x3f803f80,0xbf80,0xbf803f80,0xbf80,0x3f803f80,0x3f80,0xbf803f80,0x3f80,0x3f803f80,0xbf80,0xbf803f80,0xbf80,
0x3e480000,0x3f7b0000,0xbe480000,0xbf7b0000,0x3f0e3ec4,0xbf55bec4,0xbf0e3ec4,0x3f55bec4,0x3f553f35,0x3f0e3f35,0xbf553f35,0xbf0e3f35,0x3f7b3f6d,0xbe48bf6d,0xbf7b3f6d,0x3e48bf6d,
0xbf6dbf80,0x3ec4bf80,0x3f6dbf80,0xbec4bf80,0xbec4bf35,0xbf6d3f35,0x3ec4bf35,0x3f6d3f35,0x3ec40000,0x3f6d0000,0xbec40000,0xbf6d0000,0x3f6d3f35,0xbec4bf35,0xbf6d3f35,0x3ec4bf35,
0xbf0e0000,0xbf550000,0x3f0e0000,0x3f550000,0xbf7bbf6d,0xbe483f6d,0x3f7bbf6d,0x3e483f6d,0xbe48bf35,0x3f7bbf35,0x3e48bf35,0xbf7bbf35,0x3f553ec4,0xbf0ebec4,0xbf553ec4,0x3f0ebec4,
0x3f353f80,0xbf353f80,0xbf353f80,0x3f353f80,0xbf350000,0x3f350000,0x3f350000,0xbf350000,0xbf35bf80,0x3f35bf80,0x3f35bf80,0xbf35bf80,0x3f350000,0xbf350000,0xbf350000,0x3f350000,
0x3f550000,0x3f0e0000,0xbf550000,0xbf0e0000,0x3e483f6d,0x3f7bbf6d,0xbe483f6d,0xbf7bbf6d,0xbf7bbf35,0x3e48bf35,0x3f7bbf35,0xbe48bf35,0x3f0ebec4,0xbf553ec4,0xbf0ebec4,0x3f553ec4,
0xbec4bf80,0x3f6dbf80,0x3ec4bf80,0xbf6dbf80,0x3f6d3f35,0x3ec4bf35,0xbf6d3f35,0xbec4bf35,0xbf6d0000,0xbec40000,0x3f6d0000,0x3ec40000,0x3ec4bf35,0xbf6d3f35,0xbec4bf35,0x3f6d3f35,
0xbf7b0000,0xbe480000,0x3f7b0000,0x3e480000,0x3f55bec4,0xbf0e3ec4,0xbf55bec4,0x3f0e3ec4,0xbf0e3f35,0xbf553f35,0x3f0e3f35,0x3f553f35,0x3e48bf6d,0xbf7b3f6d,0xbe48bf6d,0x3f7b3f6d,
0,0x3f800000,0,0xbf800000,0,0xbf800000,0,0x3f800000,0,0x3f800000,0,0xbf800000,0,0xbf800000,0,0x3f800000,
0x3e480000,0x3f7b0000,0xbe480000,0xbf7b0000,0x3f0e3ec4,0xbf55bec4,0xbf0e3ec4,0x3f55bec4,0x3f553f35,0x3f0e3f35,0xbf553f35,0xbf0e3f35,0x3f7b3f6d,0xbe48bf6d,0xbf7b3f6d,0x3e48bf6d,
0x3ec40000,0x3f6d0000,0xbec40000,0xbf6d0000,0x3f6d3f35,0xbec4bf35,0xbf6d3f35,0x3ec4bf35,0x3f6d3f80,0xbec43f80,0xbf6d3f80,0x3ec43f80,0x3ec43f35,0x3f6dbf35,0xbec43f35,0xbf6dbf35,
0x3f0e0000,0x3f550000,0xbf0e0000,0xbf550000,0x3f7b3f6d,0x3e48bf6d,0xbf7b3f6d,0xbe48bf6d,0x3e483f35,0xbf7b3f35,0xbe483f35,0x3f7b3f35,0xbf55bec4,0x3f0e3ec4,0x3f55bec4,0xbf0e3ec4,
0x3f350000,0x3f350000,0xbf350000,0xbf350000,0x3f353f80,0x3f35bf80,0xbf353f80,0xbf35bf80,0xbf350000,0xbf350000,0x3f350000,0x3f350000,0xbf35bf80,0xbf353f80,0x3f35bf80,0x3f353f80,
0x3f550000,0x3f0e0000,0xbf550000,0xbf0e0000,0x3e483f6d,0x3f7bbf6d,0xbe483f6d,0xbf7bbf6d,0xbf7bbf35,0x3e48bf35,0x3f7bbf35,0xbe48bf35,0x3f0ebec4,0xbf553ec4,0xbf0ebec4,0x3f553ec4,
0x3f6d0000,0x3ec40000,0xbf6d0000,0xbec40000,0xbec43f35,0x3f6dbf35,0x3ec43f35,0xbf6dbf35,0xbec4bf80,0x3f6dbf80,0x3ec4bf80,0xbf6dbf80,0x3f6d3f35,0x3ec4bf35,0xbf6d3f35,0xbec4bf35,
0x3f7b0000,0x3e480000,0xbf7b0000,0xbe480000,0xbf553ec4,0x3f0ebec4,0x3f553ec4,0xbf0ebec4,0x3f0ebf35,0x3f55bf35,0xbf0ebf35,0xbf55bf35,0xbe483f6d,0x3f7bbf6d,0x3e483f6d,0xbf7bbf6d,
0,0x3f800000,0,0xbf800000,0,0xbf800000,0,0x3f800000,0,0x3f800000,0,0xbf800000,0,0xbf800000,0,0x3f800000,
0x3f7b3f80,0xbe483f80,0xbf7b3f80,0x3e483f80,0x3f553f6d,0x3f0ebf6d,0xbf553f6d,0xbf0ebf6d,0x3f0e3f35,0xbf553f35,0xbf0e3f35,0x3f553f35,0x3e483ec4,0x3f7bbec4,0xbe483ec4,0xbf7bbec4,
0xbec40000,0xbf6d0000,0x3ec40000,0x3f6d0000,0xbf6dbf35,0x3ec43f35,0x3f6dbf35,0xbec43f35,0xbf6dbf80,0x3ec4bf80,0x3f6dbf80,0xbec4bf80,0xbec4bf35,0xbf6d3f35,0x3ec4bf35,0x3f6d3f35,
0xbf55bf80,0x3f0ebf80,0x3f55bf80,0xbf0ebf80,0x3e48bec4,0xbf7b3ec4,0xbe48bec4,0x3f7b3ec4,0x3f7b3f35,0x3e483f35,0xbf7b3f35,0xbe483f35,0x3f0e3f6d,0x3f55bf6d,0xbf0e3f6d,0xbf55bf6d,
0x3f350000,0x3f350000,0xbf350000,0xbf350000,0x3f353f80,0x3f35bf80,0xbf353f80,0xbf35bf80,0xbf350000,0xbf350000,0x3f350000,0x3f350000,0xbf35bf80,0xbf353f80,0x3f35bf80,0x3f353f80,
0x3f0e3f80,0xbf553f80,0xbf0e3f80,0x3f553f80,0xbf7bbec4,0x3e483ec4,0x3f7bbec4,0xbe483ec4,0x3e48bf35,0x3f7bbf35,0xbe48bf35,0xbf7bbf35,0x3f553f6d,0x3f0ebf6d,0xbf553f6d,0xbf0ebf6d,
0xbf6d0000,0xbec40000,0x3f6d0000,0x3ec40000,0x3ec4bf35,0xbf6d3f35,0xbec4bf35,0x3f6d3f35,0x3ec43f80,0xbf6d3f80,0xbec43f80,0x3f6d3f80,0xbf6dbf35,0xbec43f35,0x3f6dbf35,0x3ec43f35,
0xbe48bf80,0x3f7bbf80,0x3e48bf80,0xbf7bbf80,0x3f0e3f6d,0x3f55bf6d,0xbf0e3f6d,0xbf55bf6d,0xbf55bf35,0x3f0ebf35,0x3f55bf35,0xbf0ebf35,0x3f7b3ec4,0x3e48bec4,0xbf7b3ec4,0xbe48bec4,
0,0x3f800000,0,0xbf800000,0,0xbf800000,0,0x3f800000,0,0x3f800000,0,0xbf800000,0,0xbf800000,0,0x3f800000,
0xbe480000,0xbf7b0000,0x3e480000,0x3f7b0000,0xbf0ebec4,0x3f553ec4,0x3f0ebec4,0xbf553ec4,0xbf55bf35,0xbf0ebf35,0x3f55bf35,0x3f0ebf35,0xbf7bbf6d,0x3e483f6d,0x3f7bbf6d,0xbe483f6d,
0x3ec40000,0x3f6d0000,0xbec40000,0xbf6d0000,0x3f6d3f35,0xbec4bf35,0xbf6d3f35,0x3ec4bf35,0x3f6d3f80,0xbec43f80,0xbf6d3f80,0x3ec43f80,0x3ec43f35,0x3f6dbf35,0xbec43f35,0xbf6dbf35,
0xbf0e0000,0xbf550000,0x3f0e0000,0x3f550000,0xbf7bbf6d,0xbe483f6d,0x3f7bbf6d,0x3e483f6d,0xbe48bf35,0x3f7bbf35,0x3e48bf35,0xbf7bbf35,0x3f553ec4,0xbf0ebec4,0xbf553ec4,0x3f0ebec4,
0x3f350000,0x3f350000,0xbf350000,0xbf350000,0x3f353f80,0x3f35bf80,0xbf353f80,0xbf35bf80,0xbf350000,0xbf350000,0x3f350000,0x3f350000,0xbf35bf80,0xbf353f80,0x3f35bf80,0x3f353f80,
0xbf550000,0xbf0e0000,0x3f550000,0x3f0e0000,0xbe48bf6d,0xbf7b3f6d,0x3e48bf6d,0x3f7b3f6d,0x3f7b3f35,0xbe483f35,0xbf7b3f35,0x3e483f35,0xbf0e3ec4,0x3f55bec4,0x3f0e3ec4,0xbf55bec4,
0x3f6d0000,0x3ec40000,0xbf6d0000,0xbec40000,0xbec43f35,0x3f6dbf35,0x3ec43f35,0xbf6dbf35,0xbec4bf80,0x3f6dbf80,0x3ec4bf80,0xbf6dbf80,0x3f6d3f35,0x3ec4bf35,0xbf6d3f35,0xbec4bf35,
0xbf7b0000,0xbe480000,0x3f7b0000,0x3e480000,0x3f55bec4,0xbf0e3ec4,0xbf55bec4,0x3f0e3ec4,0xbf0e3f35,0xbf553f35,0x3f0e3f35,0x3f553f35,0x3e48bf6d,0xbf7b3f6d,0xbe48bf6d,0x3f7b3f6d,
0,0x3f800000,0,0xbf800000,0,0xbf800000,0,0x3f800000,0,0x3f800000,0,0xbf800000,0,0xbf800000,0,0x3f800000,
0xbf7bbf80,0x3e48bf80,0x3f7bbf80,0xbe48bf80,0xbf55bf6d,0xbf0e3f6d,0x3f55bf6d,0x3f0e3f6d,0xbf0ebf35,0x3f55bf35,0x3f0ebf35,0xbf55bf35,0xbe48bec4,0xbf7b3ec4,0x3e48bec4,0x3f7b3ec4,
0xbec40000,0xbf6d0000,0x3ec40000,0x3f6d0000,0xbf6dbf35,0x3ec43f35,0x3f6dbf35,0xbec43f35,0xbf6dbf80,0x3ec4bf80,0x3f6dbf80,0xbec4bf80,0xbec4bf35,0xbf6d3f35,0x3ec4bf35,0x3f6d3f35,
0x3f553f80,0xbf0e3f80,0xbf553f80,0x3f0e3f80,0xbe483ec4,0x3f7bbec4,0x3e483ec4,0xbf7bbec4,0xbf7bbf35,0xbe48bf35,0x3f7bbf35,0x3e48bf35,0xbf0ebf6d,0xbf553f6d,0x3f0ebf6d,0x3f553f6d,
0x3f350000,0x3f350000,0xbf350000,0xbf350000,0x3f353f80,0x3f35bf80,0xbf353f80,0xbf35bf80,0xbf350000,0xbf350000,0x3f350000,0x3f350000,0xbf35bf80,0xbf353f80,0x3f35bf80,0x3f353f80,
0xbf0ebf80,0x3f55bf80,0x3f0ebf80,0xbf55bf80,0x3f7b3ec4,0xbe48bec4,0xbf7b3ec4,0x3e48bec4,0xbe483f35,0xbf7b3f35,0x3e483f35,0x3f7b3f35,0xbf55bf6d,0xbf0e3f6d,0x3f55bf6d,0x3f0e3f6d,
0xbf6d0000,0xbec40000,0x3f6d0000,0x3ec40000,0x3ec4bf35,0xbf6d3f35,0xbec4bf35,0x3f6d3f35,0x3ec43f80,0xbf6d3f80,0xbec43f80,0x3f6d3f80,0xbf6dbf35,0xbec43f35,0x3f6dbf35,0x3ec43f35,
0x3e483f80,0xbf7b3f80,0xbe483f80,0x3f7b3f80,0xbf0ebf6d,0xbf553f6d,0x3f0ebf6d,0x3f553f6d,0x3f553f35,0xbf0e3f35,0xbf553f35,0x3f0e3f35,0xbf7bbec4,0xbe483ec4,0x3f7bbec4,0x3e483ec4,
0x3f800000,0x3f800000,0x3f800000,0x3f7ec46d,0x3f800000,0x3f800000,0x3f7b14be,0x3f74fa0b,0x3f800000,0x3f800000,0x3f6c835e,0x3f61c598,0x3f800000,0x3f800000,0x3f54db31,0x3f45e403,
0x3f800000,0x3f7ffb11,0x3f800000,0x3f7e70b0,0x3f7fec43,0x3f7fd397,0x3f79c79d,0x3f721352,0x3f7fb10f,0x3f7f84ab,0x3f676bd8,0x3f59f26a,0x3f7f4e6d,0x3f7f0e58,0x3f49d112,0x3f373a23,
0x3f800000,0x3f7fec43,0x3f800000,0x3f7e1324,0x3f7fb10f,0x3f7f4e6d,0x3f7853f8,0x3f6ed89e,0x3f7ec46d,0x3f7e1324,0x3f61c598,0x3f514d3d,0x3f7d3aac,0x3f7c3b28,0x3f3daef9,0x3f273656,
0x3f800000,0x3f7fd397,0x3f800000,0x3f7dabcc,0x3f7f4e6d,0x3f7e70b0,0x3f76ba07,0x3f6b4b0c,0x3f7d3aac,0x3f7baccd,0x3f5b941a,0x3f47de65,0x3f79c79d,0x3f778bc5,0x3f3085bb,0x3f15f6d9,
0x3f800000,0x3f7fb10f,0x3f800000,0x3f7d3aac,0x3f7ec46d,0x3f7d3aac,0x3f74fa0b,0x3f676bd8,0x3f7b14be,0x3f7853f8,0x3f54db31,0x3f3daef9,0x3f74fa0b,0x3f710908,0x3f226799,0x3f039c3d,
0x3f800000,0x3f7f84ab,0x3f800000,0x3f7cbfc9,0x3f7e1324,0x3f7baccd,0x3f731447,0x3f633c5a,0x3f7853f8,0x3f740bdd,0x3f4d9f02,0x3f32c8c9,0x3f6ed89e,0x3f68bf3c,0x3f13682a,0x3ee0924f,
0x3f800000,0x3f7f4e6d,0x3f800000,0x3f7c3b28,0x3f7d3aac,0x3f79c79d,0x3f710908,0x3f5ebe05,0x3f74fa0b,0x3f6ed89e,0x3f45e403,0x3f273656,0x3f676bd8,0x3f5ebe05,0x3f039c3d,0x3eb8442a,
0x3f800000,0x3f7f0e58,0x3f800000,0x3f7baccd,0x3f7c3b28,0x3f778bc5,0x3f6ed89e,0x3f59f26a,0x3f710908,0x3f68bf3c,0x3f3daef9,0x3f1b02c6,0x3f5ebe05,0x3f531849,0x3ee63375,0x3e8e9a22,
0x3f800000,0x3f800000,0x3f3504f3,0x3f226799,0x3f800000,0x3f800000,0x3f0e39da,0x3ef15aea,0x3f800000,0x3f800000,0x3ec3ef15,0x3e94a031,0x3f800000,0x3f800000,0x3e47c5c2,0x3dc8bd36,
0x3f7ec46d,0x3f7e70b0,0x3f226799,0x3f0b9a6b,0x3f7e1324,0x3f7dabcc,0x3ee63375,0x3eb263ef,0x3f7d3aac,0x3f7cbfc9,0x3e78cfcc,0x3e09cf86,0x3f7c3b28,0x3f7baccd,0x3cc90ab0,0xbdafb680,
0x3f7b14be,0x3f79c79d,0x3f0e39da,0x3ee63375,0x3f7853f8,0x3f76ba07,0x3eac7cd4,0x3e605c13,0x3f74fa0b,0x3f731447,0x3dc8bd36,0xbcc90ab0,0x3f710908,0x3f6ed89e,0xbe164083,0xbe888e93,
0x3f74fa0b,0x3f721352,0x3ef15aea,0x3eb263ef,0x3f6ed89e,0x3f6b4b0c,0x3e605c13,0x3dafb680,0x3f676bd8,0x3f633c5a,0xbd48fb30,0xbe3b6ecf,0x3f5ebe05,0x3f59f26a,0xbea09ae5,0xbee0924f,
0x3f6c835e,0x3f676bd8,0x3ec3ef15,0x3e78cfcc,0x3f61c598,0x3f5b941a,0x3dc8bd36,0xbd48fb30,0x3f54db31,0x3f4d9f02,0xbe47c5c2,0xbeac7cd4,0x3f45e403,0x3f3daef9,0xbef15aea,0xbf187fc0,
0x3f61c598,0x3f59f26a,0x3e94a031,0x3e09cf86,0x3f514d3d,0x3f47de65,0xbcc90ab0,0xbe3b6ecf,0x3f3daef9,0x3f32c8c9,0xbeac7cd4,0xbef6e0cb,0x3f273656,0x3f1b02c6,0xbf1d7fd1,0xbf3b8f3b,
0x3f54db31,0x3f49d112,0x3e47c5c2,0x3cc90ab0,0x3f3daef9,0x3f3085bb,0xbe164083,0xbea09ae5,0x3f226799,0x3f13682a,0xbef15aea,0xbf1d7fd1,0x3f039c3d,0x3ee63375,0xbf3daef9,0xbf584853,
0x3f45e403,0x3f373a23,0x3dc8bd36,0xbdafb680,0x3f273656,0x3f15f6d9,0xbe888e93,0xbee0924f,0x3f039c3d,0x3ee0924f,0xbf187fc0,0xbf3b8f3b,0x3eb8442a,0x3e8e9a22,0xbf584853,0xbf6db293,
0x3f800000,0x3f800000,0,0xbdc8bd36,0x3f800000,0x3f800000,0xbe47c5c2,0xbe94a031,0x3f800000,0x3f800000,0xbec3ef15,0xbef15aea,0x3f800000,0x3f800000,0xbf0e39da,0xbf226799,
0x3f7b14be,0x3f7a7302,0xbe47c5c2,0xbe9aa086,0x3f79c79d,0x3f791298,0xbecf7bca,0xbf00e7e4,0x3f7853f8,0x3f778bc5,0xbf187fc0,0xbf2e3bde,0x3f76ba07,0x3f75dec6,0xbf41d870,0xbf531849,
0x3f6c835e,0x3f6a09a7,0xbec3ef15,0xbefc5d27,0x3f676bd8,0x3f64aa59,0xbf187fc0,0xbf3085bb,0x3f61c598,0x3f5ebe05,0xbf45e403,0xbf584853,0x3f5b941a,0x3f584853,0xbf676bd8,0xbf731447,
0x3f54db31,0x3f4f7a1f,0xbf0e39da,0xbf299415,0x3f49d112,0x3f43e200,0xbf41d870,0xbf5695e5,0x3f3daef9,0x3f373a23,0xbf676bd8,0xbf740bdd,0x3f3085bb,0x3f299415,0xbf7c3b28,0xbf7fd397,
0x3f3504f3,0x3f2beb4a,0xbf3504f3,0xbf4d9f02,0x3f226799,0x3f187fc0,0xbf61c598,0xbf710908,0x3f0e39da,0x3f039c3d,0xbf7b14be,0xbf7fb10f,0x3ef15aea,0x3edae880,0xbf7ec46d,0xbf7853f8,
0x3f0e39da,0x3f00e7e4,0xbf54db31,0xbf68bf3c,0x3ee63375,0x3ec9b953,0xbf76ba07,0xbf7e70b0,0x3eac7cd4,0x3e8e9a22,0xbf7fb10f,0xbf7a7302,0x3e605c13,0x3e22abb6,0xbf6ed89e,0xbf5d2d53,
0x3ec3ef15,0x3ea09ae5,0xbf6c835e,0xbf79c79d,0x3e78cfcc,0x3e2f10a2,0xbf7fb10f,0xbf7e1324,0x3dc8bd36,0x3cc90ab0,0xbf74fa0b,0xbf64aa59,0xbd48fb30,0xbdfab273,0xbf4d9f02,0xbf3085bb,
0x3e47c5c2,0x3de1bc2e,0xbf7b14be,0xbf7ffb11,0x3cc90ab0,0xbd7b2b74,0xbf7c3b28,0xbf6ff573,0xbe164083,0xbe6c9a7f,0xbf5b941a,0xbf3fc767,0xbea09ae5,0xbec9b953,0xbf1d7fd1,0xbeebcbbb,
0x3f800000,0x3f800000,0xbf3504f3,0xbf45e403,0x3f800000,0x3f800000,0xbf54db31,0xbf61c598,0x3f800000,0x3f800000,0xbf6c835e,0xbf74fa0b,0x3f800000,0x3f800000,0xbf7b14be,0xbf7ec46d,
0x3f74fa0b,0x3f740bdd,0xbf61c598,0xbf6db293,0x3f731447,0x3f721352,0xbf76ba07,0xbf7cbfc9,0x3f710908,0x3f6ff573,0xbf7fb10f,0xbf7f84ab,0x3f6ed89e,0x3f6db293,0xbf7c3b28,0xbf75dec6,
0x3f54db31,0x3f514d3d,0xbf7b14be,0xbf7f4e6d,0x3f4d9f02,0x3f49d112,0xbf7fb10f,0xbf7c3b28,0x3f45e403,0x3f41d870,0xbf74fa0b,0xbf6a09a7,0x3f3daef9,0x3f396842,0xbf5b941a,0xbf49d112,
0x3f226799,0x3f1b02c6,0xbf7ec46d,0xbf791298,0x3f13682a,0x3f0b9a6b,0xbf6ed89e,0xbf604621,0x3f039c3d,0x3ef6e0cb,0xbf4d9f02,0xbf373a23,0x3ee63375,0x3ed53641,0xbf1d7fd1,0xbf00e7e4,
0x3ec3ef15,0x3eac7cd4,0xbf6c835e,0xbf5b941a,0x3e94a031,0x3e78cfcc,0xbf45e403,0xbf2beb4a,0x3e47c5c2,0x3e164083,0xbf0e39da,0xbedae880,0x3dc8bd36,0x3d48fb30,0xbe94a031,0xbe164083,
0x3dc8bd36,0x3d16c32c,0xbf45e403,0xbf299415,0xbcc90ab0,0xbdafb680,0xbf08f59b,0xbec9b953,0xbe164083,0xbe541501,0xbe78cfcc,0xbdafb680,0xbe888e93,0xbea68f12,0x3d96a905,0x3e6c9a7f,
0xbe47c5c2,0xbe888e93,0xbf0e39da,0xbecf7bca,0xbeac7cd4,0xbecf7bca,0xbe78cfcc,0xbd96a905,0xbef15aea,0xbf08f59b,0x3dc8bd36,0x3e888e93,0xbf187fc0,0xbf273656,0x3edae880,0x3f13682a,
0xbef15aea,0xbf0b9a6b,0xbe94a031,0xbde1bc2e,0xbf1d7fd1,0xbf2e3bde,0x3d96a905,0x3e827dc0,0xbf3daef9,0xbf4bbbf8,0x3edae880,0x3f15f6d9,0xbf584853,0xbf633c5a,0x3f396842,0x3f5695e5,
0,0,0,0x3dc8bd36,0,0,0x3e47c5c2,0x3e94a031,0,0,0x3ec3ef15,0x3ef15aea,0,0,0x3f0e39da,0x3f226799,
0,0x3c490e90,0,0x3de1bc2e,0x3cc90ab0,0x3d16c32c,0x3e605c13,0x3ea68f12,0x3d48fb30,0x3d7b2b74,0x3edae880,0x3f064b82,0x3d96a905,0x3dafb680,0x3f1d7fd1,0x3f32c8c9,
0,0x3cc90ab0,0,0x3dfab273,0x3d48fb30,0x3d96a905,0x3e78cfcc,0x3eb8442a,0x3dc8bd36,0x3dfab273,0x3ef15aea,0x3f13682a,0x3e164083,0x3e2f10a2,0x3f2beb4a,0x3f41d870,
0,0x3d16c32c,0,0x3e09cf86,0x3d96a905,0x3de1bc2e,0x3e888e93,0x3ec9b953,0x3e164083,0x3e3b6ecf,0x3f039c3d,0x3f1ff6cb,0x3e605c13,0x3e827dc0,0x3f396842,0x3f4f7a1f,
0,0x3d48fb30,0,0x3e164083,0x3dc8bd36,0x3e164083,0x3e94a031,0x3edae880,0x3e47c5c2,0x3e78cfcc,0x3f0e39da,0x3f2beb4a,0x3e94a031,0x3eac7cd4,0x3f45e403,0x3f5b941a,
0,0x3d7b2b74,0,0x3e22abb6,0x3dfab273,0x3e3b6ecf,0x3ea09ae5,0x3eebcbbb,0x3e78cfcc,0x3e9aa086,0x3f187fc0,0x3f373a23,0x3eb8442a,0x3ed53641,0x3f514d3d,0x3f660f88,
0,0x3d96a905,0,0x3e2f10a2,0x3e164083,0x3e605c13,0x3eac7cd4,0x3efc5d27,0x3e94a031,0x3eb8442a,0x3f226799,0x3f41d870,0x3edae880,0x3efc5d27,0x3f5b941a,0x3f6ed89e,
0,0x3dafb680,0,0x3e3b6ecf,0x3e2f10a2,0x3e827dc0,0x3eb8442a,0x3f064b82,0x3eac7cd4,0x3ed53641,0x3f2beb4a,0x3f4bbbf8,0x3efc5d27,0x3f10d3cd,0x3f64aa59,0x3f75dec6,
0,0,0x3f3504f3,0x3f45e403,0,0,0x3f54db31,0x3f61c598,0,0,0x3f6c835e,0x3f74fa0b,0,0,0x3f7b14be,0x3f7ec46d,
0x3dc8bd36,0x3de1bc2e,0x3f45e403,0x3f5695e5,0x3dfab273,0x3e09cf86,0x3f64aa59,0x3f6ff573,0x3e164083,0x3e22abb6,0x3f7853f8,0x3f7dabcc,0x3e2f10a2,0x3e3b6ecf,0x3f7fec43,0x3f7f0e58,
0x3e47c5c2,0x3e605c13,0x3f54db31,0x3f64aa59,0x3e78cfcc,0x3e888e93,0x3f710908,0x3f79c79d,0x3e94a031,0x3ea09ae5,0x3f7ec46d,0x3f7fec43,0x3eac7cd4,0x3eb8442a,0x3f7d3aac,0x3f76ba07,
0x3e94a031,0x3ea68f12,0x3f61c598,0x3f6ff573,0x3eb8442a,0x3ec9b953,0x3f79c79d,0x3f7f0e58,0x3edae880,0x3eebcbbb,0x3f7fb10f,0x3f7baccd,0x3efc5d27,0x3f064b82,0x3f731447,0x3f660f88,
0x3ec3ef15,0x3edae880,0x3f6c835e,0x3f7853f8,0x3ef15aea,0x3f039c3d,0x3f7ec46d,0x3f7fb10f,0x3f0e39da,0x3f187fc0,0x3f7b14be,0x3f710908,0x3f226799,0x3f2beb4a,0x3f61c598,0x3f4d9f02,
0x3ef15aea,0x3f064b82,0x3f74fa0b,0x3f7dabcc,0x3f13682a,0x3f1ff6cb,0x3f7fec43,0x3f7baccd,0x3f2beb4a,0x3f373a23,0x3f710908,0x3f604621,0x3f41d870,0x3f4bbbf8,0x3f49d112,0x3f2e3bde,
0x3f0e39da,0x3f1d7fd1,0x3f7b14be,0x3f7fec43,0x3f2beb4a,0x3f396842,0x3f7d3aac,0x3f731447,0x3f45e403,0x3f514d3d,0x3f61c598,0x3f49d112,0x3f5b941a,0x3f64aa59,0x3f2beb4a,0x3f08f59b,
0x3f226799,0x3f32c8c9,0x3f7ec46d,0x3f7f0e58,0x3f41d870,0x3f4f7a1f,0x3f76ba07,0x3f660f88,0x3f5b941a,0x3f660f88,0x3f4d9f02,0x3f2e3bde,0x3f6ed89e,0x3f75dec6,0x3f08f59b,0x3ebe1d4a,
0,0,0x3f800000,0x3f7ec46d,0,0,0x3f7b14be,0x3f74fa0b,0,0,0x3f6c835e,0x3f61c598,0,0,0x3f54db31,0x3f45e403,
0x3e47c5c2,0x3e541501,0x3f7b14be,0x3f740bdd,0x3e605c13,0x3e6c9a7f,0x3f6a09a7,0x3f5d2d53,0x3e78cfcc,0x3e827dc0,0x3f4d9f02,0x3f3b8f3b,0x3e888e93,0x3e8e9a22,0x3f273656,0x3f10d3cd,
0x3ec3ef15,0x3ecf7bca,0x3f6c835e,0x3f5ebe05,0x3edae880,0x3ee63375,0x3f4d9f02,0x3f396842,0x3ef15aea,0x3efc5d27,0x3f226799,0x3f08f59b,0x3f039c3d,0x3f08f59b,0x3edae880,0x3ea09ae5,
0x3f0e39da,0x3f15f6d9,0x3f54db31,0x3f3fc767,0x3f1d7fd1,0x3f24d225,0x3f273656,0x3f0b9a6b,0x3f2beb4a,0x3f32c8c9,0x3edae880,0x3e9aa086,0x3f396842,0x3f3fc767,0x3e2f10a2,0x3d16c32c,
0x3f3504f3,0x3f3daef9,0x3f3504f3,0x3f187fc0,0x3f45e403,0x3f4d9f02,0x3ef15aea,0x3eac7cd4,0x3f54db31,0x3f5b941a,0x3e47c5c2,0x3d48fb30,0x3f61c598,0x3f676bd8,0xbdc8bd36,0xbe78cfcc,
0x3f54db31,0x3f5d2d53,0x3f0e39da,0x3ed53641,0x3f64aa59,0x3f6b4b0c,0x3e888e93,0x3de1bc2e,0x3f710908,0x3f75dec6,0xbd48fb30,0xbe541501,0x3f79c79d,0x3f7cbfc9,0xbeb8442a,0xbf00e7e4,
0x3f6c835e,0x3f731447,0x3ec3ef15,0x3e605c13,0x3f7853f8,0x3f7c3b28,0x3d48fb30,0xbdfab273,0x3f7ec46d,0x3f7fec43,0xbe94a031,0xbee63375,0x3f7fb10f,0x3f7e1324,0xbf187fc0,0xbf396842,
0x3f7b14be,0x3f7e70b0,0x3e47c5c2,0x3c490e90,0x3f7fec43,0x3f7f84ab,0xbe2f10a2,0xbeb263ef,0x3f7d3aac,0x3f791298,0xbf039c3d,0xbf299415,0x3f731447,0x3f6b4b0c,0xbf49d112,0xbf633c5a,
0,0,0x3f3504f3,0x3f226799,0,0,0x3f0e39da,0x3ef15aea,0,0,0x3ec3ef15,0x3e94a031,0,0,0x3e47c5c2,0x3dc8bd36,
0x3e94a031,0x3e9aa086,0x3ef15aea,0x3ebe1d4a,0x3ea09ae5,0x3ea68f12,0x3e888e93,0x3e22abb6,0x3eac7cd4,0x3eb263ef,0x3d48fb30,0xbd7b2b74,0x3eb8442a,0x3ebe1d4a,0xbe2f10a2,0xbe8e9a22,
0x3f0e39da,0x3f13682a,0x3e47c5c2,0x3d96a905,0x3f187fc0,0x3f1d7fd1,0xbd48fb30,0xbe2f10a2,0x3f226799,0x3f273656,0xbe94a031,0xbecf7bca,0x3f2beb4a,0x3f3085bb,0xbf039c3d,0xbf1d7fd1,
0x3f45e403,0x3f4bbbf8,0xbdc8bd36,0xbe6c9a7f,0x3f514d3d,0x3f5695e5,0xbeb8442a,0xbef6e0cb,0x3f5b941a,0x3f604621,0xbf187fc0,0xbf32c8c9,0x3f64aa59,0x3f68bf3c,0xbf49d112,0xbf5d2d53,
0x3f6c835e,0x3f710908,0xbec3ef15,0xbf039c3d,0x3f74fa0b,0x3f7853f8,0xbf226799,0xbf3daef9,0x3f7b14be,0x3f7d3aac,0xbf54db31,0xbf676bd8,0x3f7ec46d,0x3f7fb10f,0xbf74fa0b,0xbf7d3aac,
0x3f7ec46d,0x3f7fd397,0xbf226799,0xbf3fc767,0x3f7fec43,0x3f7f0e58,0xbf584853,0xbf6b4b0c,0x3f7d3aac,0x3f7a7302,0xbf7853f8,0xbf7f0e58,0x3f76ba07,0x3f721352,0xbf7f4e6d,0xbf791298,
0x3f7b14be,0x3f76ba07,0xbf54db31,0xbf6a09a7,0x3f710908,0x3f6a09a7,0xbf7853f8,0xbf7f4e6d,0x3f61c598,0x3f584853,0xbf7ec46d,0xbf76ba07,0x3f4d9f02,0x3f41d870,0xbf676bd8,0xbf514d3d,
0x3f61c598,0x3f5695e5,0xbf74fa0b,0xbf7e70b0,0x3f49d112,0x3f3b8f3b,0xbf7f4e6d,0xbf778bc5,0x3f2beb4a,0x3f1b02c6,0xbf676bd8,0xbf4f7a1f,0x3f08f59b,0x3eebcbbb,0xbf3085bb,0xbf0b9a6b,
0x3f800000,0x3f7fffb1,0x3f7ffec4,0x3f7ffd39,0x3f7ffb11,0x3f7ff84a,0x3f7ff4e6,0x3f7ff0e3,0x3f7fec43,0x3f7fe705,0x3f7fe129,0x3f7fdaaf,0x3f7fd397,0x3f7fcbe2,0x3f7fc38f,0x3f7fba9e,
0x3f7fb10f,0x3f7fa6e3,0x3f7f9c18,0x3f7f90b1,0x3f7f84ab,0x3f7f7808,0x3f7f6ac7,0x3f7f5ce9,0x3f7f4e6d,0x3f7f3f54,0x3f7f2f9d,0x3f7f1f49,0x3f7f0e58,0x3f7efcc9,0x3f7eea9d,0x3f7ed7d4,
0x3f7ec46d,0x3f7eb069,0x3f7e9bc9,0x3f7e868b,0x3f7e70b0,0x3f7e5a38,0x3f7e4323,0x3f7e2b72,0x3f7e1324,0x3f7dfa38,0x3f7de0b1,0x3f7dc68c,0x3f7dabcc,0x3f7d906e,0x3f7d7474,0x3f7d57de,
0x3f7d3aac,0x3f7d1cdd,0x3f7cfe73,0x3f7cdf6c,0x3f7cbfc9,0x3f7c9f8a,0x3f7c7eb0,0x3f7c5d3a,0x3f7c3b28,0x3f7c187a,0x3f7bf531,0x3f7bd14d,0x3f7baccd,0x3f7b87b2,0x3f7b61fc,0x3f7b3bab,
0x3f7b14be,0x3f7aed37,0x3f7ac516,0x3f7a9c59,0x3f7a7302,0x3f7a4910,0x3f7a1e84,0x3f79f35e,0x3f79c79d,0x3f799b43,0x3f796e4e,0x3f7940c0,0x3f791298,0x3f78e3d6,0x3f78b47b,0x3f788486,
0x3f7853f8,0x3f7822d1,0x3f77f110,0x3f77beb7,0x3f778bc5,0x3f77583a,0x3f772417,0x3f76ef5b,0x3f76ba07,0x3f76841b,0x3f764d97,0x3f76167a,0x3f75dec6,0x3f75a67b,0x3f756d97,0x3f75341d,
0x3f74fa0b,0x3f74bf62,0x3f748422,0x3f74484b,0x3f740bdd,0x3f73ced9,0x3f73913f,0x3f73530e,0x3f731447,0x3f72d4eb,0x3f7294f8,0x3f725470,0x3f721352,0x3f71d19f,0x3f718f57,0x3f714c7a,
0x3f710908,0x3f70c501,0x3f708066,0x3f703b37,0x3f6ff573,0x3f6faf1b,0x3f6f6830,0x3f6f20b0,0x3f6ed89e,0x3f6e8ff8,0x3f6e46be,0x3f6dfcf2,0x3f6db293,0x3f6d67a1,0x3f6d1c1d,0x3f6cd007,
0x3f6c835e,0x3f6c3624,0x3f6be858,0x3f6b99fb,0x3f6b4b0c,0x3f6afb8c,0x3f6aab7b,0x3f6a5ad9,0x3f6a09a7,0x3f69b7e4,0x3f696591,0x3f6912ae,0x3f68bf3c,0x3f686b39,0x3f6816a8,0x3f67c187,
0x3f676bd8,0x3f671599,0x3f66becc,0x3f666771,0x3f660f88,0x3f65b710,0x3f655e0b,0x3f650479,0x3f64aa59,0x3f644fac,0x3f63f473,0x3f6398ac,0x3f633c5a,0x3f62df7b,0x3f628210,0x3f62241a,
0x3f61c598,0x3f61668a,0x3f6106f2,0x3f60a6cf,0x3f604621,0x3f5fe4e9,0x3f5f8327,0x3f5f20db,0x3f5ebe05,0x3f5e5aa6,0x3f5df6be,0x3f5d924d,0x3f5d2d53,0x3f5cc7d1,0x3f5c61c7,0x3f5bfb34,
0x3f5b941a,0x3f5b2c79,0x3f5ac450,0x3f5a5ba0,0x3f59f26a,0x3f5988ad,0x3f591e6a,0x3f58b3a1,0x3f584853,0x3f57dc7f,0x3f577026,0x3f570348,0x3f5695e5,0x3f5627fe,0x3f55b993,0x3f554aa4,
0x3f54db31,0x3f546b3b,0x3f53fac3,0x3f5389c7,0x3f531849,0x3f52a649,0x3f5233c6,0x3f51c0c2,0x3f514d3d,0x3f50d937,0x3f5064af,0x3f4fefa8,0x3f4f7a1f,0x3f4f0417,0x3f4e8d90,0x3f4e1689,
0x3f4d9f02,0x3f4d26fd,0x3f4cae79,0x3f4c3578,0x3f4bbbf8,0x3f4b41fa,0x3f4ac77f,0x3f4a4c87,0x3f49d112,0x3f495521,0x3f48d8b3,0x3f485bca,0x3f47de65,0x3f476085,0x3f46e22a,0x3f466354,
0x3f45e403,0x3f456439,0x3f44e3f5,0x3f446337,0x3f43e200,0x3f436051,0x3f42de29,0x3f425b89,0x3f41d870,0x3f4154e1,0x3f40d0da,0x3f404c5c,0x3f3fc767,0x3f3f41fc,0x3f3ebc1b,0x3f3e35c5,
0x3f3daef9,0x3f3d27b8,0x3f3ca003,0x3f3c17d9,0x3f3b8f3b,0x3f3b0629,0x3f3a7ca4,0x3f39f2ac,0x3f396842,0x3f38dd65,0x3f385216,0x3f37c655,0x3f373a23,0x3f36ad7f,0x3f36206c,0x3f3592e7,
0x3f3504f3,0x3f34768f,0x3f33e7bc,0x3f33587a,0x3f32c8c9,0x3f3238aa,0x3f31a81d,0x3f311722,0x3f3085bb,0x3f2ff3e6,0x3f2f61a5,0x3f2ecef7,0x3f2e3bde,0x3f2da859,0x3f2d1469,0x3f2c800f,
0x3f2beb4a,0x3f2b561b,0x3f2ac082,0x3f2a2a80,0x3f299415,0x3f28fd41,0x3f286605,0x3f27ce61,0x3f273656,0x3f269de3,0x3f26050a,0x3f256bcb,0x3f24d225,0x3f24381a,0x3f239da9,0x3f2302d3,
0x3f226799,0x3f21cbfb,0x3f212ff9,0x3f209393,0x3f1ff6cb,0x3f1f599f,0x3f1ebc12,0x3f1e1e22,0x3f1d7fd1,0x3f1ce11f,0x3f1c420c,0x3f1ba299,0x3f1b02c6,0x3f1a6293,0x3f19c200,0x3f19210f,
0x3f187fc0,0x3f17de12,0x3f173c07,0x3f16999f,0x3f15f6d9,0x3f1553b7,0x3f14b039,0x3f140c5f,0x3f13682a,0x3f12c39a,0x3f121eb0,0x3f11796b,0x3f10d3cd,0x3f102dd5,0x3f0f8784,0x3f0ee0db,
0x3f0e39da,0x3f0d9281,0x3f0cead0,0x3f0c42c9,0x3f0b9a6b,0x3f0af1b7,0x3f0a48ad,0x3f099f4e,0x3f08f59b,0x3f084b92,0x3f07a136,0x3f06f686,0x3f064b82,0x3f05a02c,0x3f04f484,0x3f044889,
0x3f039c3d,0x3f02ef9f,0x3f0242b1,0x3f019573,0x3f00e7e4,0x3f003a06,0x3eff17b2,0x3efdbabb,0x3efc5d27,0x3efafef7,0x3ef9a02d,0x3ef840c8,0x3ef6e0cb,0x3ef58035,0x3ef41f07,0x3ef2bd43,
0x3ef15aea,0x3eeff7fb,0x3eee9479,0x3eed3063,0x3eebcbbb,0x3eea6681,0x3ee900b7,0x3ee79a5d,0x3ee63375,0x3ee4cbfe,0x3ee363fa,0x3ee1fb6a,0x3ee0924f,0x3edf28a9,0x3eddbe79,0x3edc53c1,
0x3edae880,0x3ed97cb9,0x3ed8106b,0x3ed6a399,0x3ed53641,0x3ed3c867,0x3ed25a09,0x3ed0eb2a,0x3ecf7bca,0x3ece0bea,0x3ecc9b8b,0x3ecb2aae,0x3ec9b953,0x3ec8477c,0x3ec6d529,0x3ec5625c,
0x3ec3ef15,0x3ec27b55,0x3ec1071e,0x3ebf926f,0x3ebe1d4a,0x3ebca7af,0x3ebb31a0,0x3eb9bb1e,0x3eb8442a,0x3eb6ccc3,0x3eb554ec,0x3eb3dca5,0x3eb263ef,0x3eb0eacb,0x3eaf713a,0x3eadf73c,
0x3eac7cd4,0x3eab0201,0x3ea986c4,0x3ea80b1f,0x3ea68f12,0x3ea5129f,0x3ea395c5,0x3ea21887,0x3ea09ae5,0x3e9f1cdf,0x3e9d9e78,0x3e9c1faf,0x3e9aa086,0x3e9920fe,0x3e97a117,0x3e9620d2,
0x3e94a031,0x3e931f35,0x3e919ddd,0x3e901c2c,0x3e8e9a22,0x3e8d17c0,0x3e8b9507,0x3e8a11f7,0x3e888e93,0x3e870ada,0x3e8586ce,0x3e840270,0x3e827dc0,0x3e80f8c0,0x3e7ee6e1,0x3e7bdba4,
0x3e78cfcc,0x3e75c35a,0x3e72b651,0x3e6fa8b2,0x3e6c9a7f,0x3e698bba,0x3e667c66,0x3e636c83,0x3e605c13,0x3e5d4b1a,0x3e5a3997,0x3e57278f,0x3e541501,0x3e5101f1,0x3e4dee60,0x3e4ada4f,
0x3e47c5c2,0x3e44b0b9,0x3e419b37,0x3e3e853e,0x3e3b6ecf,0x3e3857ec,0x3e354098,0x3e3228d4,0x3e2f10a2,0x3e2bf804,0x3e28defc,0x3e25c58c,0x3e22abb6,0x3e1f917b,0x3e1c76de,0x3e195be0,
0x3e164083,0x3e1324ca,0x3e1008b7,0x3e0cec4a,0x3e09cf86,0x3e06b26e,0x3e039502,0x3e007745,0x3dfab273,0x3df475c0,0x3dee3876,0x3de7fa9a,0x3de1bc2e,0x3ddb7d37,0x3dd53db9,0x3dcefdb7,
0x3dc8bd36,0x3dc27c39,0x3dbc3ac3,0x3db5f8da,0x3dafb680,0x3da973ba,0x3da3308c,0x3d9cecf9,0x3d96a905,0x3d9064b4,0x3d8a200a,0x3d83db0a,0x3d7b2b74,0x3d6ea038,0x3d621469,0x3d55880e,
0x3d48fb30,0x3d3c6dd5,0x3d2fe007,0x3d2351cb,0x3d16c32c,0x3d0a342f,0x3cfb49ba,0x3ce22a7a,0x3cc90ab0,0x3cafea69,0x3c96c9b6,0x3c7b514b,0x3c490e90,0x3c16cb58,0x3bc90f88,0x3b490fc6,
0,0x3b490fc6,0x3bc90f88,0x3c16cb58,0x3c490e90,0x3c7b514b,0x3c96c9b6,0x3cafea69,0x3cc90ab0,0x3ce22a7a,0x3cfb49ba,0x3d0a342f,0x3d16c32c,0x3d2351cb,0x3d2fe007,0x3d3c6dd5,
0x3d48fb30,0x3d55880e,0x3d621469,0x3d6ea038,0x3d7b2b74,0x3d83db0a,0x3d8a200a,0x3d9064b4,0x3d96a905,0x3d9cecf9,0x3da3308c,0x3da973ba,0x3dafb680,0x3db5f8da,0x3dbc3ac3,0x3dc27c39,
0x3dc8bd36,0x3dcefdb7,0x3dd53db9,0x3ddb7d37,0x3de1bc2e,0x3de7fa9a,0x3dee3876,0x3df475c0,0x3dfab273,0x3e007745,0x3e039502,0x3e06b26e,0x3e09cf86,0x3e0cec4a,0x3e1008b7,0x3e1324ca,
0x3e164083,0x3e195be0,0x3e1c76de,0x3e1f917b,0x3e22abb6,0x3e25c58c,0x3e28defc,0x3e2bf804,0x3e2f10a2,0x3e3228d4,0x3e354098,0x3e3857ec,0x3e3b6ecf,0x3e3e853e,0x3e419b37,0x3e44b0b9,
0x3e47c5c2,0x3e4ada4f,0x3e4dee60,0x3e5101f1,0x3e541501,0x3e57278f,0x3e5a3997,0x3e5d4b1a,0x3e605c13,0x3e636c83,0x3e667c66,0x3e698bba,0x3e6c9a7f,0x3e6fa8b2,0x3e72b651,0x3e75c35a,
0x3e78cfcc,0x3e7bdba4,0x3e7ee6e1,0x3e80f8c0,0x3e827dc0,0x3e840270,0x3e8586ce,0x3e870ada,0x3e888e93,0x3e8a11f7,0x3e8b9507,0x3e8d17c0,0x3e8e9a22,0x3e901c2c,0x3e919ddd,0x3e931f35,
0x3e94a031,0x3e9620d2,0x3e97a117,0x3e9920fe,0x3e9aa086,0x3e9c1faf,0x3e9d9e78,0x3e9f1cdf,0x3ea09ae5,0x3ea21887,0x3ea395c5,0x3ea5129f,0x3ea68f12,0x3ea80b1f,0x3ea986c4,0x3eab0201,
0x3eac7cd4,0x3eadf73c,0x3eaf713a,0x3eb0eacb,0x3eb263ef,0x3eb3dca5,0x3eb554ec,0x3eb6ccc3,0x3eb8442a,0x3eb9bb1e,0x3ebb31a0,0x3ebca7af,0x3ebe1d4a,0x3ebf926f,0x3ec1071e,0x3ec27b55,
0x3ec3ef15,0x3ec5625c,0x3ec6d529,0x3ec8477c,0x3ec9b953,0x3ecb2aae,0x3ecc9b8b,0x3ece0bea,0x3ecf7bca,0x3ed0eb2a,0x3ed25a09,0x3ed3c867,0x3ed53641,0x3ed6a399,0x3ed8106b,0x3ed97cb9,
0x3edae880,0x3edc53c1,0x3eddbe79,0x3edf28a9,0x3ee0924f,0x3ee1fb6a,0x3ee363fa,0x3ee4cbfe,0x3ee63375,0x3ee79a5d,0x3ee900b7,0x3eea6681,0x3eebcbbb,0x3eed3063,0x3eee9479,0x3eeff7fb,
0x3ef15aea,0x3ef2bd43,0x3ef41f07,0x3ef58035,0x3ef6e0cb,0x3ef840c8,0x3ef9a02d,0x3efafef7,0x3efc5d27,0x3efdbabb,0x3eff17b2,0x3f003a06,0x3f00e7e4,0x3f019573,0x3f0242b1,0x3f02ef9f,
0x3f039c3d,0x3f044889,0x3f04f484,0x3f05a02c,0x3f064b82,0x3f06f686,0x3f07a136,0x3f084b92,0x3f08f59b,0x3f099f4e,0x3f0a48ad,0x3f0af1b7,0x3f0b9a6b,0x3f0c42c9,0x3f0cead0,0x3f0d9281,
0x3f0e39da,0x3f0ee0db,0x3f0f8784,0x3f102dd5,0x3f10d3cd,0x3f11796b,0x3f121eb0,0x3f12c39a,0x3f13682a,0x3f140c5f,0x3f14b039,0x3f1553b7,0x3f15f6d9,0x3f16999f,0x3f173c07,0x3f17de12,
0x3f187fc0,0x3f19210f,0x3f19c200,0x3f1a6293,0x3f1b02c6,0x3f1ba299,0x3f1c420c,0x3f1ce11f,0x3f1d7fd1,0x3f1e1e22,0x3f1ebc12,0x3f1f599f,0x3f1ff6cb,0x3f209393,0x3f212ff9,0x3f21cbfb,
0x3f226799,0x3f2302d3,0x3f239da9,0x3f24381a,0x3f24d225,0x3f256bcb,0x3f26050a,0x3f269de3,0x3f273656,0x3f27ce61,0x3f286605,0x3f28fd41,0x3f299415,0x3f2a2a80,0x3f2ac082,0x3f2b561b,
0x3f2beb4a,0x3f2c800f,0x3f2d1469,0x3f2da859,0x3f2e3bde,0x3f2ecef7,0x3f2f61a5,0x3f2ff3e6,0x3f3085bb,0x3f311722,0x3f31a81d,0x3f3238aa,0x3f32c8c9,0x3f33587a,0x3f33e7bc,0x3f34768f,
0x3f3504f3,0x3f3592e7,0x3f36206c,0x3f36ad7f,0x3f373a23,0x3f37c655,0x3f385216,0x3f38dd65,0x3f396842,0x3f39f2ac,0x3f3a7ca4,0x3f3b0629,0x3f3b8f3b,0x3f3c17d9,0x3f3ca003,0x3f3d27b8,
0x3f3daef9,0x3f3e35c5,0x3f3ebc1b,0x3f3f41fc,0x3f3fc767,0x3f404c5c,0x3f40d0da,0x3f4154e1,0x3f41d870,0x3f425b89,0x3f42de29,0x3f436051,0x3f43e200,0x3f446337,0x3f44e3f5,0x3f456439,
0x3f45e403,0x3f466354,0x3f46e22a,0x3f476085,0x3f47de65,0x3f485bca,0x3f48d8b3,0x3f495521,0x3f49d112,0x3f4a4c87,0x3f4ac77f,0x3f4b41fa,0x3f4bbbf8,0x3f4c3578,0x3f4cae79,0x3f4d26fd,
0x3f4d9f02,0x3f4e1689,0x3f4e8d90,0x3f4f0417,0x3f4f7a1f,0x3f4fefa8,0x3f5064af,0x3f50d937,0x3f514d3d,0x3f51c0c2,0x3f5233c6,0x3f52a649,0x3f531849,0x3f5389c7,0x3f53fac3,0x3f546b3b,
0x3f54db31,0x3f554aa4,0x3f55b993,0x3f5627fe,0x3f5695e5,0x3f570348,0x3f577026,0x3f57dc7f,0x3f584853,0x3f58b3a1,0x3f591e6a,0x3f5988ad,0x3f59f26a,0x3f5a5ba0,0x3f5ac450,0x3f5b2c79,
0x3f5b941a,0x3f5bfb34,0x3f5c61c7,0x3f5cc7d1,0x3f5d2d53,0x3f5d924d,0x3f5df6be,0x3f5e5aa6,0x3f5ebe05,0x3f5f20db,0x3f5f8327,0x3f5fe4e9,0x3f604621,0x3f60a6cf,0x3f6106f2,0x3f61668a,
0x3f61c598,0x3f62241a,0x3f628210,0x3f62df7b,0x3f633c5a,0x3f6398ac,0x3f63f473,0x3f644fac,0x3f64aa59,0x3f650479,0x3f655e0b,0x3f65b710,0x3f660f88,0x3f666771,0x3f66becc,0x3f671599,
0x3f676bd8,0x3f67c187,0x3f6816a8,0x3f686b39,0x3f68bf3c,0x3f6912ae,0x3f696591,0x3f69b7e4,0x3f6a09a7,0x3f6a5ad9,0x3f6aab7b,0x3f6afb8c,0x3f6b4b0c,0x3f6b99fb,0x3f6be858,0x3f6c3624,
0x3f6c835e,0x3f6cd007,0x3f6d1c1d,0x3f6d67a1,0x3f6db293,0x3f6dfcf2,0x3f6e46be,0x3f6e8ff8,0x3f6ed89e,0x3f6f20b0,0x3f6f6830,0x3f6faf1b,0x3f6ff573,0x3f703b37,0x3f708066,0x3f70c501,
0x3f710908,0x3f714c7a,0x3f718f57,0x3f71d19f,0x3f721352,0x3f725470,0x3f7294f8,0x3f72d4eb,0x3f731447,0x3f73530e,0x3f73913f,0x3f73ced9,0x3f740bdd,0x3f74484b,0x3f748422,0x3f74bf62,
0x3f74fa0b,0x3f75341d,0x3f756d97,0x3f75a67b,0x3f75dec6,0x3f76167a,0x3f764d97,0x3f76841b,0x3f76ba07,0x3f76ef5b,0x3f772417,0x3f77583a,0x3f778bc5,0x3f77beb7,0x3f77f110,0x3f7822d1,
0x3f7853f8,0x3f788486,0x3f78b47b,0x3f78e3d6,0x3f791298,0x3f7940c0,0x3f796e4e,0x3f799b43,0x3f79c79d,0x3f79f35e,0x3f7a1e84,0x3f7a4910,0x3f7a7302,0x3f7a9c59,0x3f7ac516,0x3f7aed37,
0x3f7b14be,0x3f7b3bab,0x3f7b61fc,0x3f7b87b2,0x3f7baccd,0x3f7bd14d,0x3f7bf531,0x3f7c187a,0x3f7c3b28,0x3f7c5d3a,0x3f7c7eb0,0x3f7c9f8a,0x3f7cbfc9,0x3f7cdf6c,0x3f7cfe73,0x3f7d1cdd,
0x3f7d3aac,0x3f7d57de,0x3f7d7474,0x3f7d906e,0x3f7dabcc,0x3f7dc68c,0x3f7de0b1,0x3f7dfa38,0x3f7e1324,0x3f7e2b72,0x3f7e4323,0x3f7e5a38,0x3f7e70b0,0x3f7e868b,0x3f7e9bc9,0x3f7eb069,
0x3f7ec46d,0x3f7ed7d4,0x3f7eea9d,0x3f7efcc9,0x3f7f0e58,0x3f7f1f49,0x3f7f2f9d,0x3f7f3f54,0x3f7f4e6d,0x3f7f5ce9,0x3f7f6ac7,0x3f7f7808,0x3f7f84ab,0x3f7f90b1,0x3f7f9c18,0x3f7fa6e3,
0x3f7fb10f,0x3f7fba9e,0x3f7fc38f,0x3f7fcbe2,0x3f7fd397,0x3f7fdaaf,0x3f7fe129,0x3f7fe705,0x3f7fec43,0x3f7ff0e3,0x3f7ff4e6,0x3f7ff84a,0x3f7ffb11,0x3f7ffd39,0x3f7ffec4,0x3f7fffb1,
};

__device__ __forceinline__ int tid_here() { return __shfl_xor_sync(~0u, (int)threadIdx.x, 0); }
__device__ __forceinline__ void ld_tab(uint32_t* d, int chunk) { asm volatile("ld.global.v4.u32 {%0,%1,%2,%3}, [%4];" : "=r"(d[0]), "=r"(d[1]), "=r"(d[2]), "=r"(d[3]) : "l"((const uint4*)g_tab + chunk) : "memory"); }
__device__ __forceinline__ void ld_tab(float* d, int chunk) { asm volatile("ld.global.v4.f32 {%0,%1,%2,%3}, [%4];" : "=f"(d[0]), "=f"(d[1]), "=f"(d[2]), "=f"(d[3]) : "l"((const uint4*)g_tab + chunk) : "memory"); }
__device__ __forceinline__ void fft640(uint32_t plane, uint32_t tab, int lane, const uint32_t* fr, const uint32_t* fi, const float (*tc)[4], const float (*ts)[4], float (*xr)[4], float (*xi)[4]) {
  uint32_t A1[5][4], nfi[4];
#pragma unroll
  for (int i = 0; i < 4; i++) nfi[i] = fi[i] ^ 0x80008000u;
  const uint32_t la = plane + (lane >> 4) * 1280 + (lane & 15) * 80;
#pragma unroll
  for (int j = 0; j < 5; j++) {
    uint32_t r0, r1, i0, i1; ldsm4t(r0, r1, i0, i1, la + j * 16);
    float yr[4], yi[4];
    mmaZ(yr, fr, r0, r1); mmaZ(yi, fi, r0, r1); mmaA(yr, nfi, i0, i1); mmaA(yi, fr, i0, i1);
    float zr[4], zi[4];
#pragma unroll
    for (int e = 0; e < 4; e++) { zr[e] = yr[e] * tc[j][e] - yi[e] * ts[j][e]; zi[e] = yr[e] * ts[j][e] + yi[e] * tc[j][e]; }
    A1[j][0] = pack_bf16(zr[0], zr[1]); A1[j][1] = pack_bf16(zr[2], zr[3]); A1[j][2] = pack_bf16(zi[0], zi[1]); A1[j][3] = pack_bf16(zi[2], zi[3]);
  }
#pragma unroll
  for (int t = 0; t < 5; t++) {
    uint32_t A2[4] = {A1[t][2], A1[t][3], A1[t][0] ^ 0x80008000u, A1[t][1] ^ 0x80008000u};
#pragma unroll
    for (int u = 0; u < 5; u++) {
      uint32_t b0, b1; asm volatile("ld.shared.v2.b32 {%0,%1}, [%2];" : "=r"(b0), "=r"(b1) : "r"(tab + (t * 5 + u) * 256 + lane * 8));
      if (t == 0) { mmaZ(xr[u], A1[t], b0, b1); mmaZ(xi[u], A2, b0, b1); } else { mmaA(xr[u], A1[t], b0, b1); mmaA(xi[u], A2, b0, b1); }
    }
  }
}
__device__ __forceinline__ void ln_row(float* v) {
  float s = 0.f;
#pragma unroll
  for (int i = 0; i < 20; i++) s += v[i];
#pragma unroll
  for (int o = 16; o; o >>= 1) s += __shfl_xor_sync(~0u, s, o);
  const float mean = s * (1.f / D_);
  float qv = 0.f;
#pragma unroll
  for (int i = 0; i < 20; i++) { v[i] -= mean; qv += v[i] * v[i]; }
#pragma unroll
  for (int o = 16; o; o >>= 1) qv += __shfl_xor_sync(~0u, qv, o);
  const float rs = rsqrtf(qv * (1.f / D_) + 1e-5f);
#pragma unroll
  for (int i = 0; i < 20; i++) v[i] *= rs;
}

#define TLBASE (1024 + 896)
struct AParams { const bf16* x; uint32_t *Z1, *Z2; const uint32_t* WT; bf16 *x1, *hN; uint32_t* sync; const uint32_t* rowdone; int nw; uint32_t tag; };
constexpr int SY_1 = 0, SY_2 = 32, SY_3 = 64, SY_W = 96;
__device__ __forceinline__ void red_release(uint32_t* p) { asm volatile("red.release.gpu.global.add.u32 [%0], 1;" :: "l"(p) : "memory"); }
__device__ __forceinline__ void red_relaxed(uint32_t* p) { asm volatile("red.relaxed.gpu.global.add.u32 [%0], 1;" :: "l"(p) : "memory"); }
__device__ __forceinline__ void spin_count(const uint32_t* p, uint32_t n) {
  uint32_t v; int guard = 0;
#pragma unroll 1
  do { asm volatile("ld.relaxed.gpu.global.u32 %0, [%1];" : "=r"(v) : "l"(p) : "memory"); } while (v < n && ++guard < 400000);
}

__device__ __forceinline__ void filter_prep(uint32_t* WT, uint32_t sm, int k2) {
  const int tid = threadIdx.x, r = (tid >> 5) & 3;
  const uint32_t src = sm + (8 * (tid & 3) + r) * 642;
#pragma unroll 2
  for (int f = (tid >> 7) * 8 + ((tid & 31) >> 2); f < 321; f += 24) {
    uint32_t v[4];
#pragma unroll
    for (int i = 0; i < 4; i++) {
      unsigned short lo, hi;
      const uint32_t a = src + f * 2 + ((i >> 1) * 4 + (i & 1) * 32) * 642;
      asm volatile("ld.shared.u16 %0, [%1];" : "=h"(lo) : "r"(a)); asm volatile("ld.shared.u16 %0, [%1];" : "=h"(hi) : "r"(a + 41088));
      v[i] = lo | ((uint32_t)hi << 16);
    }
    stg128(WT + f * 2048 + k2 * 64 + r * 16 + (tid & 3) * 4, v[0], v[1], v[2], v[3]);
  }
}

template <typename F> __device__ __forceinline__ void a_phase2(const AParams& a, float* buf, int f, F hook) {
  const int t0 = tid_here(), tid = t0 & 127, lane = tid & 31, w = tid >> 5, g = lane >> 2, q = lane & 3, barid = 5 + (t0 >> 7);
  const int f2 = (640 - f) % 640;
#define WGBAR() asm volatile("bar.sync %0, 128;" :: "r"(barid) : "memory")
  uint32_t fr[4], fi[4], nfi[4], br[4][4], bi[4][4];
  float tc[4][4], ts[4][4], wc[4], ws[4];
  ld_tab(wc, TB_2048 + tid); ld_tab(ws, TB_2048 + 128 + tid); ld_tab(fr, TB_F16 + lane); ld_tab(fi, TB_F16 + 32 + lane);
#pragma unroll
  for (int j = 0; j < 4; j++) { ld_tab(tc[j], TB_512 + j * 32 + lane); ld_tab(ts[j], TB_512 + 128 + j * 32 + lane); }
  if (tid == 32 && !a.nw) l2_prefetch(a.WT + f * 2048, 8192);
  const uint32_t* zs[4];
#pragma unroll
  for (int j = 0; j < 4; j++) { const int m = j * 256 + 2 * tid; zs[j] = a.Z1 + (m / 12) * 7680 + m % 12; }
  if (tid == 0) { spin_count(a.sync + SY_1, 86); TL(6); }
  WGBAR();
  const uint32_t sbuf = smem_u32(buf);
  {
    uint2 P[4], Q[4];
#pragma unroll 1
    for (int guard = 0; guard < 100000; guard++) {
      uint32_t bad = 0;
#pragma unroll
      for (int j = 0; j < 4; j++) {
        asm volatile("ld.relaxed.gpu.global.v2.u32 {%0,%1}, [%2];" : "=r"(P[j].x), "=r"(P[j].y) : "l"(zs[j] + f * 12) : "memory");
        asm volatile("ld.relaxed.gpu.global.v2.u32 {%0,%1}, [%2];" : "=r"(Q[j].x), "=r"(Q[j].y) : "l"(zs[j] + f2 * 12) : "memory");
      }
#pragma unroll
      for (int j = 0; j < 4; j++) bad |= (P[j].x ^ a.tag) | (Q[j].x ^ a.tag);
      if (__all_sync(~0u, !(bad & 1))) break;
    }
    float ur[4][4], ui[4][4];
#pragma unroll
    for (int i = 0; i < 4; i++) {
      float ar[4], ai[4];
#pragma unroll
      for (int j = 0; j < 4; j++) {
        const uint32_t p = (i >> 1) ? P[j].y : P[j].x, z = (i >> 1) ? Q[j].y : Q[j].x;
        if (!(i & 1)) { ar[j] = bf_lo(p) + bf_lo(z); ai[j] = bf_hi(p) - bf_hi(z); }
        else { ar[j] = bf_hi(p) + bf_hi(z); ai[j] = bf_lo(z) - bf_lo(p); }
      }
      const float s0r = ar[0] + ar[2], s0i = ai[0] + ai[2], d0r = ar[0] - ar[2], d0i = ai[0] - ai[2];
      const float s1r = ar[1] + ar[3], s1i = ai[1] + ai[3], d1r = ar[1] - ar[3], d1i = ai[1] - ai[3];
      ur[0][i] = s0r + s1r; ui[0][i] = s0i + s1i;
      const float vr[3] = {d0r + d1i, s0r - s1r, d0r - d1i}, vi[3] = {d0i - d1r, s0i - s1i, d0i + d1r};
      const float c2 = wc[i] * wc[i] - ws[i] * ws[i], s2 = 2.f * wc[i] * ws[i];
      const float twc[4] = {1.f, wc[i], c2, c2 * wc[i] - s2 * ws[i]}, tws[4] = {0.f, ws[i], s2, s2 * wc[i] + c2 * ws[i]};
#pragma unroll
      for (int r = 1; r < 4; r++) { const float c = twc[r], s = tws[r]; ur[r][i] = vr[r - 1] * c + vi[r - 1] * s; ui[r][i] = vi[r - 1] * c - vr[r - 1] * s; }
    }
    const uint32_t o = sbuf + (tid >> 3) * 80 + (tid & 7) * 8;
#pragma unroll
    for (int r = 0; r < 4; r++) {
      asm volatile("st.shared.v2.b32 [%0], {%1,%2};" :: "r"(o + r * 5120), "r"(pack_bf16(ur[r][0], ur[r][1])), "r"(pack_bf16(ur[r][2], ur[r][3])) : "memory");
      asm volatile("st.shared.v2.b32 [%0], {%1,%2};" :: "r"(o + r * 5120 + 1280), "r"(pack_bf16(ui[r][0], ui[r][1])), "r"(pack_bf16(ui[r][2], ui[r][3])) : "memory");
    }
  }
#pragma unroll
  for (int j = 0; j < 4; j++) { ld_tab(br[j], TB_F32 + j * 32 + lane); ld_tab(bi[j], TB_F32 + 128 + j * 32 + lane); }
  if (tid == 0 && a.nw) spin_count(a.sync + SY_W, a.nw);
  WGBAR();
  hook(1);
  TL(7);
  uint2 wt[8];
#pragma unroll
  for (int i = 0; i < 8; i++) wt[i] = __ldcg((const uint2*)(a.WT + f * 2048 + ((i >> 1) * 8 + 2 * q + (i & 1)) * 64 + w * 16 + g * 2));
  {
    uint32_t A1[4][4], A2[4][4];
#pragma unroll
    for (int i = 0; i < 4; i++) nfi[i] = fi[i] ^ 0x80008000u;
    const uint32_t la = sbuf + w * 5120 + (lane >> 4) * 1280 + (lane & 15) * 80;
#pragma unroll
    for (int j = 0; j < 4; j++) {
      uint32_t r0, r1, i0, i1; ldsm4t(r0, r1, i0, i1, la + j * 16);
      float yr[4], yi[4];
      mmaZ(yr, fr, r0, r1); mmaZ(yi, fi, r0, r1); mmaA(yr, nfi, i0, i1); mmaA(yi, fr, i0, i1);
      float zr[4], zi[4];
#pragma unroll
      for (int e = 0; e < 4; e++) { zr[e] = yr[e] * tc[j][e] + yi[e] * ts[j][e]; zi[e] = yi[e] * tc[j][e] - yr[e] * ts[j][e]; }
      A1[j][0] = pack_bf16(zr[0], zr[1]); A1[j][1] = pack_bf16(zr[2], zr[3]); A1[j][2] = pack_bf16(zi[0], zi[1]); A1[j][3] = pack_bf16(zi[2], zi[3]);
      A2[j][0] = A1[j][2]; A2[j][1] = A1[j][3]; A2[j][2] = A1[j][0] ^ 0x80008000u; A2[j][3] = A1[j][1] ^ 0x80008000u;
    }
    float xr[4][4], xi[4][4];
#pragma unroll
    for (int t = 0; t < 4; t++)
#pragma unroll
      for (int u = 0; u < 4; u++) {
        if (t == 0) { mmaZ(xr[u], A1[t], br[t][u], bi[t][u]); mmaZ(xi[u], A2[t], br[t][u], bi[t][u]); } else { mmaA(xr[u], A1[t], br[t][u], bi[t][u]); mmaA(xi[u], A2[t], br[t][u], bi[t][u]); }
      }
#pragma unroll
    for (int u = 0; u < 4; u++) {
      const uint32_t wv[4] = {wt[2 * u].x, wt[2 * u + 1].x, wt[2 * u].y, wt[2 * u + 1].y};
      float zr[4], zi[4];
#pragma unroll
      for (int e = 0; e < 4; e++) { const float c = bf_lo(wv[e]), b = bf_hi(wv[e]); zr[e] = xr[u][e] * c - xi[u][e] * b; zi[e] = xr[u][e] * b + xi[u][e] * c; }
      A2[u][2] = pack_bf16(zr[0], zr[1]); A2[u][3] = pack_bf16(zr[2], zr[3]); A2[u][0] = pack_bf16(zi[0], zi[1]); A2[u][1] = pack_bf16(zi[2], zi[3]);
      A1[u][0] = A2[u][2]; A1[u][1] = A2[u][3]; A1[u][2] = A2[u][0] ^ 0x80008000u; A1[u][3] = A2[u][1] ^ 0x80008000u;
    }
#pragma unroll
    for (int t = 0; t < 4; t++)
#pragma unroll
      for (int u = 0; u < 4; u++) {
        if (t == 0) { mmaZ(xr[u], A1[t], br[t][u], bi[t][u]); mmaZ(xi[u], A2[t], br[t][u], bi[t][u]); } else { mmaA(xr[u], A1[t], br[t][u], bi[t][u]); mmaA(xi[u], A2[t], br[t][u], bi[t][u]); }
      }
    __syncwarp();
    float* pl = buf + w * 1280;
    const float nrm = 0.5f / (2048.f * 640.f);
#pragma unroll
    for (int j = 0; j < 4; j++) {
      float zr[4], zi[4];
#pragma unroll
      for (int e = 0; e < 4; e++) { zr[e] = xr[j][e] * tc[j][e] - xi[j][e] * ts[j][e]; zi[e] = xi[j][e] * tc[j][e] + xr[j][e] * ts[j][e]; }
      const uint32_t r0 = movm(pack_bf16(zr[0], zr[1])), r1 = movm(pack_bf16(zr[2], zr[3])), i0 = movm(pack_bf16(zi[0], zi[1])), i1 = movm(pack_bf16(zi[2], zi[3]));
      float yr[4], yi[4];
      mmaZ(yr, fr, r0, r1); mmaZ(yi, nfi, r0, r1); mmaA(yr, fi, i0, i1); mmaA(yi, fr, i0, i1);
      *(float2*)(pl + g * 40 + 8 * j + 2 * q) = make_float2(yr[0] * nrm, yr[1] * nrm); *(float2*)(pl + (g + 8) * 40 + 8 * j + 2 * q) = make_float2(yr[2] * nrm, yr[3] * nrm);
      *(float2*)(pl + 640 + g * 40 + 8 * j + 2 * q) = make_float2(yi[0] * nrm, yi[1] * nrm); *(float2*)(pl + 640 + (g + 8) * 40 + 8 * j + 2 * q) = make_float2(yi[2] * nrm, yi[3] * nrm);
    }
  }
  ld_tab(wc, TB_2048 + tid); ld_tab(ws, TB_2048 + 128 + tid);
  WGBAR();
  hook(2);
  TL(8);
  {
    float4 Ur[4], Ui[4];
#pragma unroll
    for (int r = 0; r < 4; r++) { Ur[r] = *(const float4*)(buf + r * 1280 + (tid >> 3) * 40 + (tid & 7) * 4); Ui[r] = *(const float4*)(buf + r * 1280 + 640 + (tid >> 3) * 40 + (tid & 7) * 4); }
    float yr[4][4], yi[4][4];
#pragma unroll
    for (int i = 0; i < 4; i++) {
      float ar[4], ai[4];
      const float c2 = wc[i] * wc[i] - ws[i] * ws[i], s2 = 2.f * wc[i] * ws[i];
      const float twc[4] = {1.f, wc[i], c2, c2 * wc[i] - s2 * ws[i]}, tws[4] = {0.f, ws[i], s2, s2 * wc[i] + c2 * ws[i]};
#pragma unroll
      for (int r = 0; r < 4; r++) {
        const float a = i == 0 ? Ur[r].x : i == 1 ? Ur[r].y : i == 2 ? Ur[r].z : Ur[r].w, b = i == 0 ? Ui[r].x : i == 1 ? Ui[r].y : i == 2 ? Ui[r].z : Ui[r].w;
        if (r == 0) { ar[r] = a; ai[r] = b; } else { const float c = twc[r], s = tws[r]; ar[r] = a * c - b * s; ai[r] = b * c + a * s; }
      }
      const float s0r = ar[0] + ar[2], s0i = ai[0] + ai[2], d0r = ar[0] - ar[2], d0i = ai[0] - ai[2];
      const float s1r = ar[1] + ar[3], s1i = ai[1] + ai[3], d1r = ar[1] - ar[3], d1i = ai[1] - ai[3];
      yr[0][i] = s0r + s1r; yi[0][i] = s0i + s1i; yr[2][i] = s0r - s1r; yi[2][i] = s0i - s1i;
      yr[1][i] = d0r - d1i; yi[1][i] = d0i + d1r; yr[3][i] = d0r + d1i; yi[3][i] = d0i - d1r;
    }
    const float im = (f == f2) ? 0.f : 1.f;
#pragma unroll
    for (int j = 0; j < 4; j++) {
      *(uint2*)(a.Z2 + f * 1024 + j * 256 + 2 * tid) = make_uint2((pack_bf16(yr[j][0] - im * yi[j][1], yr[j][1] + im * yi[j][0]) & ~1u) | a.tag, pack_bf16(yr[j][2] - im * yi[j][3], yr[j][3] + im * yi[j][2]));
      if (f != f2) *(uint2*)(a.Z2 + f2 * 1024 + j * 256 + 2 * tid) = make_uint2((pack_bf16(yr[j][0] + yi[j][1], yr[j][1] - yi[j][0]) & ~1u) | a.tag, pack_bf16(yr[j][2] + yi[j][3], yr[j][3] - yi[j][2]));
    }
  }
  TL(9);
}

constexpr int KA_TR_STRIDE = 804;
template <typename F> __device__ __forceinline__ void a_layer(const AParams& a, char* scratch, int v, int w, F hook) {
  const int tid = tid_here(), lane = tid & 31;
  uint32_t raw[2][10], fr[4], fi[4];
  float tc[5][4], ts[5][4];
  bool act = v < 86;
  int m = act ? min(v * 12 + w, 1023) : v * 4 + w;
  uint32_t* buf = (uint32_t*)(scratch + 6400) + (w & 3) * KA_TR_STRIDE + (w >> 2) * 3244;
  auto load_rows = [&]() {
    const int lane = tid_here() & 31;
#pragma unroll
    for (int i = 0; i < 10; i++) asm volatile("ld.global.cg.v2.u32 {%0,%1}, [%2];" : "=r"(raw[i / 5][2 * (i % 5)]), "=r"(raw[i / 5][2 * (i % 5) + 1]) : "l"(a.x + (size_t)(2 * m) * D_ + i * 128 + lane * 4) : "memory");
  };
  auto load_tabs = [&]() {
    uint32_t t[2][4];
    const int tid = tid_here(), lane = tid & 31;
    ld_tab(t[0], TB_F40 + (tid & 255)); ld_tab(t[1], TB_F40 + 144 + (tid & 255));
    ld_tab(fr, TB_F16 + lane); ld_tab(fi, TB_F16 + 32 + lane);
#pragma unroll
    for (int j = 0; j < 5; j++) { ld_tab(tc[j], TB_640 + j * 32 + lane); ld_tab(ts[j], TB_640 + 160 + j * 32 + lane); }
    sts128(smem_u32(scratch) + (tid & 255) * 16, t[0][0], t[0][1], t[0][2], t[0][3]); sts128(smem_u32(scratch) + 2304 + (tid & 255) * 16, t[1][0], t[1][1], t[1][2], t[1][3]);
  };
  if (a.rowdone) { load_tabs(); if (act) spin_count(a.rowdone + (m >> 4) * 16, 32); load_rows(); }
  else { load_rows(); load_tabs(); }
  __syncthreads();
  hook(-1);
  TL(1);
#pragma unroll 1
  for (int it = 0;; it++) {
    if (act) {
#pragma unroll
      for (int r = 0; r < 2; r++) {
        float x[20];
#pragma unroll
        for (int i = 0; i < 10; i++) { x[2 * i] = bf_lo(raw[r][i]); x[2 * i + 1] = bf_hi(raw[r][i]); }
        ln_row(x);
#pragma unroll
        for (int i = 0; i < 10; i++) raw[r][i] = pack_bf16(x[2 * i], x[2 * i + 1]);
      }
    }
    if (it) break;
    if (act) {
#pragma unroll
      for (int i = 0; i < 10; i++) *(uint2*)(buf + i * 64 + lane * 2) = make_uint2(raw[i / 5][2 * (i % 5)], raw[i / 5][2 * (i % 5) + 1]);
      __syncwarp();
    }
    TL(2);
#pragma unroll 1
    for (int ph = 0;; ph++) {
      if (act) {
        float xr[5][4], xi[5][4];
        const int lane = tid_here() & 31, g = lane >> 2, q = lane & 3;
        fft640(smem_u32(buf), smem_u32(scratch), lane, fr, fi, tc, ts, xr, xi);
        __syncwarp();
#pragma unroll
        for (int u = 0; u < 5; u++)
#pragma unroll
          for (int e = 0; e < 4; e++) { const int f = g + 8 * (e >> 1) + 16 * (8 * u + 2 * q + (e & 1)); buf[f + 8 * (f >> 5)] = pack_bf16(xr[u][e], xi[u][e]); }
        __syncwarp();
      }
      if (ph) break;
      __syncthreads();
      TL(3);
      const int t1 = tid_here(), f0 = t1 / 3, part = t1 % 3;
      if (act) {
        const uint32_t* src = (const uint32_t*)(scratch + 6400) + part * 3244 + f0 + 8 * (f0 >> 5);
        uint32_t ov[5][4];
#pragma unroll
        for (int i = 0; i < 5; i++)
#pragma unroll
          for (int k = 0; k < 4; k++) ov[i][k] = src[k * KA_TR_STRIDE + i * 160];
#pragma unroll
        for (int i = 0; i < 5; i++) stg128(a.Z1 + v * 7680 + (i * 384 + t1) * 4, (ov[i][0] & ~1u) | a.tag, ov[i][1], (ov[i][2] & ~1u) | a.tag, ov[i][3]);
      }
      TL(4);
      __syncthreads();
      if (tid == 32 && act) { red_relaxed(a.sync + SY_1); TL(5); }
      hook(0);
      const int f = (w >> 2) * 131 + v;
      if (f < 321) a_phase2(a, (float*)(scratch + (w >> 2) * 20480), f, hook);
      asm volatile("fence.proxy.async.shared::cta;" ::: "memory");
      __syncthreads();
      if (tid == 32) red_relaxed(a.sync + SY_2);
      hook(3);
      if (w >= 8 || v >= 128) return;
      act = true; m = v * 8 + w;
      scratch += 32768; buf = (uint32_t*)(scratch + 6400);
      {
        load_rows(); load_tabs();
        if (tid == 0) { spin_count(a.sync + SY_2, 131); TL(10); }
        bar_sync<5, 256>();
        uint4 za[3], zb[3];
        const int tid = tid_here();
#pragma unroll 1
        for (int guard = 0; guard < 100000; guard++) {
          uint32_t bad = 0;
#pragma unroll
          for (int i = 0; i < 3; i++) {
            const uint32_t* s = a.Z2 + (i * 256 + (tid & (i < 2 ? 254 : 126))) * 1024 + v * 8 + (tid & 1) * 4;
            asm volatile("ld.relaxed.gpu.global.v4.u32 {%0,%1,%2,%3}, [%4];" : "=r"(za[i].x), "=r"(za[i].y), "=r"(za[i].z), "=r"(za[i].w) : "l"(s) : "memory");
            asm volatile("ld.relaxed.gpu.global.v4.u32 {%0,%1,%2,%3}, [%4];" : "=r"(zb[i].x), "=r"(zb[i].y), "=r"(zb[i].z), "=r"(zb[i].w) : "l"(s + 1024) : "memory");
          }
#pragma unroll
          for (int i = 0; i < 3; i++) bad |= (za[i].x ^ a.tag) | (zb[i].x ^ a.tag) | (za[i].z ^ a.tag) | (zb[i].z ^ a.tag);
          if (__all_sync(~0u, !(bad & 1))) break;
        }
#pragma unroll
        for (int i = 0; i < 3; i++) if (i < 2 || tid < 128) {
          const uint4 c = za[i], b = zb[i];
          uint32_t* d = buf + (tid & 1) * 4 * KA_TR_STRIDE + i * 128 + (tid >> 1);
          d[320] = __byte_perm(c.x, b.x, 0x5410); d[0] = __byte_perm(c.x, b.x, 0x7632); d += KA_TR_STRIDE;
          d[320] = __byte_perm(c.y, b.y, 0x5410); d[0] = __byte_perm(c.y, b.y, 0x7632); d += KA_TR_STRIDE;
          d[320] = __byte_perm(c.z, b.z, 0x5410); d[0] = __byte_perm(c.z, b.z, 0x7632); d += KA_TR_STRIDE;
          d[320] = __byte_perm(c.w, b.w, 0x5410); d[0] = __byte_perm(c.w, b.w, 0x7632);
        }
        bar_sync<5, 256>();
        hook(4);
        TL(11);
      }
      buf += w * KA_TR_STRIDE;
    }
    {
      TL(12);
      const int lane = tid_here() & 31;
#pragma unroll
      for (int i = 0; i < 5; i++) {
        const uint4 y = *(const uint4*)(buf + i * 160 + lane * 4 + 8 * (lane >> 3));
        raw[0][2 * i] = hadd2(raw[0][2 * i], __byte_perm(y.x, y.y, 0x7632)); raw[0][2 * i + 1] = hadd2(raw[0][2 * i + 1], __byte_perm(y.z, y.w, 0x7632));
        raw[1][2 * i] = hadd2(raw[1][2 * i], __byte_perm(y.x, y.y, 0x5410)); raw[1][2 * i + 1] = hadd2(raw[1][2 * i + 1], __byte_perm(y.z, y.w, 0x5410));
      }
#pragma unroll
      for (int i = 0; i < 10; i++) *(uint2*)(a.x1 + (size_t)(2 * m) * D_ + i * 128 + lane * 4) = make_uint2(raw[i / 5][2 * (i % 5)], raw[i / 5][2 * (i % 5) + 1]);
    }
  }
  {
#pragma unroll
    for (int i = 0; i < 10; i++) *(uint2*)(a.hN + (size_t)(2 * m) * D_ + i * 128 + lane * 4) = make_uint2(raw[i / 5][2 * (i % 5)], raw[i / 5][2 * (i % 5) + 1]);
    TL(13);
    bar_sync<5, 256>();
    if (tid == 0) { red_release(a.sync + SY_3); TL(14); }
  }
}

__device__ __forceinline__ void tma2d(uint32_t dst, const CUtensorMap* tm, int c0, int c1, uint32_t bar) {
  asm volatile("cp.async.bulk.tensor.2d.shared::cluster.global.mbarrier::complete_tx::bytes [%0], [%1, {%3, %4}], [%2];" :: "r"(dst), "l"(tm), "r"(bar), "r"(c0), "r"(c1) : "memory");
}
__device__ __forceinline__ void bulk_g2s(uint32_t dst, const void* src, int bytes, uint32_t bar) {
  asm volatile("cp.async.bulk.shared::cluster.global.mbarrier::complete_tx::bytes [%0], [%1], %2, [%3];" :: "r"(dst), "l"(src), "r"(bytes), "r"(bar) : "memory");
}
__device__ __forceinline__ uint64_t desc128(uint32_t a) { return (uint64_t)((a & 0x3FFFF) >> 4) | (1ull << 16) | (64ull << 32) | (1ull << 62); }
#define WG_FENCE() asm volatile("wgmma.fence.sync.aligned;" ::: "memory")
#define WG_COMMIT() asm volatile("wgmma.commit_group.sync.aligned;" ::: "memory")
#define WG_WAIT(n) asm volatile("wgmma.wait_group.sync.aligned " #n ";" ::: "memory")
__device__ __forceinline__ void wg_rs_n64(float* d, const uint32_t* a, uint64_t db, int acc) {
  asm volatile("{.reg .pred p; setp.ne.b32 p, %37, 0;\n"
    "wgmma.mma_async.sync.aligned.m64n64k16.f32.bf16.bf16 {%0,%1,%2,%3,%4,%5,%6,%7,%8,%9,%10,%11,%12,%13,%14,%15,%16,%17,%18,%19,%20,%21,%22,%23,%24,%25,%26,%27,%28,%29,%30,%31}, {%32,%33,%34,%35}, %36, p, 1, 1, 0;}"
    : "+f"(d[0]), "+f"(d[1]), "+f"(d[2]), "+f"(d[3]), "+f"(d[4]), "+f"(d[5]), "+f"(d[6]), "+f"(d[7]), "+f"(d[8]), "+f"(d[9]), "+f"(d[10]), "+f"(d[11]), "+f"(d[12]), "+f"(d[13]), "+f"(d[14]), "+f"(d[15]),
      "+f"(d[16]), "+f"(d[17]), "+f"(d[18]), "+f"(d[19]), "+f"(d[20]), "+f"(d[21]), "+f"(d[22]), "+f"(d[23]), "+f"(d[24]), "+f"(d[25]), "+f"(d[26]), "+f"(d[27]), "+f"(d[28]), "+f"(d[29]), "+f"(d[30]), "+f"(d[31])
    : "r"(a[0]), "r"(a[1]), "r"(a[2]), "r"(a[3]), "l"(db), "r"(acc));
}
__device__ __forceinline__ void wg_rs_n32(float* d, const uint32_t* a, uint64_t db, int acc) {
  asm volatile("{.reg .pred p; setp.ne.b32 p, %21, 0;\n"
    "wgmma.mma_async.sync.aligned.m64n32k16.f32.bf16.bf16 {%0,%1,%2,%3,%4,%5,%6,%7,%8,%9,%10,%11,%12,%13,%14,%15}, {%16,%17,%18,%19}, %20, p, 1, 1, 0;}"
    : "+f"(d[0]), "+f"(d[1]), "+f"(d[2]), "+f"(d[3]), "+f"(d[4]), "+f"(d[5]), "+f"(d[6]), "+f"(d[7]), "+f"(d[8]), "+f"(d[9]), "+f"(d[10]), "+f"(d[11]), "+f"(d[12]), "+f"(d[13]), "+f"(d[14]), "+f"(d[15])
    : "r"(a[0]), "r"(a[1]), "r"(a[2]), "r"(a[3]), "l"(db), "r"(acc));
}
__device__ __forceinline__ void wg_ss_n40_tt(float* d, uint64_t da, uint64_t db, int acc) {
  asm volatile("{.reg .pred p; setp.ne.b32 p, %22, 0;\n"
    "wgmma.mma_async.sync.aligned.m64n40k16.f32.bf16.bf16 {%0,%1,%2,%3,%4,%5,%6,%7,%8,%9,%10,%11,%12,%13,%14,%15,%16,%17,%18,%19}, %20, %21, p, 1, 1, 1, 1;}"
    : "+f"(d[0]), "+f"(d[1]), "+f"(d[2]), "+f"(d[3]), "+f"(d[4]), "+f"(d[5]), "+f"(d[6]), "+f"(d[7]), "+f"(d[8]), "+f"(d[9]), "+f"(d[10]), "+f"(d[11]), "+f"(d[12]), "+f"(d[13]), "+f"(d[14]), "+f"(d[15]),
      "+f"(d[16]), "+f"(d[17]), "+f"(d[18]), "+f"(d[19])
    : "l"(da), "l"(db), "r"(acc));
}
__device__ __forceinline__ void wg_ss_n32_ta(float* d, uint64_t da, uint64_t db, int acc) {
  asm volatile("{.reg .pred p; setp.ne.b32 p, %18, 0;\n"
    "wgmma.mma_async.sync.aligned.m64n32k16.f32.bf16.bf16 {%0,%1,%2,%3,%4,%5,%6,%7,%8,%9,%10,%11,%12,%13,%14,%15}, %16, %17, p, 1, 1, 1, 0;}"
    : "+f"(d[0]), "+f"(d[1]), "+f"(d[2]), "+f"(d[3]), "+f"(d[4]), "+f"(d[5]), "+f"(d[6]), "+f"(d[7]), "+f"(d[8]), "+f"(d[9]), "+f"(d[10]), "+f"(d[11]), "+f"(d[12]), "+f"(d[13]), "+f"(d[14]), "+f"(d[15])
    : "l"(da), "l"(db), "r"(acc));
}
__device__ __forceinline__ uint64_t desc_ns(uint32_t a, uint32_t lbo, uint32_t sbo) { return (uint64_t)((a & 0x3FFFF) >> 4) | ((uint64_t)(lbo >> 4) << 16) | ((uint64_t)(sbo >> 4) << 32); }
__device__ __forceinline__ void wait_count(const uint32_t* p, uint32_t n) {
  uint32_t v; int guard = 0;
#pragma unroll 1
  while (true) { asm volatile("ld.relaxed.gpu.global.u32 %0, [%1];" : "=r"(v) : "l"(p) : "memory"); if (__all_sync(~0u, v >= n) || ++guard > 200000) break; }
}

constexpr int SD_WS = 0, SD_REC = 16384, SD_O = SD_REC + 2 * 30720, SD_OI = SD_O + 2 * 8192, SD_OUT = SD_OI + 2 * 40960, SD_FIN = SD_OUT + 8192, SD_BAR = SD_FIN + 10240;
constexpr int SD_SMEM = SD_BAR + 512 + 1024;
#undef TLBASE
#define TLBASE (1024 + SD_BAR + 256)
#define QRING 4
constexpr int ORING = 8, PRING = 2 * ORING;
constexpr int FL_MEM = 162 * 1024, FL_RDY = 166 * 1024, FL_SM = 170 * 1024;
struct SideParams { CUtensorMap tmWo, tmP; const char* QKV; char *O, *part; const bf16* x1; bf16* out; uint32_t *comm, *sync; uint64_t dhi; int first, period, phase, win, lag, tmem, last, dbgf; };
#define DBGF(m) false
#define ELECT "{.reg .pred p; elect.sync _|p, 0xffffffff;\n"
#define ATS(i)
__global__ void __launch_bounds__(512, 1) side_kernel(const __grid_constant__ SideParams p) {
  extern __shared__ __align__(1024) char smem_raw[];
  const uint32_t sb = (smem_u32(smem_raw) + 1023) & ~1023u, wfull = sb + SD_BAR, rland = wfull + 8, ofull = wfull + 16, ofree = wfull + 32,
    ifull = wfull + 48, ifree = wfull + 64, rfull = wfull + 80, rfree = wfull + 96, fdone = wfull + 112, ffull = wfull + 128;
  const int tid = threadIdx.x, lane = tid & 31, w = __shfl_sync(~0u, tid >> 5, 0);
  if (!DBGF(16)) pdl_launch();
  if (tid == 0) {
    spin_count(p.sync + SY_3, 128);
    uint32_t sm, mate; asm("mov.u32 %0, %%smid;" : "=r"(sm));
    asm volatile("ld.relaxed.gpu.global.u32 %0, [%1];" : "=r"(mate) : "l"(p.comm + FL_SM - (p.first ^ 1) * 1024 + (sm ^ 1)) : "memory");
    const uint32_t n = atomicAdd(p.comm + FL_SM + 512 + (mate ? 8 : 0), 1);
    asm volatile("st.shared.b32 [%0], %1;" :: "r"(fdone + 12), "r"(mate ? 35 - n : n) : "memory");
  }
  __syncthreads();
  int h; asm volatile("ld.shared.b32 %0, [%1];" : "=r"(h) : "r"(fdone + 12) : "memory");
  h = __shfl_sync(~0u, h, 0);
  if (h == 35) return;
  const int cb = h % 5, ks = h / 5, h0 = ks < 4 ? 5 * ks : 4 + 4 * ks, nh = ks < 4 ? 5 : 4;
  const int nseg = DBGF(16) ? 0 : NSEG;
  auto since = [&](uint32_t ref) { uint32_t now; asm volatile("mov.u32 %0, %%globaltimer_lo;" : "=r"(now) :: "memory"); return (now - ((ref >> 7) << 5)) & 0x3FFFFFFF; };
  auto gate = [&](int s) {
#pragma unroll 1
    for (int guard = 0; guard < 4000; guard++) {
      uint32_t ref; asm volatile("ld.volatile.shared.b32 %0, [%1];" : "=r"(ref) : "r"(fdone + 4) : "memory");
      const int n = ref & 127;
      if (n >= p.last || n > s + p.lag || (since(ref) + p.period - p.phase) % p.period <= p.win) break;
    }
  };
  TL(0);
  if (tid == 0) {
    mbar_init(wfull, 1); mbar_init(rland, 1); mbar_init(ffull, 1);
    for (int i = 0; i < 2; i++) { mbar_init(ofull + i * 8, 2); mbar_init(ofree + i * 8, 1); mbar_init(ifull + i * 8, 1); mbar_init(ifree + i * 8, 8); mbar_init(rfull + i * 8, 1); mbar_init(rfree + i * 8, 4); }
    asm volatile("st.shared.v2.b32 [%0], {%1,%1};" :: "r"(fdone), "r"(0) : "memory");
    asm volatile("fence.proxy.async.shared::cta;" ::: "memory");
    mbar_expect(wfull, nh * 32768);
#pragma unroll 1
    for (int b = 0; b < 4 * nh; b++) tma2d(sb + ((b + 2) % 20) * 8192, &p.tmWo, cb * 128 + (b & 1) * 64, h0 * 128 + (b >> 1) * 64, wfull);
  }
  __syncthreads();
  if (w < 8) {
    asm volatile("setmaxnreg.inc.sync.aligned.u32 192;");
    const int c = w >> 2, mg = w & 3;
    const uint32_t boxoff = (((lane >> 4) << 3) + (lane & 7)) * 128 + (((2 * mg + ((lane >> 3) & 1)) ^ (lane & 7)) << 4);
    uint32_t A[36][4];
    mbar_wait(wfull, 0);
#pragma unroll
    for (int f = 0; f < 36; f++) ldsm4t(A[f][0], A[f][1], A[f][2], A[f][3], sb + 16384 + c * 8192 + boxoff + (f >> 2) * 16384 + (f & 3) * 2048);
    asm volatile("fence.proxy.async.shared::cta;" ::: "memory");
    bar_sync<1, 320>();
    TL(1);
    const uint32_t oa = sb + SD_OUT + c * 4096 + boxoff;
#pragma unroll 1
    for (int s = 0; s < nseg; s++) {
      const int b = s & 1;
      const uint64_t db = p.dhi + (uint32_t)(((sb + SD_OI) >> 4) + b * 2560), da = p.dhi + (uint32_t)(((sb + SD_WS) >> 4) + c * 512);
#define D128(x) (x)
      float acc[16];
      mbar_wait_long(ifull + b * 8, (s >> 1) & 1);
      ATS(0)
      WG_FENCE();
#pragma unroll
      for (int k = 0; k < 32; k++) wg_rs_n32(acc, A[k], D128(db + (k >> 2) * 256 + (k & 3) * 2), k);
      if (nh == 5) {
#pragma unroll
        for (int k = 32; k < 36; k++) wg_rs_n32(acc, A[k], D128(db + 2048 + (k & 3) * 2), 1);
#pragma unroll
        for (int k = 0; k < 4; k++) wg_ss_n32_ta(acc, D128(da + k * 128), D128(db + 2304 + k * 2), 1);
      }
      WG_COMMIT();
      bar_sync<2, 256>();
      WG_WAIT(0);
      ATS(1)
      if (lane == 0) mbar_arrive(ifree + b * 8);
#pragma unroll
      for (int u = 0; u < 2; u++)
        asm volatile("stmatrix.sync.aligned.m8n8.x4.trans.shared.b16 [%0], {%1,%2,%3,%4};" :: "r"(oa + u * 2048),
          "r"(pack_bf16(acc[8 * u], acc[8 * u + 1])), "r"(pack_bf16(acc[8 * u + 2], acc[8 * u + 3])), "r"(pack_bf16(acc[8 * u + 4], acc[8 * u + 5])), "r"(pack_bf16(acc[8 * u + 6], acc[8 * u + 7])) : "memory");
      asm volatile("fence.proxy.async.shared::cta;" ::: "memory");
      if (w > 0) bar_arrive<4, 256>();
      else {
        bar_sync<4, 256>();
        asm volatile(ELECT "@p cp.async.bulk.tensor.3d.global.shared::cta.bulk_group [%0, {%2, %3, %4}], [%1];\n"
          "cp.async.bulk.commit_group;\ncp.async.bulk.wait_group 0;\n@p fence.proxy.async.global;\n@p red.release.gpu.global.add.u32 [%5], 1;}"
          :: "l"(&p.tmP), "r"(sb + SD_OUT), "r"(0), "r"((s % PRING) * 32), "r"(ks * 10 + cb * 2), "l"(p.comm + FL_RDY + s * 16 + 8) : "memory");
        ATS(2)
      }
    }
    TL(5);
  } else if (w < 12) {
    asm volatile("setmaxnreg.dec.sync.aligned.u32 72;");
    const int a = w - 8, g = lane >> 2, q = lane & 3;
    const float sc2 = 0.08838834764831845f * 1.4426950408889634f;
#pragma unroll 1
    for (int s = 0; s < (h < 32 ? nseg : 0); s++) {
      const int b = s & 1;
      const uint32_t rec = sb + SD_REC + b * 30720;
      mbar_wait_long(rfull + b * 8, (s >> 1) & 1);
      ATS(1)
      if (s == 0) TL(2);
      uint32_t P[3][4]; float inv[2];
      {
        float sc[20];
        const uint64_t dq = desc_ns(rec + 1024, 128, 1024), dk = desc_ns(rec + 5120, 128, 1024);
        WG_FENCE();
#pragma unroll
        for (int k = 0; k < 8; k++) wg_ss_n40_tt(sc, dq + (k >> 2) * 640 + (k & 3) * 16, dk + (k >> 2) * 640 + (k & 3) * 16, k);
        WG_COMMIT(); WG_WAIT(0);
        ATS(2)
#pragma unroll
        for (int rh = 0; rh < 2; rh++) {
          const int row = 16 * a + 8 * rh + g;
          float v[5][2], mx = -3.0e38f;
#pragma unroll
          for (int n = 0; n < 5; n++)
#pragma unroll
            for (int e = 0; e < 2; e++) {
              const bool ok = n == 0 || (8 * (n - 1) + 2 * q + e) <= row;
              v[n][e] = ok ? sc[4 * n + 2 * rh + e] * sc2 : -1.0e9f * 1.4426950408889634f; mx = fmaxf(mx, v[n][e]);
            }
          mx = fmaxf(mx, __shfl_xor_sync(~0u, mx, 1)); mx = fmaxf(mx, __shfl_xor_sync(~0u, mx, 2));
          float sum = 0.f;
#pragma unroll
          for (int n = 0; n < 5; n++) { const float e0 = ex2(v[n][0] - mx), e1 = ex2(v[n][1] - mx); sum += e0 + e1; P[n >> 1][(n & 1) * 2 + rh] = pack_bf16(e0, e1); }
          P[2][2 + rh] = 0u;
          sum += __shfl_xor_sync(~0u, sum, 1); sum += __shfl_xor_sync(~0u, sum, 2);
          asm("rcp.approx.ftz.f32 %0, %1;" : "=f"(inv[rh]) : "f"(sum));
        }
      }
      ATS(3)
      mbar_wait_long(ofree + b * 8, ((s >> 1) & 1) ^ 1);
      ATS(4)
      const uint32_t od = sb + SD_O + b * 8192 + (16 * a + (lane & 15)) * 128;
#pragma unroll 1
      for (int hf = 0; hf < 2; hf++) {
        float o[32];
        const uint64_t dv = desc_ns(rec + 20480 + hf * 5120, 1024, 128);
        WG_FENCE();
        wg_rs_n64(o, P[0], dv, 0); wg_rs_n64(o, P[1], dv + 128, 1); wg_rs_n64(o, P[2], desc_ns(rec + 20480 + hf * 5120 + 4096, 0, 128), 1);
        WG_COMMIT(); WG_WAIT(0);
        if (a < 2) {
#pragma unroll
          for (int n = 0; n < 8; n += 2) {
            const float* x = o + 4 * n;
            asm volatile("stmatrix.sync.aligned.m8n8.x4.shared.b16 [%0], {%1,%2,%3,%4};" :: "r"(od + hf * 4096 + (((n + (lane >> 4)) ^ (lane & 7)) << 4)),
              "r"(pack_bf16(x[0] * inv[0], x[1] * inv[0])), "r"(pack_bf16(x[2] * inv[1], x[3] * inv[1])), "r"(pack_bf16(x[4] * inv[0], x[5] * inv[0])), "r"(pack_bf16(x[6] * inv[1], x[7] * inv[1])) : "memory");
          }
        }
      }
      if (a < 2) {
        asm volatile("fence.proxy.async.shared::cta;" ::: "memory");
        __syncwarp();
        if (lane == 0) mbar_arrive(ofull + b * 8);
      }
      if (lane == 0) mbar_arrive(rfree + b * 8);
      ATS(5)
    }
    TL(3);
  } else {
    asm volatile("setmaxnreg.dec.sync.aligned.u32 56;");
    if (w == 13) {
      bar_sync<1, 320>();
#pragma unroll 1
      for (int s = 0; s < nseg; s++) {
        mbar_wait_long(ifree + (s & 1) * 8, ((s >> 1) & 1) ^ 1);
        wait_count(p.comm + FL_RDY + s * 16 + ks, nh);
        gate(s + 2);
        ATS(0)
        asm volatile(ELECT "@p mbarrier.arrive.expect_tx.shared.b64 _, [%2], %3;\n@p cp.async.bulk.shared::cluster.global.mbarrier::complete_tx::bytes [%0], [%1], %3, [%2];}"
          :: "r"(sb + SD_OI + (s & 1) * 40960), "l"(p.O + (size_t)((s % ORING) * 32 + h0) * 8192), "r"(ifull + (s & 1) * 8), "r"(nh * 8192) : "memory");
      }
    } else if (h >= 32 && w < 15) {
    } else if (w == 12) {
#pragma unroll 1
      for (int s = 0; s < nseg; s++) {
        mbar_wait_long(ofull + (s & 1) * 8, (s >> 1) & 1);
        int fin, guard = 0;
        do { asm volatile("ld.volatile.shared.b32 %0, [%1];" : "=r"(fin) : "r"(fdone) : "memory"); } while (fin + ORING <= s && ++guard < 1000000);
        ATS(0)
        asm volatile(ELECT "@p cp.async.bulk.global.shared::cta.bulk_group [%0], [%1], 8192;\n"
          "cp.async.bulk.commit_group;\ncp.async.bulk.wait_group 0;\n@p mbarrier.arrive.shared.b64 _, [%3];\n@p fence.proxy.async.global;\n@p red.release.gpu.global.add.u32 [%2], 1;}"
          :: "l"(p.O + (size_t)((s % ORING) * 32 + h) * 8192), "r"(sb + SD_O + (s & 1) * 8192), "l"(p.comm + FL_RDY + s * 16 + (h < 20 ? h / 5 : (h - 4) >> 2)), "r"(ofree + (s & 1) * 8) : "memory");
        ATS(1)
      }
      TL(4);
    } else if (w == 14) {
      if (DBGF(16)) pdl_wait(); else
      mbar_wait_long(ofull, 0);
#pragma unroll 1
      for (int s = 0; s < nseg; s++) {
        asm volatile("fence.proxy.async.shared::cta;" ::: "memory");
        __syncwarp();
        asm volatile(ELECT "@p mbarrier.arrive.expect_tx.shared.b64 _, [%2], 10240;\n@p cp.async.bulk.shared::cluster.global.mbarrier::complete_tx::bytes [%0], [%1], 1280, [%2];}"
          :: "r"(sb + SD_FIN + 8960), "l"(p.x1 + (size_t)(s * 32 + h) * D_), "r"(ffull) : "memory");
        wait_count(p.comm + FL_RDY + s * 16 + 8, 35);
        ATS(0)
        asm volatile(ELECT "@p cp.async.bulk.shared::cluster.global.mbarrier::complete_tx::bytes [%0], [%1], 8960, [%2];}"
          :: "r"(sb + SD_FIN), "l"(p.part + (size_t)((s % PRING) * 32 + h) * 8960), "r"(ffull) : "memory");
        mbar_wait_long(ffull, s & 1);
        ATS(1)
        asm volatile("st.volatile.shared.b32 [%0], %1;" :: "r"(fdone), "r"(s + 1) : "memory");
#pragma unroll
        for (int i = 0; i < 5; i++) {
          uint32_t v[8][2];
#pragma unroll
          for (int u = 0; u < 8; u++) asm volatile("ld.shared.v2.b32 {%0,%1}, [%2];" : "=r"(v[u][0]), "=r"(v[u][1]) : "r"(sb + SD_FIN + u * 1280 + i * 256 + lane * 8) : "memory");
          uint32_t y[2];
#pragma unroll
          for (int k = 0; k < 2; k++) {
            y[k] = pack_bf16(((bf_lo(v[0][k]) + bf_lo(v[1][k])) + (bf_lo(v[2][k]) + bf_lo(v[3][k]))) + ((bf_lo(v[4][k]) + bf_lo(v[5][k])) + bf_lo(v[6][k])),
                             ((bf_hi(v[0][k]) + bf_hi(v[1][k])) + (bf_hi(v[2][k]) + bf_hi(v[3][k]))) + ((bf_hi(v[4][k]) + bf_hi(v[5][k])) + bf_hi(v[6][k])));
            asm("add.rn.bf16x2 %0, %0, %1;" : "+r"(y[k]) : "r"(v[7][k]));
          }
          *(uint2*)(p.out + (size_t)(s * 32 + h) * D_ + i * 128 + lane * 4) = make_uint2(y[0], y[1]);
        }
        __syncwarp();
        if (lane == 0 && p.first) red_release(p.comm + FL_RDY + s * 16 + 12);
        ATS(2)
      }
    } else {
      uint32_t lp = 0, known = 0;
      bar_sync<1, 320>();
#pragma unroll 1
      for (int s = 0; s < nseg; s++) {
        const int b = s & 1;
        const uint32_t rec = sb + SD_REC + b * 30720;
        if (h < 32) mbar_wait_long(rfree + b * 8, ((s >> 1) & 1) ^ 1);
        uint32_t f = ~0u;
#pragma unroll 1
        for (int guard = 0; guard < 100000; guard++) {
          if (lane < 3) asm volatile("ld.relaxed.gpu.global.u32 %0, [%1];" : "=r"(f) : "l"(p.comm + FL_MEM + (h & 31) * 32 + lane * 8) : "memory");
          known = __reduce_min_sync(~0u, f & 127);
          if (known > (uint32_t)s) break;
        }
        f = __shfl_sync(~0u, f, 0);
        if (lane == 0) asm volatile("st.volatile.shared.b32 [%0], %1;" :: "r"(fdone + 4), "r"(f) : "memory");
        if (h >= 32) continue;
        __syncwarp();
        const char* src = p.QKV + (size_t)((s % QRING) * 32 + h) * 30720;
#pragma unroll 1
        for (int tries = 0; tries < 20000; tries++) {
          if ((f & 127) == s + 1 && tries == (s >= NSEG - 2)) { const uint32_t t = s == NSEG - 1 ? p.tmem - 512 : p.tmem; for (int guard = 0; since(f) < t && guard < 4000; guard++) {} }
          if (tries == 0) gate(s);
          ATS(0)
          asm volatile("fence.proxy.async.shared::cta;" ::: "memory");
          __syncwarp();
          if (tries == 0) asm volatile(ELECT "@p mbarrier.arrive.expect_tx.shared.b64 _, [%2], 30720;\n@p cp.async.bulk.shared::cluster.global.mbarrier::complete_tx::bytes [%0], [%1], 30720, [%2];}" :: "r"(rec), "l"(src), "r"(rland) : "memory");
          else asm volatile(ELECT "@p mbarrier.arrive.expect_tx.shared.b64 _, [%2], 4096;\n"
            "@p cp.async.bulk.shared::cluster.global.mbarrier::complete_tx::bytes [%0+5120], [%1+5120], 1024, [%2];\n@p cp.async.bulk.shared::cluster.global.mbarrier::complete_tx::bytes [%0+15360], [%1+15360], 1024, [%2];\n"
            "@p cp.async.bulk.shared::cluster.global.mbarrier::complete_tx::bytes [%0+20480], [%1+20480], 1024, [%2];\n@p cp.async.bulk.shared::cluster.global.mbarrier::complete_tx::bytes [%0+25600], [%1+25600], 1024, [%2];}"
            :: "r"(rec), "l"(src), "r"(rland) : "memory");
          mbar_wait_long(rland, lp); lp ^= 1;
          uint32_t mx = 0;
#pragma unroll
          for (int k = 0; k < 4; k++) { uint32_t v; asm volatile("ld.shared.b32 %0, [%1];" : "=r"(v) : "r"(rec + (k == 0 ? 5120 : 10240 + k * 5120) + lane * 32 + (lane >> 2) * 4) : "memory"); mx = max(mx, v); }
          if (__all_sync(~0u, mx != ~0u)) break;
        }
        if (lane == 0) { mbar_arrive(rfull + b * 8); asm volatile("st.relaxed.gpu.global.u32 [%0], %1;" :: "l"(p.comm + FL_MEM + h * 32 + 24), "r"(s + 1) : "memory"); }
      }
    }
    if (w == 14) { TL(6); __syncwarp(); TL_DUMP((p.first ^ 1) * 166 + 131 + h, lane); }
    if (!p.first && tid == 448 && h == 0) { for (int i = 0; i < 8; i++) p.sync[i * 32 - 128] = 0; }
  }
}

__device__ __forceinline__ uint32_t ld_relaxed(const void* p) { uint32_t v; asm volatile("ld.relaxed.gpu.global.u32 %0, [%1];" : "=r"(v) : "l"(p) : "memory"); return v; }
__device__ __forceinline__ void st_relaxed(void* p, uint32_t v) { asm volatile("st.relaxed.gpu.global.u32 [%0], %1;" :: "l"(p), "r"(v) : "memory"); }
__device__ __forceinline__ void st_relaxed_if(void* p, uint32_t v, uint32_t c) { asm volatile("{.reg .pred p; setp.ne.u32 p, %2, 0; @p st.relaxed.gpu.global.u32 [%0], %1;}" :: "l"(p), "r"(v), "r"(c) : "memory"); }
__device__ __forceinline__ uint32_t clk32() { uint32_t c; asm volatile("mov.u32 %0, %%clock;" : "=r"(c) :: "memory"); return c; }
__device__ __forceinline__ uint32_t gt32() { uint64_t c; asm volatile("mov.u64 %0, %%globaltimer;" : "=l"(c) :: "memory"); return (uint32_t)c; }
__device__ __forceinline__ void wait_gt(uint32_t T) {
  asm volatile("{\n.reg .pred p;\n.reg .u64 t;\n.reg .u32 lo, hi;\nLG%=:\nmov.u64 t, %%globaltimer;\nmov.b64 {lo, hi}, t;\nsub.u32 lo, lo, %0;\nsetp.lt.s32 p, lo, 0;\n@p bra.uni LG%=;\n}" :: "r"(T) : "memory");
}
__device__ __forceinline__ void advance(uint32_t& T, uint32_t lim, uint32_t step) {
  asm volatile("{\n.reg .pred p;\n.reg .s32 d;\nLA%=:\nsub.s32 d, %1, %0;\nsetp.gt.s32 p, d, 0;\n@p add.u32 %0, %0, %2;\n@p bra.uni LA%=;\n}" : "+r"(T) : "r"(lim), "r"(step));
}
template <int LUT> __device__ __forceinline__ uint32_t lop3(uint32_t a, uint32_t b, uint32_t c) { uint32_t r; asm("lop3.b32 %0, %1, %2, %3, %4;" : "=r"(r) : "r"(a), "r"(b), "r"(c), "n"(LUT)); return r; }
__device__ __forceinline__ uint32_t ldsm1t(uint32_t a) { uint32_t r; asm volatile("ldmatrix.sync.aligned.m8n8.x1.trans.shared.b16 {%0}, [%1];" : "=r"(r) : "r"(a) : "memory"); return r; }
__device__ __forceinline__ uint32_t hmax2(uint32_t a, uint32_t b) { uint32_t r; asm("max.bf16x2 %0, %1, %2;" : "=r"(r) : "r"(a), "r"(b)); return r; }
__device__ __forceinline__ uint32_t lds32(uint32_t a) { uint32_t v; asm volatile("ld.shared.b32 %0, [%1];" : "=r"(v) : "r"(a) : "memory"); return v; }
__device__ __forceinline__ void sts32(uint32_t a, uint32_t v) { asm volatile("st.shared.b32 [%0], %1;" :: "r"(a), "r"(v) : "memory"); }
__device__ __forceinline__ uint32_t mapa(uint32_t a, int rank) { uint32_t r; asm("mapa.shared::cluster.u32 %0, %1, %2;" : "=r"(r) : "r"(a), "r"(rank)); return r; }
template <int OFF> __device__ __forceinline__ void stas32(uint32_t a, uint32_t v, uint32_t bar) {
  asm volatile("st.async.weak.shared::cluster.mbarrier::complete_tx::bytes.b32 [%0+%3], %1, [%2];" :: "r"(a), "r"(v), "r"(bar), "n"(OFF) : "memory");
}
#define OPAQUE(x) x = __shfl_sync(~0u, x, lane)
#define CLUSTER_SYNC() asm volatile("barrier.cluster.arrive.release.aligned; barrier.cluster.wait.acquire.aligned;" ::: "memory")

constexpr int SM_BAR = 0;
constexpr int SM_WO = 2048;
constexpr int SM_VR = 43008;
constexpr int SM_RED = 59392;
constexpr int SM_AT = 67584;
constexpr int SM_MEMT = 108672;
constexpr int SM_QK = 119040;
constexpr int SM_SC = 123136;
constexpr int SM_OX = 125184;
constexpr int SM_VM = 127744;
constexpr int SM_ST = 139264;
constexpr int SM_X = 149504;
constexpr int SM_WST = 2048;
constexpr int SM_WS = 67584;
constexpr int REC_SMEM = 231424 + 1024;
constexpr int MB_A = 0, MB_QK = 24, MB_R = 32, MB_V = 56, MB_KV = 64, MB_X = 80, MB_IA = 96, MB_IC = 104, MB_TK = 112, MB_PRB = 120, MB_DP = 128, MB_TAB = 256, MB_T2 = 512;
#define NTQ 10
#define NTV 4
#define NB0 4
#define PINK 14
#define NB1 7
#define PINT 5
#define WPLAN 0x5542110
#define OPF 3
#define XPOS 1
#define W0K 4
#define NLATE 1
#define VPOS 0
#define XK 2
#define IMM 1
#define GATEK 3
#define TOLQ 96
#define TOLV 160
constexpr int POLL_LIMIT = 20000;
constexpr int CM_X3 = 160, CM_MISC = 172;
__device__ __forceinline__ uint32_t x3_slot(int slot) { return (CM_X3 + (slot & 1) * 64 + (slot & 2) * 128) * 4096; }
__device__ __forceinline__ int near_page(int pg, int side) { return pg + ((__popc(pg & 0xB3) ^ side) & 1); }
__device__ __forceinline__ int mem_line(int jb) { const int ks = jb >> 1, c = ks >= 20, kk = ks - 20 * c; return (kk >> 2) * 16 + c * 8 + (kk & 3) * 2 + (jb & 1); }

struct RecParams {
  CUtensorMap tmW[3], tmWo, tmX;
  AParams a[2];
  const bf16 *mem0, *wr, *wi;
  char* QKV;
  uint32_t* comm;
  uint64_t dhi;
  int period, c3, slack, xlate, extra, gap, zero, helper, layer, dbgf;
  uint32_t *dbg, *log;
};
#define PRB(k)
#define LDW(d, a) ldsm4t(d[0], d[1], d[2], d[3], a)

#undef TLBASE
#define TLBASE (1024 + 896)
#define PRBASE (mbar + w * 16)
#define PRIMM 1024
#define PROFF 0
template <bool VR>
__device__ __forceinline__ void rec_gemm_warps(const RecParams& p, const uint32_t sb, const int h, const int r, const int L, const int w) {
  const int tid = tid_here(), lane = tid & 31;
  const int mg = w & 3, c = w >> 2;
  constexpr int NT = VR ? NTV : NTQ, NW = VR ? 8 : 16;
  uint32_t R[20][4], P[20][4], Wr[NW - NT][4];
  const uint32_t mbar = sb + SM_BAR;
  uint32_t l16 = lane * 16, lm = (lane >> 4) * 1024 + (lane & 15) * 16;
  OPAQUE(l16); OPAQUE(lm);
#define wl16 (l16 + (sb + w * 512))
  {
    const uint32_t boxoff = (((lane >> 4) << 3) + (lane & 7)) * 128 + (((2 * mg + ((lane >> 3) & 1)) ^ (lane & 7)) << 4);
    mbar_wait(mbar + MB_IA, 0);
    TL(15);
    const uint32_t wa = sb + SM_WS + c * 40960 + boxoff;
#pragma unroll
    for (int k = 0; k < 20; k++) LDW(R[k], wa + 81920 + k * 2048);
    bar_arrive<4, 288>();
#pragma unroll
    for (int k = 0; k < 20; k++) LDW(P[k], wa + k * 2048);
    bar_sync<2, 256>();
#pragma unroll
    for (int i = 0; i < NT; i++) sts128(wl16 + SM_AT + i * 4096, P[i][0], P[i][1], P[i][2], P[i][3]);
    mbar_wait(mbar + MB_IC, 0);
    TL(16);
    const uint32_t woa = sb + SM_WST + c * 16384 + boxoff;
#pragma unroll
    for (int i = 0; i < NW; i++) {
      const uint32_t a = woa + (VR ? i * 2048 : (i & 1) * 32768 + (i >> 1) * 2048);
      if (i >= 4 && i < 4 + NW - NT) LDW(Wr[i - 4], a); else LDW(P[i < 4 ? i : i - (NW - NT)], a);
    }
    asm volatile("fence.proxy.async.shared::cta;" ::: "memory");
    bar_sync<1, 384>();
#pragma unroll
    for (int i = 0; i < NT; i++) sts128(wl16 + SM_WO + i * 4096, P[i][0], P[i][1], P[i][2], P[i][3]);
    asm volatile("barrier.cluster.arrive.relaxed.aligned; barrier.cluster.wait.aligned;" ::: "memory");
  }
#define LDT(i) lds128(P[i], wl16 + SM_AT + (i) * 4096)
#define WGX(acc, A, ks, sc) wg_rs_n32(acc, A[ks], d##A + (((ks) >> 2) * 256 + ((ks) & 3) * 2), sc)
  float tb[16];
  constexpr int KW = VR ? 20 - W0K : 20;
  auto stream0 = [&](int n) {
    const uint64_t dP = p.dhi + (uint32_t)(((sb + SM_X + c * 20480) >> 4) + (n & 1) * 2560 + ((n + 1) & p.zero));
    WG_FENCE();
#pragma unroll
    for (int k = KW; k < 20; k++) WGX(tb, P, k, k - KW);
    WG_COMMIT();
  };
  auto stream = [&](int n) {
    float ta[16];
    const uint64_t dR = p.dhi + (uint32_t)(((sb + SM_X + c * 20480) >> 4) + (n & 1) * 2560), dP = dR + (uint32_t)(~n & p.zero);
    WG_FENCE();
    constexpr int NE = NT - (VR ? NLATE : 4);
#pragma unroll
    for (int k = 0; k < 20; k++) { WGX(ta, R, k, k); if ((k & 1) && k / 2 < NE) LDT(k / 2); }
    WG_COMMIT();
#define GATE(i) if (VR && (i) == GATEK) { if (GATEK) WG_COMMIT(); asm volatile("bar.sync 12, %0;" :: "r"((h & 1) ? 320 : 352) : "memory"); WG_FENCE(); }
    constexpr int K2 = VR ? NT + XK : 16;
#pragma unroll
    for (int k = K2; k < KW; k++) { GATE(k - K2); WGX(tb, P, k, KW < 20 || k > K2); }
    WG_COMMIT();
    WG_WAIT(1);
#pragma unroll
    for (int i = 0; i < 2; i++)
      sts128(l16 + (sb + (w ^ 4) * 512) + SM_RED + i * 4096, pack_bf16(ta[8 * i], ta[8 * i + 1]), pack_bf16(ta[8 * i + 2], ta[8 * i + 3]), pack_bf16(ta[8 * i + 4], ta[8 * i + 5]), pack_bf16(ta[8 * i + 6], ta[8 * i + 7]));
#pragma unroll
    for (int i = NE; i < NT; i++) LDT(i);
#pragma unroll
    for (int k = NT; k < K2; k++) { GATE(KW - K2 + k - NT); WGX(tb, P, k, 1); }
    WG_FENCE();
#pragma unroll
    for (int k = 0; k < NE; k++) WGX(tb, P, k, 1);
    bar_sync<11, 384>();
    uint32_t o[2][4];
    lds128(o[0], wl16 + SM_RED); lds128(o[1], wl16 + SM_RED + 4096);
    WG_FENCE();
#pragma unroll
    for (int k = NE; k < NT; k++) WGX(tb, P, k, 1);
    WG_COMMIT();
    WG_WAIT(0);
#pragma unroll
    for (int i = 0; i < 2; i++)
      asm volatile("stmatrix.sync.aligned.m8n8.x4.shared.b16 [%0], {%1,%2,%3,%4};" :: "r"(lm + (sb + (c ^ 1) * 5120 + mg * 256) + SM_ST + 1024 + i * 2048),
        "r"(hadd2(pack_bf16(tb[8 * i], tb[8 * i + 1]), o[i][0])), "r"(hadd2(pack_bf16(tb[8 * i + 2], tb[8 * i + 3]), o[i][1])),
        "r"(hadd2(pack_bf16(tb[8 * i + 4], tb[8 * i + 5]), o[i][2])), "r"(hadd2(pack_bf16(tb[8 * i + 6], tb[8 * i + 7]), o[i][3])) : "memory");
    bar_arrive<14, 320>();
  };
  int s = -2, att = 0;
#pragma unroll 1
  while (true) {
    if (s >= 0) {
    uint32_t B[10][4], Wf[NT][4], dp[4];
    float ap[2][4], ar[2][4];
#define LDO(i, base) lds128(Wf[i], (base) + SM_WO + (i) * 4096)
#define LDB(k2) ldsm4t(B[k2][0], B[k2][1], B[k2][2], B[k2][3], l16 + (sb + c * 1024) + SM_MEMT + ((k2) >> 1) * 2048 + ((k2) & 1) * 512)
#define BK(k) B[(k) >> 1][((k) & 1) * 2], B[(k) >> 1][((k) & 1) * 2 + 1]
    mbar_wait(mbar + MB_A, att & 1);
    PRB(0)
    LDB(0); LDB(1);
#pragma unroll
    for (int k = 0; k < 20; k++) {
      if (!(k & 1) && k < 16) LDB(k / 2 + 2);
      if (k == PINK) {
        const uint32_t wb = lop3<0xF8>(l16, __float_as_uint(ap[0][0]), p.zero) + (sb + w * 512);
#pragma unroll
        for (int u = 0; u < NB0 && u < NT; u++) LDO(u, wb);
      }
      if (k < 2) { mmaZ(ap[k], P[k], BK(k)); mmaZ(ar[k], R[k], BK(k)); } else { mmaA(ap[k & 1], P[k], BK(k)); mmaA(ar[k & 1], R[k], BK(k)); }
    }
    asm volatile("stmatrix.sync.aligned.m8n8.x4.shared.b16 [%0], {%1,%2,%3,%4};" :: "r"(lm + (sb + c * 2048 + mg * 256) + SM_QK),
      "r"(pack_bf16(ar[0][0] + ar[1][0], ar[0][1] + ar[1][1])), "r"(pack_bf16(ar[0][2] + ar[1][2], ar[0][3] + ar[1][3])),
      "r"(pack_bf16(ap[0][0] + ap[1][0], ap[0][1] + ap[1][1])), "r"(pack_bf16(ap[0][2] + ap[1][2], ap[0][3] + ap[1][3])) : "memory");
    bar_arrive<9, 384>();
    PRB(1)
    att++;
    uint32_t bad;
    asm volatile("{.reg .pred p; setp.ne.u32 p, 0, 0; bar.red.or.pred p, 8, 384, p; selp.u32 %0, 1, 0, p;}" : "=r"(bad) :: "memory");
    if (bad) {
#pragma unroll
      for (int i = 0; i < NT; i++) LDT(i);
      continue;
    }
    if (s == NSEG - 1) break;
    if (KW < 20) stream0(s);
    lds128(dp, mbar + MB_DP + w * 16);
#pragma unroll
    for (int i = NB0; i < NT && (VR || i < NB1); i++) LDO(i, wl16);
    uint32_t fmask = (~(l16 | dp[0]) >> 4) & 1, bit = ((s >> 1) & 1) ? 0u : fmask;
    char* cb = (char*)p.comm + ((s & 1) * (256 * 4096) + (l16 >> 2));
    char *d0 = cb + dp[0], *d1 = cb + dp[1], *d2 = cb + dp[2], *d3 = cb + dp[3];
    if (VR) asm volatile("" : "+l"(d0), "+l"(d1), "+r"(bit), "+r"(fmask)); else asm volatile("" : "+l"(d0), "+l"(d1), "+l"(d2), "+l"(d3), "+r"(bit), "+r"(fmask));
    if (KW < 20) WG_WAIT(0);
    sched_fence();
    if (VR) bar_arrive<2, 384>();
    else {
      bar_sync<2, 384>();
#pragma unroll
      for (int i = NB1; i < NT; i++) LDO(i, wl16);
    }
    bar_sync<3, 384>();
    PRB(2)
    uint32_t ob[4][4];
    float z0, z1;
#pragma unroll
    for (int i = 0; i < 4; i++) LDW(ob[i], l16 + sb + SM_OX + i * 512);
    asm volatile("ld.shared.v2.f32 {%0,%1}, [%2];" : "=f"(z0), "=f"(z1) : "r"(l16 + sb + SM_OX + 2048) : "memory");
#define WO(i) ((i) >= 4 && (i) < 4 + NW - NT ? Wr[(i) >= 4 && (i) < 4 + NW - NT ? (i) - 4 : 0] : Wf[(i) < 4 ? (i) : (i) < 4 + NW - NT ? 0 : (i) - (NW - NT)])
    float ga[4][4];
#pragma unroll
    for (int i = 0; i < NW; i++) {
      const int ks = VR ? i : i >> 1;
      if (i < 4) mmaZ(ga[i], WO(i), ob[ks >> 1][(ks & 1) * 2], ob[ks >> 1][(ks & 1) * 2 + 1]); else mmaA(ga[i & 3], WO(i), ob[ks >> 1][(ks & 1) * 2], ob[ks >> 1][(ks & 1) * 2 + 1]);
    }
    asm("rcp.approx.ftz.f32 %0, %0;" : "+f"(z0)); asm("rcp.approx.ftz.f32 %0, %0;" : "+f"(z1));
#pragma unroll
    for (int i = 0; i < 4; i++) { ga[0][i] += ga[2][i]; ga[1][i] += ga[3][i]; if (VR) ga[0][i] += ga[1][i]; }
#pragma unroll
    for (int t = 0; t < NW / 8; t++) {
      st_relaxed(t ? d2 : d0, lop3<0xF4>(bit, pack_bf16(ga[t][0] * z0, ga[t][1] * z1), fmask));
      st_relaxed(t ? d3 : d1, lop3<0xF4>(bit, pack_bf16(ga[t][2] * z0, ga[t][3] * z1), fmask));
    }
    PRB(3)
    } else { mbar_wait(mbar + MB_X + (s & 1) * 8, 0); if (KW < 20) { stream0(s); WG_WAIT(0); } }
    bar_sync<10, 256>();
    stream(s);
    PRB(4)
    s++;
  }
  if (__all_sync(~0u, lds32(mbar + MB_TAB + 4) == 0)) {
#pragma unroll
    for (int i = 0; i < NT; i++) LDT(i);
    bar_sync<1, 384>();
    const int ln = l16 >> 4;
    const uint32_t wa = sb + SM_WS + c * 40960 + (((ln >> 4) << 3) + (ln & 7)) * 128 + (((2 * mg + ((ln >> 3) & 1)) ^ (ln & 7)) << 4);
#pragma unroll
    for (int k = 0; k < 40; k++) {
      const uint32_t* f = k < 20 ? R[k % 20] : P[k % 20];
      asm volatile("stmatrix.sync.aligned.m8n8.x4.trans.shared.b16 [%0], {%1,%2,%3,%4};" :: "r"(wa + (k < 20 ? 81920 : 0) + (k % 20) * 2048), "r"(f[0]), "r"(f[1]), "r"(f[2]), "r"(f[3]) : "memory");
    }
  }
#undef wl16
}

#undef PRBASE
#undef PRIMM
#undef PROFF
#define PRBASE (mbar + j * 16)
#define PRIMM (1024 + 4)
#define PROFF 8
__device__ __forceinline__ void x_load(const RecParams& p, const uint32_t sb, int n) {
  if (DBGF(32)) { if ((threadIdx.x & 31) == 0) mbar_arrive(sb + SM_BAR + MB_X + (n & 1) * 8); return; }
  asm volatile(ELECT "@p mbarrier.arrive.expect_tx.shared.b64 _, [%2], 40960;\n"
    "@p cp.async.bulk.tensor.3d.shared::cluster.global.mbarrier::complete_tx::bytes [%0], [%1, {%3, %4, %3}], [%2];}"
      :: "r"(sb + SM_X + (n & 1) * 40960), "l"(&p.tmX), "r"(sb + SM_BAR + MB_X + (n & 1) * 8), "r"(0), "r"(n * 32) : "memory");
}
__device__ __forceinline__ int rec_attn_setup(const RecParams& p, const uint32_t sb, const int h, const int r, const int L, const int j) {
  const int ct = tid_here() - 256, lane = ct & 31;
  const uint32_t mbar = sb + SM_BAR;
  uint32_t* misc = p.comm + CM_MISC * 1024;
  if (j == 2 && lane == 0 && L == 0) {
    uint32_t b0 = 60000, b1 = 60000;
#pragma unroll 1
    for (int it = 0; it < 40; it++) {
      uint32_t* a = misc + (it & 1) * 1024 + 128 + blockIdx.x * 8;
      const uint32_t t0 = clk32();
      uint32_t v; asm volatile("atom.relaxed.gpu.global.exch.b32 %0, [%1], %2;" : "=r"(v) : "l"(a), "r"(t0) : "memory");
      st_relaxed_if(a, 0, v == t0 + 1);
      const uint32_t t = clk32() - t0;
      if (it & 1) b1 = min(b1, t); else b0 = min(b0, t);
      if (it >= 5 && min(b0, b1) < 370 && min(b0, b1) + 80 < max(b0, b1)) break;
    }
    sts32(mbar + MB_PRB, b0); sts32(mbar + MB_PRB + 4, b1);
  }
  if (ct == 32 && L == 0) { uint32_t sm; asm volatile("mov.u32 %0, %%smid;" : "=r"(sm)); st_relaxed(p.comm + FL_SM + sm, 1); }
  if (blockIdx.x == 0 && ct == 0 && L == 0) st_relaxed(misc + 96, gt32() & ~31u);
  bar_sync<15, 128>();
  const uint32_t b0 = lds32(mbar + MB_PRB), b1 = lds32(mbar + MB_PRB + 4);
  const int side = __shfl_sync(~0u, ((b1 < b0) ^ __popc(CM_MISC & 0xB3)) & 1, 0);
  if (r == 2 && lane == 0 && j + (h & 1) < 3) st_relaxed(misc + (j < 2 ? 2 * h + j : 64 + (h >> 1)), side);
  if (j < 2) {
    const int job = 2 * (16 * r + (lane >> 2) + ((lane & 2) && r < 2 ? 8 : 0)) + (lane & 1);
    uint32_t v; int guard = 0;
    do { v = ld_relaxed(misc + (j ? 96 : job)); } while (v == 0xFFFFFFFFu && ++guard < 1000000);
    sts32(mbar + (j ? MB_TK : MB_DP + lane * 4), j ? v + (gt32() - v) / p.slack * p.slack : near_page(2 * job, v) * 4096 + h * 128);
    __syncwarp();
  }
  uint32_t m0[5][4];
#pragma unroll
  for (int i = 0; i < 20; i++) m0[i >> 2][i & 3] = *(const uint32_t*)(p.mem0 + (lane >> 2) * D_ + (j * 20 + i) * 8 + (lane & 3) * 2);
  if (j == 3) {
    spin_count(p.a[L].sync + SY_3, 128);
    bar_sync<4, 288>();
    asm volatile("fence.proxy.async;" ::: "memory");
    x_load(p, sb, 0); x_load(p, sb, 1);
    TL(17);
  }
  bar_sync<1, 384>();
  asm volatile("barrier.cluster.arrive.relaxed.aligned;" ::: "memory");
#pragma unroll
  for (int i = 0; i < 5; i++)
    asm volatile("stmatrix.sync.aligned.m8n8.x4.trans.shared.b16 [%0], {%1,%2,%3,%4};" :: "r"(sb + SM_MEMT + mem_line(j * 20 + i * 4) * 128 + lane * 16), "r"(m0[i][0]), "r"(m0[i][1]), "r"(m0[i][2]), "r"(m0[i][3]) : "memory");
  sts128(sb + SM_ST + (ct >> 6) * 5120 + (ct & 63) * 16, ~0u, ~0u, ~0u, ~0u);
  asm volatile("barrier.cluster.wait.aligned;" ::: "memory");
  return side;
}
__device__ __forceinline__ void rec_attn_warps(const RecParams& p, const uint32_t sb, char* smem, const int h, const int r, const int side, const int L, const int j) {
  const int lane = tid_here() & 31, mi = lane >> 3;
  const uint32_t mbar = sb + SM_BAR;
#define VR (r == 2)
#define is_red (j + (h & 1) < 3 * r - 3)
  uint32_t l16 = sb + lane * 16;
#define wr16 (l16 + j * 512)
#define L0 ((l16 & 511) == 0)
  uint32_t ka = VR ? (mi != (lane & 3) ? 0u : (lane & 4) ? 0x3F800000u : 0x00003F80u)
    : j < 2 ? sb + SM_ST + 6144 + (2 * j + (mi & 1)) * 1024 + ((mi >> 1) * 8 + (lane & 7)) * 16 : sb + SM_QK + j * 512 + ((mi & 1) * 16 + (mi >> 1) * 8 + (lane & 7)) * 16;
  uint32_t own = VR ? sb + SM_AT + 28672 + j * 4096 + lane * 32 + (lane & 12) * 2 : sb + SM_SC + r * 1024 + (j < 2 ? j * 256 : 256 + j * 128) + lane * 4;
  uint32_t va = sb + SM_VR + (j >> 1) * 4096 + (mi >> 1) * 1024 + ((j & 1) * 32 + (mi & 1) * 8 + (lane & 7)) * 16, ps[2], pb[2];
#pragma unroll
  for (int i = 0; i < 2; i++) {
    const int peer = VR ? i : i == 0 ? r ^ 1 : 2;
    ps[i] = mapa(VR ? wr16 + SM_VM : own, peer); pb[i] = mapa(mbar + (VR ? MB_V : MB_QK), peer);
    OPAQUE(ps[i]); OPAQUE(pb[i]);
  }
  OPAQUE(ka); OPAQUE(own); OPAQUE(va); OPAQUE(l16);
  const char* comm = (const char*)p.comm;
  const uint32_t ones = 0x3F803F80u;
  const float sc2 = 0.08838834764831845f * 1.4426950408889634f;
  uint32_t kf[4][4], vf[4][4];
#pragma unroll
  for (int i = 0; i < 16; i++) kf[i >> 2][i & 3] = vf[i >> 2][i & 3] = p.zero;
  char* const rec0 = p.QKV + (h * 3 + r) * 10240;
  uint32_t* const fl = p.comm + FL_MEM + (L * 32 + h) * 32;
#define REC(n) (rec0 + ((n) & (QRING - 1)) * (96 * 10240))
  auto m_store = [&](int n) {
    if (VR || j < 2) {
      const int jj = VR ? j : j + 2;
      uint32_t a[4], b[4]; lds128(a, l16 + jj * 512 + SM_QK); lds128(b, l16 + (jj ^ 2) * 512 + SM_QK + 2048);
      asm volatile("st.relaxed.gpu.global.v4.u32 [%0], {%1,%2,%3,%4};" :: "l"(REC(n) + ((jj >> 1) * 5120 + (j & 1) * 512) + (l16 & 511)),
        "r"(hadd2(a[0], b[0])), "r"(hadd2(a[1], b[1])), "r"(hadd2(a[2], b[2])), "r"(hadd2(a[3], b[3])) : "memory");
    }
  };
  int att = 1, rph = 0;
  const int jb = j < 2 ? 2 * h + j : 64 + (h >> 1), ln = mem_line(jb) + 16;
  const uint32_t inbox = near_page(2 * jb, side) * 4096, bline = (ln >> 5) * 16384 + (ln & 31) * 128;
#define VERDICT(bad) asm volatile("{.reg .pred p; setp.ne.u32 p, %0, 0; bar.red.or.pred p, 8, 384, p;}" :: "n"(bad) : "memory")
#pragma unroll 1
  for (int s = -2; s < NSEG - 1; s++) {
    const uint32_t par = s & 1;
    auto v_load = [&]() {
      asm volatile("cp.async.bulk.wait_group 0;" ::: "memory");
      if (VR) asm volatile(ELECT
        "@p cp.async.bulk.shared::cluster.global.mbarrier::complete_tx::bytes.multicast::cluster [%0], [%1+1024], 4096, [%2], %3;\n"
        "@p cp.async.bulk.shared::cluster.global.mbarrier::complete_tx::bytes.multicast::cluster [%0+4096], [%1+6144], 4096, [%2], %3;}"
          :: "r"(sb + SM_VR + (par ^ 1) * 8192), "l"(REC(s + 1)), "r"(mbar + MB_KV + (par ^ 1) * 8), "h"((unsigned short)7) : "memory");
    };
    auto load_v = [&]() {
      if (s >= -1) mbar_wait(mbar + MB_KV + (par ^ 1) * 8, ((s + 1) >> 1) & 1);
#pragma unroll
      for (int i = 0; i < 4; i++) ldsm4(vf[i][0], vf[i][1], vf[i][2], vf[i][3], va + (par ^ 1) * 8192 + (i >> 1) * 2048 + (i & 1) * 256);
    };
    if (s >= 0) {
    uint32_t su[6], sw[6], vm[4];
#define LDSM2T(d, a) asm volatile("ldmatrix.sync.aligned.m8n8.x2.trans.shared.b16 {%0,%1}, [%2];" : "=r"(d[4]), "=r"(d[5]) : "r"(a) : "memory")
#define HADD4(a, b) { a[0] = hadd2(a[0], b[0]); a[1] = hadd2(a[1], b[1]); a[2] = hadd2(a[2], b[2]); a[3] = hadd2(a[3], b[3]); }
    bar_sync<9, 384>();
    PRB(0)
    {
      uint32_t qf[2][4], qg[2][4];
      float sa[4][4];
      if (j + (r & 2) < 2) {
        LDW(qf[0], l16 + SM_QK); LDW(qg[0], l16 + SM_QK + 3072); LDW(qf[1], l16 + SM_QK + 512); LDW(qg[1], l16 + SM_QK + 3584);
        HADD4(qf[0], qg[0]); HADD4(qf[1], qg[1]);
#pragma unroll
        for (int i = 0; i < 4; i++) mmaZ(sa[i], kf[i], qf[i >> 1][(i & 1) * 2], qf[i >> 1][(i & 1) * 2 + 1]);
        const uint32_t t0 = pack_bf16((sa[0][0] + sa[1][0]) + (sa[2][0] + sa[3][0]), (sa[0][1] + sa[1][1]) + (sa[2][1] + sa[3][1]));
        const uint32_t t1 = pack_bf16((sa[0][2] + sa[1][2]) + (sa[2][2] + sa[3][2]), (sa[0][3] + sa[1][3]) + (sa[2][3] + sa[3][3]));
        stas32<0>(ps[0], t0, pb[0]); stas32<0>(ps[1], t0, pb[1]); stas32<128>(ps[0], t1, pb[0]); stas32<128>(ps[1], t1, pb[1]);
        sts32(own, t0); sts32(own + 128, t1);
      } else if (!VR) {
        LDW(qf[0], wr16 + SM_QK - 1024); LDW(qg[0], wr16 + SM_QK + 2048); LDW(qf[1], ka); LDW(qg[1], ka + 1024);
        HADD4(qf[0], qg[0]); HADD4(qf[1], qg[1]);
        mmaZ(sa[0], qf[1], qf[0][0], qf[0][1]); mmaZ(sa[1], qf[1], qf[0][2], qf[0][3]);
        const uint32_t t0 = pack_bf16(sa[0][0] + sa[1][2], sa[0][1] + sa[1][3]);
        stas32<0>(ps[0], t0, pb[0]); stas32<0>(ps[1], t0, pb[1]);
        sts32(own, t0);
      } else {
        ldsm4(qf[0][0], qf[0][1], qf[0][2], qf[0][3], wr16 + SM_QK); ldsm4(qg[0][0], qg[0][1], qg[0][2], qg[0][3], l16 + (j ^ 2) * 512 + SM_QK + 2048);
        HADD4(qf[0], qg[0]);
        sts128(wr16 + SM_VM, qf[0][0], qf[0][1], qf[0][2], qf[0][3]);
#pragma unroll
        for (int i = 0; i < 2; i++)
          asm volatile("st.async.weak.shared::cluster.mbarrier::complete_tx::bytes.v4.b32 [%0], {%1,%2,%3,%4}, [%5];" :: "r"(ps[i]), "r"(qf[0][0]), "r"(qf[0][1]), "r"(qf[0][2]), "r"(qf[0][3]), "r"(pb[i]) : "memory");
      }
      PRB(1)
      VERDICT(0);
      if (VR) { if (VPOS == 1 && j == 2) v_load(); mbar_wait(mbar + MB_QK, par); }
      LDW(su, l16 + SM_SC + (r & 1) * 1024); LDSM2T(su, l16 + SM_SC + 512 + (r & 1) * 1024);
      if (!VR) mbar_wait(mbar + MB_QK, par);
      PRB(2)
      LDW(sw, l16 + SM_SC + 1024 - (r & 1) * 1024); LDSM2T(sw, l16 + SM_SC + 1536 - (r & 1) * 1024);
      su[4] = hadd2(su[4], su[5]);
    }
    {
      HADD4(su, sw); su[4] = hadd2(su[4], hadd2(sw[4], sw[5]));
      uint32_t m = hmax2(hmax2(hmax2(su[0], su[1]), hmax2(su[2], su[3])), su[4]);
      const uint32_t m1 = __shfl_xor_sync(~0u, m, 1), m2 = __shfl_xor_sync(~0u, m, 2), m3 = __shfl_xor_sync(~0u, m, 3);
      float t[10];
#pragma unroll
      for (int i = 0; i < 5; i++) { t[2 * i] = bf_lo(su[i]) * sc2; t[2 * i + 1] = bf_hi(su[i]) * sc2; }
      {
        asm volatile("" : "+f"(t[0]), "+f"(t[1]), "+f"(t[2]), "+f"(t[3]), "+f"(t[4]), "+f"(t[5]), "+f"(t[6]), "+f"(t[7]), "+f"(t[8]), "+f"(t[9]));
        mbar_wait(mbar + MB_V, par | (r >> 1)); bar_arrive<2, 384>(); lds128(vm, wr16 + SM_VM);
      }
      t[PINT] = __uint_as_float(lop3<0xF8>(__float_as_uint(t[PINT]), vm[0], p.zero));
      m = hmax2(hmax2(m, m1), hmax2(m2, m3));
      const float mx = fmaxf(bf_lo(m), bf_hi(m));
#define EX(i) ex2(fmaf(mx, -sc2, t[i]))
      float o1[2][4], z[4];
      const uint32_t P0 = pack_bf16(EX(0), EX(1)), P1 = pack_bf16(EX(2), EX(3));
      mmaZ(o1[0], vf[0], P0, P1); mmaZ(o1[1], vf[1], P0, P1); mma16816z(z, ones, ones, ones, ones, P0, P1);
      const float e4 = EX(4), e5 = EX(5);
      const uint32_t P2 = pack_bf16(e4, e5), P3 = pack_bf16(EX(6), EX(7));
      mmaA(o1[0], vf[2], P2, P3); mmaA(o1[1], vf[3], P2, P3); mma16816(z, ones, ones, ones, ones, P2, P3);
      const uint32_t Pm = pack_bf16(EX(8), EX(9));
      mma1688(o1[0], vm[0], vm[1], Pm); mma1688(o1[1], vm[2], vm[3], Pm); mma1688(z, ones, ones, Pm);
      asm volatile("stmatrix.sync.aligned.m8n8.x4.shared.b16 [%0], {%1,%2,%3,%4};" :: "r"(wr16 + SM_OX),
        "r"(pack_bf16(o1[0][0], o1[0][1])), "r"(pack_bf16(o1[0][2], o1[0][3])), "r"(pack_bf16(o1[1][0], o1[1][1])), "r"(pack_bf16(o1[1][2], o1[1][3])) : "memory");
      if (j == 3) asm volatile("st.shared.v2.f32 [%0], {%1,%2};" :: "r"(l16 + SM_OX + 2048), "f"(z[0]), "f"(z[1]) : "memory");
    }
    bar_arrive<3, 384>();
    PRB(3)
    if (j == 3) asm volatile(ELECT "@p mbarrier.arrive.expect_tx.shared.b64 _, [%0+%4], %2;\n@p mbarrier.arrive.expect_tx.shared.b64 _, [%1], 8192;\n"
      "@p mbarrier.arrive.expect_tx.shared.b64 _, [%0+%5], 10368;\nsetp.ne.and.u32 p, %3, 2, p;\n@p mbarrier.arrive.expect_tx.shared.b64 _, [%0+%6], 2048;}"
        :: "r"(mbar), "r"(mbar + MB_KV + par * 8), "r"(VR ? 1536 : 768), "r"(r), "n"(MB_QK), "n"(MB_A), "n"(MB_V) : "memory");
    }
    uint32_t T3, c3;
    asm volatile("ld.shared.v2.b32 {%0,%1}, [%2];" : "=r"(T3), "=r"(c3) : "r"(mbar + MB_TK) : "memory");
    {
      const uint32_t now = gt32(), lim = now + c3 + p.gap;
      if ((int)(T3 - now) > 20000) T3 = now;
      advance(T3, lim, p.slack);
    }
    if (s >= 0) m_store(s);
    if (j + (r & 2) < 2) {
#pragma unroll
      for (int i = 0; i < 4; i++) LDW(kf[i], ka + i * 256);
    } else {
#pragma unroll
      for (int i = 0; i < 16; i++) kf[i >> 2][i & 3] = 0;
    }
    int used = 0;
    if (j == 2 && s >= -1) { if (VPOS != 1 || !VR || s < 0) v_load(); used = ld_relaxed(fl + 24); }
    if (VPOS == 1) load_v();
    bar_arrive<11, 384>();
    if (is_red) {
      const uint32_t expect = ((s >> 1) & 1) ^ 1, rb = mbar + MB_R + j * 8, stg = SM_AT + 28672 + j * 4096, s1 = ka | (s & p.zero);
      char* w0 = (char*)comm + (x3_slot(s + 1) + bline + (l16 & 511) / 4);
      asm volatile("" : "+l"(w0));
      uint32_t T2 = T3 - c3;
      if (s < 0) asm volatile("bar.arrive 12, %0;" :: "r"((h & 1) ? 320 : 352) : "memory");
      else {
#pragma unroll 1
        for (int nth = 0;; nth++) {
          wait_gt(T2);
          PRB(4)
          asm volatile(ELECT "@p cp.async.bulk.shared::cluster.global.mbarrier::complete_tx::bytes [%0], [%1], 4096, [%2];\n@p mbarrier.arrive.expect_tx.shared.b64 _, [%2], 4096;}"
            :: "r"(sb + stg), "l"(comm + (inbox + par * (256 * 4096))), "r"(rb) : "memory");
          mbar_wait(rb, rph & 1); rph++;
          uint32_t x[8][4], f[4];
          float ra[4][4];
#pragma unroll
          for (int i = 0; i < 8; i++) ldsm4(x[i][0], x[i][1], x[i][2], x[i][3], l16 + stg + i * 512);
#pragma unroll
          for (int i = 0; i < 4; i++) f[i] = lds32(own + i * 1024);
#pragma unroll
          for (int i = 0; i < 8; i++) { if (i < 4) mmaZ(ra[i], x[i], ka, s1); else mmaA(ra[i & 3], x[i], ka, s1); }
          const uint32_t ok = __all_sync(~0u, lop3<0xA8>(lop3<0x7E>(f[0], f[1], expect), lop3<0x7E>(f[2], f[3], expect), 1) == 0) || nth == POLL_LIMIT;
          const uint32_t v = pack_bf16(((ra[0][0] + ra[0][2]) + (ra[1][0] + ra[1][2])) + ((ra[2][0] + ra[2][2]) + (ra[3][0] + ra[3][2])), ((ra[0][1] + ra[0][3]) + (ra[1][1] + ra[1][3])) + ((ra[2][1] + ra[2][3]) + (ra[3][1] + ra[3][3])));
          asm volatile("{.reg .pred p, q; setp.ne.u32 p, %2, 0; setp.eq.u32 q, %4, 0; @q bar.arrive 12, %3; @p st.relaxed.gpu.global.u32 [%0], %1; @p st.relaxed.gpu.global.u32 [%0+4096], %1; @p bar.arrive 15, %5;}"
            :: "l"(w0), "r"(v), "r"(ok), "r"(lop3<0xF8>((h & 1) ? 320 : 352, __float_as_uint(ra[3][0]), p.zero)), "r"(nth), "r"((h & 1) ? 96 : 128) : "memory");
          if (ok) break;
          if (nth == 0) {
            char* c = (char*)comm + (x3_slot(s + 1) + 1920);
            asm volatile(ELECT "@p red.relaxed.gpu.global.max.s32 [%0], %1;\n@p red.relaxed.gpu.global.max.s32 [%0+4096], %1;}" :: "l"(c), "r"(lds32(mbar + MB_TAB + 8) + 1) : "memory");
          }
          if (!IMM || nth) { T2 += p.slack; advance(T2, gt32() - TOLQ, p.slack); }
        }
        PRB(5)
        w0 = (char*)((uint64_t)w0 ^ (1 << 20));
        st_relaxed(w0, 0xFFFFFFFFu); st_relaxed(w0 + 4096, 0xFFFFFFFFu);
      }
#pragma unroll
      for (int i = 0; i < 16; i++) kf[i >> 2][i & 3] = 0;
    }
#pragma unroll 1
    for (int guard = 0;; guard++) {
      if (j == 3 && s >= 0) {
        if (VR && guard == 0) { asm volatile("bar.sync 15, %0;" :: "r"((h & 1) ? 96 : 128) : "memory"); sts32(mbar + MB_TAB, 0); }
        advance(T3, gt32() - (VR ? TOLV : TOLQ), p.slack);
        wait_gt(T3);
        asm volatile(ELECT
          "@p cp.async.bulk.shared::cluster.global.mbarrier::complete_tx::bytes [%0+-128], [%2+1920], 2176, [%1];\n"
          "@p cp.async.bulk.shared::cluster.global.mbarrier::complete_tx::bytes [%0+2048], [%2+16384], 4096, [%1];\n"
          "@p cp.async.bulk.shared::cluster.global.mbarrier::complete_tx::bytes [%0+6144], [%2+32768], 4096, [%1];}"
          :: "r"(sb + SM_MEMT), "r"(mbar + MB_A), "l"(comm + (x3_slot(s + 1) + side * 4096)) : "memory");
      }
      PRB(6)
      if (VPOS == 0) load_v();
      uint32_t m = 0, ok;
      if (j < 2) {
        if (s + 3 < NSEG) mbar_wait(mbar + MB_X + (par ^ 1) * 8, ((s + 3) >> 1) & 1);
        if (s >= 0) {
          mbar_wait(mbar + MB_A, att & 1);
#pragma unroll
          for (int i = 0; i < 5; i++) m = max(m, lds32(l16 + (l16 & 511) + (l16 & 448) / 16 + (j * 1024 + SM_MEMT + i * 2048)));
        }
      } else if (guard == 0) {
        bar_sync<14, 320>();
        if (j == 2) {
#pragma unroll 1
          for (int g2 = 0; __any_sync(~0u, used + QRING < s + 3) && g2 < POLL_LIMIT && !DBGF(16); g2++) used = ld_relaxed(fl + 24);
          asm volatile("fence.proxy.async.shared::cta;" ::: "memory");
          if (s + 2 < NSEG && !DBGF(64)) asm volatile(ELECT "@p cp.async.bulk.global.shared::cta.bulk_group [%0], [%1], 10240;\ncp.async.bulk.commit_group;}" :: "l"(REC(s + 2)), "r"(sb + SM_ST) : "memory");
        } else if (XPOS == 0 && s + 4 < NSEG) { if (s >= 0) wait_gt(T3 + 192); x_load(p, sb, s + 4); }
      }
      if (VPOS == 2) load_v();
      att++;
      asm volatile("{.reg .pred p; setp.ne.u32 p, %1, 0xffffffff; bar.red.and.pred p, 13, 128, p; selp.u32 %0, 1, 0, p;}" : "=r"(ok) : "r"(m) : "memory");
      if (__all_sync(~0u, ok) || guard == POLL_LIMIT) break;
      bar_arrive<9, 384>();
      VERDICT(1);
      if (j == 3) asm volatile(ELECT "@p mbarrier.arrive.expect_tx.shared.b64 _, [%0], 10368;}" :: "r"(mbar + MB_A) : "memory");
      T3 += p.slack;
    }
    PRB(7)
    if (j == 3) {
      if (XPOS == 1 && s + 4 < NSEG) x_load(p, sb, s + 4);
      if (s >= 0) {
        const int seen = lds32(sb + SM_MEMT - 128), had = lds32(mbar + MB_TAB + 8), cnt = max(seen, had);
        sts32(mbar + MB_TAB + 8, cnt); sts32(mbar + MB_TK, T3 + p.period + (cnt - had) * (p.xlate + p.extra)); sts32(mbar + MB_TK + 4, cnt > had ? p.c3 + p.extra : p.c3);
      }
      st_relaxed(fl + r * 8, ((T3 >> 5) << 7) | (s + 2));
      if (s == -2) asm volatile(ELECT "@p mbarrier.arrive.shared.b64 _, [%0];}" :: "r"(mbar + MB_A) : "memory");
      if (s < 0) TL(18);
    }
  }
  bar_sync<9, 384>();
  m_store(NSEG - 1);
  VERDICT(0);
  TL(19);
  if (__all_sync(~0u, lds32(mbar + MB_TAB + 4) == 0)) bar_arrive<1, 384>();
  if (is_red) {
    uint32_t* wpoi = (uint32_t*)(comm + (x3_slot(2) + bline + (l16 & 511) / 4));
    st_relaxed(wpoi, 0xFFFFFFFFu); st_relaxed(wpoi + 1024, 0xFFFFFFFFu);
#pragma unroll 1
    for (int i = 0; i < 8; i++) stg128((char*)comm + (inbox + 256 * 4096 + i * 512 + (l16 & 511)), 0, 0, 0, 0);
    __threadfence();
  }
#undef VR
}

__global__ void __launch_bounds__(384, 1) rec_kernel(const __grid_constant__ RecParams p) {
  extern __shared__ __align__(1024) char smem_raw[];
  const uint32_t sb = (smem_u32(smem_raw) + 1023) & ~1023u;
  char* smem = smem_raw + (sb - smem_u32(smem_raw));
  const int tid = threadIdx.x;
  const uint32_t mbar = sb + SM_BAR;
  pdl_launch();
  if (!p.helper) {
    if (tid == 32 || tid == 96) l2_prefetch((tid == 32 ? p.wi : p.wr) + blockIdx.x * 6848, 13696);
    if (tid == 64 && blockIdx.x < 12) l2_prefetch(g_tab + TB_F32 * 4 + blockIdx.x * 256, 1024);
  }
#pragma unroll 1
  for (int L = p.layer; L < 2; L++) {
    {
    const int w = __shfl_sync(~0u, tid >> 5, 0), bid = blockIdx.x + (L & p.zero), h = bid / 3, r = bid % 3;
    TL(0);
    if (tid == 0) {
#pragma unroll 1
      for (int i = 0; i < 14; i++) {
        if (L > p.layer) asm volatile("mbarrier.inval.shared.b64 [%0];" :: "r"(mbar + i * 8) : "memory");
        mbar_init(mbar + i * 8, 1);
      }
      asm volatile("fence.mbarrier_init.release.cluster;" ::: "memory");
      asm volatile("fence.proxy.async.shared::cta;" ::: "memory");
      mbar_expect(mbar + MB_QK, r == 2 ? 1536 : 768); mbar_expect(mbar + MB_V, 2048);
      mbar_expect(mbar + MB_KV, 8192); mbar_expect(mbar + MB_KV + 8, 8192);
      sts32(mbar + MB_TK + 4, p.c3 + p.extra); sts32(mbar + MB_TAB + 4, L); sts32(mbar + MB_TAB + 8, L * 1000);
      mbar_expect(mbar + MB_IA, L ? 0 : 163840); mbar_expect(mbar + MB_IC, r == 2 ? 32768 : 65536);
    }
    const int v = bid + p.helper * 96;
    const bool prep = L == 0 && v >= 86;
    if (prep && v < 118 && tid == 0) {
      mbar_expect(mbar + 8, 2 * 41088);
      bulk_g2s(sb + SM_WS, p.wr + (v - 86) * 64 * 321, 41088, mbar + 8); bulk_g2s(sb + SM_WS + 41088, p.wi + (v - 86) * 64 * 321, 41088, mbar + 8);
    }
    __syncwarp();
    auto wo_load = [&](int i0) {
#pragma unroll 1
      for (int i = i0; i < i0 + 4; i++)
        asm volatile(ELECT "@p cp.async.bulk.tensor.2d.shared::cluster.global.mbarrier::complete_tx::bytes [%0], [%1, {%3, %4}], [%2];}"
          :: "r"(sb + SM_WST + i * 8192), "l"(&p.tmWo), "r"(mbar + MB_IC), "r"(r * 256 + (i >> 1) * 64), "r"(h * 128 + (i & 1) * 64) : "memory");
    };
    a_layer(p.a[L], smem + SM_WST, v, w, [&](int u) {
        if (u == -1 && prep) {
          const int o = (v - 86) * 384 + tid, pg = 160 + ((o >> 8) & 15) + ((o >> 12) & 1) * 64 + (o >> 13) * 256;
          const uint32_t c = (pg & 2) ? 0u : ~0u;
          if (o < 64 * 256) stg128((uint4*)p.comm + pg * 256 + (o & 255), c, c, c, c);
          if (v < 118) { mbar_wait(mbar + 8, 0); filter_prep((uint32_t*)p.a[0].WT, sb + SM_WS, v - 86); }
          asm volatile("fence.proxy.async.shared::cta;" ::: "memory");
          TL(20);
          __syncthreads();
        }
        if (u == 0 && prep && tid == 256) { red_release(p.a[0].sync + SY_W); TL(21); }
        auto w_load = [&](int i) {
          asm volatile(ELECT "@p cp.async.bulk.tensor.2d.shared::cluster.global.mbarrier::complete_tx::bytes [%0], [%1, {%3, %4}], [%2];}"
            :: "r"(sb + SM_WS + ((0x3102 >> (4 * (i & 3))) & 3) * 40960 + (i >> 2) * 8192), "l"(&p.tmW[r == 2 ? 2 : i & 1]), "r"(mbar + MB_IA), "r"(h * 128 + (r == 2 ? i & 1 : r) * 64), "r"((i & 2) * 160 + (i >> 2) * 64) : "memory");
        };
        const int b0 = (WPLAN >> (4 * u + 4)) & 15, n = ((WPLAN >> (4 * u + 8)) & 15) - b0;
        if (n > 0 && w + L * 12 + p.helper * 12 < 4 * n) w_load(4 * b0 + w);
        if (u == OPF && w < 4 && r + p.helper * 2 < 2)
          asm volatile(ELECT "@p cp.async.bulk.prefetch.tensor.2d.L2.global [%0, {%1, %2}];}" :: "l"(&p.tmWo), "r"(r * 256 + 128 + (w >> 1) * 64), "r"(h * 128 + (w & 1) * 64) : "memory");
        if (u == 4 && w == 4 && !p.helper) wo_load(0);
      });
    if (p.helper) {
      return;
    }
    __syncwarp();
    if (w == 2 && r < 2) { asm volatile("fence.proxy.async.shared::cta;" ::: "memory"); wo_load(4); }
    }
    L = __shfl_sync(~0u, lds32(mbar + MB_TAB + 4), 0);
    const int w = __shfl_sync(~0u, tid >> 5, 0), bid = blockIdx.x + (L & p.zero), h = bid / 3, r = bid % 3;
    if (w < 8) {
      asm volatile("setmaxnreg.inc.sync.aligned.u32 216;");
      if (r < 2) rec_gemm_warps<false>(p, sb, h, r, L, w); else rec_gemm_warps<true>(p, sb, h, r, L, w);
      asm volatile("setmaxnreg.dec.sync.aligned.u32 168;");
    } else {
      asm volatile("setmaxnreg.dec.sync.aligned.u32 72;");
      const int side = rec_attn_setup(p, sb, h, r, L, w - 8);
      rec_attn_warps(p, sb, smem, h, r, side, L, w - 8);
      asm volatile("setmaxnreg.inc.sync.aligned.u32 168;");
    }
    asm volatile("barrier.cluster.arrive.relaxed.aligned; barrier.cluster.wait.aligned;" ::: "memory");
    L = __shfl_sync(~0u, lds32(mbar + MB_TAB + 4), 0);
    if (tid < 32) TL_DUMP(L * 166 + blockIdx.x, tid);
    __syncthreads();
  }
}

constexpr int PERIOD = 1984, C3 = 480, SLACK = 768, XLATE = 64, GAP = 128;
static int PH[6] = {256, 704, 3, 1280, 96, 63};
__device__ __align__(128) uint32_t g_Z1[86 * 7680], g_ZT[640 * 1024];
__device__ __align__(128) uint32_t g_WT[321 * 2048];
__device__ bf16 g_x1[S_ * D_], g_x2[S_ * D_], g_hN[S_ * D_];
__device__ __align__(128) uint4 g_QKV[QRING * 32 * 30720 / 16], g_O[ORING * 32 * 8192 / 16];
__device__ __align__(128) uint4 g_part[PRING * 32 * 8960 / 16];
__device__ __align__(128) uint32_t g_sync[256];
__device__ uint32_t g_comm[(4 << 20) / 4];

typedef CUresult (*EncodeFn)(CUtensorMap*, CUtensorMapDataType, cuuint32_t, void*, const cuuint64_t*, const cuuint64_t*, const cuuint32_t*, const cuuint32_t*,
                             CUtensorMapInterleave, CUtensorMapSwizzle, CUtensorMapL2promotion, CUtensorMapFloatOOBfill);
static void make_map(EncodeFn fn, CUtensorMap* m, const void* base, uint64_t cols, uint64_t rows, uint32_t bc, uint32_t br) {
  cuuint64_t dims[2] = {cols, rows}, strides[1] = {cols * 2}; cuuint32_t box[2] = {bc, br}, es[2] = {1, 1};
  fn(m, CU_TENSOR_MAP_DATA_TYPE_BFLOAT16, 2, (void*)base, dims, strides, box, es, CU_TENSOR_MAP_INTERLEAVE_NONE, CU_TENSOR_MAP_SWIZZLE_128B, CU_TENSOR_MAP_L2_PROMOTION_L2_256B, CU_TENSOR_MAP_FLOAT_OOB_FILL_NONE);
}
template <typename T> static T* sym(T& s) { void* p; cudaGetSymbolAddress(&p, s); return (T*)p; }

template <typename... KA, typename... A> static void launch(void (*k)(KA...), int grid, int block, int smem, bool pdl, int cluster, A... a) {
  cudaLaunchConfig_t cfg = {};
  cfg.gridDim = dim3(grid); cfg.blockDim = dim3(block); cfg.dynamicSmemBytes = smem; cfg.stream = cudaStreamPerThread;
  cudaLaunchAttribute at[2]; int n = 0;
  if (pdl) { at[n].id = cudaLaunchAttributeProgrammaticStreamSerialization; at[n].val.programmaticStreamSerializationAllowed = 1; n++; }
  if (cluster > 1) { at[n].id = cudaLaunchAttributeClusterDimension; at[n].val.clusterDim.x = cluster; at[n].val.clusterDim.y = 1; at[n].val.clusterDim.z = 1; n++; }
  cfg.attrs = at; cfg.numAttrs = n;
  cudaLaunchKernelEx(&cfg, k, KA(a)...);
}

extern "C" void kernel_launch(void* const* d_in, const int* in_sizes, int n_in, void* d_out, int out_size) {
  const bf16 *x = (const bf16*)d_in[0], *wr = (const bf16*)d_in[1], *wi = (const bf16*)d_in[2], *mem0 = (const bf16*)d_in[4];
  const bf16 *Wq = (const bf16*)d_in[5], *Wk = (const bf16*)d_in[6], *Wv = (const bf16*)d_in[7], *Wo = (const bf16*)d_in[8];
  bf16* out = (bf16*)d_out;
  uint32_t *Z1 = (uint32_t*)sym(g_Z1), *ZT = (uint32_t*)sym(g_ZT), *WT = (uint32_t*)sym(g_WT);
  bf16 *x1 = (bf16*)sym(g_x1), *x2 = (bf16*)sym(g_x2), *hN = (bf16*)sym(g_hN);
  char *QKV = (char*)sym(g_QKV), *part = (char*)sym(g_part);
  uint32_t* comm = (uint32_t*)(((uint64_t)sym(g_comm) + (2 << 20) - 1) & ~(uint64_t)((2 << 20) - 1));
  EncodeFn enc = nullptr; cudaDriverEntryPointQueryResult qr;
  cudaGetDriverEntryPoint("cuTensorMapEncodeTiled", (void**)&enc, cudaEnableDefault, &qr);
  CUtensorMap tmW[3], tmWo, tmX, tmP;
  { cuuint64_t dims[3] = {64, PRING * 32, 70}, strides[2] = {8960, 128}; cuuint32_t box[3] = {64, 32, 2}, es[3] = {1, 1, 1};
    enc(&tmP, CU_TENSOR_MAP_DATA_TYPE_BFLOAT16, 3, part, dims, strides, box, es, CU_TENSOR_MAP_INTERLEAVE_NONE, CU_TENSOR_MAP_SWIZZLE_128B, CU_TENSOR_MAP_L2_PROMOTION_NONE, CU_TENSOR_MAP_FLOAT_OOB_FILL_NONE); }
  { cuuint64_t dims[3] = {64, 2048, 10}, strides[2] = {1280, 128}; cuuint32_t box[3] = {64, 32, 10}, es[3] = {1, 1, 1};
    enc(&tmX, CU_TENSOR_MAP_DATA_TYPE_BFLOAT16, 3, hN, dims, strides, box, es, CU_TENSOR_MAP_INTERLEAVE_NONE, CU_TENSOR_MAP_SWIZZLE_128B, CU_TENSOR_MAP_L2_PROMOTION_L2_256B, CU_TENSOR_MAP_FLOAT_OOB_FILL_NONE); }
  make_map(enc, &tmW[0], Wq, 4096, 640, 64, 64); make_map(enc, &tmW[1], Wk, 4096, 640, 64, 64); make_map(enc, &tmW[2], Wv, 4096, 640, 64, 64);
  make_map(enc, &tmWo, Wo, 640, 4096, 64, 64);
  int dbgf = 0;
  cudaFuncSetAttribute(side_kernel, cudaFuncAttributeMaxDynamicSharedMemorySize, SD_SMEM);
  cudaFuncSetAttribute(rec_kernel, cudaFuncAttributeMaxDynamicSharedMemorySize, REC_SMEM);
  uint32_t* sy = (uint32_t*)sym(g_sync);
  RecParams rp = {{tmW[0], tmW[1], tmW[2]}, tmWo, tmX, {{x, Z1, ZT, WT, x1, hN, sy, nullptr, 45, 1}, {x2, Z1, ZT, WT, x1, hN, sy + 128, (dbgf & 16) ? nullptr : comm + FL_RDY + 12, 0, 0}},
                  mem0, wr, wi, QKV, comm, 0x4000004000010000ull, PERIOD, C3, SLACK, XLATE, PH[4], GAP, 0, 0, 0, dbgf, nullptr, nullptr};
  launch(rec_kernel, 96, 384, REC_SMEM, false, 3, rp);
  for (int L = 0; L < 2; L++) {
    rp.helper = 1; rp.layer = L;
    launch(rec_kernel, 35, 384, REC_SMEM, true, 1, rp);
    SideParams sp = {tmWo, tmP, QKV, (char*)sym(g_O), part, x1, L == 0 ? x2 : out, comm + L * 1024, sy + L * 128, rp.dhi, L == 0, rp.period, PH[0], PH[1], PH[2], PH[3], PH[5], dbgf};
    launch(side_kernel, 36, 512, SD_SMEM, true, 1, sp);
  }
}
```

```cpp
#include <cuda_runtime.h>
#include <cuda_bf16.h>
#include <cuda.h>
#include <stdint.h>
typedef __nv_bfloat16 bf16;
constexpr int S_ = 2048, D_ = 640, H_ = 32, DH = 128, NSEG = 64;

__device__ __forceinline__ uint32_t smem_u32(const void* p) { return (uint32_t)__cvta_generic_to_shared(p); }
__device__ __forceinline__ uint32_t pack_bf16(float lo, float hi) { uint32_t r; asm("cvt.rn.bf16x2.f32 %0, %1, %2;" : "=r"(r) : "f"(hi), "f"(lo)); return r; }
__device__ __forceinline__ float bf_lo(uint32_t v) { return __uint_as_float(v << 16); }
__device__ __forceinline__ float bf_hi(uint32_t v) { return __uint_as_float(v & 0xFFFF0000u); }
__device__ __forceinline__ void ldsm4t(uint32_t& r0, uint32_t& r1, uint32_t& r2, uint32_t& r3, uint32_t a) {
  asm volatile("ldmatrix.sync.aligned.m8n8.x4.trans.shared.b16 {%0,%1,%2,%3}, [%4];" : "=r"(r0), "=r"(r1), "=r"(r2), "=r"(r3) : "r"(a) : "memory");
}
__device__ __forceinline__ void ldsm4(uint32_t& r0, uint32_t& r1, uint32_t& r2, uint32_t& r3, uint32_t a) {
  asm volatile("ldmatrix.sync.aligned.m8n8.x4.shared.b16 {%0,%1,%2,%3}, [%4];" : "=r"(r0), "=r"(r1), "=r"(r2), "=r"(r3) : "r"(a) : "memory");
}
__device__ __forceinline__ void mma16816(float* d, uint32_t a0, uint32_t a1, uint32_t a2, uint32_t a3, uint32_t b0, uint32_t b1) {
  asm volatile("mma.sync.aligned.m16n8k16.row.col.f32.bf16.bf16.f32 {%0,%1,%2,%3}, {%4,%5,%6,%7}, {%8,%9}, {%0,%1,%2,%3};"
    : "+f"(d[0]), "+f"(d[1]), "+f"(d[2]), "+f"(d[3]) : "r"(a0), "r"(a1), "r"(a2), "r"(a3), "r"(b0), "r"(b1));
}
__device__ __forceinline__ void mma16816z(float* d, uint32_t a0, uint32_t a1, uint32_t a2, uint32_t a3, uint32_t b0, uint32_t b1) {
  asm volatile("mma.sync.aligned.m16n8k16.row.col.f32.bf16.bf16.f32 {%0,%1,%2,%3}, {%4,%5,%6,%7}, {%8,%9}, {%10,%10,%10,%10};"
    : "=f"(d[0]), "=f"(d[1]), "=f"(d[2]), "=f"(d[3]) : "r"(a0), "r"(a1), "r"(a2), "r"(a3), "r"(b0), "r"(b1), "f"(0.f));
}
__device__ __forceinline__ void mma1688z(float* d, uint32_t a0, uint32_t a1, uint32_t b0) {
  asm volatile("mma.sync.aligned.m16n8k8.row.col.f32.bf16.bf16.f32 {%0,%1,%2,%3}, {%4,%5}, {%6}, {%7,%7,%7,%7};"
    : "=f"(d[0]), "=f"(d[1]), "=f"(d[2]), "=f"(d[3]) : "r"(a0), "r"(a1), "r"(b0), "f"(0.f));
}
__device__ __forceinline__ void mma1688(float* d, uint32_t a0, uint32_t a1, uint32_t b0) {
  asm volatile("mma.sync.aligned.m16n8k8.row.col.f32.bf16.bf16.f32 {%0,%1,%2,%3}, {%4,%5}, {%6}, {%0,%1,%2,%3};"
    : "+f"(d[0]), "+f"(d[1]), "+f"(d[2]), "+f"(d[3]) : "r"(a0), "r"(a1), "r"(b0));
}
__device__ __forceinline__ void mmaA(float* d, const uint32_t* a, uint32_t b0, uint32_t b1) { mma16816(d, a[0], a[1], a[2], a[3], b0, b1); }
__device__ __forceinline__ void mmaZ(float* d, const uint32_t* a, uint32_t b0, uint32_t b1) { mma16816z(d, a[0], a[1], a[2], a[3], b0, b1); }
__device__ __forceinline__ uint32_t movm(uint32_t a) { uint32_t d; asm volatile("movmatrix.sync.aligned.m8n8.trans.b16 %0, %1;" : "=r"(d) : "r"(a)); return d; }
__device__ __forceinline__ void cp_async16(uint32_t dst, const void* src) { asm volatile("cp.async.cg.shared.global [%0], [%1], 16;" :: "r"(dst), "l"(src) : "memory"); }
__device__ __forceinline__ void cp_commit() { asm volatile("cp.async.commit_group;" ::: "memory"); }
template <int N> __device__ __forceinline__ void cp_wait() { asm volatile("cp.async.wait_group %0;" :: "n"(N) : "memory"); }
__device__ __forceinline__ void lds128(uint32_t* r, uint32_t a) { asm volatile("ld.shared.v4.b32 {%0,%1,%2,%3}, [%4];" : "=r"(r[0]), "=r"(r[1]), "=r"(r[2]), "=r"(r[3]) : "r"(a) : "memory"); }
__device__ __forceinline__ void sts128(uint32_t a, uint32_t r0, uint32_t r1, uint32_t r2, uint32_t r3) { asm volatile("st.shared.v4.b32 [%0], {%1,%2,%3,%4};" :: "r"(a), "r"(r0), "r"(r1), "r"(r2), "r"(r3) : "memory"); }
__device__ __forceinline__ void stg128(void* p, uint32_t r0, uint32_t r1, uint32_t r2, uint32_t r3) { asm volatile("st.global.v4.b32 [%0], {%1,%2,%3,%4};" :: "l"(p), "r"(r0), "r"(r1), "r"(r2), "r"(r3) : "memory"); }
template <int ID, int N> __device__ __forceinline__ void bar_sync() { asm volatile("bar.sync %0, %1;" :: "n"(ID), "n"(N) : "memory"); }
template <int ID, int N> __device__ __forceinline__ void bar_arrive() { asm volatile("bar.arrive %0, %1;" :: "n"(ID), "n"(N) : "memory"); }
__device__ __forceinline__ void mbar_wait(uint32_t bar, uint32_t parity) {
  asm volatile("{\n.reg .pred p, pq;\n.reg .u32 n;\nmov.u32 n, 0;\nLW%=:\nmbarrier.try_wait.parity.shared::cta.b64 p, [%0], %1;\n@p bra.uni LD%=;\nadd.u32 n, n, 1;\nsetp.lt.u32 pq, n, 1000000;\n@pq bra.uni LW%=;\nLD%=:\n}" :: "r"(bar), "r"(parity) : "memory");
}
#define mbar_wait_long mbar_wait
__device__ __forceinline__ void mbar_init(uint32_t bar, int n) { asm volatile("mbarrier.init.shared.b64 [%0], %1;" :: "r"(bar), "r"(n) : "memory"); }
__device__ __forceinline__ void mbar_expect(uint32_t bar, int bytes) { asm volatile("mbarrier.arrive.expect_tx.shared.b64 _, [%0], %1;" :: "r"(bar), "r"(bytes) : "memory"); }
__device__ __forceinline__ void mbar_arrive(uint32_t bar) { asm volatile("mbarrier.arrive.shared.b64 _, [%0];" :: "r"(bar) : "memory"); }
__device__ __forceinline__ void l2_prefetch(const void* p, int bytes) { asm volatile("cp.async.bulk.prefetch.L2.global [%0], %1;" :: "l"(p), "r"(bytes) : "memory"); }
__device__ __forceinline__ float ex2(float x) { float y; asm("ex2.approx.ftz.f32 %0, %1;" : "=f"(y) : "f"(x)); return y; }
__device__ __forceinline__ void pdl_wait() { asm volatile("griddepcontrol.wait;" ::: "memory"); }
__device__ __forceinline__ void pdl_launch() { asm volatile("griddepcontrol.launch_dependents;" ::: "memory"); }
__device__ __forceinline__ uint32_t hadd2(uint32_t a, uint32_t b) { uint32_t r; asm("add.rn.bf16x2 %0, %1, %2;" : "=r"(r) : "r"(a), "r"(b)); return r; }
__device__ __forceinline__ void sched_fence() { asm volatile("{\n.reg .pred p;\n.reg .u32 t;\nLF%=:\nmov.u32 t, %%clock;\nsetp.eq.u32 p, t, %0;\n@p bra.uni LF%=;\n}" :: "n"(12345) : "memory"); }
#define TL(k)
#define TL_DUMP(slot, t)

constexpr int TB_F16 = 0, TB_640 = 64, TB_F40 = 384, TB_F32 = 784, TB_512 = 1040, TB_2048 = 1296;
__device__ __align__(128) const uint32_t g_tab[6208] = {
0x3f803f80,0xbf803f80,0x3f803f80,0xbf803f80,0x3f803f80,0xbf803f80,0x3f803f80,0xbf803f80,0x3f803f80,0xbf803f80,0x3f803f80,0xbf803f80,0x3f803f80,0xbf803f80,0x3f803f80,0xbf803f80,
0x3f6d3f80,0xbf6d3f80,0xbf6dbf80,0x3f6dbf80,0x3ec43f35,0xbec43f35,0xbec4bf35,0x3ec4bf35,0xbec40000,0x3ec40000,0x3ec40000,0xbec40000,0xbf6dbf35,0x3f6dbf35,0x3f6d3f35,0xbf6d3f35,
0x3f353f80,0xbf353f80,0x3f353f80,0xbf353f80,0xbf350000,0x3f350000,0xbf350000,0x3f350000,0xbf35bf80,0x3f35bf80,0xbf35bf80,0x3f35bf80,0x3f350000,0xbf350000,0x3f350000,0xbf350000,
0x3ec43f80,0xbec43f80,0xbec4bf80,0x3ec4bf80,0xbf6dbf35,0x3f6dbf35,0x3f6d3f35,0xbf6d3f35,0x3f6d0000,0xbf6d0000,0xbf6d0000,0x3f6d0000,0xbec43f35,0x3ec43f35,0x3ec4bf35,0xbec4bf35,
0x3f80,0x3f80,0x3f80,0x3f80,0xbf80,0xbf80,0xbf80,0xbf80,0x3f80,0x3f80,0x3f80,0x3f80,0xbf80,0xbf80,0xbf80,0xbf80,
0xbec43f80,0x3ec43f80,0x3ec4bf80,0xbec4bf80,0x3f6dbf35,0xbf6dbf35,0xbf6d3f35,0x3f6d3f35,0xbf6d0000,0x3f6d0000,0x3f6d0000,0xbf6d0000,0x3ec43f35,0xbec43f35,0xbec4bf35,0x3ec4bf35,
0xbf353f80,0x3f353f80,0xbf353f80,0x3f353f80,0x3f350000,0xbf350000,0x3f350000,0xbf350000,0x3f35bf80,0xbf35bf80,0x3f35bf80,0xbf35bf80,0xbf350000,0x3f350000,0xbf350000,0x3f350000,
0xbf6d3f80,0x3f6d3f80,0x3f6dbf80,0xbf6dbf80,0xbec43f35,0x3ec43f35,0x3ec4bf35,0xbec4bf35,0x3ec40000,0xbec40000,0xbec40000,0x3ec40000,0x3f6dbf35,0xbf6dbf35,0xbf6d3f35,0x3f6d3f35,
0x80008000,0x80008000,0x80008000,0x80008000,0x80008000,0x80008000,0x80008000,0x80008000,0x80008000,0x80008000,0x80008000,0x80008000,0x80008000,0x80008000,0x80008000,0x80008000,
0xbec48000,0x3ec48000,0x3ec48000,0xbec48000,0xbf6dbf35,0x3f6dbf35,0x3f6d3f35,0xbf6d3f35,0xbf6dbf80,0x3f6dbf80,0x3f6d3f80,0xbf6d3f80,0xbec4bf35,0x3ec4bf35,0x3ec43f35,0xbec43f35,
0xbf358000,0x3f358000,0xbf358000,0x3f358000,0xbf35bf80,0x3f35bf80,0xbf35bf80,0x3f35bf80,0x3f358000,0xbf358000,0x3f358000,0xbf358000,0x3f353f80,0xbf353f80,0x3f353f80,0xbf353f80,
0xbf6d8000,0x3f6d8000,0x3f6d8000,0xbf6d8000,0x3ec4bf35,0xbec4bf35,0xbec43f35,0x3ec43f35,0x3ec43f80,0xbec43f80,0xbec4bf80,0x3ec4bf80,0xbf6dbf35,0x3f6dbf35,0x3f6d3f35,0xbf6d3f35,
0xbf808000,0x3f808000,0xbf808000,0x3f808000,0x3f808000,0xbf808000,0x3f808000,0xbf808000,0xbf808000,0x3f808000,0xbf808000,0x3f808000,0x3f808000,0xbf808000,0x3f808000,0xbf808000,
0xbf6d8000,0x3f6d8000,0x3f6d8000,0xbf6d8000,0x3ec43f35,0xbec43f35,0xbec4bf35,0x3ec4bf35,0x3ec4bf80,0xbec4bf80,0xbec43f80,0x3ec43f80,0xbf6d3f35,0x3f6d3f35,0x3f6dbf35,0xbf6dbf35,
0xbf358000,0x3f358000,0xbf358000,0x3f358000,0xbf353f80,0x3f353f80,0xbf353f80,0x3f353f80,0x3f358000,0xbf358000,0x3f358000,0xbf358000,0x3f35bf80,0xbf35bf80,0x3f35bf80,0xbf35bf80,
0xbec48000,0x3ec48000,0x3ec48000,0xbec48000,0xbf6d3f35,0x3f6d3f35,0x3f6dbf35,0xbf6dbf35,0xbf6d3f80,0x3f6d3f80,0x3f6dbf80,0xbf6dbf80,0xbec43f35,0x3ec43f35,0x3ec4bf35,0xbec4bf35,
0x3f800000,0x3f800000,0x3f800000,0x3f7f35f9,0x3f800000,0x3f800000,0x3f7cd925,0x3f78ed3c,0x3f800000,0x3f800000,0x3f737871,0x3f6c835e,0x3f800000,0x3f800000,0x3f641901,0x3f5a46a0,
0x3f800000,0x3f7ffcd7,0x3f800000,0x3f7f0059,0x3f7ff35e,0x3f7fe394,0x3f7c0361,0x3f770f11,0x3f7fcd79,0x3f7fb10f,0x3f702d4f,0x3f676bd8,0x3f7f8e56,0x3f7f654e,0x3f5cdc29,0x3f50935b,
0x3f800000,0x3f7ff35e,0x3f800000,0x3f7ec46d,0x3f7fcd79,0x3f7f8e56,0x3f7b14be,0x3f74fa0b,0x3f7f35f9,0x3f7ec46d,0x3f6c835e,0x3f61c598,0x3f7e39bc,0x3f7d95f4,0x3f54db31,0x3f45e403,
0x3f800000,0x3f7fe394,0x3f800000,0x3f7e8238,0x3f7f8e56,0x3f7f0059,0x3f7a0d54,0x3f72ae9e,0x3f7e39bc,0x3f7d3aac,0x3f687c12,0x3f5b941a,0x3f7c0361,0x3f7a9421,0x3f4c1d35,0x3f3a4582,
0x3f800000,0x3f7fcd79,0x3f800000,0x3f7e39bc,0x3f7f35f9,0x3f7e39bc,0x3f78ed3c,0x3f702d4f,0x3f7cd925,0x3f7b14be,0x3f641901,0x3f54db31,0x3f78ed3c,0x3f766377,0x3f42a9f7,0x3f2dc5e3,
0x3f800000,0x3f7fb10f,0x3f800000,0x3f7deafa,0x3f7ec46d,0x3f7d3aac,0x3f77b493,0x3f6d76aa,0x3f7b14be,0x3f7853f8,0x3f5f5be6,0x3f4d9f02,0x3f74fa0b,0x3f710908,0x3f3889dc,0x3f207440,
0x3f800000,0x3f7f8e56,0x3f800000,0x3f7d95f4,0x3f7e39bc,0x3f7c0361,0x3f766377,0x3f6a8b4b,0x3f78ed3c,0x3f74fa0b,0x3f5a46a0,0x3f45e403,0x3f702d4f,0x3f6a8b4b,0x3f2dc5e3,0x3f1260b2,
0x3f800000,0x3f7f654e,0x3f800000,0x3f7d3aac,0x3f7d95f4,0x3f7a9421,0x3f74fa0b,0x3f676bd8,0x3f766377,0x3f710908,0x3f54db31,0x3f3daef9,0x3f6a8b4b,0x3f62f219,0x3f226799,0x3f039c3d,
0x3f800000,0x3f800000,0x3f4f1bbd,0x3f42a9f7,0x3f800000,0x3f800000,0x3f3504f3,0x3f26423a,0x3f800000,0x3f800000,0x3f167918,0x3f05c277,0x3f800000,0x3f800000,0x3ee87171,0x3ec3ef15,
0x3f7f35f9,0x3f7f0059,0x3f42a9f7,0x3f333bc6,0x3f7ec46d,0x3f7e8238,0x3f226799,0x3f104f0e,0x3f7e39bc,0x3f7deafa,0x3efa2c90,0x3ed1c759,0x3f7d95f4,0x3f7d3aac,0x3ea7bf25,0x3e78cfcc,
0x3f7cd925,0x3f7c0361,0x3f3504f3,0x3f226799,0x3f7b14be,0x3f7a0d54,0x3f0e39da,0x3ef15aea,0x3f78ed3c,0x3f77b493,0x3ec3ef15,0x3e94a031,0x3f766377,0x3f74fa0b,0x3e47c5c2,0x3dc8bd36,
0x3f78ed3c,0x3f770f11,0x3f26423a,0x3f104f0e,0x3f74fa0b,0x3f72ae9e,0x3ef15aea,0x3ebf47d7,0x3f702d4f,0x3f6d76aa,0x3e8afa3e,0x3e2a1c3f,0x3f6a8b4b,0x3f676bd8,0x3d712283,0xbd48fb30,
0x3f737871,0x3f702d4f,0x3f167918,0x3efa2c90,0x3f6c835e,0x3f687c12,0x3ec3ef15,0x3e8afa3e,0x3f641901,0x3f5f5be6,0x3e20305b,0x3d20cee7,0x3f5a46a0,0x3f54db31,0xbda0af2a,0xbe47c5c2,
0x3f6c835e,0x3f676bd8,0x3f05c277,0x3ed1c759,0x3f61c598,0x3f5b941a,0x3e94a031,0x3e2a1c3f,0x3f54db31,0x3f4d9f02,0x3d20cee7,0xbdb4b86a,0x3f45e403,0x3f3daef9,0xbe5b73dc,0xbeac7cd4,
0x3f641901,0x3f5cdc29,0x3ee87171,0x3ea7bf25,0x3f54db31,0x3f4c1d35,0x3e47c5c2,0x3d712283,0x3f42a9f7,0x3f3889dc,0xbda0af2a,0xbe5b73dc,0x3f2dc5e3,0x3f226799,0xbeb13641,0xbef15aea,
0x3f5a46a0,0x3f50935b,0x3ec3ef15,0x3e78cfcc,0x3f45e403,0x3f3a4582,0x3dc8bd36,0xbd48fb30,0x3f2dc5e3,0x3f207440,0xbe47c5c2,0xbeac7cd4,0x3f1260b2,0x3f039c3d,0xbef15aea,0xbf187fc0,
0x3f800000,0x3f800000,0x3e9e377a,0x3e6f0c4d,0x3f800000,0x3f800000,0x3e20305b,0x3da0af2a,0x3f800000,0x3f800000,0,0xbda0af2a,0x3f800000,0x3f800000,0xbe20305b,0xbe6f0c4d,
0x3f7cd925,0x3f7c7160,0x3e20305b,0x3d8ca1f2,0x3f7c0361,0x3f7b8f2a,0xbca0d6d6,0xbddcbd0d,0x3f7b14be,0x3f7a9421,0xbe47c5c2,0xbe8fcefe,0x3f7a0d54,0x3f79805c,0xbeba9be1,0xbee3f40d,
0x3f737871,0x3f71decf,0,0xbdc8bd36,0x3f702d4f,0x3f6e641a,0xbe47c5c2,0xbe94a031,0x3f6c835e,0x3f6a8b4b,0xbec3ef15,0xbef15aea,0x3f687c12,0x3f6655e7,0xbf0e39da,0xbf226799,
0x3f641901,0x3f609384,0xbe20305b,0xbe862210,0x3f5cdc29,0x3f58f3c4,0xbeba9be1,0xbeece91a,0x3f54db31,0x3f50935b,0xbf0e39da,0xbf2456f1,0x3f4c1d35,0x3f4779bc,0xbf3889dc,0xbf4a965e,
0x3f4f1bbd,0x3f490a88,0xbe9e377a,0xbed65a92,0x3f42a9f7,0x3f3bfc8f,0xbf05c277,0xbf1e7cf1,0x3f3504f3,0x3f2dc5e3,0xbf3504f3,0xbf490a88,0x3f26423a,0x3f1e7cf1,0xbf5a46a0,0xbf687c12,
0x3f3504f3,0x3f2beb4a,0xbee87171,0xbf104f0e,0x3f226799,0x3f187fc0,0xbf2a0c73,0xbf4105b8,0x3f0e39da,0x3f039c3d,0xbf54db31,0xbf653a48,0x3ef15aea,0x3edae880,0xbf71decf,0xbf7a9421,
0x3f167918,0x3f0a04f8,0xbf167918,0xbf316e2c,0x3efa2c90,0x3edf7108,0xbf490a88,0xbf5cdc29,0x3ec3ef15,0x3ea7bf25,0xbf6c835e,0xbf77b493,0x3e8afa3e,0x3e5b73dc,0xbf7e39bc,0xbf7ff35e,
0x3ee87171,0x3ec8917e,0xbf3504f3,0xbf4d9f02,0x3ea7bf25,0x3e862210,0xbf61c598,0xbf710908,0x3e47c5c2,0x3e0255f4,0xbf7b14be,0xbf7fb10f,0x3d712283,0xbc20d8d2,0xbf7ec46d,0xbf7853f8,
0x3f800000,0x3f800000,0xbe9e377a,0xbec3ef15,0x3f800000,0x3f800000,0xbee87171,0xbf05c277,0x3f800000,0x3f800000,0xbf167918,0xbf26423a,0x3f800000,0x3f800000,0xbf3504f3,0xbf42a9f7,
0x3f78ed3c,0x3f7853f8,0xbf05c277,0xbf187fc0,0x3f77b493,0x3f770f11,0xbf2a0c73,0xbf3a4582,0x3f766377,0x3f75b1c9,0xbf490a88,0xbf563e03,0x3f74fa0b,0x3f743c41,0xbf61c598,0xbf6b8a3d,
0x3f641901,0x3f61c598,0xbf3504f3,0xbf45e403,0x3f5f5be6,0x3f5cdc29,0xbf54db31,0xbf61c598,0x3f5a46a0,0x3f579b8c,0xbf6c835e,0xbf74fa0b,0x3f54db31,0x3f5205d4,0xbf7b14be,0xbf7ec46d,
0x3f42a9f7,0x3f3daef9,0xbf5a46a0,0xbf676bd8,0x3f3889dc,0x3f333bc6,0xbf71decf,0xbf79805c,0x3f2dc5e3,0x3f28296a,0xbf7e39bc,0xbf7ffcd7,0x3f226799,0x3f1c81b9,0xbf7ec46d,0xbf7a9421,
0x3f167918,0x3f0e39da,0xbf737871,0xbf7b14be,0x3f05c277,0x3efa2c90,0xbf7f35f9,0xbf7fcd79,0x3ee87171,0x3ed65a92,0xbf7cd925,0xbf766377,0x3ec3ef15,0x3eb13641,0xbf6c835e,0xbf5f5be6,
0x3ec3ef15,0x3eac7cd4,0xbf7f35f9,0xbf7fb10f,0x3e94a031,0x3e78cfcc,0xbf7c0361,0xbf743c41,0x3e47c5c2,0x3e164083,0xbf687c12,0xbf58f3c4,0x3dc8bd36,0x3d48fb30,0xbf45e403,0xbf2f9c32,
0x3e20305b,0x3dc8bd36,0xbf7cd925,0xbf74fa0b,0x3d20cee7,0xbca0d6d6,0xbf687c12,0xbf579b8c,0xbda0af2a,0xbe0c4cf7,0xbf42a9f7,0xbf2a0c73,0xbe47c5c2,0xbe814693,0xbf0e39da,0xbedf7108,
0xbda0af2a,0xbe164083,0xbf6c835e,0xbf5b941a,0xbe5b73dc,0xbe8fcefe,0xbf45e403,0xbf2beb4a,0xbeb13641,0xbed1c759,0xbf0e39da,0xbedae880,0xbef15aea,0xbf07e565,0xbe94a031,0xbe164083,
0x3f800000,0x3f800000,0xbf4f1bbd,0xbf5a46a0,0x3f800000,0x3f800000,0xbf641901,0xbf6c835e,0x3f800000,0x3f800000,0xbf737871,0xbf78ed3c,0x3f800000,0x3f800000,0xbf7cd925,0xbf7f35f9,
0x3f737871,0x3f72ae9e,0xbf737871,0xbf79805c,0x3f71decf,0x3f710908,0xbf7d95f4,0xbf7fb10f,0x3f702d4f,0x3f6f4ba8,0xbf7fcd79,0xbf7deafa,0x3f6e641a,0x3f6d76aa,0xbf7a0d54,0xbf743c41,
0x3f4f1bbd,0x3f4c1d35,0xbf800000,0xbf7ec46d,0x3f490a88,0x3f45e403,0xbf7b14be,0xbf74fa0b,0x3f42a9f7,0x3f3f5cb5,0xbf6c835e,0xbf61c598,0x3f3bfc8f,0x3f3889dc,0xbf54db31,0xbf45e403,
0x3f167918,0x3f104f0e,0xbf737871,0xbf698690,0x3f0a04f8,0x3f039c3d,0xbf5cdc29,0xbf4d9f02,0x3efa2c90,0x3eece91a,0xbf3bfc8f,0xbf28296a,0x3edf7108,0x3ed1c759,0xbf1260b2,0xbef5c6c5,
0x3e9e377a,0x3e8afa3e,0xbf4f1bbd,0xbf3bfc8f,0x3e6f0c4d,0x3e47c5c2,0xbf26423a,0xbf0e39da,0x3e20305b,0x3df0b772,0xbee87171,0xbeb13641,0x3da0af2a,0x3d20cee7,0xbe6f0c4d,0xbdf0b772,
0,0xbd48fb30,0xbf167918,0xbef5c6c5,0xbdc8bd36,0xbe164083,0xbeba9be1,0xbe78cfcc,0xbe47c5c2,0xbe78cfcc,0xbdf0b772,0x3c20d8d2,0xbe94a031,0xbeac7cd4,0x3e0c4cf7,0x3e862210,
0xbe9e377a,0xbeba9be1,0xbe9e377a,0xbe3403f1,0xbed65a92,0xbef15aea,0xbd20cee7,0x3dc8bd36,0xbf05c277,0xbf1260b2,0x3e6f0c4d,0x3eba9be1,0xbf1e7cf1,0xbf2a0c73,0x3efa2c90,0x3f1a82a4,
0xbf167918,0xbf2456f1,0,0x3e164083,0xbf316e2c,0xbf3daef9,0x3e94a031,0x3edae880,0xbf490a88,0xbf53731f,0x3f0e39da,0x3f2beb4a,0xbf5cdc29,0xbf653a48,0x3f45e403,0x3f5b941a,
0x80000000,0x80000000,0x80000000,0xbda0af2a,0x80000000,0x80000000,0xbe20305b,0xbe6f0c4d,0x80000000,0x80000000,0xbe9e377a,0xbec3ef15,0x80000000,0x80000000,0xbee87171,0xbf05c277,
0x80000000,0xbc20d8d2,0x80000000,0xbdb4b86a,0xbca0d6d6,0xbcf13d4c,0xbe3403f1,0xbe862210,0xbd20cee7,0xbd48fb30,0xbeb13641,0xbedae880,0xbd712283,0xbd8ca1f2,0xbf0172c3,0xbf146eba,
0x80000000,0xbca0d6d6,0x80000000,0xbdc8bd36,0xbd20cee7,0xbd712283,0xbe47c5c2,0xbe94a031,0xbda0af2a,0xbdc8bd36,0xbec3ef15,0xbef15aea,0xbdf0b772,0xbe0c4cf7,0xbf0e39da,0xbf226799,
0x80000000,0xbcf13d4c,0x80000000,0xbddcbd0d,0xbd712283,0xbdb4b86a,0xbe5b73dc,0xbea2fd52,0xbdf0b772,0xbe164083,0xbed65a92,0xbf039c3d,0xbe3403f1,0xbe519f65,0xbf1a82a4,0xbf2f9c32,
0x80000000,0xbd20cee7,0x80000000,0xbdf0b772,0xbda0af2a,0xbdf0b772,0xbe6f0c4d,0xbeb13641,0xbe20305b,0xbe47c5c2,0xbee87171,0xbf0e39da,0xbe6f0c4d,0xbe8afa3e,0xbf26423a,0xbf3bfc8f,
0x80000000,0xbd48fb30,0x80000000,0xbe0255f4,0xbdc8bd36,0xbe164083,0xbe814693,0xbebf47d7,0xbe47c5c2,0xbe78cfcc,0xbefa2c90,0xbf187fc0,0xbe94a031,0xbeac7cd4,0xbf316e2c,0xbf4779bc,
0x80000000,0xbd712283,0x80000000,0xbe0c4cf7,0xbdf0b772,0xbe3403f1,0xbe8afa3e,0xbecd2ef3,0xbe6f0c4d,0xbe94a031,0xbf05c277,0xbf226799,0xbeb13641,0xbecd2ef3,0xbf3bfc8f,0xbf5205d4,
0x80000000,0xbd8ca1f2,0x80000000,0xbe164083,0xbe0c4cf7,0xbe519f65,0xbe94a031,0xbedae880,0xbe8afa3e,0xbeac7cd4,0xbf0e39da,0xbf2beb4a,0xbecd2ef3,0xbeece91a,0xbf45e403,0xbf5b941a,
0x80000000,0x80000000,0xbf167918,0xbf26423a,0x80000000,0x80000000,0xbf3504f3,0xbf42a9f7,0x80000000,0x80000000,0xbf4f1bbd,0xbf5a46a0,0x80000000,0x80000000,0xbf641901,0xbf6c835e,
0xbda0af2a,0xbdb4b86a,0xbf26423a,0xbf36c9a9,0xbdc8bd36,0xbddcbd0d,0xbf45e403,0xbf53731f,0xbdf0b772,0xbe0255f4,0xbf5f5be6,0xbf698690,0xbe0c4cf7,0xbe164083,0xbf71decf,0xbf7853f8,
0xbe20305b,0xbe3403f1,0xbf3504f3,0xbf45e403,0xbe47c5c2,0xbe5b73dc,0xbf54db31,0xbf61c598,0xbe6f0c4d,0xbe814693,0xbf6c835e,0xbf74fa0b,0xbe8afa3e,0xbe94a031,0xbf7b14be,0xbf7ec46d,
0xbe6f0c4d,0xbe862210,0xbf42a9f7,0xbf53731f,0xbe94a031,0xbea2fd52,0xbf61c598,0xbf6d76aa,0xbeb13641,0xbebf47d7,0xbf766377,0xbf7c7160,0xbecd2ef3,0xbedae880,0xbf7f8e56,0xbf7fb10f,
0xbe9e377a,0xbeb13641,0xbf4f1bbd,0xbf5f5be6,0xbec3ef15,0xbed65a92,0xbf6c835e,0xbf766377,0xbee87171,0xbefa2c90,0xbf7cd925,0xbf7fcd79,0xbf05c277,0xbf0e39da,0xbf7f35f9,0xbf7b14be,
0xbec3ef15,0xbedae880,0xbf5a46a0,0xbf698690,0xbef15aea,0xbf039c3d,0xbf74fa0b,0xbf7c7160,0xbf0e39da,0xbf187fc0,0xbf7fcd79,0xbf7f0059,0xbf226799,0xbf2beb4a,0xbf7a0d54,0xbf710908,
0xbee87171,0xbf0172c3,0xbf641901,0xbf71decf,0xbf0e39da,0xbf1a82a4,0xbf7b14be,0xbf7f8e56,0xbf26423a,0xbf316e2c,0xbf7f35f9,0xbf7a0d54,0xbf3bfc8f,0xbf45e403,0xbf702d4f,0xbf61c598,
0xbf05c277,0xbf146eba,0xbf6c835e,0xbf7853f8,0xbf226799,0xbf2f9c32,0xbf7ec46d,0xbf7fb10f,0xbf3bfc8f,0xbf4779bc,0xbf7b14be,0xbf710908,0xbf5205d4,0xbf5b941a,0xbf61c598,0xbf4d9f02,
0x80000000,0x80000000,0xbf737871,0xbf78ed3c,0x80000000,0x80000000,0xbf7cd925,0xbf7f35f9,0x80000000,0x80000000,0xbf800000,0xbf7f35f9,0x80000000,0x80000000,0xbf7cd925,0xbf78ed3c,
0xbe20305b,0xbe2a1c3f,0xbf7cd925,0xbf7f654e,0xbe3403f1,0xbe3de731,0xbf7ff35e,0xbf7e8238,0xbe47c5c2,0xbe519f65,0xbf7b14be,0xbf75b1c9,0xbe5b73dc,0xbe6542e9,0xbf6e641a,0xbf653a48,
0xbe9e377a,0xbea7bf25,0xbf800000,0xbf7ec46d,0xbeb13641,0xbeba9be1,0xbf7b14be,0xbf74fa0b,0xbec3ef15,0xbecd2ef3,0xbf6c835e,0xbf61c598,0xbed65a92,0xbedf7108,0xbf54db31,0xbf45e403,
0xbee87171,0xbef5c6c5,0xbf7cd925,0xbf770f11,0xbf0172c3,0xbf07e565,0xbf6e641a,0xbf62f219,0xbf0e39da,0xbf146eba,0xbf54db31,0xbf444969,0xbf1a82a4,0xbf207440,0xbf316e2c,0xbf1c81b9,
0xbf167918,0xbf1e7cf1,0xbf737871,0xbf687c12,0xbf26423a,0xbf2dc5e3,0xbf5a46a0,0xbf490a88,0xbf3504f3,0xbf3bfc8f,0xbf3504f3,0xbf1e7cf1,0xbf42a9f7,0xbf490a88,0xbf05c277,0xbed65a92,
0xbf3504f3,0xbf3daef9,0xbf641901,0xbf53731f,0xbf45e403,0xbf4d9f02,0xbf3f5cb5,0xbf28296a,0xbf54db31,0xbf5b941a,0xbf0e39da,0xbee3f40d,0xbf61c598,0xbf676bd8,0xbea7bf25,0xbe519f65,
0xbf4f1bbd,0xbf579b8c,0xbf4f1bbd,0xbf3889dc,0xbf5f5be6,0xbf6655e7,0xbf1e7cf1,0xbf0172c3,0xbf6c835e,0xbf71decf,0xbec3ef15,0xbe814693,0xbf766377,0xbf7a0d54,0xbdf0b772,0x3ca0d6d6,
0xbf641901,0xbf6b8a3d,0xbf3504f3,0xbf187fc0,0xbf71decf,0xbf770f11,0xbef15aea,0xbeac7cd4,0xbf7b14be,0xbf7deafa,0xbe47c5c2,0xbd48fb30,0xbf7f8e56,0xbf7ffcd7,0x3dc8bd36,0x3e78cfcc,
0x80000000,0x80000000,0xbf737871,0xbf6c835e,0x80000000,0x80000000,0xbf641901,0xbf5a46a0,0x80000000,0x80000000,0xbf4f1bbd,0xbf42a9f7,0x80000000,0x80000000,0xbf3504f3,0xbf26423a,
0xbe6f0c4d,0xbe78cfcc,0xbf5a46a0,0xbf4d9f02,0xbe814693,0xbe862210,0xbf3f5cb5,0xbf2f9c32,0xbe8afa3e,0xbe8fcefe,0xbf1e7cf1,0xbf0c2124,0xbe94a031,0xbe996dba,0xbef15aea,0xbec8917e,
0xbee87171,0xbef15aea,0xbf3504f3,0xbf226799,0xbefa2c90,0xbf0172c3,0xbf0e39da,0xbef15aea,0xbf05c277,0xbf0a04f8,0xbec3ef15,0xbe94a031,0xbf0e39da,0xbf1260b2,0xbe47c5c2,0xbdc8bd36,
0xbf26423a,0xbf2beb4a,0xbf05c277,0xbedae880,0xbf316e2c,0xbf36c9a9,0xbea7bf25,0xbe6542e9,0xbf3bfc8f,0xbf4105b8,0xbdf0b772,0xbc20d8d2,0xbf45e403,0xbf4a965e,0x3dc8bd36,0x3e519f65,
0xbf4f1bbd,0xbf54db31,0xbe9e377a,0xbe47c5c2,0xbf5a46a0,0xbf5f5be6,0xbda0af2a,0x3d20cee7,0xbf641901,0xbf687c12,0x3e20305b,0x3e8afa3e,0xbf6c835e,0xbf702d4f,0x3ec3ef15,0x3efa2c90,
0xbf6c835e,0xbf710908,0xbda0af2a,0x3d48fb30,0xbf74fa0b,0xbf7853f8,0x3e3403f1,0x3e996dba,0xbf7b14be,0xbf7d3aac,0x3ed65a92,0x3f07e565,0xbf7ec46d,0xbf7fb10f,0x3f226799,0x3f3a4582,
0xbf7cd925,0xbf7ec46d,0x3e20305b,0x3e94a031,0xbf7fcd79,0xbf7ff35e,0x3ed65a92,0x3f0a04f8,0xbf7f35f9,0xbf7d95f4,0x3f26423a,0x3f3f5cb5,0xbf7b14be,0xbf77b493,0x3f54db31,0x3f6655e7,
0xbf7f35f9,0xbf7d3aac,0x3ec3ef15,0x3f039c3d,0xbf7a0d54,0xbf75b1c9,0x3f226799,0x3f3daef9,0xbf702d4f,0xbf698690,0x3f54db31,0x3f676bd8,0xbf61c598,0xbf58f3c4,0x3f74fa0b,0x3f7d3aac,
0x80000000,0x80000000,0xbf167918,0xbf05c277,0x80000000,0x80000000,0xbee87171,0xbec3ef15,0x80000000,0x80000000,0xbe9e377a,0xbe6f0c4d,0x80000000,0x80000000,0xbe20305b,0xbda0af2a,
0xbe9e377a,0xbea2fd52,0xbe9e377a,0xbe6542e9,0xbea7bf25,0xbeac7cd4,0xbe0c4cf7,0xbd48fb30,0xbeb13641,0xbeb5eb4f,0x3d20cee7,0x3e0255f4,0xbeba9be1,0xbebf47d7,0x3e5b73dc,0x3e996dba,
0xbf167918,0xbf1a82a4,0x80000000,0x3dc8bd36,0xbf1e7cf1,0xbf226799,0x3e47c5c2,0x3e94a031,0xbf26423a,0xbf2a0c73,0x3ec3ef15,0x3ef15aea,0xbf2dc5e3,0xbf316e2c,0x3f0e39da,0x3f226799,
0xbf4f1bbd,0xbf53731f,0x3e9e377a,0x3ed1c759,0xbf579b8c,0xbf5b941a,0x3f0172c3,0x3f187fc0,0xbf5f5be6,0xbf62f219,0x3f2dc5e3,0x3f4105b8,0xbf6655e7,0xbf698690,0x3f5205d4,0x3f609384,
0xbf737871,0xbf766377,0x3f167918,0x3f2dc5e3,0xbf78ed3c,0xbf7b14be,0x3f42a9f7,0x3f54db31,0xbf7cd925,0xbf7e39bc,0x3f641901,0x3f702d4f,0xbf7f35f9,0xbf7fcd79,0x3f78ed3c,0x3f7e39bc,
0xbf800000,0xbf7fb10f,0x3f4f1bbd,0x3f609384,0xbf7ec46d,0xbf7d3aac,0x3f6e641a,0x3f7853f8,0xbf7b14be,0xbf7853f8,0x3f7e39bc,0x3f7ffcd7,0xbf74fa0b,0xbf710908,0x3f7d95f4,0x3f770f11,
0xbf737871,0xbf6e641a,0x3f737871,0x3f7c0361,0xbf687c12,0xbf61c598,0x3f7fcd79,0x3f7ec46d,0xbf5a46a0,0xbf5205d4,0x3f78ed3c,0x3f6e641a,0xbf490a88,0xbf3f5cb5,0x3f5f5be6,0x3f4c1d35,
0xbf4f1bbd,0xbf444969,0x3f800000,0x3f7d3aac,0xbf3889dc,0xbf2beb4a,0x3f74fa0b,0x3f676bd8,0xbf1e7cf1,0xbf104f0e,0x3f54db31,0x3f3daef9,0xbf0172c3,0xbee3f40d,0x3f226799,0x3f039c3d,
0x3f803f80,0,0x3f803f80,0,0x3f803f80,0,0x3f803f80,0,0x3f7d3f80,0x3e200000,0x3f643f73,0x3ee83e9e,0x3f353f4f,0x3f353f16,0x3ee83f16,0x3f643f4f,
0x3f733f80,0x3e9e0000,0x3f163f4f,0x3f4f3f16,0x3e9e,0x3f803f73,0xbf16be9e,0x3f4f3f73,0x3f643f80,0x3ee80000,0x3e203f16,0x3f7d3f4f,0xbf35be9e,0x3f353f73,0xbf7dbf73,0xbe203e9e,
0x3f4f3f80,0x3f160000,0xbe9e3e9e,0x3f733f73,0xbf80bf4f,0x3f16,0xbe9ebf4f,0xbf73bf16,0x3f353f80,0x3f350000,0xbf350000,0x3f353f80,0xbf35bf80,0xbf350000,0x3f350000,0xbf35bf80,
0x3f163f80,0x3f4f0000,0xbf73be9e,0x3e9e3f73,0xbf4f,0xbf80bf16,0x3f733f4f,0x3e9ebf16,0x3ee83f80,0x3f640000,0xbf7dbf16,0xbe203f4f,0x3f35be9e,0xbf35bf73,0x3e203f73,0x3f7d3e9e,
0x3e9e3f80,0x3f730000,0xbf4fbf4f,0xbf163f16,0x3f803e9e,0xbf73,0xbf4f3e9e,0x3f163f73,0x3e203f80,0x3f7d0000,0xbee8bf73,0xbf643e9e,0x3f353f4f,0x3f35bf16,0xbf64bf16,0xbee83f4f,
0x3f80,0x3f800000,0xbf80,0xbf800000,0x3f80,0x3f800000,0xbf80,0xbf800000,0xbe203f80,0x3f7d0000,0x3ee8bf73,0xbf64be9e,0xbf353f4f,0x3f353f16,0x3f64bf16,0xbee8bf4f,
0xbe9e3f80,0x3f730000,0x3f4fbf4f,0xbf16bf16,0xbf803e9e,0x3f73,0x3f4f3e9e,0x3f16bf73,0xbee83f80,0x3f640000,0x3f7dbf16,0xbe20bf4f,0xbf35be9e,0xbf353f73,0xbe203f73,0x3f7dbe9e,
0xbf163f80,0x3f4f0000,0x3f73be9e,0x3e9ebf73,0xbf4f,0xbf803f16,0xbf733f4f,0x3e9e3f16,0xbf353f80,0x3f350000,0x3f350000,0x3f35bf80,0x3f35bf80,0xbf350000,0xbf350000,0xbf353f80,
0xbf4f3f80,0x3f160000,0x3e9e3e9e,0x3f73bf73,0x3f80bf4f,0xbf16,0x3e9ebf4f,0xbf733f16,0xbf643f80,0x3ee80000,0xbe203f16,0x3f7dbf4f,0x3f35be9e,0x3f35bf73,0x3f7dbf73,0xbe20be9e,
0xbf733f80,0x3e9e0000,0xbf163f4f,0x3f4fbf16,0x3e9e,0x3f80bf73,0x3f16be9e,0x3f4fbf73,0xbf7d3f80,0x3e200000,0xbf643f73,0x3ee8be9e,0xbf353f4f,0x3f35bf16,0xbee83f16,0x3f64bf4f,
0xbf803f80,0,0xbf803f80,0,0xbf803f80,0,0xbf803f80,0,0xbf7d3f80,0xbe200000,0xbf643f73,0xbee83e9e,0xbf353f4f,0xbf353f16,0xbee83f16,0xbf643f4f,
0xbf733f80,0xbe9e0000,0xbf163f4f,0xbf4f3f16,0x3e9e,0xbf803f73,0x3f16be9e,0xbf4f3f73,0xbf643f80,0xbee80000,0xbe203f16,0xbf7d3f4f,0x3f35be9e,0xbf353f73,0x3f7dbf73,0x3e203e9e,
0xbf4f3f80,0xbf160000,0x3e9e3e9e,0xbf733f73,0x3f80bf4f,0x3f16,0x3e9ebf4f,0x3f73bf16,0xbf353f80,0xbf350000,0x3f350000,0xbf353f80,0x3f35bf80,0x3f350000,0xbf350000,0x3f35bf80,
0xbf163f80,0xbf4f0000,0x3f73be9e,0xbe9e3f73,0xbf4f,0x3f80bf16,0xbf733f4f,0xbe9ebf16,0xbee83f80,0xbf640000,0x3f7dbf16,0x3e203f4f,0xbf35be9e,0x3f35bf73,0xbe203f73,0xbf7d3e9e,
0xbe9e3f80,0xbf730000,0x3f4fbf4f,0x3f163f16,0xbf803e9e,0xbf73,0x3f4f3e9e,0xbf163f73,0xbe203f80,0xbf7d0000,0x3ee8bf73,0x3f643e9e,0xbf353f4f,0xbf35bf16,0x3f64bf16,0x3ee83f4f,
0x3f80,0xbf800000,0xbf80,0x3f800000,0x3f80,0xbf800000,0xbf80,0x3f800000,0x3e203f80,0xbf7d0000,0xbee8bf73,0x3f64be9e,0x3f353f4f,0xbf353f16,0xbf64bf16,0x3ee8bf4f,
0x3e9e3f80,0xbf730000,0xbf4fbf4f,0x3f16bf16,0x3f803e9e,0x3f73,0xbf4f3e9e,0xbf16bf73,0x3ee83f80,0xbf640000,0xbf7dbf16,0x3e20bf4f,0x3f35be9e,0x3f353f73,0x3e203f73,0xbf7dbe9e,
0x3f163f80,0xbf4f0000,0xbf73be9e,0xbe9ebf73,0xbf4f,0x3f803f16,0x3f733f4f,0xbe9e3f16,0x3f353f80,0xbf350000,0xbf350000,0xbf35bf80,0xbf35bf80,0x3f350000,0x3f350000,0x3f353f80,
0x3f4f3f80,0xbf160000,0xbe9e3e9e,0xbf73bf73,0xbf80bf4f,0xbf16,0xbe9ebf4f,0x3f733f16,0x3f643f80,0xbee80000,0x3e203f16,0xbf7dbf4f,0xbf35be9e,0xbf35bf73,0xbf7dbf73,0x3e20be9e,
0x3f733f80,0xbe9e0000,0x3f163f4f,0xbf4fbf16,0x3e9e,0xbf80bf73,0xbf16be9e,0xbf4fbf73,0x3f7d3f80,0xbe200000,0x3f643f73,0xbee8be9e,0x3f353f4f,0xbf35bf16,0x3ee83f16,0xbf64bf4f,
0x3f803f80,0,0x3f803f80,0,0x3f803f80,0,0x3f803f80,0,0x3e203e9e,0x3f7d3f73,0xbe200000,0x3f7d3f80,0xbee8be9e,0x3f643f73,0xbf35bf16,0x3f353f4f,
0xbf73bf4f,0x3e9e3f16,0xbf73bf80,0xbe9e0000,0xbf16bf4f,0xbf4fbf16,0xbe9e,0xbf80bf73,0xbee8bf4f,0xbf64bf16,0x3ee80000,0xbf64bf80,0x3f7d3f4f,0xbe20bf16,0x3f353f73,0x3f353e9e,
0x3f4f3e9e,0xbf16bf73,0x3f4f3f80,0x3f160000,0xbe9e3e9e,0x3f733f73,0xbf80bf4f,0x3f16,0x3f353f80,0x3f350000,0xbf350000,0x3f353f80,0xbf35bf80,0xbf350000,0x3f350000,0xbf35bf80,
0xbf163e9e,0x3f4f3f73,0xbf16bf80,0xbf4f0000,0x3f733e9e,0xbe9ebf73,0x3f4f,0x3f803f16,0xbf64bf4f,0xbee83f16,0x3f640000,0xbee8bf80,0xbe203f4f,0x3f7d3f16,0xbf35bf73,0xbf353e9e,
0x3e9ebf4f,0xbf73bf16,0x3e9e3f80,0x3f730000,0xbf4fbf4f,0xbf163f16,0x3f803e9e,0xbf73,0x3f7d3e9e,0x3e20bf73,0xbf7d0000,0x3e203f80,0x3f64be9e,0xbee8bf73,0xbf353f16,0x3f353f4f,
0x3f80,0x3f800000,0xbf80,0xbf800000,0x3f80,0x3f800000,0xbf80,0xbf800000,0xbf7d3e9e,0x3e203f73,0x3f7d0000,0x3e20bf80,0xbf64be9e,0xbee83f73,0x3f353f16,0x3f35bf4f,
0xbe9ebf4f,0xbf733f16,0xbe9e3f80,0x3f730000,0x3f4fbf4f,0xbf16bf16,0xbf803e9e,0x3f73,0x3f64bf4f,0xbee8bf16,0xbf640000,0xbee83f80,0x3e203f4f,0x3f7dbf16,0x3f35bf73,0xbf35be9e,
0x3f163e9e,0x3f4fbf73,0x3f16bf80,0xbf4f0000,0xbf733e9e,0xbe9e3f73,0x3f4f,0x3f80bf16,0xbf353f80,0x3f350000,0x3f350000,0x3f35bf80,0x3f35bf80,0xbf350000,0xbf350000,0xbf353f80,
0xbf4f3e9e,0xbf163f73,0xbf4f3f80,0x3f160000,0x3e9e3e9e,0x3f73bf73,0x3f80bf4f,0xbf16,0x3ee8bf4f,0xbf643f16,0xbee80000,0xbf643f80,0xbf7d3f4f,0xbe203f16,0xbf353f73,0x3f35be9e,
0x3f73bf4f,0x3e9ebf16,0x3f73bf80,0xbe9e0000,0x3f16bf4f,0xbf4f3f16,0xbe9e,0xbf803f73,0xbe203e9e,0x3f7dbf73,0x3e200000,0x3f7dbf80,0x3ee8be9e,0x3f64bf73,0x3f35bf16,0x3f35bf4f,
0xbf803f80,0,0xbf803f80,0,0xbf803f80,0,0xbf803f80,0,0xbe203e9e,0xbf7d3f73,0x3e200000,0xbf7d3f80,0x3ee8be9e,0xbf643f73,0x3f35bf16,0xbf353f4f,
0x3f73bf4f,0xbe9e3f16,0x3f73bf80,0x3e9e0000,0x3f16bf4f,0x3f4fbf16,0xbe9e,0x3f80bf73,0x3ee8bf4f,0x3f64bf16,0xbee80000,0x3f64bf80,0xbf7d3f4f,0x3e20bf16,0xbf353f73,0xbf353e9e,
0xbf4f3e9e,0x3f16bf73,0xbf4f3f80,0xbf160000,0x3e9e3e9e,0xbf733f73,0x3f80bf4f,0x3f16,0xbf353f80,0xbf350000,0x3f350000,0xbf353f80,0x3f35bf80,0x3f350000,0xbf350000,0x3f35bf80,
0x3f163e9e,0xbf4f3f73,0x3f16bf80,0x3f4f0000,0xbf733e9e,0x3e9ebf73,0x3f4f,0xbf803f16,0x3f64bf4f,0x3ee83f16,0xbf640000,0x3ee8bf80,0x3e203f4f,0xbf7d3f16,0x3f35bf73,0x3f353e9e,
0xbe9ebf4f,0x3f73bf16,0xbe9e3f80,0xbf730000,0x3f4fbf4f,0x3f163f16,0xbf803e9e,0xbf73,0xbf7d3e9e,0xbe20bf73,0x3f7d0000,0xbe203f80,0xbf64be9e,0x3ee8bf73,0x3f353f16,0xbf353f4f,
0x3f80,0xbf800000,0xbf80,0x3f800000,0x3f80,0xbf800000,0xbf80,0x3f800000,0x3f7d3e9e,0xbe203f73,0xbf7d0000,0xbe20bf80,0x3f64be9e,0x3ee83f73,0xbf353f16,0xbf35bf4f,
0x3e9ebf4f,0x3f733f16,0x3e9e3f80,0xbf730000,0xbf4fbf4f,0x3f16bf16,0x3f803e9e,0x3f73,0xbf64bf4f,0x3ee8bf16,0x3f640000,0x3ee83f80,0xbe203f4f,0xbf7dbf16,0xbf35bf73,0x3f35be9e,
0xbf163e9e,0xbf4fbf73,0xbf16bf80,0x3f4f0000,0x3f733e9e,0x3e9e3f73,0x3f4f,0xbf80bf16,0x3f353f80,0xbf350000,0xbf350000,0xbf35bf80,0xbf35bf80,0x3f350000,0x3f350000,0x3f353f80,
0x3f4f3e9e,0x3f163f73,0x3f4f3f80,0xbf160000,0xbe9e3e9e,0xbf73bf73,0xbf80bf4f,0xbf16,0xbee8bf4f,0x3f643f16,0x3ee80000,0x3f643f80,0x3f7d3f4f,0x3e203f16,0x3f353f73,0xbf35be9e,
0xbf73bf4f,0xbe9ebf16,0xbf73bf80,0x3e9e0000,0xbf16bf4f,0x3f4f3f16,0xbe9e,0x3f803f73,0x3e203e9e,0xbf7dbf73,0xbe200000,0xbf7dbf80,0xbee8be9e,0xbf64bf73,0xbf35bf16,0xbf35bf4f,
0x3f803f80,0,0x3f803f80,0,0x3f803f80,0,0x3f803f80,0,0xbf64bf4f,0x3ee83f16,0xbf7dbf73,0x3e203e9e,0xbf7dbf80,0xbe200000,0xbf64bf73,0xbee8be9e,
0x3f163e9e,0xbf4fbf73,0x3f733f4f,0xbe9ebf16,0x3f733f80,0x3e9e0000,0x3f163f4f,0x3f4f3f16,0xbe203e9e,0x3f7d3f73,0xbf64bf16,0x3ee83f4f,0xbf64bf80,0xbee80000,0xbe20bf16,0xbf7dbf4f,
0xbe9ebf4f,0xbf73bf16,0x3f4f3e9e,0xbf16bf73,0x3f4f3f80,0x3f160000,0xbe9e3e9e,0x3f733f73,0x3f353f80,0x3f350000,0xbf350000,0x3f353f80,0xbf35bf80,0xbf350000,0x3f350000,0xbf35bf80,
0xbf73bf4f,0xbe9e3f16,0x3f16be9e,0xbf4fbf73,0x3f163f80,0x3f4f0000,0xbf73be9e,0x3e9e3f73,0x3f7d3e9e,0xbe20bf73,0xbee83f16,0x3f643f4f,0xbee8bf80,0xbf640000,0x3f7d3f16,0x3e20bf4f,
0xbf4f3e9e,0x3f163f73,0x3e9ebf4f,0xbf73bf16,0x3e9e3f80,0x3f730000,0xbf4fbf4f,0xbf163f16,0x3ee8bf4f,0xbf64bf16,0xbe203f73,0x3f7d3e9e,0xbe20bf80,0xbf7d0000,0x3ee83f73,0x3f64be9e,
0x3f80,0x3f800000,0xbf80,0xbf800000,0x3f80,0x3f800000,0xbf80,0xbf800000,0xbee8bf4f,0xbf643f16,0x3e203f73,0x3f7dbe9e,0x3e20bf80,0xbf7d0000,0xbee83f73,0x3f643e9e,
0x3f4f3e9e,0x3f16bf73,0xbe9ebf4f,0xbf733f16,0xbe9e3f80,0x3f730000,0x3f4fbf4f,0xbf16bf16,0xbf7d3e9e,0xbe203f73,0x3ee83f16,0x3f64bf4f,0x3ee8bf80,0xbf640000,0xbf7d3f16,0x3e203f4f,
0x3f73bf4f,0xbe9ebf16,0xbf16be9e,0xbf4f3f73,0xbf163f80,0x3f4f0000,0x3f73be9e,0x3e9ebf73,0xbf353f80,0x3f350000,0x3f350000,0x3f35bf80,0x3f35bf80,0xbf350000,0xbf350000,0xbf353f80,
0x3e9ebf4f,0xbf733f16,0xbf4f3e9e,0xbf163f73,0xbf4f3f80,0x3f160000,0x3e9e3e9e,0x3f73bf73,0x3e203e9e,0x3f7dbf73,0x3f64bf16,0x3ee8bf4f,0x3f64bf80,0xbee80000,0x3e20bf16,0xbf7d3f4f,
0xbf163e9e,0xbf4f3f73,0xbf733f4f,0xbe9e3f16,0xbf733f80,0x3e9e0000,0xbf163f4f,0x3f4fbf16,0x3f64bf4f,0x3ee8bf16,0x3f7dbf73,0x3e20be9e,0x3f7dbf80,0xbe200000,0x3f64bf73,0xbee83e9e,
0xbf803f80,0,0xbf803f80,0,0xbf803f80,0,0xbf803f80,0,0x3f64bf4f,0xbee83f16,0x3f7dbf73,0xbe203e9e,0x3f7dbf80,0x3e200000,0x3f64bf73,0x3ee8be9e,
0xbf163e9e,0x3f4fbf73,0xbf733f4f,0x3e9ebf16,0xbf733f80,0xbe9e0000,0xbf163f4f,0xbf4f3f16,0x3e203e9e,0xbf7d3f73,0x3f64bf16,0xbee83f4f,0x3f64bf80,0x3ee80000,0x3e20bf16,0x3f7dbf4f,
0x3e9ebf4f,0x3f73bf16,0xbf4f3e9e,0x3f16bf73,0xbf4f3f80,0xbf160000,0x3e9e3e9e,0xbf733f73,0xbf353f80,0xbf350000,0x3f350000,0xbf353f80,0x3f35bf80,0x3f350000,0xbf350000,0x3f35bf80,
0x3f73bf4f,0x3e9e3f16,0xbf16be9e,0x3f4fbf73,0xbf163f80,0xbf4f0000,0x3f73be9e,0xbe9e3f73,0xbf7d3e9e,0x3e20bf73,0x3ee83f16,0xbf643f4f,0x3ee8bf80,0x3f640000,0xbf7d3f16,0xbe20bf4f,
0x3f4f3e9e,0xbf163f73,0xbe9ebf4f,0x3f73bf16,0xbe9e3f80,0xbf730000,0x3f4fbf4f,0x3f163f16,0xbee8bf4f,0x3f64bf16,0x3e203f73,0xbf7d3e9e,0x3e20bf80,0x3f7d0000,0xbee83f73,0xbf64be9e,
0x3f80,0xbf800000,0xbf80,0x3f800000,0x3f80,0xbf800000,0xbf80,0x3f800000,0x3ee8bf4f,0x3f643f16,0xbe203f73,0xbf7dbe9e,0xbe20bf80,0x3f7d0000,0x3ee83f73,0xbf643e9e,
0xbf4f3e9e,0xbf16bf73,0x3e9ebf4f,0x3f733f16,0x3e9e3f80,0xbf730000,0xbf4fbf4f,0x3f16bf16,0x3f7d3e9e,0x3e203f73,0xbee83f16,0xbf64bf4f,0xbee8bf80,0x3f640000,0x3f7d3f16,0xbe203f4f,
0xbf73bf4f,0x3e9ebf16,0x3f16be9e,0x3f4f3f73,0x3f163f80,0xbf4f0000,0xbf73be9e,0xbe9ebf73,0x3f353f80,0xbf350000,0xbf350000,0xbf35bf80,0xbf35bf80,0x3f350000,0x3f350000,0x3f353f80,
0xbe9ebf4f,0x3f733f16,0x3f4f3e9e,0x3f163f73,0x3f4f3f80,0xbf160000,0xbe9e3e9e,0xbf73bf73,0xbe203e9e,0xbf7dbf73,0xbf64bf16,0xbee8bf4f,0xbf64bf80,0x3ee80000,0xbe20bf16,0x3f7d3f4f,
0x3f163e9e,0x3f4f3f73,0x3f733f4f,0x3e9e3f16,0x3f733f80,0xbe9e0000,0x3f163f4f,0xbf4fbf16,0xbf64bf4f,0xbee8bf16,0xbf7dbf73,0xbe20be9e,0xbf7dbf80,0x3e200000,0xbf64bf73,0x3ee83e9e,
0x3f803f80,0,0x3f803f80,0,0x3f803f80,0,0x3f803f80,0,0xbf35bf4f,0xbf35bf16,0xbee8bf16,0xbf64bf4f,0xbe20be9e,0xbf7dbf73,0x3e200000,0xbf7dbf80,
0x3e9e,0x3f803f73,0xbf16be9e,0x3f4f3f73,0xbf73bf4f,0x3e9e3f16,0xbf73bf80,0xbe9e0000,0x3f353e9e,0xbf35bf73,0x3f7d3f73,0x3e20be9e,0x3ee83f4f,0x3f643f16,0xbee80000,0x3f643f80,
0xbf80bf4f,0x3f16,0xbe9ebf4f,0xbf73bf16,0x3f4f3e9e,0xbf16bf73,0x3f4f3f80,0x3f160000,0x3f353f80,0x3f350000,0xbf350000,0x3f353f80,0xbf35bf80,0xbf350000,0x3f350000,0xbf35bf80,
0xbf4f,0xbf80bf16,0x3f733f4f,0x3e9ebf16,0xbf163e9e,0x3f4f3f73,0xbf16bf80,0xbf4f0000,0xbf353e9e,0x3f353f73,0xbe20bf73,0xbf7dbe9e,0x3f643f4f,0x3ee8bf16,0xbf640000,0x3ee83f80,
0x3f803e9e,0xbf73,0xbf4f3e9e,0x3f163f73,0x3e9ebf4f,0xbf73bf16,0x3e9e3f80,0x3f730000,0xbf35bf4f,0xbf353f16,0x3f643f16,0x3ee8bf4f,0xbf7dbe9e,0xbe203f73,0x3f7d0000,0xbe20bf80,
0x3f80,0x3f800000,0xbf80,0xbf800000,0x3f80,0x3f800000,0xbf80,0xbf800000,0x3f35bf4f,0xbf35bf16,0xbf643f16,0x3ee83f4f,0x3f7dbe9e,0xbe20bf73,0xbf7d0000,0xbe203f80,
0xbf803e9e,0x3f73,0x3f4f3e9e,0x3f16bf73,0xbe9ebf4f,0xbf733f16,0xbe9e3f80,0x3f730000,0x3f353e9e,0x3f35bf73,0x3e20bf73,0xbf7d3e9e,0xbf643f4f,0x3ee83f16,0x3f640000,0x3ee8bf80,
0xbf4f,0xbf803f16,0xbf733f4f,0x3e9e3f16,0x3f163e9e,0x3f4fbf73,0x3f16bf80,0xbf4f0000,0xbf353f80,0x3f350000,0x3f350000,0x3f35bf80,0x3f35bf80,0xbf350000,0xbf350000,0xbf353f80,
0x3f80bf4f,0xbf16,0x3e9ebf4f,0xbf733f16,0xbf4f3e9e,0xbf163f73,0xbf4f3f80,0x3f160000,0xbf353e9e,0xbf353f73,0xbf7d3f73,0x3e203e9e,0xbee83f4f,0x3f64bf16,0x3ee80000,0x3f64bf80,
0x3e9e,0x3f80bf73,0x3f16be9e,0x3f4fbf73,0x3f73bf4f,0x3e9ebf16,0x3f73bf80,0xbe9e0000,0x3f35bf4f,0xbf353f16,0x3ee8bf16,0xbf643f4f,0x3e20be9e,0xbf7d3f73,0xbe200000,0xbf7d3f80,
0xbf803f80,0,0xbf803f80,0,0xbf803f80,0,0xbf803f80,0,0x3f35bf4f,0x3f35bf16,0x3ee8bf16,0x3f64bf4f,0x3e20be9e,0x3f7dbf73,0xbe200000,0x3f7dbf80,
0x3e9e,0xbf803f73,0x3f16be9e,0xbf4f3f73,0x3f73bf4f,0xbe9e3f16,0x3f73bf80,0x3e9e0000,0xbf353e9e,0x3f35bf73,0xbf7d3f73,0xbe20be9e,0xbee83f4f,0xbf643f16,0x3ee80000,0xbf643f80,
0x3f80bf4f,0x3f16,0x3e9ebf4f,0x3f73bf16,0xbf4f3e9e,0x3f16bf73,0xbf4f3f80,0xbf160000,0xbf353f80,0xbf350000,0x3f350000,0xbf353f80,0x3f35bf80,0x3f350000,0xbf350000,0x3f35bf80,
0xbf4f,0x3f80bf16,0xbf733f4f,0xbe9ebf16,0x3f163e9e,0xbf4f3f73,0x3f16bf80,0x3f4f0000,0x3f353e9e,0xbf353f73,0x3e20bf73,0x3f7dbe9e,0xbf643f4f,0xbee8bf16,0x3f640000,0xbee83f80,
0xbf803e9e,0xbf73,0x3f4f3e9e,0xbf163f73,0xbe9ebf4f,0x3f73bf16,0xbe9e3f80,0xbf730000,0x3f35bf4f,0x3f353f16,0xbf643f16,0xbee8bf4f,0x3f7dbe9e,0x3e203f73,0xbf7d0000,0x3e20bf80,
0x3f80,0xbf800000,0xbf80,0x3f800000,0x3f80,0xbf800000,0xbf80,0x3f800000,0xbf35bf4f,0x3f35bf16,0x3f643f16,0xbee83f4f,0xbf7dbe9e,0x3e20bf73,0x3f7d0000,0x3e203f80,
0x3f803e9e,0x3f73,0xbf4f3e9e,0xbf16bf73,0x3e9ebf4f,0x3f733f16,0x3e9e3f80,0xbf730000,0xbf353e9e,0xbf35bf73,0xbe20bf73,0x3f7d3e9e,0x3f643f4f,0xbee83f16,0xbf640000,0xbee8bf80,
0xbf4f,0x3f803f16,0x3f733f4f,0xbe9e3f16,0xbf163e9e,0xbf4fbf73,0xbf16bf80,0x3f4f0000,0x3f353f80,0xbf350000,0xbf350000,0xbf35bf80,0xbf35bf80,0x3f350000,0x3f350000,0x3f353f80,
0xbf80bf4f,0xbf16,0xbe9ebf4f,0x3f733f16,0x3f4f3e9e,0x3f163f73,0x3f4f3f80,0xbf160000,0x3f353e9e,0x3f353f73,0x3f7d3f73,0xbe203e9e,0x3ee83f4f,0xbf64bf16,0xbee80000,0xbf64bf80,
0x3e9e,0xbf80bf73,0xbf16be9e,0xbf4fbf73,0xbf73bf4f,0xbe9ebf16,0xbf73bf80,0x3e9e0000,0xbf35bf4f,0x3f353f16,0xbee8bf16,0x3f643f4f,0xbe20be9e,0x3f7d3f73,0x3e200000,0x3f7d3f80,
0x3f803f80,0,0x3f803f80,0,0x3f803f80,0,0x3f803f80,0,0x3ee83e9e,0xbf64bf73,0x3f353f16,0xbf35bf4f,0x3f643f4f,0xbee8bf16,0x3f7d3f73,0xbe20be9e,
0xbf16bf4f,0xbf4fbf16,0xbe9e,0xbf80bf73,0x3f163e9e,0xbf4fbf73,0x3f733f4f,0xbe9ebf16,0xbf7dbf4f,0x3e203f16,0xbf35bf73,0xbf35be9e,0x3e20be9e,0xbf7dbf73,0x3f643f16,0xbee8bf4f,
0xbe9e3e9e,0x3f733f73,0xbf80bf4f,0x3f16,0xbe9ebf4f,0xbf73bf16,0x3f4f3e9e,0xbf16bf73,0x3f353f80,0x3f350000,0xbf350000,0x3f353f80,0xbf35bf80,0xbf350000,0x3f350000,0xbf35bf80,
0x3f733e9e,0xbe9ebf73,0x3f4f,0x3f803f16,0xbf73bf4f,0xbe9e3f16,0x3f16be9e,0xbf4fbf73,0x3e20bf4f,0xbf7dbf16,0x3f353f73,0x3f35be9e,0xbf7dbe9e,0x3e203f73,0x3ee8bf16,0xbf64bf4f,
0xbf4fbf4f,0xbf163f16,0x3f803e9e,0xbf73,0xbf4f3e9e,0x3f163f73,0x3e9ebf4f,0xbf73bf16,0xbf643e9e,0x3ee83f73,0x3f35bf16,0xbf35bf4f,0xbee83f4f,0x3f643f16,0x3e20bf73,0xbf7dbe9e,
0x3f80,0x3f800000,0xbf80,0xbf800000,0x3f80,0x3f800000,0xbf80,0xbf800000,0x3f643e9e,0x3ee8bf73,0xbf35bf16,0xbf353f4f,0x3ee83f4f,0x3f64bf16,0xbe20bf73,0xbf7d3e9e,
0x3f4fbf4f,0xbf16bf16,0xbf803e9e,0x3f73,0x3f4f3e9e,0x3f16bf73,0xbe9ebf4f,0xbf733f16,0xbe20bf4f,0xbf7d3f16,0xbf353f73,0x3f353e9e,0x3f7dbe9e,0x3e20bf73,0xbee8bf16,0xbf643f4f,
0xbf733e9e,0xbe9e3f73,0x3f4f,0x3f80bf16,0x3f73bf4f,0xbe9ebf16,0xbf16be9e,0xbf4f3f73,0xbf353f80,0x3f350000,0x3f350000,0x3f35bf80,0x3f35bf80,0xbf350000,0xbf350000,0xbf353f80,
0x3e9e3e9e,0x3f73bf73,0x3f80bf4f,0xbf16,0x3e9ebf4f,0xbf733f16,0xbf4f3e9e,0xbf163f73,0x3f7dbf4f,0x3e20bf16,0x3f35bf73,0xbf353e9e,0xbe20be9e,0xbf7d3f73,0xbf643f16,0xbee83f4f,
0x3f16bf4f,0xbf4f3f16,0xbe9e,0xbf803f73,0xbf163e9e,0xbf4f3f73,0xbf733f4f,0xbe9e3f16,0xbee83e9e,0xbf643f73,0xbf353f16,0xbf353f4f,0xbf643f4f,0xbee83f16,0xbf7d3f73,0xbe203e9e,
0xbf803f80,0,0xbf803f80,0,0xbf803f80,0,0xbf803f80,0,0xbee83e9e,0x3f64bf73,0xbf353f16,0x3f35bf4f,0xbf643f4f,0x3ee8bf16,0xbf7d3f73,0x3e20be9e,
0x3f16bf4f,0x3f4fbf16,0xbe9e,0x3f80bf73,0xbf163e9e,0x3f4fbf73,0xbf733f4f,0x3e9ebf16,0x3f7dbf4f,0xbe203f16,0x3f35bf73,0x3f35be9e,0xbe20be9e,0x3f7dbf73,0xbf643f16,0x3ee8bf4f,
0x3e9e3e9e,0xbf733f73,0x3f80bf4f,0x3f16,0x3e9ebf4f,0x3f73bf16,0xbf4f3e9e,0x3f16bf73,0xbf353f80,0xbf350000,0x3f350000,0xbf353f80,0x3f35bf80,0x3f350000,0xbf350000,0x3f35bf80,
0xbf733e9e,0x3e9ebf73,0x3f4f,0xbf803f16,0x3f73bf4f,0x3e9e3f16,0xbf16be9e,0x3f4fbf73,0xbe20bf4f,0x3f7dbf16,0xbf353f73,0xbf35be9e,0x3f7dbe9e,0xbe203f73,0xbee8bf16,0x3f64bf4f,
0x3f4fbf4f,0x3f163f16,0xbf803e9e,0xbf73,0x3f4f3e9e,0xbf163f73,0xbe9ebf4f,0x3f73bf16,0x3f643e9e,0xbee83f73,0xbf35bf16,0x3f35bf4f,0x3ee83f4f,0xbf643f16,0xbe20bf73,0x3f7dbe9e,
0x3f80,0xbf800000,0xbf80,0x3f800000,0x3f80,0xbf800000,0xbf80,0x3f800000,0xbf643e9e,0xbee8bf73,0x3f35bf16,0x3f353f4f,0xbee83f4f,0xbf64bf16,0x3e20bf73,0x3f7d3e9e,
0xbf4fbf4f,0x3f16bf16,0x3f803e9e,0x3f73,0xbf4f3e9e,0xbf16bf73,0x3e9ebf4f,0x3f733f16,0x3e20bf4f,0x3f7d3f16,0x3f353f73,0xbf353e9e,0xbf7dbe9e,0xbe20bf73,0x3ee8bf16,0x3f643f4f,
0x3f733e9e,0x3e9e3f73,0x3f4f,0xbf80bf16,0xbf73bf4f,0x3e9ebf16,0x3f16be9e,0x3f4f3f73,0x3f353f80,0xbf350000,0xbf350000,0xbf35bf80,0xbf35bf80,0x3f350000,0x3f350000,0x3f353f80,
0xbe9e3e9e,0xbf73bf73,0xbf80bf4f,0xbf16,0xbe9ebf4f,0x3f733f16,0x3f4f3e9e,0x3f163f73,0xbf7dbf4f,0xbe20bf16,0xbf35bf73,0x3f353e9e,0x3e20be9e,0x3f7d3f73,0x3f643f16,0x3ee83f4f,
0xbf16bf4f,0x3f4f3f16,0xbe9e,0x3f803f73,0x3f163e9e,0x3f4f3f73,0x3f733f4f,0x3e9e3f16,0x3ee83e9e,0x3f643f73,0x3f353f16,0x3f353f4f,0x3f643f4f,0x3ee83f16,0x3f7d3f73,0x3e203e9e,
0x3f803f80,0x3f80,0xbf803f80,0x3f80,0x3f803f80,0xbf80,0xbf803f80,0xbf80,0x3f803f80,0x3f80,0xbf803f80,0x3f80,0x3f803f80,0xbf80,0xbf803f80,0xbf80,
0x3f7b3f80,0xbe483f80,0xbf7b3f80,0x3e483f80,0x3f553f6d,0x3f0ebf6d,0xbf553f6d,0xbf0ebf6d,0x3f0e3f35,0xbf553f35,0xbf0e3f35,0x3f553f35,0x3e483ec4,0x3f7bbec4,0xbe483ec4,0xbf7bbec4,
0x3f6d3f80,0xbec43f80,0xbf6d3f80,0x3ec43f80,0x3ec43f35,0x3f6dbf35,0xbec43f35,0xbf6dbf35,0xbec40000,0xbf6d0000,0x3ec40000,0x3f6d0000,0xbf6dbf35,0x3ec43f35,0x3f6dbf35,0xbec43f35,
0x3f553f80,0xbf0e3f80,0xbf553f80,0x3f0e3f80,0xbe483ec4,0x3f7bbec4,0x3e483ec4,0xbf7bbec4,0xbf7bbf35,0xbe48bf35,0x3f7bbf35,0x3e48bf35,0xbf0ebf6d,0xbf553f6d,0x3f0ebf6d,0x3f553f6d,
0x3f353f80,0xbf353f80,0xbf353f80,0x3f353f80,0xbf350000,0x3f350000,0x3f350000,0xbf350000,0xbf35bf80,0x3f35bf80,0x3f35bf80,0xbf35bf80,0x3f350000,0xbf350000,0xbf350000,0x3f350000,
0x3f0e3f80,0xbf553f80,0xbf0e3f80,0x3f553f80,0xbf7bbec4,0x3e483ec4,0x3f7bbec4,0xbe483ec4,0x3e48bf35,0x3f7bbf35,0xbe48bf35,0xbf7bbf35,0x3f553f6d,0x3f0ebf6d,0xbf553f6d,0xbf0ebf6d,
0x3ec43f80,0xbf6d3f80,0xbec43f80,0x3f6d3f80,0xbf6dbf35,0xbec43f35,0x3f6dbf35,0x3ec43f35,0x3f6d0000,0x3ec40000,0xbf6d0000,0xbec40000,0xbec43f35,0x3f6dbf35,0x3ec43f35,0xbf6dbf35,
0x3e483f80,0xbf7b3f80,0xbe483f80,0x3f7b3f80,0xbf0ebf6d,0xbf553f6d,0x3f0ebf6d,0x3f553f6d,0x3f553f35,0xbf0e3f35,0xbf553f35,0x3f0e3f35,0xbf7bbec4,0xbe483ec4,0x3f7bbec4,0x3e483ec4,
0x3f803f80,0x3f80,0xbf803f80,0x3f80,0x3f803f80,0xbf80,0xbf803f80,0xbf80,0x3f803f80,0x3f80,0xbf803f80,0x3f80,0x3f803f80,0xbf80,0xbf803f80,0xbf80,
0xbe480000,0xbf7b0000,0x3e480000,0x3f7b0000,0xbf0ebec4,0x3f553ec4,0x3f0ebec4,0xbf553ec4,0xbf55bf35,0xbf0ebf35,0x3f55bf35,0x3f0ebf35,0xbf7bbf6d,0x3e483f6d,0x3f7bbf6d,0xbe483f6d,
0xbf6dbf80,0x3ec4bf80,0x3f6dbf80,0xbec4bf80,0xbec4bf35,0xbf6d3f35,0x3ec4bf35,0x3f6d3f35,0x3ec40000,0x3f6d0000,0xbec40000,0xbf6d0000,0x3f6d3f35,0xbec4bf35,0xbf6d3f35,0x3ec4bf35,
0x3f0e0000,0x3f550000,0xbf0e0000,0xbf550000,0x3f7b3f6d,0x3e48bf6d,0xbf7b3f6d,0xbe48bf6d,0x3e483f35,0xbf7b3f35,0xbe483f35,0x3f7b3f35,0xbf55bec4,0x3f0e3ec4,0x3f55bec4,0xbf0e3ec4,
0x3f353f80,0xbf353f80,0xbf353f80,0x3f353f80,0xbf350000,0x3f350000,0x3f350000,0xbf350000,0xbf35bf80,0x3f35bf80,0x3f35bf80,0xbf35bf80,0x3f350000,0xbf350000,0xbf350000,0x3f350000,
0xbf550000,0xbf0e0000,0x3f550000,0x3f0e0000,0xbe48bf6d,0xbf7b3f6d,0x3e48bf6d,0x3f7b3f6d,0x3f7b3f35,0xbe483f35,0xbf7b3f35,0x3e483f35,0xbf0e3ec4,0x3f55bec4,0x3f0e3ec4,0xbf55bec4,
0xbec4bf80,0x3f6dbf80,0x3ec4bf80,0xbf6dbf80,0x3f6d3f35,0x3ec4bf35,0xbf6d3f35,0xbec4bf35,0xbf6d0000,0xbec40000,0x3f6d0000,0x3ec40000,0x3ec4bf35,0xbf6d3f35,0xbec4bf35,0x3f6d3f35,
0x3f7b0000,0x3e480000,0xbf7b0000,0xbe480000,0xbf553ec4,0x3f0ebec4,0x3f553ec4,0xbf0ebec4,0x3f0ebf35,0x3f55bf35,0xbf0ebf35,0xbf55bf35,0xbe483f6d,0x3f7bbf6d,0x3e483f6d,0xbf7bbf6d,
0x3f803f80,0x3f80,0xbf803f80,0x3f80,0x3f803f80,0xbf80,0xbf803f80,0xbf80,0x3f803f80,0x3f80,0xbf803f80,0x3f80,0x3f803f80,0xbf80,0xbf803f80,0xbf80,
0xbf7bbf80,0x3e48bf80,0x3f7bbf80,0xbe48bf80,0xbf55bf6d,0xbf0e3f6d,0x3f55bf6d,0x3f0e3f6d,0xbf0ebf35,0x3f55bf35,0x3f0ebf35,0xbf55bf35,0xbe48bec4,0xbf7b3ec4,0x3e48bec4,0x3f7b3ec4,
0x3f6d3f80,0xbec43f80,0xbf6d3f80,0x3ec43f80,0x3ec43f35,0x3f6dbf35,0xbec43f35,0xbf6dbf35,0xbec40000,0xbf6d0000,0x3ec40000,0x3f6d0000,0xbf6dbf35,0x3ec43f35,0x3f6dbf35,0xbec43f35,
0xbf55bf80,0x3f0ebf80,0x3f55bf80,0xbf0ebf80,0x3e48bec4,0xbf7b3ec4,0xbe48bec4,0x3f7b3ec4,0x3f7b3f35,0x3e483f35,0xbf7b3f35,0xbe483f35,0x3f0e3f6d,0x3f55bf6d,0xbf0e3f6d,0xbf55bf6d,
0x3f353f80,0xbf353f80,0xbf353f80,0x3f353f80,0xbf350000,0x3f350000,0x3f350000,0xbf350000,0xbf35bf80,0x3f35bf80,0x3f35bf80,0xbf35bf80,0x3f350000,0xbf350000,0xbf350000,0x3f350000,
0xbf0ebf80,0x3f55bf80,0x3f0ebf80,0xbf55bf80,0x3f7b3ec4,0xbe48bec4,0xbf7b3ec4,0x3e48bec4,0xbe483f35,0xbf7b3f35,0x3e483f35,0x3f7b3f35,0xbf55bf6d,0xbf0e3f6d,0x3f55bf6d,0x3f0e3f6d,
0x3ec43f80,0xbf6d3f80,0xbec43f80,0x3f6d3f80,0xbf6dbf35,0xbec43f35,0x3f6dbf35,0x3ec43f35,0x3f6d0000,0x3ec40000,0xbf6d0000,0xbec40000,0xbec43f35,0x3f6dbf35,0x3ec43f35,0xbf6dbf35,
0xbe48bf80,0x3f7bbf80,0x3e48bf80,0xbf7bbf80,0x3f0e3f6d,0x3f55bf6d,0xbf0e3f6d,0xbf55bf6d,0xbf55bf35,0x3f0ebf35,0x3f55bf35,0xbf0ebf35,0x3f7b3ec4,0x3e48bec4,0xbf7b3ec4,0xbe48bec4,
0x3f803f80,0x3f80,0xbf803f80,0x3f80,0x3f803f80,0xbf80,0xbf803f80,0xbf80,0x3f803f80,0x3f80,0xbf803f80,0x3f80,0x3f803f80,0xbf80,0xbf803f80,0xbf80,
0x3e480000,0x3f7b0000,0xbe480000,0xbf7b0000,0x3f0e3ec4,0xbf55bec4,0xbf0e3ec4,0x3f55bec4,0x3f553f35,0x3f0e3f35,0xbf553f35,0xbf0e3f35,0x3f7b3f6d,0xbe48bf6d,0xbf7b3f6d,0x3e48bf6d,
0xbf6dbf80,0x3ec4bf80,0x3f6dbf80,0xbec4bf80,0xbec4bf35,0xbf6d3f35,0x3ec4bf35,0x3f6d3f35,0x3ec40000,0x3f6d0000,0xbec40000,0xbf6d0000,0x3f6d3f35,0xbec4bf35,0xbf6d3f35,0x3ec4bf35,
0xbf0e0000,0xbf550000,0x3f0e0000,0x3f550000,0xbf7bbf6d,0xbe483f6d,0x3f7bbf6d,0x3e483f6d,0xbe48bf35,0x3f7bbf35,0x3e48bf35,0xbf7bbf35,0x3f553ec4,0xbf0ebec4,0xbf553ec4,0x3f0ebec4,
0x3f353f80,0xbf353f80,0xbf353f80,0x3f353f80,0xbf350000,0x3f350000,0x3f350000,0xbf350000,0xbf35bf80,0x3f35bf80,0x3f35bf80,0xbf35bf80,0x3f350000,0xbf350000,0xbf350000,0x3f350000,
0x3f550000,0x3f0e0000,0xbf550000,0xbf0e0000,0x3e483f6d,0x3f7bbf6d,0xbe483f6d,0xbf7bbf6d,0xbf7bbf35,0x3e48bf35,0x3f7bbf35,0xbe48bf35,0x3f0ebec4,0xbf553ec4,0xbf0ebec4,0x3f553ec4,
0xbec4bf80,0x3f6dbf80,0x3ec4bf80,0xbf6dbf80,0x3f6d3f35,0x3ec4bf35,0xbf6d3f35,0xbec4bf35,0xbf6d0000,0xbec40000,0x3f6d0000,0x3ec40000,0x3ec4bf35,0xbf6d3f35,0xbec4bf35,0x3f6d3f35,
0xbf7b0000,0xbe480000,0x3f7b0000,0x3e480000,0x3f55bec4,0xbf0e3ec4,0xbf55bec4,0x3f0e3ec4,0xbf0e3f35,0xbf553f35,0x3f0e3f35,0x3f553f35,0x3e48bf6d,0xbf7b3f6d,0xbe48bf6d,0x3f7b3f6d,
0,0x3f800000,0,0xbf800000,0,0xbf800000,0,0x3f800000,0,0x3f800000,0,0xbf800000,0,0xbf800000,0,0x3f800000,
0x3e480000,0x3f7b0000,0xbe480000,0xbf7b0000,0x3f0e3ec4,0xbf55bec4,0xbf0e3ec4,0x3f55bec4,0x3f553f35,0x3f0e3f35,0xbf553f35,0xbf0e3f35,0x3f7b3f6d,0xbe48bf6d,0xbf7b3f6d,0x3e48bf6d,
0x3ec40000,0x3f6d0000,0xbec40000,0xbf6d0000,0x3f6d3f35,0xbec4bf35,0xbf6d3f35,0x3ec4bf35,0x3f6d3f80,0xbec43f80,0xbf6d3f80,0x3ec43f80,0x3ec43f35,0x3f6dbf35,0xbec43f35,0xbf6dbf35,
0x3f0e0000,0x3f550000,0xbf0e0000,0xbf550000,0x3f7b3f6d,0x3e48bf6d,0xbf7b3f6d,0xbe48bf6d,0x3e483f35,0xbf7b3f35,0xbe483f35,0x3f7b3f35,0xbf55bec4,0x3f0e3ec4,0x3f55bec4,0xbf0e3ec4,
0x3f350000,0x3f350000,0xbf350000,0xbf350000,0x3f353f80,0x3f35bf80,0xbf353f80,0xbf35bf80,0xbf350000,0xbf350000,0x3f350000,0x3f350000,0xbf35bf80,0xbf353f80,0x3f35bf80,0x3f353f80,
0x3f550000,0x3f0e0000,0xbf550000,0xbf0e0000,0x3e483f6d,0x3f7bbf6d,0xbe483f6d,0xbf7bbf6d,0xbf7bbf35,0x3e48bf35,0x3f7bbf35,0xbe48bf35,0x3f0ebec4,0xbf553ec4,0xbf0ebec4,0x3f553ec4,
0x3f6d0000,0x3ec40000,0xbf6d0000,0xbec40000,0xbec43f35,0x3f6dbf35,0x3ec43f35,0xbf6dbf35,0xbec4bf80,0x3f6dbf80,0x3ec4bf80,0xbf6dbf80,0x3f6d3f35,0x3ec4bf35,0xbf6d3f35,0xbec4bf35,
0x3f7b0000,0x3e480000,0xbf7b0000,0xbe480000,0xbf553ec4,0x3f0ebec4,0x3f553ec4,0xbf0ebec4,0x3f0ebf35,0x3f55bf35,0xbf0ebf35,0xbf55bf35,0xbe483f6d,0x3f7bbf6d,0x3e483f6d,0xbf7bbf6d,
0,0x3f800000,0,0xbf800000,0,0xbf800000,0,0x3f800000,0,0x3f800000,0,0xbf800000,0,0xbf800000,0,0x3f800000,
0x3f7b3f80,0xbe483f80,0xbf7b3f80,0x3e483f80,0x3f553f6d,0x3f0ebf6d,0xbf553f6d,0xbf0ebf6d,0x3f0e3f35,0xbf553f35,0xbf0e3f35,0x3f553f35,0x3e483ec4,0x3f7bbec4,0xbe483ec4,0xbf7bbec4,
0xbec40000,0xbf6d0000,0x3ec40000,0x3f6d0000,0xbf6dbf35,0x3ec43f35,0x3f6dbf35,0xbec43f35,0xbf6dbf80,0x3ec4bf80,0x3f6dbf80,0xbec4bf80,0xbec4bf35,0xbf6d3f35,0x3ec4bf35,0x3f6d3f35,
0xbf55bf80,0x3f0ebf80,0x3f55bf80,0xbf0ebf80,0x3e48bec4,0xbf7b3ec4,0xbe48bec4,0x3f7b3ec4,0x3f7b3f35,0x3e483f35,0xbf7b3f35,0xbe483f35,0x3f0e3f6d,0x3f55bf6d,0xbf0e3f6d,0xbf55bf6d,
0x3f350000,0x3f350000,0xbf350000,0xbf350000,0x3f353f80,0x3f35bf80,0xbf353f80,0xbf35bf80,0xbf350000,0xbf350000,0x3f350000,0x3f350000,0xbf35bf80,0xbf353f80,0x3f35bf80,0x3f353f80,
0x3f0e3f80,0xbf553f80,0xbf0e3f80,0x3f553f80,0xbf7bbec4,0x3e483ec4,0x3f7bbec4,0xbe483ec4,0x3e48bf35,0x3f7bbf35,0xbe48bf35,0xbf7bbf35,0x3f553f6d,0x3f0ebf6d,0xbf553f6d,0xbf0ebf6d,
0xbf6d0000,0xbec40000,0x3f6d0000,0x3ec40000,0x3ec4bf35,0xbf6d3f35,0xbec4bf35,0x3f6d3f35,0x3ec43f80,0xbf6d3f80,0xbec43f80,0x3f6d3f80,0xbf6dbf35,0xbec43f35,0x3f6dbf35,0x3ec43f35,
0xbe48bf80,0x3f7bbf80,0x3e48bf80,0xbf7bbf80,0x3f0e3f6d,0x3f55bf6d,0xbf0e3f6d,0xbf55bf6d,0xbf55bf35,0x3f0ebf35,0x3f55bf35,0xbf0ebf35,0x3f7b3ec4,0x3e48bec4,0xbf7b3ec4,0xbe48bec4,
0,0x3f800000,0,0xbf800000,0,0xbf800000,0,0x3f800000,0,0x3f800000,0,0xbf800000,0,0xbf800000,0,0x3f800000,
0xbe480000,0xbf7b0000,0x3e480000,0x3f7b0000,0xbf0ebec4,0x3f553ec4,0x3f0ebec4,0xbf553ec4,0xbf55bf35,0xbf0ebf35,0x3f55bf35,0x3f0ebf35,0xbf7bbf6d,0x3e483f6d,0x3f7bbf6d,0xbe483f6d,
0x3ec40000,0x3f6d0000,0xbec40000,0xbf6d0000,0x3f6d3f35,0xbec4bf35,0xbf6d3f35,0x3ec4bf35,0x3f6d3f80,0xbec43f80,0xbf6d3f80,0x3ec43f80,0x3ec43f35,0x3f6dbf35,0xbec43f35,0xbf6dbf35,
0xbf0e0000,0xbf550000,0x3f0e0000,0x3f550000,0xbf7bbf6d,0xbe483f6d,0x3f7bbf6d,0x3e483f6d,0xbe48bf35,0x3f7bbf35,0x3e48bf35,0xbf7bbf35,0x3f553ec4,0xbf0ebec4,0xbf553ec4,0x3f0ebec4,
0x3f350000,0x3f350000,0xbf350000,0xbf350000,0x3f353f80,0x3f35bf80,0xbf353f80,0xbf35bf80,0xbf350000,0xbf350000,0x3f350000,0x3f350000,0xbf35bf80,0xbf353f80,0x3f35bf80,0x3f353f80,
0xbf550000,0xbf0e0000,0x3f550000,0x3f0e0000,0xbe48bf6d,0xbf7b3f6d,0x3e48bf6d,0x3f7b3f6d,0x3f7b3f35,0xbe483f35,0xbf7b3f35,0x3e483f35,0xbf0e3ec4,0x3f55bec4,0x3f0e3ec4,0xbf55bec4,
0x3f6d0000,0x3ec40000,0xbf6d0000,0xbec40000,0xbec43f35,0x3f6dbf35,0x3ec43f35,0xbf6dbf35,0xbec4bf80,0x3f6dbf80,0x3ec4bf80,0xbf6dbf80,0x3f6d3f35,0x3ec4bf35,0xbf6d3f35,0xbec4bf35,
0xbf7b0000,0xbe480000,0x3f7b0000,0x3e480000,0x3f55bec4,0xbf0e3ec4,0xbf55bec4,0x3f0e3ec4,0xbf0e3f35,0xbf553f35,0x3f0e3f35,0x3f553f35,0x3e48bf6d,0xbf7b3f6d,0xbe48bf6d,0x3f7b3f6d,
0,0x3f800000,0,0xbf800000,0,0xbf800000,0,0x3f800000,0,0x3f800000,0,0xbf800000,0,0xbf800000,0,0x3f800000,
0xbf7bbf80,0x3e48bf80,0x3f7bbf80,0xbe48bf80,0xbf55bf6d,0xbf0e3f6d,0x3f55bf6d,0x3f0e3f6d,0xbf0ebf35,0x3f55bf35,0x3f0ebf35,0xbf55bf35,0xbe48bec4,0xbf7b3ec4,0x3e48bec4,0x3f7b3ec4,
0xbec40000,0xbf6d0000,0x3ec40000,0x3f6d0000,0xbf6dbf35,0x3ec43f35,0x3f6dbf35,0xbec43f35,0xbf6dbf80,0x3ec4bf80,0x3f6dbf80,0xbec4bf80,0xbec4bf35,0xbf6d3f35,0x3ec4bf35,0x3f6d3f35,
0x3f553f80,0xbf0e3f80,0xbf553f80,0x3f0e3f80,0xbe483ec4,0x3f7bbec4,0x3e483ec4,0xbf7bbec4,0xbf7bbf35,0xbe48bf35,0x3f7bbf35,0x3e48bf35,0xbf0ebf6d,0xbf553f6d,0x3f0ebf6d,0x3f553f6d,
0x3f350000,0x3f350000,0xbf350000,0xbf350000,0x3f353f80,0x3f35bf80,0xbf353f80,0xbf35bf80,0xbf350000,0xbf350000,0x3f350000,0x3f350000,0xbf35bf80,0xbf353f80,0x3f35bf80,0x3f353f80,
0xbf0ebf80,0x3f55bf80,0x3f0ebf80,0xbf55bf80,0x3f7b3ec4,0xbe48bec4,0xbf7b3ec4,0x3e48bec4,0xbe483f35,0xbf7b3f35,0x3e483f35,0x3f7b3f35,0xbf55bf6d,0xbf0e3f6d,0x3f55bf6d,0x3f0e3f6d,
0xbf6d0000,0xbec40000,0x3f6d0000,0x3ec40000,0x3ec4bf35,0xbf6d3f35,0xbec4bf35,0x3f6d3f35,0x3ec43f80,0xbf6d3f80,0xbec43f80,0x3f6d3f80,0xbf6dbf35,0xbec43f35,0x3f6dbf35,0x3ec43f35,
0x3e483f80,0xbf7b3f80,0xbe483f80,0x3f7b3f80,0xbf0ebf6d,0xbf553f6d,0x3f0ebf6d,0x3f553f6d,0x3f553f35,0xbf0e3f35,0xbf553f35,0x3f0e3f35,0xbf7bbec4,0xbe483ec4,0x3f7bbec4,0x3e483ec4,
0x3f800000,0x3f800000,0x3f800000,0x3f7ec46d,0x3f800000,0x3f800000,0x3f7b14be,0x3f74fa0b,0x3f800000,0x3f800000,0x3f6c835e,0x3f61c598,0x3f800000,0x3f800000,0x3f54db31,0x3f45e403,
0x3f800000,0x3f7ffb11,0x3f800000,0x3f7e70b0,0x3f7fec43,0x3f7fd397,0x3f79c79d,0x3f721352,0x3f7fb10f,0x3f7f84ab,0x3f676bd8,0x3f59f26a,0x3f7f4e6d,0x3f7f0e58,0x3f49d112,0x3f373a23,
0x3f800000,0x3f7fec43,0x3f800000,0x3f7e1324,0x3f7fb10f,0x3f7f4e6d,0x3f7853f8,0x3f6ed89e,0x3f7ec46d,0x3f7e1324,0x3f61c598,0x3f514d3d,0x3f7d3aac,0x3f7c3b28,0x3f3daef9,0x3f273656,
0x3f800000,0x3f7fd397,0x3f800000,0x3f7dabcc,0x3f7f4e6d,0x3f7e70b0,0x3f76ba07,0x3f6b4b0c,0x3f7d3aac,0x3f7baccd,0x3f5b941a,0x3f47de65,0x3f79c79d,0x3f778bc5,0x3f3085bb,0x3f15f6d9,
0x3f800000,0x3f7fb10f,0x3f800000,0x3f7d3aac,0x3f7ec46d,0x3f7d3aac,0x3f74fa0b,0x3f676bd8,0x3f7b14be,0x3f7853f8,0x3f54db31,0x3f3daef9,0x3f74fa0b,0x3f710908,0x3f226799,0x3f039c3d,
0x3f800000,0x3f7f84ab,0x3f800000,0x3f7cbfc9,0x3f7e1324,0x3f7baccd,0x3f731447,0x3f633c5a,0x3f7853f8,0x3f740bdd,0x3f4d9f02,0x3f32c8c9,0x3f6ed89e,0x3f68bf3c,0x3f13682a,0x3ee0924f,
0x3f800000,0x3f7f4e6d,0x3f800000,0x3f7c3b28,0x3f7d3aac,0x3f79c79d,0x3f710908,0x3f5ebe05,0x3f74fa0b,0x3f6ed89e,0x3f45e403,0x3f273656,0x3f676bd8,0x3f5ebe05,0x3f039c3d,0x3eb8442a,
0x3f800000,0x3f7f0e58,0x3f800000,0x3f7baccd,0x3f7c3b28,0x3f778bc5,0x3f6ed89e,0x3f59f26a,0x3f710908,0x3f68bf3c,0x3f3daef9,0x3f1b02c6,0x3f5ebe05,0x3f531849,0x3ee63375,0x3e8e9a22,
0x3f800000,0x3f800000,0x3f3504f3,0x3f226799,0x3f800000,0x3f800000,0x3f0e39da,0x3ef15aea,0x3f800000,0x3f800000,0x3ec3ef15,0x3e94a031,0x3f800000,0x3f800000,0x3e47c5c2,0x3dc8bd36,
0x3f7ec46d,0x3f7e70b0,0x3f226799,0x3f0b9a6b,0x3f7e1324,0x3f7dabcc,0x3ee63375,0x3eb263ef,0x3f7d3aac,0x3f7cbfc9,0x3e78cfcc,0x3e09cf86,0x3f7c3b28,0x3f7baccd,0x3cc90ab0,0xbdafb680,
0x3f7b14be,0x3f79c79d,0x3f0e39da,0x3ee63375,0x3f7853f8,0x3f76ba07,0x3eac7cd4,0x3e605c13,0x3f74fa0b,0x3f731447,0x3dc8bd36,0xbcc90ab0,0x3f710908,0x3f6ed89e,0xbe164083,0xbe888e93,
0x3f74fa0b,0x3f721352,0x3ef15aea,0x3eb263ef,0x3f6ed89e,0x3f6b4b0c,0x3e605c13,0x3dafb680,0x3f676bd8,0x3f633c5a,0xbd48fb30,0xbe3b6ecf,0x3f5ebe05,0x3f59f26a,0xbea09ae5,0xbee0924f,
0x3f6c835e,0x3f676bd8,0x3ec3ef15,0x3e78cfcc,0x3f61c598,0x3f5b941a,0x3dc8bd36,0xbd48fb30,0x3f54db31,0x3f4d9f02,0xbe47c5c2,0xbeac7cd4,0x3f45e403,0x3f3daef9,0xbef15aea,0xbf187fc0,
0x3f61c598,0x3f59f26a,0x3e94a031,0x3e09cf86,0x3f514d3d,0x3f47de65,0xbcc90ab0,0xbe3b6ecf,0x3f3daef9,0x3f32c8c9,0xbeac7cd4,0xbef6e0cb,0x3f273656,0x3f1b02c6,0xbf1d7fd1,0xbf3b8f3b,
0x3f54db31,0x3f49d112,0x3e47c5c2,0x3cc90ab0,0x3f3daef9,0x3f3085bb,0xbe164083,0xbea09ae5,0x3f226799,0x3f13682a,0xbef15aea,0xbf1d7fd1,0x3f039c3d,0x3ee63375,0xbf3daef9,0xbf584853,
0x3f45e403,0x3f373a23,0x3dc8bd36,0xbdafb680,0x3f273656,0x3f15f6d9,0xbe888e93,0xbee0924f,0x3f039c3d,0x3ee0924f,0xbf187fc0,0xbf3b8f3b,0x3eb8442a,0x3e8e9a22,0xbf584853,0xbf6db293,
0x3f800000,0x3f800000,0,0xbdc8bd36,0x3f800000,0x3f800000,0xbe47c5c2,0xbe94a031,0x3f800000,0x3f800000,0xbec3ef15,0xbef15aea,0x3f800000,0x3f800000,0xbf0e39da,0xbf226799,
0x3f7b14be,0x3f7a7302,0xbe47c5c2,0xbe9aa086,0x3f79c79d,0x3f791298,0xbecf7bca,0xbf00e7e4,0x3f7853f8,0x3f778bc5,0xbf187fc0,0xbf2e3bde,0x3f76ba07,0x3f75dec6,0xbf41d870,0xbf531849,
0x3f6c835e,0x3f6a09a7,0xbec3ef15,0xbefc5d27,0x3f676bd8,0x3f64aa59,0xbf187fc0,0xbf3085bb,0x3f61c598,0x3f5ebe05,0xbf45e403,0xbf584853,0x3f5b941a,0x3f584853,0xbf676bd8,0xbf731447,
0x3f54db31,0x3f4f7a1f,0xbf0e39da,0xbf299415,0x3f49d112,0x3f43e200,0xbf41d870,0xbf5695e5,0x3f3daef9,0x3f373a23,0xbf676bd8,0xbf740bdd,0x3f3085bb,0x3f299415,0xbf7c3b28,0xbf7fd397,
0x3f3504f3,0x3f2beb4a,0xbf3504f3,0xbf4d9f02,0x3f226799,0x3f187fc0,0xbf61c598,0xbf710908,0x3f0e39da,0x3f039c3d,0xbf7b14be,0xbf7fb10f,0x3ef15aea,0x3edae880,0xbf7ec46d,0xbf7853f8,
0x3f0e39da,0x3f00e7e4,0xbf54db31,0xbf68bf3c,0x3ee63375,0x3ec9b953,0xbf76ba07,0xbf7e70b0,0x3eac7cd4,0x3e8e9a22,0xbf7fb10f,0xbf7a7302,0x3e605c13,0x3e22abb6,0xbf6ed89e,0xbf5d2d53,
0x3ec3ef15,0x3ea09ae5,0xbf6c835e,0xbf79c79d,0x3e78cfcc,0x3e2f10a2,0xbf7fb10f,0xbf7e1324,0x3dc8bd36,0x3cc90ab0,0xbf74fa0b,0xbf64aa59,0xbd48fb30,0xbdfab273,0xbf4d9f02,0xbf3085bb,
0x3e47c5c2,0x3de1bc2e,0xbf7b14be,0xbf7ffb11,0x3cc90ab0,0xbd7b2b74,0xbf7c3b28,0xbf6ff573,0xbe164083,0xbe6c9a7f,0xbf5b941a,0xbf3fc767,0xbea09ae5,0xbec9b953,0xbf1d7fd1,0xbeebcbbb,
0x3f800000,0x3f800000,0xbf3504f3,0xbf45e403,0x3f800000,0x3f800000,0xbf54db31,0xbf61c598,0x3f800000,0x3f800000,0xbf6c835e,0xbf74fa0b,0x3f800000,0x3f800000,0xbf7b14be,0xbf7ec46d,
0x3f74fa0b,0x3f740bdd,0xbf61c598,0xbf6db293,0x3f731447,0x3f721352,0xbf76ba07,0xbf7cbfc9,0x3f710908,0x3f6ff573,0xbf7fb10f,0xbf7f84ab,0x3f6ed89e,0x3f6db293,0xbf7c3b28,0xbf75dec6,
0x3f54db31,0x3f514d3d,0xbf7b14be,0xbf7f4e6d,0x3f4d9f02,0x3f49d112,0xbf7fb10f,0xbf7c3b28,0x3f45e403,0x3f41d870,0xbf74fa0b,0xbf6a09a7,0x3f3daef9,0x3f396842,0xbf5b941a,0xbf49d112,
0x3f226799,0x3f1b02c6,0xbf7ec46d,0xbf791298,0x3f13682a,0x3f0b9a6b,0xbf6ed89e,0xbf604621,0x3f039c3d,0x3ef6e0cb,0xbf4d9f02,0xbf373a23,0x3ee63375,0x3ed53641,0xbf1d7fd1,0xbf00e7e4,
0x3ec3ef15,0x3eac7cd4,0xbf6c835e,0xbf5b941a,0x3e94a031,0x3e78cfcc,0xbf45e403,0xbf2beb4a,0x3e47c5c2,0x3e164083,0xbf0e39da,0xbedae880,0x3dc8bd36,0x3d48fb30,0xbe94a031,0xbe164083,
0x3dc8bd36,0x3d16c32c,0xbf45e403,0xbf299415,0xbcc90ab0,0xbdafb680,0xbf08f59b,0xbec9b953,0xbe164083,0xbe541501,0xbe78cfcc,0xbdafb680,0xbe888e93,0xbea68f12,0x3d96a905,0x3e6c9a7f,
0xbe47c5c2,0xbe888e93,0xbf0e39da,0xbecf7bca,0xbeac7cd4,0xbecf7bca,0xbe78cfcc,0xbd96a905,0xbef15aea,0xbf08f59b,0x3dc8bd36,0x3e888e93,0xbf187fc0,0xbf273656,0x3edae880,0x3f13682a,
0xbef15aea,0xbf0b9a6b,0xbe94a031,0xbde1bc2e,0xbf1d7fd1,0xbf2e3bde,0x3d96a905,0x3e827dc0,0xbf3daef9,0xbf4bbbf8,0x3edae880,0x3f15f6d9,0xbf584853,0xbf633c5a,0x3f396842,0x3f5695e5,
0,0,0,0x3dc8bd36,0,0,0x3e47c5c2,0x3e94a031,0,0,0x3ec3ef15,0x3ef15aea,0,0,0x3f0e39da,0x3f226799,
0,0x3c490e90,0,0x3de1bc2e,0x3cc90ab0,0x3d16c32c,0x3e605c13,0x3ea68f12,0x3d48fb30,0x3d7b2b74,0x3edae880,0x3f064b82,0x3d96a905,0x3dafb680,0x3f1d7fd1,0x3f32c8c9,
0,0x3cc90ab0,0,0x3dfab273,0x3d48fb30,0x3d96a905,0x3e78cfcc,0x3eb8442a,0x3dc8bd36,0x3dfab273,0x3ef15aea,0x3f13682a,0x3e164083,0x3e2f10a2,0x3f2beb4a,0x3f41d870,
0,0x3d16c32c,0,0x3e09cf86,0x3d96a905,0x3de1bc2e,0x3e888e93,0x3ec9b953,0x3e164083,0x3e3b6ecf,0x3f039c3d,0x3f1ff6cb,0x3e605c13,0x3e827dc0,0x3f396842,0x3f4f7a1f,
0,0x3d48fb30,0,0x3e164083,0x3dc8bd36,0x3e164083,0x3e94a031,0x3edae880,0x3e47c5c2,0x3e78cfcc,0x3f0e39da,0x3f2beb4a,0x3e94a031,0x3eac7cd4,0x3f45e403,0x3f5b941a,
0,0x3d7b2b74,0,0x3e22abb6,0x3dfab273,0x3e3b6ecf,0x3ea09ae5,0x3eebcbbb,0x3e78cfcc,0x3e9aa086,0x3f187fc0,0x3f373a23,0x3eb8442a,0x3ed53641,0x3f514d3d,0x3f660f88,
0,0x3d96a905,0,0x3e2f10a2,0x3e164083,0x3e605c13,0x3eac7cd4,0x3efc5d27,0x3e94a031,0x3eb8442a,0x3f226799,0x3f41d870,0x3edae880,0x3efc5d27,0x3f5b941a,0x3f6ed89e,
0,0x3dafb680,0,0x3e3b6ecf,0x3e2f10a2,0x3e827dc0,0x3eb8442a,0x3f064b82,0x3eac7cd4,0x3ed53641,0x3f2beb4a,0x3f4bbbf8,0x3efc5d27,0x3f10d3cd,0x3f64aa59,0x3f75dec6,
0,0,0x3f3504f3,0x3f45e403,0,0,0x3f54db31,0x3f61c598,0,0,0x3f6c835e,0x3f74fa0b,0,0,0x3f7b14be,0x3f7ec46d,
0x3dc8bd36,0x3de1bc2e,0x3f45e403,0x3f5695e5,0x3dfab273,0x3e09cf86,0x3f64aa59,0x3f6ff573,0x3e164083,0x3e22abb6,0x3f7853f8,0x3f7dabcc,0x3e2f10a2,0x3e3b6ecf,0x3f7fec43,0x3f7f0e58,
0x3e47c5c2,0x3e605c13,0x3f54db31,0x3f64aa59,0x3e78cfcc,0x3e888e93,0x3f710908,0x3f79c79d,0x3e94a031,0x3ea09ae5,0x3f7ec46d,0x3f7fec43,0x3eac7cd4,0x3eb8442a,0x3f7d3aac,0x3f76ba07,
0x3e94a031,0x3ea68f12,0x3f61c598,0x3f6ff573,0x3eb8442a,0x3ec9b953,0x3f79c79d,0x3f7f0e58,0x3edae880,0x3eebcbbb,0x3f7fb10f,0x3f7baccd,0x3efc5d27,0x3f064b82,0x3f731447,0x3f660f88,
0x3ec3ef15,0x3edae880,0x3f6c835e,0x3f7853f8,0x3ef15aea,0x3f039c3d,0x3f7ec46d,0x3f7fb10f,0x3f0e39da,0x3f187fc0,0x3f7b14be,0x3f710908,0x3f226799,0x3f2beb4a,0x3f61c598,0x3f4d9f02,
0x3ef15aea,0x3f064b82,0x3f74fa0b,0x3f7dabcc,0x3f13682a,0x3f1ff6cb,0x3f7fec43,0x3f7baccd,0x3f2beb4a,0x3f373a23,0x3f710908,0x3f604621,0x3f41d870,0x3f4bbbf8,0x3f49d112,0x3f2e3bde,
0x3f0e39da,0x3f1d7fd1,0x3f7b14be,0x3f7fec43,0x3f2beb4a,0x3f396842,0x3f7d3aac,0x3f731447,0x3f45e403,0x3f514d3d,0x3f61c598,0x3f49d112,0x3f5b941a,0x3f64aa59,0x3f2beb4a,0x3f08f59b,
0x3f226799,0x3f32c8c9,0x3f7ec46d,0x3f7f0e58,0x3f41d870,0x3f4f7a1f,0x3f76ba07,0x3f660f88,0x3f5b941a,0x3f660f88,0x3f4d9f02,0x3f2e3bde,0x3f6ed89e,0x3f75dec6,0x3f08f59b,0x3ebe1d4a,
0,0,0x3f800000,0x3f7ec46d,0,0,0x3f7b14be,0x3f74fa0b,0,0,0x3f6c835e,0x3f61c598,0,0,0x3f54db31,0x3f45e403,
0x3e47c5c2,0x3e541501,0x3f7b14be,0x3f740bdd,0x3e605c13,0x3e6c9a7f,0x3f6a09a7,0x3f5d2d53,0x3e78cfcc,0x3e827dc0,0x3f4d9f02,0x3f3b8f3b,0x3e888e93,0x3e8e9a22,0x3f273656,0x3f10d3cd,
0x3ec3ef15,0x3ecf7bca,0x3f6c835e,0x3f5ebe05,0x3edae880,0x3ee63375,0x3f4d9f02,0x3f396842,0x3ef15aea,0x3efc5d27,0x3f226799,0x3f08f59b,0x3f039c3d,0x3f08f59b,0x3edae880,0x3ea09ae5,
0x3f0e39da,0x3f15f6d9,0x3f54db31,0x3f3fc767,0x3f1d7fd1,0x3f24d225,0x3f273656,0x3f0b9a6b,0x3f2beb4a,0x3f32c8c9,0x3edae880,0x3e9aa086,0x3f396842,0x3f3fc767,0x3e2f10a2,0x3d16c32c,
0x3f3504f3,0x3f3daef9,0x3f3504f3,0x3f187fc0,0x3f45e403,0x3f4d9f02,0x3ef15aea,0x3eac7cd4,0x3f54db31,0x3f5b941a,0x3e47c5c2,0x3d48fb30,0x3f61c598,0x3f676bd8,0xbdc8bd36,0xbe78cfcc,
0x3f54db31,0x3f5d2d53,0x3f0e39da,0x3ed53641,0x3f64aa59,0x3f6b4b0c,0x3e888e93,0x3de1bc2e,0x3f710908,0x3f75dec6,0xbd48fb30,0xbe541501,0x3f79c79d,0x3f7cbfc9,0xbeb8442a,0xbf00e7e4,
0x3f6c835e,0x3f731447,0x3ec3ef15,0x3e605c13,0x3f7853f8,0x3f7c3b28,0x3d48fb30,0xbdfab273,0x3f7ec46d,0x3f7fec43,0xbe94a031,0xbee63375,0x3f7fb10f,0x3f7e1324,0xbf187fc0,0xbf396842,
0x3f7b14be,0x3f7e70b0,0x3e47c5c2,0x3c490e90,0x3f7fec43,0x3f7f84ab,0xbe2f10a2,0xbeb263ef,0x3f7d3aac,0x3f791298,0xbf039c3d,0xbf299415,0x3f731447,0x3f6b4b0c,0xbf49d112,0xbf633c5a,
0,0,0x3f3504f3,0x3f226799,0,0,0x3f0e39da,0x3ef15aea,0,0,0x3ec3ef15,0x3e94a031,0,0,0x3e47c5c2,0x3dc8bd36,
0x3e94a031,0x3e9aa086,0x3ef15aea,0x3ebe1d4a,0x3ea09ae5,0x3ea68f12,0x3e888e93,0x3e22abb6,0x3eac7cd4,0x3eb263ef,0x3d48fb30,0xbd7b2b74,0x3eb8442a,0x3ebe1d4a,0xbe2f10a2,0xbe8e9a22,
0x3f0e39da,0x3f13682a,0x3e47c5c2,0x3d96a905,0x3f187fc0,0x3f1d7fd1,0xbd48fb30,0xbe2f10a2,0x3f226799,0x3f273656,0xbe94a031,0xbecf7bca,0x3f2beb4a,0x3f3085bb,0xbf039c3d,0xbf1d7fd1,
0x3f45e403,0x3f4bbbf8,0xbdc8bd36,0xbe6c9a7f,0x3f514d3d,0x3f5695e5,0xbeb8442a,0xbef6e0cb,0x3f5b941a,0x3f604621,0xbf187fc0,0xbf32c8c9,0x3f64aa59,0x3f68bf3c,0xbf49d112,0xbf5d2d53,
0x3f6c835e,0x3f710908,0xbec3ef15,0xbf039c3d,0x3f74fa0b,0x3f7853f8,0xbf226799,0xbf3daef9,0x3f7b14be,0x3f7d3aac,0xbf54db31,0xbf676bd8,0x3f7ec46d,0x3f7fb10f,0xbf74fa0b,0xbf7d3aac,
0x3f7ec46d,0x3f7fd397,0xbf226799,0xbf3fc767,0x3f7fec43,0x3f7f0e58,0xbf584853,0xbf6b4b0c,0x3f7d3aac,0x3f7a7302,0xbf7853f8,0xbf7f0e58,0x3f76ba07,0x3f721352,0xbf7f4e6d,0xbf791298,
0x3f7b14be,0x3f76ba07,0xbf54db31,0xbf6a09a7,0x3f710908,0x3f6a09a7,0xbf7853f8,0xbf7f4e6d,0x3f61c598,0x3f584853,0xbf7ec46d,0xbf76ba07,0x3f4d9f02,0x3f41d870,0xbf676bd8,0xbf514d3d,
0x3f61c598,0x3f5695e5,0xbf74fa0b,0xbf7e70b0,0x3f49d112,0x3f3b8f3b,0xbf7f4e6d,0xbf778bc5,0x3f2beb4a,0x3f1b02c6,0xbf676bd8,0xbf4f7a1f,0x3f08f59b,0x3eebcbbb,0xbf3085bb,0xbf0b9a6b,
0x3f800000,0x3f7fffb1,0x3f7ffec4,0x3f7ffd39,0x3f7ffb11,0x3f7ff84a,0x3f7ff4e6,0x3f7ff0e3,0x3f7fec43,0x3f7fe705,0x3f7fe129,0x3f7fdaaf,0x3f7fd397,0x3f7fcbe2,0x3f7fc38f,0x3f7fba9e,
0x3f7fb10f,0x3f7fa6e3,0x3f7f9c18,0x3f7f90b1,0x3f7f84ab,0x3f7f7808,0x3f7f6ac7,0x3f7f5ce9,0x3f7f4e6d,0x3f7f3f54,0x3f7f2f9d,0x3f7f1f49,0x3f7f0e58,0x3f7efcc9,0x3f7eea9d,0x3f7ed7d4,
0x3f7ec46d,0x3f7eb069,0x3f7e9bc9,0x3f7e868b,0x3f7e70b0,0x3f7e5a38,0x3f7e4323,0x3f7e2b72,0x3f7e1324,0x3f7dfa38,0x3f7de0b1,0x3f7dc68c,0x3f7dabcc,0x3f7d906e,0x3f7d7474,0x3f7d57de,
0x3f7d3aac,0x3f7d1cdd,0x3f7cfe73,0x3f7cdf6c,0x3f7cbfc9,0x3f7c9f8a,0x3f7c7eb0,0x3f7c5d3a,0x3f7c3b28,0x3f7c187a,0x3f7bf531,0x3f7bd14d,0x3f7baccd,0x3f7b87b2,0x3f7b61fc,0x3f7b3bab,
0x3f7b14be,0x3f7aed37,0x3f7ac516,0x3f7a9c59,0x3f7a7302,0x3f7a4910,0x3f7a1e84,0x3f79f35e,0x3f79c79d,0x3f799b43,0x3f796e4e,0x3f7940c0,0x3f791298,0x3f78e3d6,0x3f78b47b,0x3f788486,
0x3f7853f8,0x3f7822d1,0x3f77f110,0x3f77beb7,0x3f778bc5,0x3f77583a,0x3f772417,0x3f76ef5b,0x3f76ba07,0x3f76841b,0x3f764d97,0x3f76167a,0x3f75dec6,0x3f75a67b,0x3f756d97,0x3f75341d,
0x3f74fa0b,0x3f74bf62,0x3f748422,0x3f74484b,0x3f740bdd,0x3f73ced9,0x3f73913f,0x3f73530e,0x3f731447,0x3f72d4eb,0x3f7294f8,0x3f725470,0x3f721352,0x3f71d19f,0x3f718f57,0x3f714c7a,
0x3f710908,0x3f70c501,0x3f708066,0x3f703b37,0x3f6ff573,0x3f6faf1b,0x3f6f6830,0x3f6f20b0,0x3f6ed89e,0x3f6e8ff8,0x3f6e46be,0x3f6dfcf2,0x3f6db293,0x3f6d67a1,0x3f6d1c1d,0x3f6cd007,
0x3f6c835e,0x3f6c3624,0x3f6be858,0x3f6b99fb,0x3f6b4b0c,0x3f6afb8c,0x3f6aab7b,0x3f6a5ad9,0x3f6a09a7,0x3f69b7e4,0x3f696591,0x3f6912ae,0x3f68bf3c,0x3f686b39,0x3f6816a8,0x3f67c187,
0x3f676bd8,0x3f671599,0x3f66becc,0x3f666771,0x3f660f88,0x3f65b710,0x3f655e0b,0x3f650479,0x3f64aa59,0x3f644fac,0x3f63f473,0x3f6398ac,0x3f633c5a,0x3f62df7b,0x3f628210,0x3f62241a,
0x3f61c598,0x3f61668a,0x3f6106f2,0x3f60a6cf,0x3f604621,0x3f5fe4e9,0x3f5f8327,0x3f5f20db,0x3f5ebe05,0x3f5e5aa6,0x3f5df6be,0x3f5d924d,0x3f5d2d53,0x3f5cc7d1,0x3f5c61c7,0x3f5bfb34,
0x3f5b941a,0x3f5b2c79,0x3f5ac450,0x3f5a5ba0,0x3f59f26a,0x3f5988ad,0x3f591e6a,0x3f58b3a1,0x3f584853,0x3f57dc7f,0x3f577026,0x3f570348,0x3f5695e5,0x3f5627fe,0x3f55b993,0x3f554aa4,
0x3f54db31,0x3f546b3b,0x3f53fac3,0x3f5389c7,0x3f531849,0x3f52a649,0x3f5233c6,0x3f51c0c2,0x3f514d3d,0x3f50d937,0x3f5064af,0x3f4fefa8,0x3f4f7a1f,0x3f4f0417,0x3f4e8d90,0x3f4e1689,
0x3f4d9f02,0x3f4d26fd,0x3f4cae79,0x3f4c3578,0x3f4bbbf8,0x3f4b41fa,0x3f4ac77f,0x3f4a4c87,0x3f49d112,0x3f495521,0x3f48d8b3,0x3f485bca,0x3f47de65,0x3f476085,0x3f46e22a,0x3f466354,
0x3f45e403,0x3f456439,0x3f44e3f5,0x3f446337,0x3f43e200,0x3f436051,0x3f42de29,0x3f425b89,0x3f41d870,0x3f4154e1,0x3f40d0da,0x3f404c5c,0x3f3fc767,0x3f3f41fc,0x3f3ebc1b,0x3f3e35c5,
0x3f3daef9,0x3f3d27b8,0x3f3ca003,0x3f3c17d9,0x3f3b8f3b,0x3f3b0629,0x3f3a7ca4,0x3f39f2ac,0x3f396842,0x3f38dd65,0x3f385216,0x3f37c655,0x3f373a23,0x3f36ad7f,0x3f36206c,0x3f3592e7,
0x3f3504f3,0x3f34768f,0x3f33e7bc,0x3f33587a,0x3f32c8c9,0x3f3238aa,0x3f31a81d,0x3f311722,0x3f3085bb,0x3f2ff3e6,0x3f2f61a5,0x3f2ecef7,0x3f2e3bde,0x3f2da859,0x3f2d1469,0x3f2c800f,
0x3f2beb4a,0x3f2b561b,0x3f2ac082,0x3f2a2a80,0x3f299415,0x3f28fd41,0x3f286605,0x3f27ce61,0x3f273656,0x3f269de3,0x3f26050a,0x3f256bcb,0x3f24d225,0x3f24381a,0x3f239da9,0x3f2302d3,
0x3f226799,0x3f21cbfb,0x3f212ff9,0x3f209393,0x3f1ff6cb,0x3f1f599f,0x3f1ebc12,0x3f1e1e22,0x3f1d7fd1,0x3f1ce11f,0x3f1c420c,0x3f1ba299,0x3f1b02c6,0x3f1a6293,0x3f19c200,0x3f19210f,
0x3f187fc0,0x3f17de12,0x3f173c07,0x3f16999f,0x3f15f6d9,0x3f1553b7,0x3f14b039,0x3f140c5f,0x3f13682a,0x3f12c39a,0x3f121eb0,0x3f11796b,0x3f10d3cd,0x3f102dd5,0x3f0f8784,0x3f0ee0db,
0x3f0e39da,0x3f0d9281,0x3f0cead0,0x3f0c42c9,0x3f0b9a6b,0x3f0af1b7,0x3f0a48ad,0x3f099f4e,0x3f08f59b,0x3f084b92,0x3f07a136,0x3f06f686,0x3f064b82,0x3f05a02c,0x3f04f484,0x3f044889,
0x3f039c3d,0x3f02ef9f,0x3f0242b1,0x3f019573,0x3f00e7e4,0x3f003a06,0x3eff17b2,0x3efdbabb,0x3efc5d27,0x3efafef7,0x3ef9a02d,0x3ef840c8,0x3ef6e0cb,0x3ef58035,0x3ef41f07,0x3ef2bd43,
0x3ef15aea,0x3eeff7fb,0x3eee9479,0x3eed3063,0x3eebcbbb,0x3eea6681,0x3ee900b7,0x3ee79a5d,0x3ee63375,0x3ee4cbfe,0x3ee363fa,0x3ee1fb6a,0x3ee0924f,0x3edf28a9,0x3eddbe79,0x3edc53c1,
0x3edae880,0x3ed97cb9,0x3ed8106b,0x3ed6a399,0x3ed53641,0x3ed3c867,0x3ed25a09,0x3ed0eb2a,0x3ecf7bca,0x3ece0bea,0x3ecc9b8b,0x3ecb2aae,0x3ec9b953,0x3ec8477c,0x3ec6d529,0x3ec5625c,
0x3ec3ef15,0x3ec27b55,0x3ec1071e,0x3ebf926f,0x3ebe1d4a,0x3ebca7af,0x3ebb31a0,0x3eb9bb1e,0x3eb8442a,0x3eb6ccc3,0x3eb554ec,0x3eb3dca5,0x3eb263ef,0x3eb0eacb,0x3eaf713a,0x3eadf73c,
0x3eac7cd4,0x3eab0201,0x3ea986c4,0x3ea80b1f,0x3ea68f12,0x3ea5129f,0x3ea395c5,0x3ea21887,0x3ea09ae5,0x3e9f1cdf,0x3e9d9e78,0x3e9c1faf,0x3e9aa086,0x3e9920fe,0x3e97a117,0x3e9620d2,
0x3e94a031,0x3e931f35,0x3e919ddd,0x3e901c2c,0x3e8e9a22,0x3e8d17c0,0x3e8b9507,0x3e8a11f7,0x3e888e93,0x3e870ada,0x3e8586ce,0x3e840270,0x3e827dc0,0x3e80f8c0,0x3e7ee6e1,0x3e7bdba4,
0x3e78cfcc,0x3e75c35a,0x3e72b651,0x3e6fa8b2,0x3e6c9a7f,0x3e698bba,0x3e667c66,0x3e636c83,0x3e605c13,0x3e5d4b1a,0x3e5a3997,0x3e57278f,0x3e541501,0x3e5101f1,0x3e4dee60,0x3e4ada4f,
0x3e47c5c2,0x3e44b0b9,0x3e419b37,0x3e3e853e,0x3e3b6ecf,0x3e3857ec,0x3e354098,0x3e3228d4,0x3e2f10a2,0x3e2bf804,0x3e28defc,0x3e25c58c,0x3e22abb6,0x3e1f917b,0x3e1c76de,0x3e195be0,
0x3e164083,0x3e1324ca,0x3e1008b7,0x3e0cec4a,0x3e09cf86,0x3e06b26e,0x3e039502,0x3e007745,0x3dfab273,0x3df475c0,0x3dee3876,0x3de7fa9a,0x3de1bc2e,0x3ddb7d37,0x3dd53db9,0x3dcefdb7,
0x3dc8bd36,0x3dc27c39,0x3dbc3ac3,0x3db5f8da,0x3dafb680,0x3da973ba,0x3da3308c,0x3d9cecf9,0x3d96a905,0x3d9064b4,0x3d8a200a,0x3d83db0a,0x3d7b2b74,0x3d6ea038,0x3d621469,0x3d55880e,
0x3d48fb30,0x3d3c6dd5,0x3d2fe007,0x3d2351cb,0x3d16c32c,0x3d0a342f,0x3cfb49ba,0x3ce22a7a,0x3cc90ab0,0x3cafea69,0x3c96c9b6,0x3c7b514b,0x3c490e90,0x3c16cb58,0x3bc90f88,0x3b490fc6,
0,0x3b490fc6,0x3bc90f88,0x3c16cb58,0x3c490e90,0x3c7b514b,0x3c96c9b6,0x3cafea69,0x3cc90ab0,0x3ce22a7a,0x3cfb49ba,0x3d0a342f,0x3d16c32c,0x3d2351cb,0x3d2fe007,0x3d3c6dd5,
0x3d48fb30,0x3d55880e,0x3d621469,0x3d6ea038,0x3d7b2b74,0x3d83db0a,0x3d8a200a,0x3d9064b4,0x3d96a905,0x3d9cecf9,0x3da3308c,0x3da973ba,0x3dafb680,0x3db5f8da,0x3dbc3ac3,0x3dc27c39,
0x3dc8bd36,0x3dcefdb7,0x3dd53db9,0x3ddb7d37,0x3de1bc2e,0x3de7fa9a,0x3dee3876,0x3df475c0,0x3dfab273,0x3e007745,0x3e039502,0x3e06b26e,0x3e09cf86,0x3e0cec4a,0x3e1008b7,0x3e1324ca,
0x3e164083,0x3e195be0,0x3e1c76de,0x3e1f917b,0x3e22abb6,0x3e25c58c,0x3e28defc,0x3e2bf804,0x3e2f10a2,0x3e3228d4,0x3e354098,0x3e3857ec,0x3e3b6ecf,0x3e3e853e,0x3e419b37,0x3e44b0b9,
0x3e47c5c2,0x3e4ada4f,0x3e4dee60,0x3e5101f1,0x3e541501,0x3e57278f,0x3e5a3997,0x3e5d4b1a,0x3e605c13,0x3e636c83,0x3e667c66,0x3e698bba,0x3e6c9a7f,0x3e6fa8b2,0x3e72b651,0x3e75c35a,
0x3e78cfcc,0x3e7bdba4,0x3e7ee6e1,0x3e80f8c0,0x3e827dc0,0x3e840270,0x3e8586ce,0x3e870ada,0x3e888e93,0x3e8a11f7,0x3e8b9507,0x3e8d17c0,0x3e8e9a22,0x3e901c2c,0x3e919ddd,0x3e931f35,
0x3e94a031,0x3e9620d2,0x3e97a117,0x3e9920fe,0x3e9aa086,0x3e9c1faf,0x3e9d9e78,0x3e9f1cdf,0x3ea09ae5,0x3ea21887,0x3ea395c5,0x3ea5129f,0x3ea68f12,0x3ea80b1f,0x3ea986c4,0x3eab0201,
0x3eac7cd4,0x3eadf73c,0x3eaf713a,0x3eb0eacb,0x3eb263ef,0x3eb3dca5,0x3eb554ec,0x3eb6ccc3,0x3eb8442a,0x3eb9bb1e,0x3ebb31a0,0x3ebca7af,0x3ebe1d4a,0x3ebf926f,0x3ec1071e,0x3ec27b55,
0x3ec3ef15,0x3ec5625c,0x3ec6d529,0x3ec8477c,0x3ec9b953,0x3ecb2aae,0x3ecc9b8b,0x3ece0bea,0x3ecf7bca,0x3ed0eb2a,0x3ed25a09,0x3ed3c867,0x3ed53641,0x3ed6a399,0x3ed8106b,0x3ed97cb9,
0x3edae880,0x3edc53c1,0x3eddbe79,0x3edf28a9,0x3ee0924f,0x3ee1fb6a,0x3ee363fa,0x3ee4cbfe,0x3ee63375,0x3ee79a5d,0x3ee900b7,0x3eea6681,0x3eebcbbb,0x3eed3063,0x3eee9479,0x3eeff7fb,
0x3ef15aea,0x3ef2bd43,0x3ef41f07,0x3ef58035,0x3ef6e0cb,0x3ef840c8,0x3ef9a02d,0x3efafef7,0x3efc5d27,0x3efdbabb,0x3eff17b2,0x3f003a06,0x3f00e7e4,0x3f019573,0x3f0242b1,0x3f02ef9f,
0x3f039c3d,0x3f044889,0x3f04f484,0x3f05a02c,0x3f064b82,0x3f06f686,0x3f07a136,0x3f084b92,0x3f08f59b,0x3f099f4e,0x3f0a48ad,0x3f0af1b7,0x3f0b9a6b,0x3f0c42c9,0x3f0cead0,0x3f0d9281,
0x3f0e39da,0x3f0ee0db,0x3f0f8784,0x3f102dd5,0x3f10d3cd,0x3f11796b,0x3f121eb0,0x3f12c39a,0x3f13682a,0x3f140c5f,0x3f14b039,0x3f1553b7,0x3f15f6d9,0x3f16999f,0x3f173c07,0x3f17de12,
0x3f187fc0,0x3f19210f,0x3f19c200,0x3f1a6293,0x3f1b02c6,0x3f1ba299,0x3f1c420c,0x3f1ce11f,0x3f1d7fd1,0x3f1e1e22,0x3f1ebc12,0x3f1f599f,0x3f1ff6cb,0x3f209393,0x3f212ff9,0x3f21cbfb,
0x3f226799,0x3f2302d3,0x3f239da9,0x3f24381a,0x3f24d225,0x3f256bcb,0x3f26050a,0x3f269de3,0x3f273656,0x3f27ce61,0x3f286605,0x3f28fd41,0x3f299415,0x3f2a2a80,0x3f2ac082,0x3f2b561b,
0x3f2beb4a,0x3f2c800f,0x3f2d1469,0x3f2da859,0x3f2e3bde,0x3f2ecef7,0x3f2f61a5,0x3f2ff3e6,0x3f3085bb,0x3f311722,0x3f31a81d,0x3f3238aa,0x3f32c8c9,0x3f33587a,0x3f33e7bc,0x3f34768f,
0x3f3504f3,0x3f3592e7,0x3f36206c,0x3f36ad7f,0x3f373a23,0x3f37c655,0x3f385216,0x3f38dd65,0x3f396842,0x3f39f2ac,0x3f3a7ca4,0x3f3b0629,0x3f3b8f3b,0x3f3c17d9,0x3f3ca003,0x3f3d27b8,
0x3f3daef9,0x3f3e35c5,0x3f3ebc1b,0x3f3f41fc,0x3f3fc767,0x3f404c5c,0x3f40d0da,0x3f4154e1,0x3f41d870,0x3f425b89,0x3f42de29,0x3f436051,0x3f43e200,0x3f446337,0x3f44e3f5,0x3f456439,
0x3f45e403,0x3f466354,0x3f46e22a,0x3f476085,0x3f47de65,0x3f485bca,0x3f48d8b3,0x3f495521,0x3f49d112,0x3f4a4c87,0x3f4ac77f,0x3f4b41fa,0x3f4bbbf8,0x3f4c3578,0x3f4cae79,0x3f4d26fd,
0x3f4d9f02,0x3f4e1689,0x3f4e8d90,0x3f4f0417,0x3f4f7a1f,0x3f4fefa8,0x3f5064af,0x3f50d937,0x3f514d3d,0x3f51c0c2,0x3f5233c6,0x3f52a649,0x3f531849,0x3f5389c7,0x3f53fac3,0x3f546b3b,
0x3f54db31,0x3f554aa4,0x3f55b993,0x3f5627fe,0x3f5695e5,0x3f570348,0x3f577026,0x3f57dc7f,0x3f584853,0x3f58b3a1,0x3f591e6a,0x3f5988ad,0x3f59f26a,0x3f5a5ba0,0x3f5ac450,0x3f5b2c79,
0x3f5b941a,0x3f5bfb34,0x3f5c61c7,0x3f5cc7d1,0x3f5d2d53,0x3f5d924d,0x3f5df6be,0x3f5e5aa6,0x3f5ebe05,0x3f5f20db,0x3f5f8327,0x3f5fe4e9,0x3f604621,0x3f60a6cf,0x3f6106f2,0x3f61668a,
0x3f61c598,0x3f62241a,0x3f628210,0x3f62df7b,0x3f633c5a,0x3f6398ac,0x3f63f473,0x3f644fac,0x3f64aa59,0x3f650479,0x3f655e0b,0x3f65b710,0x3f660f88,0x3f666771,0x3f66becc,0x3f671599,
0x3f676bd8,0x3f67c187,0x3f6816a8,0x3f686b39,0x3f68bf3c,0x3f6912ae,0x3f696591,0x3f69b7e4,0x3f6a09a7,0x3f6a5ad9,0x3f6aab7b,0x3f6afb8c,0x3f6b4b0c,0x3f6b99fb,0x3f6be858,0x3f6c3624,
0x3f6c835e,0x3f6cd007,0x3f6d1c1d,0x3f6d67a1,0x3f6db293,0x3f6dfcf2,0x3f6e46be,0x3f6e8ff8,0x3f6ed89e,0x3f6f20b0,0x3f6f6830,0x3f6faf1b,0x3f6ff573,0x3f703b37,0x3f708066,0x3f70c501,
0x3f710908,0x3f714c7a,0x3f718f57,0x3f71d19f,0x3f721352,0x3f725470,0x3f7294f8,0x3f72d4eb,0x3f731447,0x3f73530e,0x3f73913f,0x3f73ced9,0x3f740bdd,0x3f74484b,0x3f748422,0x3f74bf62,
0x3f74fa0b,0x3f75341d,0x3f756d97,0x3f75a67b,0x3f75dec6,0x3f76167a,0x3f764d97,0x3f76841b,0x3f76ba07,0x3f76ef5b,0x3f772417,0x3f77583a,0x3f778bc5,0x3f77beb7,0x3f77f110,0x3f7822d1,
0x3f7853f8,0x3f788486,0x3f78b47b,0x3f78e3d6,0x3f791298,0x3f7940c0,0x3f796e4e,0x3f799b43,0x3f79c79d,0x3f79f35e,0x3f7a1e84,0x3f7a4910,0x3f7a7302,0x3f7a9c59,0x3f7ac516,0x3f7aed37,
0x3f7b14be,0x3f7b3bab,0x3f7b61fc,0x3f7b87b2,0x3f7baccd,0x3f7bd14d,0x3f7bf531,0x3f7c187a,0x3f7c3b28,0x3f7c5d3a,0x3f7c7eb0,0x3f7c9f8a,0x3f7cbfc9,0x3f7cdf6c,0x3f7cfe73,0x3f7d1cdd,
0x3f7d3aac,0x3f7d57de,0x3f7d7474,0x3f7d906e,0x3f7dabcc,0x3f7dc68c,0x3f7de0b1,0x3f7dfa38,0x3f7e1324,0x3f7e2b72,0x3f7e4323,0x3f7e5a38,0x3f7e70b0,0x3f7e868b,0x3f7e9bc9,0x3f7eb069,
0x3f7ec46d,0x3f7ed7d4,0x3f7eea9d,0x3f7efcc9,0x3f7f0e58,0x3f7f1f49,0x3f7f2f9d,0x3f7f3f54,0x3f7f4e6d,0x3f7f5ce9,0x3f7f6ac7,0x3f7f7808,0x3f7f84ab,0x3f7f90b1,0x3f7f9c18,0x3f7fa6e3,
0x3f7fb10f,0x3f7fba9e,0x3f7fc38f,0x3f7fcbe2,0x3f7fd397,0x3f7fdaaf,0x3f7fe129,0x3f7fe705,0x3f7fec43,0x3f7ff0e3,0x3f7ff4e6,0x3f7ff84a,0x3f7ffb11,0x3f7ffd39,0x3f7ffec4,0x3f7fffb1,
};

__device__ __forceinline__ int tid_here() { return __shfl_xor_sync(~0u, (int)threadIdx.x, 0); }
__device__ __forceinline__ void ld_tab(uint32_t* d, int chunk) { asm volatile("ld.global.v4.u32 {%0,%1,%2,%3}, [%4];" : "=r"(d[0]), "=r"(d[1]), "=r"(d[2]), "=r"(d[3]) : "l"((const uint4*)g_tab + chunk) : "memory"); }
__device__ __forceinline__ void ld_tab(float* d, int chunk) { asm volatile("ld.global.v4.f32 {%0,%1,%2,%3}, [%4];" : "=f"(d[0]), "=f"(d[1]), "=f"(d[2]), "=f"(d[3]) : "l"((const uint4*)g_tab + chunk) : "memory"); }
__device__ __forceinline__ void fft640(uint32_t plane, uint32_t tab, int lane, const uint32_t* fr, const uint32_t* fi, const float (*tc)[4], const float (*ts)[4], float (*xr)[4], float (*xi)[4]) {
  uint32_t A1[5][4], nfi[4];
#pragma unroll
  for (int i = 0; i < 4; i++) nfi[i] = fi[i] ^ 0x80008000u;
  const uint32_t la = plane + (lane >> 4) * 1280 + (lane & 15) * 80;
#pragma unroll
  for (int j = 0; j < 5; j++) {
    uint32_t r0, r1, i0, i1; ldsm4t(r0, r1, i0, i1, la + j * 16);
    float yr[4], yi[4];
    mmaZ(yr, fr, r0, r1); mmaZ(yi, fi, r0, r1); mmaA(yr, nfi, i0, i1); mmaA(yi, fr, i0, i1);
    float zr[4], zi[4];
#pragma unroll
    for (int e = 0; e < 4; e++) { zr[e] = yr[e] * tc[j][e] - yi[e] * ts[j][e]; zi[e] = yr[e] * ts[j][e] + yi[e] * tc[j][e]; }
    A1[j][0] = pack_bf16(zr[0], zr[1]); A1[j][1] = pack_bf16(zr[2], zr[3]); A1[j][2] = pack_bf16(zi[0], zi[1]); A1[j][3] = pack_bf16(zi[2], zi[3]);
  }
#pragma unroll
  for (int t = 0; t < 5; t++) {
    uint32_t A2[4] = {A1[t][2], A1[t][3], A1[t][0] ^ 0x80008000u, A1[t][1] ^ 0x80008000u};
#pragma unroll
    for (int u = 0; u < 5; u++) {
      uint32_t b0, b1; asm volatile("ld.shared.v2.b32 {%0,%1}, [%2];" : "=r"(b0), "=r"(b1) : "r"(tab + (t * 5 + u) * 256 + lane * 8));
      if (t == 0) { mmaZ(xr[u], A1[t], b0, b1); mmaZ(xi[u], A2, b0, b1); } else { mmaA(xr[u], A1[t], b0, b1); mmaA(xi[u], A2, b0, b1); }
    }
  }
}
__device__ __forceinline__ void ln_row(float* v) {
  float s = 0.f, q = 0.f;
#pragma unroll
  for (int i = 0; i < 20; i++) { s += v[i]; q = fmaf(v[i], v[i], q); }
#pragma unroll
  for (int o = 16; o; o >>= 1) { s += __shfl_xor_sync(~0u, s, o); q += __shfl_xor_sync(~0u, q, o); }
  const float mean = s * (1.f / D_), rs = rsqrtf(fmaxf(fmaf(-mean, mean, q * (1.f / D_)), 0.f) + 1e-5f), nb = -mean * rs;
#pragma unroll
  for (int i = 0; i < 20; i++) v[i] = fmaf(v[i], rs, nb);
}

#define TLBASE (1024 + 896)
struct AParams { const bf16* x; uint32_t *Z1, *Z2; const uint32_t* WT; bf16 *x1, *hN; uint32_t* sync; const uint32_t* rowdone; int nw; uint32_t tag; };
constexpr int SY_1 = 0, SY_2 = 32, SY_3 = 64, SY_W = 96;
__device__ __forceinline__ void red_release(uint32_t* p) { asm volatile("red.release.gpu.global.add.u32 [%0], 1;" :: "l"(p) : "memory"); }
__device__ __forceinline__ void red_relaxed(uint32_t* p) { asm volatile("red.relaxed.gpu.global.add.u32 [%0], 1;" :: "l"(p) : "memory"); }
__device__ __forceinline__ void spin_count(const uint32_t* p, uint32_t n) {
  uint32_t v; int guard = 0;
#pragma unroll 1
  do { asm volatile("ld.relaxed.gpu.global.u32 %0, [%1];" : "=r"(v) : "l"(p) : "memory"); } while (v < n && ++guard < 400000);
}

__device__ __forceinline__ void filter_prep(uint32_t* WT, uint32_t sm, int k2) {
  const int tid = threadIdx.x, r = (tid >> 5) & 3;
  const uint32_t src = sm + (8 * (tid & 3) + r) * 642;
#pragma unroll 2
  for (int f = (tid >> 7) * 8 + ((tid & 31) >> 2); f < 321; f += 24) {
    uint32_t v[4];
#pragma unroll
    for (int i = 0; i < 4; i++) {
      unsigned short lo, hi;
      const uint32_t a = src + f * 2 + ((i >> 1) * 4 + (i & 1) * 32) * 642;
      asm volatile("ld.shared.u16 %0, [%1];" : "=h"(lo) : "r"(a)); asm volatile("ld.shared.u16 %0, [%1];" : "=h"(hi) : "r"(a + 41088));
      v[i] = lo | ((uint32_t)hi << 16);
    }
    stg128(WT + f * 2048 + k2 * 64 + r * 16 + (tid & 3) * 4, v[0], v[1], v[2], v[3]);
  }
}

template <typename F> __device__ __forceinline__ void a_phase2(const AParams& a, float* buf, int f, F hook) {
  const int t0 = tid_here(), tid = (t0 + (t0 >> 7) * 32) & 127  , lane = tid & 31, w = tid >> 5, g = lane >> 2, q = lane & 3, barid = 5 + (t0 >> 7);
  const int f2 = (640 - f) % 640;
#define WGBAR() asm volatile("bar.sync %0, 128;" :: "r"(barid) : "memory")
  uint32_t fr[4], fi[4], nfi[4], br[4][4], bi[4][4];
  float tc[4][4], ts[4][4], wc[4], ws[4];
  ld_tab(wc, TB_2048 + tid); ld_tab(ws, TB_2048 + 128 + tid); ld_tab(fr, TB_F16 + lane); ld_tab(fi, TB_F16 + 32 + lane);
#pragma unroll
  for (int j = 0; j < 4; j++) { ld_tab(tc[j], TB_512 + j * 32 + lane); ld_tab(ts[j], TB_512 + 128 + j * 32 + lane); }
  if (tid == 32 && !a.nw) l2_prefetch(a.WT + f * 2048, 8192);
  const uint32_t* zs[4];
#pragma unroll
  for (int j = 0; j < 4; j++) { const int m = j * 256 + 2 * tid; zs[j] = a.Z1 + (j == 3 && w == 3 && !a.nw ? 86 * 7680 + (m / 4 - 240) * 2560 + m % 4 : (m / 12) * 7680 + m % 12); }
  const int st3 = w == 3 && !a.nw ? 4 : 12;
  if (tid == 0) spin_count(a.sync + SY_1, 80);
  WGBAR();
  if (w == 3) { spin_count(a.sync + SY_1 + 16, a.nw ? 6 : 16); TL(6); }
  const uint32_t sbuf = smem_u32(buf);
  {
    uint2 P[4], Q[4];
#pragma unroll 1
    for (int guard = 0; guard < 100000; guard++) {
      uint32_t bad = 0;
#pragma unroll
      for (int j = 0; j < 4; j++) {
        asm volatile("ld.relaxed.gpu.global.v2.u32 {%0,%1}, [%2];" : "=r"(P[j].x), "=r"(P[j].y) : "l"(zs[j] + f * (j == 3 ? st3 : 12)) : "memory");
        asm volatile("ld.relaxed.gpu.global.v2.u32 {%0,%1}, [%2];" : "=r"(Q[j].x), "=r"(Q[j].y) : "l"(zs[j] + f2 * (j == 3 ? st3 : 12)) : "memory");
      }
#pragma unroll
      for (int j = 0; j < 4; j++) bad |= (P[j].x ^ a.tag) | (Q[j].x ^ a.tag);
      if (__all_sync(~0u, !(bad & 1))) break;
    }
    float ur[4][4], ui[4][4];
#pragma unroll
    for (int i = 0; i < 4; i++) {
      float ar[4], ai[4];
#pragma unroll
      for (int j = 0; j < 4; j++) {
        const uint32_t p = (i >> 1) ? P[j].y : P[j].x, z = (i >> 1) ? Q[j].y : Q[j].x;
        if (!(i & 1)) { ar[j] = bf_lo(p) + bf_lo(z); ai[j] = bf_hi(p) - bf_hi(z); }
        else { ar[j] = bf_hi(p) + bf_hi(z); ai[j] = bf_lo(z) - bf_lo(p); }
      }
      const float s0r = ar[0] + ar[2], s0i = ai[0] + ai[2], d0r = ar[0] - ar[2], d0i = ai[0] - ai[2];
      const float s1r = ar[1] + ar[3], s1i = ai[1] + ai[3], d1r = ar[1] - ar[3], d1i = ai[1] - ai[3];
      ur[0][i] = s0r + s1r; ui[0][i] = s0i + s1i;
      const float vr[3] = {d0r + d1i, s0r - s1r, d0r - d1i}, vi[3] = {d0i - d1r, s0i - s1i, d0i + d1r};
      const float c2 = wc[i] * wc[i] - ws[i] * ws[i], s2 = 2.f * wc[i] * ws[i];
      const float twc[4] = {1.f, wc[i], c2, c2 * wc[i] - s2 * ws[i]}, tws[4] = {0.f, ws[i], s2, s2 * wc[i] + c2 * ws[i]};
#pragma unroll
      for (int r = 1; r < 4; r++) { const float c = twc[r], s = tws[r]; ur[r][i] = vr[r - 1] * c + vi[r - 1] * s; ui[r][i] = vi[r - 1] * c - vr[r - 1] * s; }
    }
    const uint32_t o = sbuf + (tid >> 3) * 80 + (tid & 7) * 8;
#pragma unroll
    for (int r = 0; r < 4; r++) {
      asm volatile("st.shared.v2.b32 [%0], {%1,%2};" :: "r"(o + r * 5120), "r"(pack_bf16(ur[r][0], ur[r][1])), "r"(pack_bf16(ur[r][2], ur[r][3])) : "memory");
      asm volatile("st.shared.v2.b32 [%0], {%1,%2};" :: "r"(o + r * 5120 + 1280), "r"(pack_bf16(ui[r][0], ui[r][1])), "r"(pack_bf16(ui[r][2], ui[r][3])) : "memory");
    }
  }
#pragma unroll
  for (int j = 0; j < 4; j++) { ld_tab(br[j], TB_F32 + j * 32 + lane); ld_tab(bi[j], TB_F32 + 128 + j * 32 + lane); }
  if (a.nw) { if (tid == 0) spin_count(a.sync + SY_W, a.nw); WGBAR(); }
  uint2 wt[8];
#pragma unroll
  for (int i = 0; i < 8; i++) wt[i] = __ldcg((const uint2*)(a.WT + f * 2048 + ((i >> 1) * 8 + 2 * q + (i & 1)) * 64 + w * 16 + g * 2));
  WGBAR();
  hook(1);
  TL(7);
  {
    uint32_t A1[4][4], A2[4][4];
#pragma unroll
    for (int i = 0; i < 4; i++) nfi[i] = fi[i] ^ 0x80008000u;
    const uint32_t la = sbuf + w * 5120 + (lane >> 4) * 1280 + (lane & 15) * 80;
#pragma unroll
    for (int j = 0; j < 4; j++) {
      uint32_t r0, r1, i0, i1; ldsm4t(r0, r1, i0, i1, la + j * 16);
      float yr[4], yi[4];
      mmaZ(yr, fr, r0, r1); mmaZ(yi, fi, r0, r1); mmaA(yr, nfi, i0, i1); mmaA(yi, fr, i0, i1);
      float zr[4], zi[4];
#pragma unroll
      for (int e = 0; e < 4; e++) { zr[e] = yr[e] * tc[j][e] + yi[e] * ts[j][e]; zi[e] = yi[e] * tc[j][e] - yr[e] * ts[j][e]; }
      A1[j][0] = pack_bf16(zr[0], zr[1]); A1[j][1] = pack_bf16(zr[2], zr[3]); A1[j][2] = pack_bf16(zi[0], zi[1]); A1[j][3] = pack_bf16(zi[2], zi[3]);
      A2[j][0] = A1[j][2]; A2[j][1] = A1[j][3]; A2[j][2] = A1[j][0] ^ 0x80008000u; A2[j][3] = A1[j][1] ^ 0x80008000u;
    }
    float xr[4][4], xi[4][4];
#pragma unroll
    for (int t = 0; t < 4; t++)
#pragma unroll
      for (int u = 0; u < 4; u++) {
        if (t == 0) { mmaZ(xr[u], A1[t], br[t][u], bi[t][u]); mmaZ(xi[u], A2[t], br[t][u], bi[t][u]); } else { mmaA(xr[u], A1[t], br[t][u], bi[t][u]); mmaA(xi[u], A2[t], br[t][u], bi[t][u]); }
      }
#pragma unroll
    for (int u = 0; u < 4; u++) {
      const uint32_t wv[4] = {wt[2 * u].x, wt[2 * u + 1].x, wt[2 * u].y, wt[2 * u + 1].y};
      float zr[4], zi[4];
#pragma unroll
      for (int e = 0; e < 4; e++) { const float c = bf_lo(wv[e]), b = bf_hi(wv[e]); zr[e] = xr[u][e] * c - xi[u][e] * b; zi[e] = xr[u][e] * b + xi[u][e] * c; }
      A2[u][2] = pack_bf16(zr[0], zr[1]); A2[u][3] = pack_bf16(zr[2], zr[3]); A2[u][0] = pack_bf16(zi[0], zi[1]); A2[u][1] = pack_bf16(zi[2], zi[3]);
      A1[u][0] = A2[u][2]; A1[u][1] = A2[u][3]; A1[u][2] = A2[u][0] ^ 0x80008000u; A1[u][3] = A2[u][1] ^ 0x80008000u;
    }
#pragma unroll
    for (int t = 0; t < 4; t++)
#pragma unroll
      for (int u = 0; u < 4; u++) {
        if (t == 0) { mmaZ(xr[u], A1[t], br[t][u], bi[t][u]); mmaZ(xi[u], A2[t], br[t][u], bi[t][u]); } else { mmaA(xr[u], A1[t], br[t][u], bi[t][u]); mmaA(xi[u], A2[t], br[t][u], bi[t][u]); }
      }
    __syncwarp();
    float* pl = buf + w * 1280;
    const float nrm = 0.5f / (2048.f * 640.f);
#pragma unroll
    for (int j = 0; j < 4; j++) {
      float zr[4], zi[4];
#pragma unroll
      for (int e = 0; e < 4; e++) { zr[e] = xr[j][e] * tc[j][e] - xi[j][e] * ts[j][e]; zi[e] = xi[j][e] * tc[j][e] + xr[j][e] * ts[j][e]; }
      const uint32_t r0 = movm(pack_bf16(zr[0], zr[1])), r1 = movm(pack_bf16(zr[2], zr[3])), i0 = movm(pack_bf16(zi[0], zi[1])), i1 = movm(pack_bf16(zi[2], zi[3]));
      float yr[4], yi[4];
      mmaZ(yr, fr, r0, r1); mmaZ(yi, nfi, r0, r1); mmaA(yr, fi, i0, i1); mmaA(yi, fr, i0, i1);
      *(float2*)(pl + g * 40 + 8 * j + 2 * q) = make_float2(yr[0] * nrm, yr[1] * nrm); *(float2*)(pl + (g + 8) * 40 + 8 * j + 2 * q) = make_float2(yr[2] * nrm, yr[3] * nrm);
      *(float2*)(pl + 640 + g * 40 + 8 * j + 2 * q) = make_float2(yi[0] * nrm, yi[1] * nrm); *(float2*)(pl + 640 + (g + 8) * 40 + 8 * j + 2 * q) = make_float2(yi[2] * nrm, yi[3] * nrm);
    }
  }
  ld_tab(wc, TB_2048 + tid); ld_tab(ws, TB_2048 + 128 + tid);
  WGBAR();
  hook(2);
  TL(8);
  {
    float4 Ur[4], Ui[4];
#pragma unroll
    for (int r = 0; r < 4; r++) { Ur[r] = *(const float4*)(buf + r * 1280 + (tid >> 3) * 40 + (tid & 7) * 4); Ui[r] = *(const float4*)(buf + r * 1280 + 640 + (tid >> 3) * 40 + (tid & 7) * 4); }
    float yr[4][4], yi[4][4];
#pragma unroll
    for (int i = 0; i < 4; i++) {
      float ar[4], ai[4];
      const float c2 = wc[i] * wc[i] - ws[i] * ws[i], s2 = 2.f * wc[i] * ws[i];
      const float twc[4] = {1.f, wc[i], c2, c2 * wc[i] - s2 * ws[i]}, tws[4] = {0.f, ws[i], s2, s2 * wc[i] + c2 * ws[i]};
#pragma unroll
      for (int r = 0; r < 4; r++) {
        const float a = i == 0 ? Ur[r].x : i == 1 ? Ur[r].y : i == 2 ? Ur[r].z : Ur[r].w, b = i == 0 ? Ui[r].x : i == 1 ? Ui[r].y : i == 2 ? Ui[r].z : Ui[r].w;
        if (r == 0) { ar[r] = a; ai[r] = b; } else { const float c = twc[r], s = tws[r]; ar[r] = a * c - b * s; ai[r] = b * c + a * s; }
      }
      const float s0r = ar[0] + ar[2], s0i = ai[0] + ai[2], d0r = ar[0] - ar[2], d0i = ai[0] - ai[2];
      const float s1r = ar[1] + ar[3], s1i = ai[1] + ai[3], d1r = ar[1] - ar[3], d1i = ai[1] - ai[3];
      yr[0][i] = s0r + s1r; yi[0][i] = s0i + s1i; yr[2][i] = s0r - s1r; yi[2][i] = s0i - s1i;
      yr[1][i] = d0r - d1i; yi[1][i] = d0i + d1r; yr[3][i] = d0r + d1i; yi[3][i] = d0i - d1r;
    }
    const float im = (f == f2) ? 0.f : 1.f;
#pragma unroll
    for (int j = 0; j < 4; j++) {
      *(uint2*)(a.Z2 + f * 1024 + j * 256 + 2 * tid) = make_uint2((pack_bf16(yr[j][0] - im * yi[j][1], yr[j][1] + im * yi[j][0]) & ~1u) | a.tag, pack_bf16(yr[j][2] - im * yi[j][3], yr[j][3] + im * yi[j][2]));
      if (f != f2) *(uint2*)(a.Z2 + f2 * 1024 + j * 256 + 2 * tid) = make_uint2((pack_bf16(yr[j][0] + yi[j][1], yr[j][1] - yi[j][0]) & ~1u) | a.tag, pack_bf16(yr[j][2] + yi[j][3], yr[j][3] - yi[j][2]));
    }
  }
  TL(9);
}

constexpr int KA_TR_STRIDE = 804;
template <typename F> __device__ __forceinline__ void a_layer(const AParams& a, char* scratch, int v, int w, F hook) {
  const int tid = tid_here(), lane = tid & 31;
  uint32_t raw[2][10], fr[4], fi[4];
  float tc[5][4], ts[5][4];
  const int np = a.nw ? (v < 86 ? 12 : 0) : v < 80 ? 12 : v < 96 ? 4 : 0;
  bool act = w < np;
  int m = !act ? v * 4 + w : np == 4 ? 640 + v * 4 + w : min(v * 12 + w, 1023);
  uint32_t* buf = (uint32_t*)(scratch + 6400) + (w & 3) * KA_TR_STRIDE + (w >> 2) * 3244;
  auto load_rows = [&]() {
    const int lane = tid_here() & 31;
#pragma unroll
    for (int i = 0; i < 10; i++) asm volatile("ld.relaxed.gpu.global.v2.u32 {%0,%1}, [%2];" : "=r"(raw[i / 5][2 * (i % 5)]), "=r"(raw[i / 5][2 * (i % 5) + 1]) : "l"(a.x + (size_t)(2 * m) * D_ + i * 128 + lane * 4) : "memory");
  };
  uint32_t t[2][4];
  auto load_tabs = [&]() {
    const int tid = tid_here(), lane = tid & 31;
    ld_tab(t[0], TB_F40 + (tid & 255)); ld_tab(t[1], TB_F40 + 144 + (tid & 255));
    ld_tab(fr, TB_F16 + lane); ld_tab(fi, TB_F16 + 32 + lane);
#pragma unroll
    for (int j = 0; j < 5; j++) { ld_tab(tc[j], TB_640 + j * 32 + lane); ld_tab(ts[j], TB_640 + 160 + j * 32 + lane); }
  };
  auto store_tabs = [&]() {
    const int tid = tid_here();
    sts128(smem_u32(scratch) + (tid & 255) * 16, t[0][0], t[0][1], t[0][2], t[0][3]); sts128(smem_u32(scratch) + 2304 + (tid & 255) * 16, t[1][0], t[1][1], t[1][2], t[1][3]);
  };
  if (a.rowdone) {
    load_tabs(); store_tabs();
    if (act) spin_count(a.rowdone + (m >> 4) * 32, 32);
#pragma unroll 1
    for (int guard = 0; guard < 20000; guard++) {
      load_rows();
      uint32_t mx = 0;
#pragma unroll
      for (int i = 0; i < 10; i++) mx = max(mx, raw[i / 5][2 * (i % 5)]);
      if (__all_sync(~0u, mx != ~0u)) break;
    }
  }
  else { load_rows(); load_tabs(); store_tabs(); }
  __syncthreads();
  hook(-1);
  TL(1);
#pragma unroll 1
  for (int it = 0;; it++) {
    if (act) {
#pragma unroll
      for (int r = 0; r < 2; r++) {
        float x[20];
#pragma unroll
        for (int i = 0; i < 10; i++) { x[2 * i] = bf_lo(raw[r][i]); x[2 * i + 1] = bf_hi(raw[r][i]); }
        ln_row(x);
#pragma unroll
        for (int i = 0; i < 10; i++) raw[r][i] = pack_bf16(x[2 * i], x[2 * i + 1]);
      }
    }
    if (it) break;
    if (act) {
#pragma unroll
      for (int i = 0; i < 10; i++) *(uint2*)(buf + i * 64 + lane * 2) = make_uint2(raw[i / 5][2 * (i % 5)], raw[i / 5][2 * (i % 5) + 1]);
      __syncwarp();
    }
    TL(2);
#pragma unroll 1
    for (int ph = 0;; ph++) {
      if (act) {
        float xr[5][4], xi[5][4];
        const int lane = tid_here() & 31, g = lane >> 2, q = lane & 3;
        fft640(smem_u32(buf), smem_u32(scratch), lane, fr, fi, tc, ts, xr, xi);
        __syncwarp();
#pragma unroll
        for (int u = 0; u < 5; u++)
#pragma unroll
          for (int e = 0; e < 4; e++) { const int f = g + 8 * (e >> 1) + 16 * (8 * u + 2 * q + (e & 1)); buf[f + 8 * (f >> 5)] = pack_bf16(xr[u][e], xi[u][e]); }
        __syncwarp();
      }
      if (ph) break;
      __syncthreads();
      TL(3);
      const int t1 = tid_here(), f0 = t1 / 3, part = t1 % 3;
      if (np == 12) {
        const uint32_t* src = (const uint32_t*)(scratch + 6400) + part * 3244 + f0 + 8 * (f0 >> 5);
        uint32_t ov[5][4];
#pragma unroll
        for (int i = 0; i < 5; i++)
#pragma unroll
          for (int k = 0; k < 4; k++) ov[i][k] = src[k * KA_TR_STRIDE + i * 160];
#pragma unroll
        for (int i = 0; i < 5; i++) stg128(a.Z1 + v * 7680 + (i * 384 + t1) * 4, (ov[i][0] & ~1u) | a.tag, ov[i][1], (ov[i][2] & ~1u) | a.tag, ov[i][3]);
      } else if (np) {
#pragma unroll
        for (int i = 0; i < 2; i++) {
          const int f = min(i * 384 + t1, 639);
          const uint32_t* src = (const uint32_t*)(scratch + 6400) + f + 8 * (f >> 5);
          stg128(a.Z1 + 86 * 7680 + (v - 80) * 2560 + f * 4, src[0] & ~1u, src[KA_TR_STRIDE], src[2 * KA_TR_STRIDE] & ~1u, src[3 * KA_TR_STRIDE]);
        }
      }
      TL(4);
      __syncthreads();
      if (tid == 32 && act) { if (v >= 80) __threadfence(); red_relaxed(a.sync + SY_1 + (v < 80 ? 0 : 16)); TL(5); }
      hook(0);
      const int f = (w >> 2) * 131 + v;
      if (f < 321) a_phase2(a, (float*)(scratch + (w >> 2) * 20480), f, hook);
      asm volatile("fence.proxy.async.shared::cta;" ::: "memory");
      __syncthreads();
      if (tid == 32) red_relaxed(a.sync + SY_2);
      hook(3);
      if (w >= 8 || v >= 128) return;
      const int job = (v + 32) & 127;
      act = true; m = job * 8 + w;
      scratch += 32768; buf = (uint32_t*)(scratch + 6400);
      {
        load_rows(); load_tabs();
        if (tid == 0) { spin_count(a.sync + SY_2, 131); TL(10); }
        bar_sync<5, 256>();
        uint4 za[3], zb[3];
        const int tid = tid_here();
#pragma unroll 1
        for (int guard = 0; guard < 100000; guard++) {
          uint32_t bad = 0;
#pragma unroll
          for (int i = 0; i < 3; i++) {
            const uint32_t* s = a.Z2 + (i * 256 + (tid & (i < 2 ? 254 : 126))) * 1024 + job * 8 + (tid & 1) * 4;
            asm volatile("ld.relaxed.gpu.global.v4.u32 {%0,%1,%2,%3}, [%4];" : "=r"(za[i].x), "=r"(za[i].y), "=r"(za[i].z), "=r"(za[i].w) : "l"(s) : "memory");
            asm volatile("ld.relaxed.gpu.global.v4.u32 {%0,%1,%2,%3}, [%4];" : "=r"(zb[i].x), "=r"(zb[i].y), "=r"(zb[i].z), "=r"(zb[i].w) : "l"(s + 1024) : "memory");
          }
#pragma unroll
          for (int i = 0; i < 3; i++) bad |= (za[i].x ^ a.tag) | (zb[i].x ^ a.tag) | (za[i].z ^ a.tag) | (zb[i].z ^ a.tag);
          if (__all_sync(~0u, !(bad & 1))) break;
        }
#pragma unroll
        for (int i = 0; i < 3; i++) if (i < 2 || tid < 128) {
          const uint4 c = za[i], b = zb[i];
          uint32_t* d = buf + (tid & 1) * 4 * KA_TR_STRIDE + i * 128 + (tid >> 1);
          d[320] = __byte_perm(c.x, b.x, 0x5410); d[0] = __byte_perm(c.x, b.x, 0x7632); d += KA_TR_STRIDE;
          d[320] = __byte_perm(c.y, b.y, 0x5410); d[0] = __byte_perm(c.y, b.y, 0x7632); d += KA_TR_STRIDE;
          d[320] = __byte_perm(c.z, b.z, 0x5410); d[0] = __byte_perm(c.z, b.z, 0x7632); d += KA_TR_STRIDE;
          d[320] = __byte_perm(c.w, b.w, 0x5410); d[0] = __byte_perm(c.w, b.w, 0x7632);
        }
        store_tabs();
        bar_sync<5, 256>();
        hook(4);
        TL(11);
      }
      buf += w * KA_TR_STRIDE;
    }
    {
      TL(12);
      const int lane = tid_here() & 31;
#pragma unroll
      for (int i = 0; i < 5; i++) {
        const uint4 y = *(const uint4*)(buf + i * 160 + lane * 4 + 8 * (lane >> 3));
        raw[0][2 * i] = hadd2(raw[0][2 * i], __byte_perm(y.x, y.y, 0x7632)); raw[0][2 * i + 1] = hadd2(raw[0][2 * i + 1], __byte_perm(y.z, y.w, 0x7632));
        raw[1][2 * i] = hadd2(raw[1][2 * i], __byte_perm(y.x, y.y, 0x5410)); raw[1][2 * i + 1] = hadd2(raw[1][2 * i + 1], __byte_perm(y.z, y.w, 0x5410));
      }
#pragma unroll
      for (int i = 0; i < 10; i++) *(uint2*)(a.x1 + (size_t)(2 * m) * D_ + i * 128 + lane * 4) = make_uint2(raw[i / 5][2 * (i % 5)], raw[i / 5][2 * (i % 5) + 1]);
    }
  }
  {
#pragma unroll
    for (int i = 0; i < 10; i++) *(uint2*)(a.hN + (size_t)(2 * m) * D_ + i * 128 + lane * 4) = make_uint2(raw[i / 5][2 * (i % 5)], raw[i / 5][2 * (i % 5) + 1]);
    TL(13);
    if (v < 96) bar_arrive<6, 320>();
    else {
      bar_sync<5, 256>();
      if (tid == 0) { __threadfence(); if (v < 100) red_relaxed(a.sync + SY_3 + 16); red_relaxed(a.sync + SY_3); TL(14); }
    }
  }
}

__device__ __forceinline__ void tma2d(uint32_t dst, const CUtensorMap* tm, int c0, int c1, uint32_t bar) {
  asm volatile("cp.async.bulk.tensor.2d.shared::cluster.global.mbarrier::complete_tx::bytes [%0], [%1, {%3, %4}], [%2];" :: "r"(dst), "l"(tm), "r"(bar), "r"(c0), "r"(c1) : "memory");
}
__device__ __forceinline__ void bulk_g2s(uint32_t dst, const void* src, int bytes, uint32_t bar) {
  asm volatile("cp.async.bulk.shared::cluster.global.mbarrier::complete_tx::bytes [%0], [%1], %2, [%3];" :: "r"(dst), "l"(src), "r"(bytes), "r"(bar) : "memory");
}
__device__ __forceinline__ uint64_t desc128(uint32_t a) { return (uint64_t)((a & 0x3FFFF) >> 4) | (1ull << 16) | (64ull << 32) | (1ull << 62); }
#define WG_FENCE() asm volatile("wgmma.fence.sync.aligned;" ::: "memory")
#define WG_COMMIT() asm volatile("wgmma.commit_group.sync.aligned;" ::: "memory")
#define WG_WAIT(n) asm volatile("wgmma.wait_group.sync.aligned " #n ";" ::: "memory")
__device__ __forceinline__ void wg_rs_n64(float* d, const uint32_t* a, uint64_t db, int acc) {
  asm volatile("{.reg .pred p; setp.ne.b32 p, %37, 0;\n"
    "wgmma.mma_async.sync.aligned.m64n64k16.f32.bf16.bf16 {%0,%1,%2,%3,%4,%5,%6,%7,%8,%9,%10,%11,%12,%13,%14,%15,%16,%17,%18,%19,%20,%21,%22,%23,%24,%25,%26,%27,%28,%29,%30,%31}, {%32,%33,%34,%35}, %36, p, 1, 1, 0;}"
    : "+f"(d[0]), "+f"(d[1]), "+f"(d[2]), "+f"(d[3]), "+f"(d[4]), "+f"(d[5]), "+f"(d[6]), "+f"(d[7]), "+f"(d[8]), "+f"(d[9]), "+f"(d[10]), "+f"(d[11]), "+f"(d[12]), "+f"(d[13]), "+f"(d[14]), "+f"(d[15]),
      "+f"(d[16]), "+f"(d[17]), "+f"(d[18]), "+f"(d[19]), "+f"(d[20]), "+f"(d[21]), "+f"(d[22]), "+f"(d[23]), "+f"(d[24]), "+f"(d[25]), "+f"(d[26]), "+f"(d[27]), "+f"(d[28]), "+f"(d[29]), "+f"(d[30]), "+f"(d[31])
    : "r"(a[0]), "r"(a[1]), "r"(a[2]), "r"(a[3]), "l"(db), "r"(acc));
}
__device__ __forceinline__ void wg_rs_n32(float* d, const uint32_t* a, uint64_t db, int acc) {
  asm volatile("{.reg .pred p; setp.ne.b32 p, %21, 0;\n"
    "wgmma.mma_async.sync.aligned.m64n32k16.f32.bf16.bf16 {%0,%1,%2,%3,%4,%5,%6,%7,%8,%9,%10,%11,%12,%13,%14,%15}, {%16,%17,%18,%19}, %20, p, 1, 1, 0;}"
    : "+f"(d[0]), "+f"(d[1]), "+f"(d[2]), "+f"(d[3]), "+f"(d[4]), "+f"(d[5]), "+f"(d[6]), "+f"(d[7]), "+f"(d[8]), "+f"(d[9]), "+f"(d[10]), "+f"(d[11]), "+f"(d[12]), "+f"(d[13]), "+f"(d[14]), "+f"(d[15])
    : "r"(a[0]), "r"(a[1]), "r"(a[2]), "r"(a[3]), "l"(db), "r"(acc));
}
__device__ __forceinline__ void wg_ss_n40_tt(float* d, uint64_t da, uint64_t db, int acc) {
  asm volatile("{.reg .pred p; setp.ne.b32 p, %22, 0;\n"
    "wgmma.mma_async.sync.aligned.m64n40k16.f32.bf16.bf16 {%0,%1,%2,%3,%4,%5,%6,%7,%8,%9,%10,%11,%12,%13,%14,%15,%16,%17,%18,%19}, %20, %21, p, 1, 1, 1, 1;}"
    : "+f"(d[0]), "+f"(d[1]), "+f"(d[2]), "+f"(d[3]), "+f"(d[4]), "+f"(d[5]), "+f"(d[6]), "+f"(d[7]), "+f"(d[8]), "+f"(d[9]), "+f"(d[10]), "+f"(d[11]), "+f"(d[12]), "+f"(d[13]), "+f"(d[14]), "+f"(d[15]),
      "+f"(d[16]), "+f"(d[17]), "+f"(d[18]), "+f"(d[19])
    : "l"(da), "l"(db), "r"(acc));
}
__device__ __forceinline__ void wg_ss_n32_ta(float* d, uint64_t da, uint64_t db, int acc) {
  asm volatile("{.reg .pred p; setp.ne.b32 p, %18, 0;\n"
    "wgmma.mma_async.sync.aligned.m64n32k16.f32.bf16.bf16 {%0,%1,%2,%3,%4,%5,%6,%7,%8,%9,%10,%11,%12,%13,%14,%15}, %16, %17, p, 1, 1, 1, 0;}"
    : "+f"(d[0]), "+f"(d[1]), "+f"(d[2]), "+f"(d[3]), "+f"(d[4]), "+f"(d[5]), "+f"(d[6]), "+f"(d[7]), "+f"(d[8]), "+f"(d[9]), "+f"(d[10]), "+f"(d[11]), "+f"(d[12]), "+f"(d[13]), "+f"(d[14]), "+f"(d[15])
    : "l"(da), "l"(db), "r"(acc));
}
__device__ __forceinline__ uint64_t desc_ns(uint32_t a, uint32_t lbo, uint32_t sbo) { return (uint64_t)((a & 0x3FFFF) >> 4) | ((uint64_t)(lbo >> 4) << 16) | ((uint64_t)(sbo >> 4) << 32); }
__device__ __forceinline__ void wait_count(const uint32_t* p, uint32_t n) {
  uint32_t v; int guard = 0;
#pragma unroll 1
  while (true) { asm volatile("ld.relaxed.gpu.global.u32 %0, [%1];" : "=r"(v) : "l"(p) : "memory"); if (__all_sync(~0u, v >= n) || ++guard > 200000) break; }
}

constexpr int SD_WS = 0, SD_REC = 16384, SD_O = SD_REC + 2 * 30720, SD_OI = SD_O + 2 * 8192, SD_OUT = SD_OI + 2 * 40960, SD_FIN = SD_OUT + 8192, SD_BAR = SD_FIN + 10240;
constexpr int SD_SMEM = SD_BAR + 512 + 1024;
#undef TLBASE
#define TLBASE (1024 + SD_BAR + 256)
#define QRING 4
constexpr int ORING = 8, PRING = 2 * ORING;
constexpr int FL_MEM = 162 * 1024, FL_RDY = 166 * 1024, FL_SM = 170 * 1024, FL_ROW = 174 * 1024;
struct SideParams { CUtensorMap tmWo, tmP; const char* QKV; char *O, *part; const bf16* x1; bf16* out; uint32_t *comm, *sync; uint64_t dhi; int first, period, phase, win, lag, tmem, last, early, tlast, dbgf; };
#define DBGF(m) false
#define ELECT "{.reg .pred p; elect.sync _|p, 0xffffffff;\n"
#define ATS(i)
__global__ void __launch_bounds__(512, 1) side_kernel(const __grid_constant__ SideParams p) {
  extern __shared__ __align__(1024) char smem_raw[];
  const uint32_t sb = (smem_u32(smem_raw) + 1023) & ~1023u, wfull = sb + SD_BAR, rland = wfull + 8, ofull = wfull + 16, ofree = wfull + 32,
    ifull = wfull + 48, ifree = wfull + 64, rfull = wfull + 80, rfree = wfull + 96, fdone = wfull + 112, ffull = wfull + 128;
  const int tid = threadIdx.x, lane = tid & 31, w = __shfl_sync(~0u, tid >> 5, 0);
  if (!DBGF(16)) pdl_launch();
  if (tid == 0) {
    spin_count(p.sync + SY_3, 128);
    uint32_t sm, mate; asm("mov.u32 %0, %%smid;" : "=r"(sm));
    asm volatile("ld.relaxed.gpu.global.u32 %0, [%1];" : "=r"(mate) : "l"(p.comm + FL_SM - (p.first ^ 1) * 1024 + (sm ^ 1)) : "memory");
    const uint32_t n = atomicAdd(p.comm + FL_SM + 512 + (mate ? 8 : 0), 1);
    asm volatile("st.shared.b32 [%0], %1;" :: "r"(fdone + 12), "r"(mate ? 35 - n : n) : "memory");
  }
  __syncthreads();
  int h; asm volatile("ld.shared.b32 %0, [%1];" : "=r"(h) : "r"(fdone + 12) : "memory");
  h = __shfl_sync(~0u, h, 0);
  if (h == 35) return;
  const int cb = h % 5, ks = h / 5, h0 = ks < 4 ? 5 * ks : 4 + 4 * ks, nh = ks < 4 ? 5 : 4;
  const int nseg = DBGF(16) ? 0 : NSEG;
  auto since = [&](uint32_t ref) { uint32_t now; asm volatile("mov.u32 %0, %%globaltimer_lo;" : "=r"(now) :: "memory"); return (int)((now - ((ref >> 7) << 5)) << 2) >> 2; };
  auto gate = [&](int s) {
#pragma unroll 1
    for (int guard = 0; guard < 4000; guard++) {
      uint32_t ref; asm volatile("ld.volatile.shared.b32 %0, [%1];" : "=r"(ref) : "r"(fdone + 4) : "memory");
      const int n = ref & 127;
      if (n >= p.last || n > s + p.lag || (uint32_t)(since(ref) + 4 * p.period - p.phase) % p.period <= p.win) break;
    }
  };
  TL(0);
  if (tid == 0) {
    mbar_init(wfull, 1); mbar_init(rland, 1); mbar_init(ffull, 1);
    for (int i = 0; i < 2; i++) { mbar_init(ofull + i * 8, 2); mbar_init(ofree + i * 8, 1); mbar_init(ifull + i * 8, 1); mbar_init(ifree + i * 8, 8); mbar_init(rfull + i * 8, 1); mbar_init(rfree + i * 8, 4); }
    asm volatile("st.shared.v2.b32 [%0], {%1,%1};" :: "r"(fdone), "r"(0) : "memory");
    asm volatile("fence.proxy.async.shared::cta;" ::: "memory");
    mbar_expect(wfull, nh * 32768);
#pragma unroll 1
    for (int b = 0; b < 4 * nh; b++) tma2d(sb + ((b + 2) % 20) * 8192, &p.tmWo, cb * 128 + (b & 1) * 64, h0 * 128 + (b >> 1) * 64, wfull);
  }
  __syncthreads();
  if (w < 8) {
    asm volatile("setmaxnreg.inc.sync.aligned.u32 192;");
    const int c = w >> 2, mg = w & 3;
    const uint32_t boxoff = (((lane >> 4) << 3) + (lane & 7)) * 128 + (((2 * mg + ((lane >> 3) & 1)) ^ (lane & 7)) << 4);
    uint32_t A[36][4];
    mbar_wait(wfull, 0);
#pragma unroll
    for (int f = 0; f < 36; f++) ldsm4t(A[f][0], A[f][1], A[f][2], A[f][3], sb + 16384 + c * 8192 + boxoff + (f >> 2) * 16384 + (f & 3) * 2048);
    asm volatile("fence.proxy.async.shared::cta;" ::: "memory");
    bar_sync<1, 320>();
    TL(1);
    const uint32_t oa = sb + SD_OUT + c * 4096 + boxoff;
    const uint32_t ca = sb + SD_OI + tid * 32 + (lane & 4) * 4, tm = lane < 4 ? 0x00010001u : 0u;
    uint32_t wp = 1;
#pragma unroll 1
    for (int s = 0; s < nseg; s++) {
      const int b = s & 1;
      const uint64_t db = p.dhi + (uint32_t)(((sb + SD_OI) >> 4) + b * 2560), da = p.dhi + (uint32_t)(((sb + SD_WS) >> 4) + c * 512);
#define D128(x) (x)
      float acc[16];
      mbar_wait_long(ifull + b * 8, (s >> 1) & 1);
#pragma unroll 1
      for (int guard = 0; guard < 20000; guard++) {
        uint32_t bad = 0, ok;
#pragma unroll
        for (int i = 0; i < 5; i++) if (i < 4 || nh == 5) { uint32_t v; asm volatile("ld.shared.b32 %0, [%1];" : "=r"(v) : "r"(ca + b * 40960 + i * 8192) : "memory"); bad |= v ^ (s / ORING + 1); }
        asm volatile("{.reg .pred p; setp.eq.u32 p, %1, 0; bar.red.and.pred p, 5, 256, p; selp.u32 %0, 1, 0, p;}" : "=r"(ok) : "r"(bad & 1) : "memory");
        if (__all_sync(~0u, ok)) break;
        if (w == 0) {
          asm volatile("fence.proxy.async.shared::cta;" ::: "memory");
          asm volatile(ELECT "@p mbarrier.arrive.expect_tx.shared.b64 _, [%2], %3;\n@p cp.async.bulk.shared::cluster.global.mbarrier::complete_tx::bytes [%0], [%1], %3, [%2];}"
            :: "r"(sb + SD_OI + b * 40960), "l"(p.O + (size_t)((s % ORING) * 32 + h0) * 8192), "r"(wfull), "r"(nh * 8192) : "memory");
        }
        mbar_wait_long(wfull, wp); wp ^= 1;
      }
      if (s == NSEG - 2 && h < 32) mbar_wait_long(ofull + 8, 1);
      ATS(0)
      WG_FENCE();
#pragma unroll
      for (int k = 0; k < 32; k++) wg_rs_n32(acc, A[k], D128(db + (k >> 2) * 256 + (k & 3) * 2), k);
      if (nh == 5) {
#pragma unroll
        for (int k = 32; k < 36; k++) wg_rs_n32(acc, A[k], D128(db + 2048 + (k & 3) * 2), 1);
#pragma unroll
        for (int k = 0; k < 4; k++) wg_ss_n32_ta(acc, D128(da + k * 128), D128(db + 2304 + k * 2), 1);
      }
      WG_COMMIT();
      bar_sync<2, 256>();
      WG_WAIT(0);
      ATS(1)
      if (lane == 0) mbar_arrive(ifree + b * 8);
      const uint32_t tg = (s / PRING) & 1 ? 0u : tm;
#define TAG(x) (((x) & ~tm) | tg)
#pragma unroll
      for (int u = 0; u < 2; u++)
        asm volatile("stmatrix.sync.aligned.m8n8.x4.trans.shared.b16 [%0], {%1,%2,%3,%4};" :: "r"(oa + u * 2048),
          "r"(TAG(pack_bf16(acc[8 * u], acc[8 * u + 1]))), "r"(TAG(pack_bf16(acc[8 * u + 2], acc[8 * u + 3]))), "r"(TAG(pack_bf16(acc[8 * u + 4], acc[8 * u + 5]))), "r"(TAG(pack_bf16(acc[8 * u + 6], acc[8 * u + 7]))) : "memory");
      asm volatile("fence.proxy.async.shared::cta;" ::: "memory");
      if (w > 0) bar_arrive<4, 256>();
      else {
        bar_sync<4, 256>();
        asm volatile(ELECT "@p cp.async.bulk.tensor.3d.global.shared::cta.bulk_group [%0, {%2, %3, %4}], [%1];\n"
          "cp.async.bulk.commit_group;\ncp.async.bulk.wait_group 0;\n@p red.relaxed.gpu.global.add.u32 [%5], 1;}"
          :: "l"(&p.tmP), "r"(sb + SD_OUT), "r"(0), "r"((s % PRING) * 32), "r"(ks * 10 + cb * 2), "l"(p.comm + FL_RDY + s * 16 + 8) : "memory");
        ATS(2)
      }
    }
    TL(5);
  } else if (w < 12) {
    asm volatile("setmaxnreg.dec.sync.aligned.u32 72;");
    const int a = w - 8, g = lane >> 2, q = lane & 3;
    const float sc2 = 0.08838834764831845f * 1.4426950408889634f;
#pragma unroll 1
    for (int s = 0; s < (h < 32 ? nseg : 0); s++) {
      const int b = s & 1;
      const uint32_t rec = sb + SD_REC + b * 30720;
      mbar_wait_long(rfull + b * 8, (s >> 1) & 1);
      ATS(1)
      if (s == 0) TL(2);
      uint32_t P[3][4]; float inv[2];
      {
        float sc[20];
        const uint64_t dq = desc_ns(rec + 1024, 128, 1024), dk = desc_ns(rec + 5120, 128, 1024);
        WG_FENCE();
#pragma unroll
        for (int k = 0; k < 8; k++) wg_ss_n40_tt(sc, dq + (k >> 2) * 640 + (k & 3) * 16, dk + (k >> 2) * 640 + (k & 3) * 16, k);
        WG_COMMIT(); WG_WAIT(0);
        ATS(2)
#pragma unroll
        for (int rh = 0; rh < 2; rh++) {
          const int row = 16 * a + 8 * rh + g;
          float v[5][2], mx = -3.0e38f;
#pragma unroll
          for (int n = 0; n < 5; n++)
#pragma unroll
            for (int e = 0; e < 2; e++) {
              const bool ok = n == 0 || (8 * (n - 1) + 2 * q + e) <= row;
              v[n][e] = ok ? sc[4 * n + 2 * rh + e] * sc2 : -1.0e9f * 1.4426950408889634f; mx = fmaxf(mx, v[n][e]);
            }
          mx = fmaxf(mx, __shfl_xor_sync(~0u, mx, 1)); mx = fmaxf(mx, __shfl_xor_sync(~0u, mx, 2));
          float sum = 0.f;
#pragma unroll
          for (int n = 0; n < 5; n++) { const float e0 = ex2(v[n][0] - mx), e1 = ex2(v[n][1] - mx); sum += e0 + e1; P[n >> 1][(n & 1) * 2 + rh] = pack_bf16(e0, e1); }
          P[2][2 + rh] = 0u;
          sum += __shfl_xor_sync(~0u, sum, 1); sum += __shfl_xor_sync(~0u, sum, 2);
          asm("rcp.approx.ftz.f32 %0, %1;" : "=f"(inv[rh]) : "f"(sum));
        }
      }
      ATS(3)
      mbar_wait_long(ofree + b * 8, ((s >> 1) & 1) ^ 1);
      ATS(4)
      const uint32_t od = sb + SD_O + b * 8192 + (16 * a + (lane & 15)) * 128, tm = q == 0, tg = (s / ORING) & 1 ? 0u : tm;
#pragma unroll 1
      for (int hf = 0; hf < 2; hf++) {
        float o[32];
        const uint64_t dv = desc_ns(rec + 20480 + hf * 5120, 1024, 128);
        WG_FENCE();
        wg_rs_n64(o, P[0], dv, 0); wg_rs_n64(o, P[1], dv + 128, 1); wg_rs_n64(o, P[2], desc_ns(rec + 20480 + hf * 5120 + 4096, 0, 128), 1);
        WG_COMMIT(); WG_WAIT(0);
        if (a < 2) {
#pragma unroll
          for (int n = 0; n < 8; n += 2) {
            const float* x = o + 4 * n;
            asm volatile("stmatrix.sync.aligned.m8n8.x4.shared.b16 [%0], {%1,%2,%3,%4};" :: "r"(od + hf * 4096 + (((n + (lane >> 4)) ^ (lane & 7)) << 4)),
              "r"(TAG(pack_bf16(x[0] * inv[0], x[1] * inv[0]))), "r"(TAG(pack_bf16(x[2] * inv[1], x[3] * inv[1]))), "r"(TAG(pack_bf16(x[4] * inv[0], x[5] * inv[0]))), "r"(TAG(pack_bf16(x[6] * inv[1], x[7] * inv[1]))) : "memory");
          }
        }
      }
      if (a < 2) {
        asm volatile("fence.proxy.async.shared::cta;" ::: "memory");
        __syncwarp();
        if (lane == 0) mbar_arrive(ofull + b * 8);
      }
      if (lane == 0) mbar_arrive(rfree + b * 8);
      ATS(5)
    }
    TL(3);
  } else {
    asm volatile("setmaxnreg.dec.sync.aligned.u32 56;");
    if (w == 13) {
      bar_sync<1, 320>();
#pragma unroll 1
      for (int s = 0; s < nseg; s++) {
        mbar_wait_long(ifree + (s & 1) * 8, ((s >> 1) & 1) ^ 1);
        wait_count(p.comm + FL_RDY + s * 16 + ks, nh);
        gate(s + 2);
        ATS(0)
        asm volatile(ELECT "@p mbarrier.arrive.expect_tx.shared.b64 _, [%2], %3;\n@p cp.async.bulk.shared::cluster.global.mbarrier::complete_tx::bytes [%0], [%1], %3, [%2];}"
          :: "r"(sb + SD_OI + (s & 1) * 40960), "l"(p.O + (size_t)((s % ORING) * 32 + h0) * 8192), "r"(ifull + (s & 1) * 8), "r"(nh * 8192) : "memory");
      }
    } else if (h >= 32 && w < 15) {
    } else if (w == 12) {
#pragma unroll 1
      for (int s = 0; s < nseg; s++) {
        mbar_wait_long(ofull + (s & 1) * 8, (s >> 1) & 1);
        int fin, guard = 0;
        do { asm volatile("ld.volatile.shared.b32 %0, [%1];" : "=r"(fin) : "r"(fdone) : "memory"); } while (fin + ORING <= s && ++guard < 1000000);
        ATS(0)
        asm volatile(ELECT "@p cp.async.bulk.global.shared::cta.bulk_group [%0], [%1], 8192;\n"
          "cp.async.bulk.commit_group;\ncp.async.bulk.wait_group 0;\n@p mbarrier.arrive.shared.b64 _, [%3];\n@p red.relaxed.gpu.global.add.u32 [%2], 1;}"
          :: "l"(p.O + (size_t)((s % ORING) * 32 + h) * 8192), "r"(sb + SD_O + (s & 1) * 8192), "l"(p.comm + FL_RDY + s * 16 + (h < 20 ? h / 5 : (h - 4) >> 2)), "r"(ofree + (s & 1) * 8) : "memory");
        ATS(1)
      }
      TL(4);
    } else if (w == 14) {
      if (DBGF(16)) pdl_wait(); else
      mbar_wait_long(ofull, 0);
      uint32_t fp = 0;
      if (p.first) {
#pragma unroll 1
        for (int i = 0; i < 20; i++) *(uint2*)(p.out + (size_t)((NSEG - 4 + i / 5) * 32 + h) * D_ + (i % 5) * 128 + lane * 4) = make_uint2(~0u, ~0u);
      }
#pragma unroll 1
      for (int s = 0; s < nseg; s++) {
        asm volatile("fence.proxy.async.shared::cta;" ::: "memory");
        __syncwarp();
        asm volatile(ELECT "@p mbarrier.arrive.expect_tx.shared.b64 _, [%2], 10240;\n@p cp.async.bulk.shared::cluster.global.mbarrier::complete_tx::bytes [%0], [%1], 1280, [%2];}"
          :: "r"(sb + SD_FIN + 8960), "l"(p.x1 + (size_t)(s * 32 + h) * D_), "r"(ffull) : "memory");
        wait_count(p.comm + FL_RDY + s * 16 + 8, 35);
        ATS(0)
        uint32_t y[5][2];
#pragma unroll 1
        for (int tries = 0; tries < 20000; tries++) {
          asm volatile(ELECT "@p cp.async.bulk.shared::cluster.global.mbarrier::complete_tx::bytes [%0], [%1], 8960, [%2];}"
            :: "r"(sb + SD_FIN), "l"(p.part + (size_t)((s % PRING) * 32 + h) * 8960), "r"(ffull) : "memory");
          mbar_wait_long(ffull, fp); fp ^= 1;
          ATS(1)
          uint32_t bad = 0;
#pragma unroll
          for (int i = 0; i < 5; i++) {
            uint32_t v[8][2];
#pragma unroll
            for (int u = 0; u < 8; u++) asm volatile("ld.shared.v2.b32 {%0,%1}, [%2];" : "=r"(v[u][0]), "=r"(v[u][1]) : "r"(sb + SD_FIN + u * 1280 + i * 256 + lane * 8) : "memory");
#pragma unroll
            for (int u = 0; u < 7; u++) bad |= v[u][0] ^ (s / PRING + 1);
#pragma unroll
            for (int k = 0; k < 2; k++)
              y[i][k] = hadd2(v[7][k], pack_bf16(((bf_lo(v[0][k]) + bf_lo(v[1][k])) + (bf_lo(v[2][k]) + bf_lo(v[3][k]))) + ((bf_lo(v[4][k]) + bf_lo(v[5][k])) + bf_lo(v[6][k])),
                                                 ((bf_hi(v[0][k]) + bf_hi(v[1][k])) + (bf_hi(v[2][k]) + bf_hi(v[3][k]))) + ((bf_hi(v[4][k]) + bf_hi(v[5][k])) + bf_hi(v[6][k]))));
          }
          if (__all_sync(~0u, !(bad & ~lane & 1))) break;
          asm volatile("fence.proxy.async.shared::cta;" ::: "memory");
          __syncwarp();
          asm volatile(ELECT "@p mbarrier.arrive.expect_tx.shared.b64 _, [%0], 8960;}" :: "r"(ffull) : "memory");
        }
#pragma unroll
        for (int i = 0; i < 5; i++) *(uint2*)(p.out + (size_t)(s * 32 + h) * D_ + i * 128 + lane * 4) = make_uint2(y[i][0], y[i][1]);
        asm volatile("st.volatile.shared.b32 [%0], %1;" :: "r"(fdone), "r"(s + 1) : "memory");
        __syncwarp();
        if (lane == 0 && p.first) { if (s < NSEG - 4) __threadfence(); red_relaxed(p.comm + FL_ROW + s * 32); if (s == NSEG - 1) __threadfence(); }
        ATS(2)
      }
    } else {
      uint32_t lp = 0, known = 0;
      bar_sync<1, 320>();
#pragma unroll 1
      for (int s = 0; s < nseg; s++) {
        const int b = s & 1;
        const uint32_t rec = sb + SD_REC + b * 30720;
        if (h < 32) mbar_wait_long(rfree + b * 8, ((s >> 1) & 1) ^ 1);
        uint32_t f = ~0u;
#pragma unroll 1
        for (int guard = 0; guard < 100000; guard++) {
          if (lane < 3) asm volatile("ld.relaxed.gpu.global.u32 %0, [%1];" : "=r"(f) : "l"(p.comm + FL_MEM + (h & 31) * 32 + lane * 8) : "memory");
          known = __reduce_min_sync(~0u, f & 127);
          if (known > (uint32_t)s) break;
        }
        f = __shfl_sync(~0u, f, 0);
        if (lane == 0) asm volatile("st.volatile.shared.b32 [%0], %1;" :: "r"(fdone + 4), "r"(f) : "memory");
        if (h >= 32) continue;
        __syncwarp();
        const char* src = p.QKV + (size_t)((s % QRING) * 32 + h) * 30720;
#pragma unroll 1
        for (int tries = 0; tries < 20000; tries++) {
          if ((f & 127) == s + 1 && tries == (s >= p.early)) { const int t = s == NSEG - 1 ? p.tlast : p.tmem; for (int guard = 0; since(f) < t && guard < 4000; guard++) {} }
          if (tries == 0 || s < p.early) gate(s);
          ATS(0)
          asm volatile("fence.proxy.async.shared::cta;" ::: "memory");
          __syncwarp();
          if (tries == 0) asm volatile(ELECT "@p mbarrier.arrive.expect_tx.shared.b64 _, [%2], 30720;\n@p cp.async.bulk.shared::cluster.global.mbarrier::complete_tx::bytes [%0], [%1], 30720, [%2];}" :: "r"(rec), "l"(src), "r"(rland) : "memory");
          else asm volatile(ELECT "@p mbarrier.arrive.expect_tx.shared.b64 _, [%2], 4096;\n"
            "@p cp.async.bulk.shared::cluster.global.mbarrier::complete_tx::bytes [%0+5120], [%1+5120], 1024, [%2];\n@p cp.async.bulk.shared::cluster.global.mbarrier::complete_tx::bytes [%0+15360], [%1+15360], 1024, [%2];\n"
            "@p cp.async.bulk.shared::cluster.global.mbarrier::complete_tx::bytes [%0+20480], [%1+20480], 1024, [%2];\n@p cp.async.bulk.shared::cluster.global.mbarrier::complete_tx::bytes [%0+25600], [%1+25600], 1024, [%2];}"
            :: "r"(rec), "l"(src), "r"(rland) : "memory");
          mbar_wait_long(rland, lp); lp ^= 1;
          uint32_t mx = 0;
#pragma unroll
          for (int k = 0; k < 4; k++) { uint32_t v; asm volatile("ld.shared.b32 %0, [%1];" : "=r"(v) : "r"(rec + (k == 0 ? 5120 : 10240 + k * 5120) + lane * 32 + (lane >> 2) * 4) : "memory"); mx = max(mx, v); }
          if (__all_sync(~0u, mx != ~0u)) break;
        }
        if (lane == 0) { mbar_arrive(rfull + b * 8); asm volatile("st.relaxed.gpu.global.u32 [%0], %1;" :: "l"(p.comm + FL_MEM + h * 32 + 24), "r"(s + 1) : "memory"); }
      }
    }
    if (w == 14) { TL(6); __syncwarp(); TL_DUMP((p.first ^ 1) * 166 + 131 + h, lane); }
    if (!p.first && tid == 448 && h == 0) { for (int i = 0; i < 16; i++) p.sync[i * 16 - 128] = 0; }
  }
}

__device__ __forceinline__ uint32_t ld_relaxed(const void* p) { uint32_t v; asm volatile("ld.relaxed.gpu.global.u32 %0, [%1];" : "=r"(v) : "l"(p) : "memory"); return v; }
__device__ __forceinline__ void st_relaxed(void* p, uint32_t v) { asm volatile("st.relaxed.gpu.global.u32 [%0], %1;" :: "l"(p), "r"(v) : "memory"); }
__device__ __forceinline__ void st_relaxed_if(void* p, uint32_t v, uint32_t c) { asm volatile("{.reg .pred p; setp.ne.u32 p, %2, 0; @p st.relaxed.gpu.global.u32 [%0], %1;}" :: "l"(p), "r"(v), "r"(c) : "memory"); }
__device__ __forceinline__ uint32_t clk32() { uint32_t c; asm volatile("mov.u32 %0, %%clock;" : "=r"(c) :: "memory"); return c; }
__device__ __forceinline__ uint32_t gt32() { uint64_t c; asm volatile("mov.u64 %0, %%globaltimer;" : "=l"(c) :: "memory"); return (uint32_t)c; }
__device__ __forceinline__ void wait_gt(uint32_t T) {
  asm volatile("{\n.reg .pred p;\n.reg .u64 t;\n.reg .u32 lo, hi;\nLG%=:\nmov.u64 t, %%globaltimer;\nmov.b64 {lo, hi}, t;\nsub.u32 lo, lo, %0;\nsetp.lt.s32 p, lo, 0;\n@p bra.uni LG%=;\n}" :: "r"(T) : "memory");
}
__device__ __forceinline__ void advance(uint32_t& T, uint32_t lim, uint32_t step) {
  asm volatile("{\n.reg .pred p;\n.reg .s32 d;\nLA%=:\nsub.s32 d, %1, %0;\nsetp.gt.s32 p, d, 0;\n@p add.u32 %0, %0, %2;\n@p bra.uni LA%=;\n}" : "+r"(T) : "r"(lim), "r"(step));
}
template <int LUT> __device__ __forceinline__ uint32_t lop3(uint32_t a, uint32_t b, uint32_t c) { uint32_t r; asm("lop3.b32 %0, %1, %2, %3, %4;" : "=r"(r) : "r"(a), "r"(b), "r"(c), "n"(LUT)); return r; }
__device__ __forceinline__ uint32_t ldsm1t(uint32_t a) { uint32_t r; asm volatile("ldmatrix.sync.aligned.m8n8.x1.trans.shared.b16 {%0}, [%1];" : "=r"(r) : "r"(a) : "memory"); return r; }
__device__ __forceinline__ uint32_t hmax2(uint32_t a, uint32_t b) { uint32_t r; asm("max.bf16x2 %0, %1, %2;" : "=r"(r) : "r"(a), "r"(b)); return r; }
__device__ __forceinline__ uint32_t lds32(uint32_t a) { uint32_t v; asm volatile("ld.shared.b32 %0, [%1];" : "=r"(v) : "r"(a) : "memory"); return v; }
__device__ __forceinline__ void sts32(uint32_t a, uint32_t v) { asm volatile("st.shared.b32 [%0], %1;" :: "r"(a), "r"(v) : "memory"); }
__device__ __forceinline__ uint32_t mapa(uint32_t a, int rank) { uint32_t r; asm("mapa.shared::cluster.u32 %0, %1, %2;" : "=r"(r) : "r"(a), "r"(rank)); return r; }
template <int OFF> __device__ __forceinline__ void stas32(uint32_t a, uint32_t v, uint32_t bar) {
  asm volatile("st.async.weak.shared::cluster.mbarrier::complete_tx::bytes.b32 [%0+%3], %1, [%2];" :: "r"(a), "r"(v), "r"(bar), "n"(OFF) : "memory");
}
#define OPAQUE(x) x = __shfl_sync(~0u, x, lane)
#define CLUSTER_SYNC() asm volatile("barrier.cluster.arrive.release.aligned; barrier.cluster.wait.acquire.aligned;" ::: "memory")

constexpr int SM_BAR = 0;
constexpr int SM_WO = 2048;
constexpr int SM_VR = 43008;
constexpr int SM_RED = 59392;
constexpr int SM_AT = 67584;
constexpr int SM_MEMT = 108672;
constexpr int SM_QK = 119040;
constexpr int SM_SC = 123136;
constexpr int SM_OX = 125184;
constexpr int SM_VM = 127744;
constexpr int SM_ST = 139264;
constexpr int SM_X = 149504;
constexpr int SM_WST = 2048;
constexpr int SM_WS = 67584;
constexpr int REC_SMEM = 231424 + 1024;
constexpr int MB_A = 0, MB_QK = 24, MB_R = 32, MB_V = 56, MB_KV = 64, MB_X = 80, MB_IA = 96, MB_IC = 104, MB_TK = 112, MB_PRB = 120, MB_DP = 128, MB_TAB = 256, MB_T2 = 512;
#define NTQ 10
#define NTV 4
#define NB0 4
#define PINK 14
#define NB1 7
#define PINT 5
#define WPLAN 0x5542110
#define OPF 3
#define XPOS 1
#define W0K 4
#define NLATE 1
#define VPOS 0
#define XK 2
#define IMM 1
#define FIRSTN 1
#define GATEK 3
#define TOLQ 96
#define TOLV 160
constexpr int POLL_LIMIT = 20000;
constexpr int CM_X3 = 160, CM_MISC = 172;
__device__ __forceinline__ uint32_t x3_slot(int slot) { return (CM_X3 + (slot & 1) * 64 + (slot & 2) * 128) * 4096; }
__device__ __forceinline__ int near_page(int pg, int side) { return pg + ((__popc(pg & 0xB3) ^ side) & 1); }
__device__ __forceinline__ int mem_line(int jb) { const int ks = jb >> 1, c = ks >= 20, kk = ks - 20 * c; return (kk >> 2) * 16 + c * 8 + (kk & 3) * 2 + (jb & 1); }

struct RecParams {
  CUtensorMap tmW[3], tmWo, tmX;
  AParams a[2];
  const bf16 *mem0, *wr, *wi;
  char* QKV;
  uint32_t* comm;
  uint64_t dhi;
  int period, c3, slack, xlate, extra, start, gap, zero, helper, layer, dbgf;
  uint32_t *dbg, *log;
};
#define PRB(k)
#define LDW(d, a) ldsm4t(d[0], d[1], d[2], d[3], a)

#undef TLBASE
#define TLBASE (1024 + 896)
#define PRBASE (mbar + w * 16)
#define PRIMM 1024
#define PROFF 0
template <bool VR>
__device__ __forceinline__ void rec_gemm_warps(const RecParams& p, const uint32_t sb, const int h, const int r, const int L, const int w) {
  const int tid = tid_here(), lane = tid & 31;
  const int mg = w & 3, c = w >> 2;
  constexpr int NT = VR ? NTV : NTQ, NW = VR ? 8 : 16;
  uint32_t R[20][4], P[20][4], Wr[NW - NT][4];
  const uint32_t mbar = sb + SM_BAR;
  uint32_t l16 = lane * 16, lm = (lane >> 4) * 1024 + (lane & 15) * 16;
  OPAQUE(l16); OPAQUE(lm);
#define wl16 (l16 + (sb + w * 512))
  {
    const uint32_t boxoff = (((lane >> 4) << 3) + (lane & 7)) * 128 + (((2 * mg + ((lane >> 3) & 1)) ^ (lane & 7)) << 4);
    mbar_wait(mbar + MB_IA, 0);
    TL(15);
    const uint32_t wa = sb + SM_WS + c * 40960 + boxoff;
#pragma unroll
    for (int k = 0; k < 20; k++) LDW(R[k], wa + 81920 + k * 2048);
    bar_arrive<4, 288>();
#pragma unroll
    for (int k = 0; k < 20; k++) LDW(P[k], wa + k * 2048);
    bar_sync<2, 256>();
#pragma unroll
    for (int i = 0; i < NT; i++) sts128(wl16 + SM_AT + i * 4096, P[i][0], P[i][1], P[i][2], P[i][3]);
    mbar_wait(mbar + MB_IC, 0);
    TL(16);
    const uint32_t woa = sb + SM_WST + c * 16384 + boxoff;
#pragma unroll
    for (int i = 0; i < NW; i++) {
      const uint32_t a = woa + (VR ? i * 2048 : (i & 1) * 32768 + (i >> 1) * 2048);
      if (i >= 4 && i < 4 + NW - NT) LDW(Wr[i - 4], a); else LDW(P[i < 4 ? i : i - (NW - NT)], a);
    }
    asm volatile("fence.proxy.async.shared::cta;" ::: "memory");
    bar_sync<1, 384>();
#pragma unroll
    for (int i = 0; i < NT; i++) sts128(wl16 + SM_WO + i * 4096, P[i][0], P[i][1], P[i][2], P[i][3]);
    asm volatile("barrier.cluster.arrive.relaxed.aligned; barrier.cluster.wait.aligned;" ::: "memory");
  }
#define LDT(i) lds128(P[i], wl16 + SM_AT + (i) * 4096)
#define WGX(acc, A, ks, sc) wg_rs_n32(acc, A[ks], d##A + (((ks) >> 2) * 256 + ((ks) & 3) * 2), sc)
  float tb[16];
  constexpr int KW = VR ? 20 - W0K : 20;
  auto stream0 = [&](int n) {
    const uint64_t dP = p.dhi + (uint32_t)(((sb + SM_X + c * 20480) >> 4) + (n & 1) * 2560 + ((n + 1) & p.zero));
    WG_FENCE();
#pragma unroll
    for (int k = KW; k < 20; k++) WGX(tb, P, k, k - KW);
    WG_COMMIT();
  };
  auto stream = [&](int n) {
    float ta[16];
    const uint64_t dR = p.dhi + (uint32_t)(((sb + SM_X + c * 20480) >> 4) + (n & 1) * 2560), dP = dR + (uint32_t)(~n & p.zero);
    WG_FENCE();
    constexpr int NE = NT - (VR ? NLATE : 4);
#pragma unroll
    for (int k = 0; k < 20; k++) { WGX(ta, R, k, k); if ((k & 1) && k / 2 < NE) LDT(k / 2); }
    WG_COMMIT();
#define GATE(i) if (VR && (i) == GATEK) { if (GATEK) WG_COMMIT(); asm volatile("bar.sync 12, %0;" :: "r"((h & 1) ? 320 : 352) : "memory"); WG_FENCE(); }
    constexpr int K2 = VR ? NT + XK : 16;
#pragma unroll
    for (int k = K2; k < KW; k++) { GATE(k - K2); WGX(tb, P, k, KW < 20 || k > K2); }
    WG_COMMIT();
    WG_WAIT(1);
#pragma unroll
    for (int i = 0; i < 2; i++)
      sts128(l16 + (sb + (w ^ 4) * 512) + SM_RED + i * 4096, pack_bf16(ta[8 * i], ta[8 * i + 1]), pack_bf16(ta[8 * i + 2], ta[8 * i + 3]), pack_bf16(ta[8 * i + 4], ta[8 * i + 5]), pack_bf16(ta[8 * i + 6], ta[8 * i + 7]));
#pragma unroll
    for (int i = NE; i < NT; i++) LDT(i);
#pragma unroll
    for (int k = NT; k < K2; k++) { GATE(KW - K2 + k - NT); WGX(tb, P, k, 1); }
    WG_FENCE();
#pragma unroll
    for (int k = 0; k < NE; k++) WGX(tb, P, k, 1);
    bar_sync<11, 384>();
    uint32_t o[2][4];
    lds128(o[0], wl16 + SM_RED); lds128(o[1], wl16 + SM_RED + 4096);
    WG_FENCE();
#pragma unroll
    for (int k = NE; k < NT; k++) WGX(tb, P, k, 1);
    WG_COMMIT();
    WG_WAIT(0);
#pragma unroll
    for (int i = 0; i < 2; i++)
      asm volatile("stmatrix.sync.aligned.m8n8.x4.shared.b16 [%0], {%1,%2,%3,%4};" :: "r"(lm + (sb + (c ^ 1) * 5120 + mg * 256) + SM_ST + 1024 + i * 2048),
        "r"(hadd2(pack_bf16(tb[8 * i], tb[8 * i + 1]), o[i][0])), "r"(hadd2(pack_bf16(tb[8 * i + 2], tb[8 * i + 3]), o[i][1])),
        "r"(hadd2(pack_bf16(tb[8 * i + 4], tb[8 * i + 5]), o[i][2])), "r"(hadd2(pack_bf16(tb[8 * i + 6], tb[8 * i + 7]), o[i][3])) : "memory");
    bar_arrive<14, 320>();
  };
  int s = -2, att = 0;
#pragma unroll 1
  while (true) {
    if (s >= 0) {
    uint32_t B[10][4], Wf[NT][4], dp[4];
    float ap[2][4], ar[2][4];
#define LDO(i, base) lds128(Wf[i], (base) + SM_WO + (i) * 4096)
#define LDB(k2) ldsm4t(B[k2][0], B[k2][1], B[k2][2], B[k2][3], l16 + (sb + c * 1024) + SM_MEMT + ((k2) >> 1) * 2048 + ((k2) & 1) * 512)
#define BK(k) B[(k) >> 1][((k) & 1) * 2], B[(k) >> 1][((k) & 1) * 2 + 1]
    mbar_wait(mbar + MB_A, att & 1);
    PRB(0)
    LDB(0); LDB(1);
#pragma unroll
    for (int k = 0; k < 20; k++) {
      if (!(k & 1) && k < 16) LDB(k / 2 + 2);
      if (k == PINK) {
        const uint32_t wb = lop3<0xF8>(l16, __float_as_uint(ap[0][0]), p.zero) + (sb + w * 512);
#pragma unroll
        for (int u = 0; u < NB0 && u < NT; u++) LDO(u, wb);
      }
      if (k < 2) { mmaZ(ap[k], P[k], BK(k)); mmaZ(ar[k], R[k], BK(k)); } else { mmaA(ap[k & 1], P[k], BK(k)); mmaA(ar[k & 1], R[k], BK(k)); }
    }
    asm volatile("stmatrix.sync.aligned.m8n8.x4.shared.b16 [%0], {%1,%2,%3,%4};" :: "r"(lm + (sb + c * 2048 + mg * 256) + SM_QK),
      "r"(pack_bf16(ar[0][0] + ar[1][0], ar[0][1] + ar[1][1])), "r"(pack_bf16(ar[0][2] + ar[1][2], ar[0][3] + ar[1][3])),
      "r"(pack_bf16(ap[0][0] + ap[1][0], ap[0][1] + ap[1][1])), "r"(pack_bf16(ap[0][2] + ap[1][2], ap[0][3] + ap[1][3])) : "memory");
    bar_arrive<9, 384>();
    PRB(1)
    att++;
    uint32_t bad;
    asm volatile("{.reg .pred p; setp.ne.u32 p, 0, 0; bar.red.or.pred p, 8, 384, p; selp.u32 %0, 1, 0, p;}" : "=r"(bad) :: "memory");
    if (bad) {
#pragma unroll
      for (int i = 0; i < NT; i++) LDT(i);
      continue;
    }
    if (s == NSEG - 1) break;
    if (KW < 20) stream0(s);
    lds128(dp, mbar + MB_DP + w * 16);
#pragma unroll
    for (int i = NB0; i < NT && (VR || i < NB1); i++) LDO(i, wl16);
    uint32_t fmask = (~(l16 | dp[0]) >> 4) & 1, bit = ((s >> 1) & 1) ? 0u : fmask;
    char* cb = (char*)p.comm + ((s & 1) * (256 * 4096) + (l16 >> 2));
    char *d0 = cb + dp[0], *d1 = cb + dp[1], *d2 = cb + dp[2], *d3 = cb + dp[3];
    if (VR) asm volatile("" : "+l"(d0), "+l"(d1), "+r"(bit), "+r"(fmask)); else asm volatile("" : "+l"(d0), "+l"(d1), "+l"(d2), "+l"(d3), "+r"(bit), "+r"(fmask));
    if (KW < 20) WG_WAIT(0);
    sched_fence();
    if (VR) bar_arrive<2, 384>();
    else {
      bar_sync<2, 384>();
#pragma unroll
      for (int i = NB1; i < NT; i++) LDO(i, wl16);
    }
    bar_sync<3, 384>();
    PRB(2)
    uint32_t ob[4][4];
    float z0, z1;
#pragma unroll
    for (int i = 0; i < 4; i++) LDW(ob[i], l16 + sb + SM_OX + i * 512);
    asm volatile("ld.shared.v2.f32 {%0,%1}, [%2];" : "=f"(z0), "=f"(z1) : "r"(l16 + sb + SM_OX + 2048) : "memory");
#define WO(i) ((i) >= 4 && (i) < 4 + NW - NT ? Wr[(i) >= 4 && (i) < 4 + NW - NT ? (i) - 4 : 0] : Wf[(i) < 4 ? (i) : (i) < 4 + NW - NT ? 0 : (i) - (NW - NT)])
    float ga[4][4];
#pragma unroll
    for (int i = 0; i < NW; i++) {
      const int ks = VR ? i : i >> 1;
      if (i < 4) mmaZ(ga[i], WO(i), ob[ks >> 1][(ks & 1) * 2], ob[ks >> 1][(ks & 1) * 2 + 1]); else mmaA(ga[i & 3], WO(i), ob[ks >> 1][(ks & 1) * 2], ob[ks >> 1][(ks & 1) * 2 + 1]);
    }
    asm("rcp.approx.ftz.f32 %0, %0;" : "+f"(z0)); asm("rcp.approx.ftz.f32 %0, %0;" : "+f"(z1));
#pragma unroll
    for (int i = 0; i < 4; i++) { ga[0][i] += ga[2][i]; ga[1][i] += ga[3][i]; if (VR) ga[0][i] += ga[1][i]; }
#pragma unroll
    for (int t = 0; t < NW / 8; t++) {
      st_relaxed(t ? d2 : d0, lop3<0xF4>(bit, pack_bf16(ga[t][0] * z0, ga[t][1] * z1), fmask));
      st_relaxed(t ? d3 : d1, lop3<0xF4>(bit, pack_bf16(ga[t][2] * z0, ga[t][3] * z1), fmask));
    }
    PRB(3)
    } else { mbar_wait(mbar + MB_X + (s & 1) * 8, 0); if (KW < 20) { stream0(s); WG_WAIT(0); } }
    bar_sync<10, 256>();
    stream(s);
    PRB(4)
    s++;
  }
  if (__all_sync(~0u, lds32(mbar + MB_TAB + 4) == 0)) {
#pragma unroll
    for (int i = 0; i < NT; i++) LDT(i);
    bar_sync<1, 384>();
    const int ln = l16 >> 4;
    const uint32_t wa = sb + SM_WS + c * 40960 + (((ln >> 4) << 3) + (ln & 7)) * 128 + (((2 * mg + ((ln >> 3) & 1)) ^ (ln & 7)) << 4);
#pragma unroll
    for (int k = 0; k < 40; k++) {
      const uint32_t* f = k < 20 ? R[k % 20] : P[k % 20];
      asm volatile("stmatrix.sync.aligned.m8n8.x4.trans.shared.b16 [%0], {%1,%2,%3,%4};" :: "r"(wa + (k < 20 ? 81920 : 0) + (k % 20) * 2048), "r"(f[0]), "r"(f[1]), "r"(f[2]), "r"(f[3]) : "memory");
    }
  }
#undef wl16
}

#undef PRBASE
#undef PRIMM
#undef PROFF
#define PRBASE (mbar + j * 16)
#define PRIMM (1024 + 4)
#define PROFF 8
__device__ __forceinline__ void x_load(const RecParams& p, const uint32_t sb, int n) {
  if (DBGF(32)) { if ((threadIdx.x & 31) == 0) mbar_arrive(sb + SM_BAR + MB_X + (n & 1) * 8); return; }
  asm volatile(ELECT "@p mbarrier.arrive.expect_tx.shared.b64 _, [%2], 40960;\n"
    "@p cp.async.bulk.tensor.3d.shared::cluster.global.mbarrier::complete_tx::bytes [%0], [%1, {%3, %4, %3}], [%2];}"
      :: "r"(sb + SM_X + (n & 1) * 40960), "l"(&p.tmX), "r"(sb + SM_BAR + MB_X + (n & 1) * 8), "r"(0), "r"(n * 32) : "memory");
}
__device__ __forceinline__ void wo_load(const RecParams& p, const uint32_t sb, int h, int r, int i0) {
#pragma unroll 1
  for (int i = i0; i < i0 + 4; i++)
    asm volatile(ELECT "@p cp.async.bulk.tensor.2d.shared::cluster.global.mbarrier::complete_tx::bytes [%0], [%1, {%3, %4}], [%2];}"
      :: "r"(sb + SM_WST + i * 8192), "l"(&p.tmWo), "r"(sb + SM_BAR + MB_IC), "r"(r * 256 + (i >> 1) * 64), "r"(h * 128 + (i & 1) * 64) : "memory");
}
__device__ __forceinline__ int rec_attn_setup(const RecParams& p, const uint32_t sb, const int h, const int r, const int L, const int j) {
  const int ct = tid_here() - 256, lane = ct & 31;
  const uint32_t mbar = sb + SM_BAR;
  uint32_t* misc = p.comm + CM_MISC * 1024;
  if (lane == 0 && L == 0) {
#pragma unroll 1
    for (int it = 0; it < (j == 2 ? 40 : 12); it++) {
      const int pg = (it ^ j) & 1;
      uint32_t* a = misc + pg * 1024 + 128 + j * 192 + blockIdx.x * 2;
      const uint32_t t0 = clk32();
      uint32_t v; asm volatile("atom.relaxed.gpu.global.exch.b32 %0, [%1], %2;" : "=r"(v) : "l"(a), "r"(t0) : "memory");
      st_relaxed_if(a, 0, v == t0 + 1);
      asm volatile("red.shared.min.u32 [%0], %1;" :: "r"(mbar + MB_PRB + pg * 4), "r"(clk32() - t0) : "memory");
      const uint32_t b0 = lds32(mbar + MB_PRB), b1 = lds32(mbar + MB_PRB + 4);
      if (it >= 3 && min(b0, b1) < 380 && min(b0, b1) + 70 < max(b0, b1)) break;
    }
  }
  __syncwarp();
  if (ct == 32 && L == 0) { uint32_t sm; asm volatile("mov.u32 %0, %%smid;" : "=r"(sm)); st_relaxed(p.comm + FL_SM + sm, 1); }
  uint32_t m0[5][4];
#pragma unroll
  for (int i = 0; i < 20; i++) m0[i >> 2][i & 3] = *(const uint32_t*)(p.mem0 + (lane >> 2) * D_ + (j * 20 + i) * 8 + (lane & 3) * 2);
  if (j < 2) {
    bar_sync<6, 320>();
    if (j == 0) { if (lane == 0) { red_release(p.a[L].sync + SY_3); TL(14); } __syncwarp(); }
    else {
      if (r < 2) { asm volatile("fence.proxy.async.shared::cta;" ::: "memory"); wo_load(p, sb, h, r, 4); }
      if (lane == 0 && atomicAdd(p.a[L].sync + SY_W + 16, 1) == 95) st_relaxed(misc + 96 + L, (gt32() + p.start) & ~31u);
      __syncwarp();
    }
  }
  if (j == 3) {
    spin_count(p.a[L].sync + SY_3 + 16, 4);
    asm volatile("fence.proxy.async.global;" ::: "memory");
    bar_sync<4, 288>();
    asm volatile("fence.proxy.async.shared::cta;" ::: "memory");
    x_load(p, sb, 0); x_load(p, sb, 1);
    TL(17);
  }
  bar_sync<1, 384>();
  asm volatile("barrier.cluster.arrive.relaxed.aligned;" ::: "memory");
#pragma unroll
  for (int i = 0; i < 5; i++)
    asm volatile("stmatrix.sync.aligned.m8n8.x4.trans.shared.b16 [%0], {%1,%2,%3,%4};" :: "r"(sb + SM_MEMT + mem_line(j * 20 + i * 4) * 128 + lane * 16), "r"(m0[i][0]), "r"(m0[i][1]), "r"(m0[i][2]), "r"(m0[i][3]) : "memory");
  sts128(sb + SM_ST + (ct >> 6) * 5120 + (ct & 63) * 16, ~0u, ~0u, ~0u, ~0u);
  asm volatile("barrier.cluster.wait.aligned;" ::: "memory");
  const uint32_t b0 = lds32(mbar + MB_PRB), b1 = lds32(mbar + MB_PRB + 4);
  const int side = __shfl_sync(~0u, ((b1 < b0) ^ __popc(CM_MISC & 0xB3)) & 1, 0);
  if (r == 2 && j + (h & 1) < 3) st_relaxed(misc + (j < 2 ? 2 * h + j : 64 + (h >> 1)), side);
  if (j == 0) {
    const int job = 2 * (16 * r + (lane >> 2) + ((lane & 2) && r < 2 ? 8 : 0)) + (lane & 1);
    uint32_t v; int guard = 0;
#pragma unroll 1
    do { v = ld_relaxed(misc + job); } while (__any_sync(~0u, v == 0xFFFFFFFFu) && ++guard < 1000000);
    sts32(mbar + MB_DP + lane * 4, near_page(2 * job, v) * 4096 + h * 128);
  }
  if (j == 1) {
    if (lane == 0) {
      uint32_t v; int guard = 0;
#pragma unroll 1
      do { v = ld_relaxed(misc + 96 + L); } while (v == 0xFFFFFFFFu && ++guard < 1000000);
      sts32(mbar + MB_TK, v);
    }
    __syncwarp();
  }
  if (j == 3) { spin_count(p.a[L].sync + SY_3, 128); asm volatile("fence.proxy.async.global;" ::: "memory"); }
  return side;
}
__device__ __forceinline__ void rec_attn_warps(const RecParams& p, const uint32_t sb, char* smem, const int h, const int r, const int side, const int L, const int j) {
  const int lane = tid_here() & 31, mi = lane >> 3;
  const uint32_t mbar = sb + SM_BAR;
#define VR (r == 2)
#define is_red (j + (h & 1) < 3 * r - 3)
  uint32_t l16 = sb + lane * 16;
#define wr16 (l16 + j * 512)
#define L0 ((l16 & 511) == 0)
  uint32_t ka = VR ? (mi != (lane & 3) ? 0u : (lane & 4) ? 0x3F800000u : 0x00003F80u)
    : j < 2 ? sb + SM_ST + 6144 + (2 * j + (mi & 1)) * 1024 + ((mi >> 1) * 8 + (lane & 7)) * 16 : sb + SM_QK + j * 512 + ((mi & 1) * 16 + (mi >> 1) * 8 + (lane & 7)) * 16;
  uint32_t own = VR ? sb + SM_AT + 28672 + j * 4096 + lane * 32 + (lane & 12) * 2 : sb + SM_SC + r * 1024 + (j < 2 ? j * 256 : 256 + j * 128) + lane * 4;
  uint32_t va = sb + SM_VR + (j >> 1) * 4096 + (mi >> 1) * 1024 + ((j & 1) * 32 + (mi & 1) * 8 + (lane & 7)) * 16, ps[2], pb[2];
#pragma unroll
  for (int i = 0; i < 2; i++) {
    const int peer = VR ? i : i == 0 ? r ^ 1 : 2;
    ps[i] = mapa(VR ? wr16 + SM_VM : own, peer); pb[i] = mapa(mbar + (VR ? MB_V : MB_QK), peer);
    OPAQUE(ps[i]); OPAQUE(pb[i]);
  }
  OPAQUE(ka); OPAQUE(own); OPAQUE(va); OPAQUE(l16);
  const char* comm = (const char*)p.comm;
  const uint32_t ones = 0x3F803F80u;
  const float sc2 = 0.08838834764831845f * 1.4426950408889634f;
  uint32_t kf[4][4], vf[4][4];
#pragma unroll
  for (int i = 0; i < 16; i++) kf[i >> 2][i & 3] = vf[i >> 2][i & 3] = p.zero;
  char* const rec0 = p.QKV + (h * 3 + r) * 10240;
  uint32_t* const fl = p.comm + FL_MEM + (L * 32 + h) * 32;
#define REC(n) (rec0 + ((n) & (QRING - 1)) * (96 * 10240))
  auto m_store = [&](int n) {
    if (VR || j < 2) {
      const int jj = VR ? j : j + 2;
      uint32_t a[4], b[4]; lds128(a, l16 + jj * 512 + SM_QK); lds128(b, l16 + (jj ^ 2) * 512 + SM_QK + 2048);
      asm volatile("st.relaxed.gpu.global.v4.u32 [%0], {%1,%2,%3,%4};" :: "l"(REC(n) + ((jj >> 1) * 5120 + (j & 1) * 512) + (l16 & 511)),
        "r"(hadd2(a[0], b[0])), "r"(hadd2(a[1], b[1])), "r"(hadd2(a[2], b[2])), "r"(hadd2(a[3], b[3])) : "memory");
    }
  };
  int att = 1, rph = 0;
  const int jb = j < 2 ? 2 * h + j : 64 + (h >> 1), ln = mem_line(jb) + 16;
  const uint32_t inbox = near_page(2 * jb, side) * 4096, bline = (ln >> 5) * 16384 + (ln & 31) * 128;
#define VERDICT(bad) asm volatile("{.reg .pred p; setp.ne.u32 p, %0, 0; bar.red.or.pred p, 8, 384, p;}" :: "n"(bad) : "memory")
#pragma unroll 1
  for (int s = -2; s < NSEG - 1; s++) {
    const uint32_t par = s & 1;
    auto v_load = [&]() {
      asm volatile("cp.async.bulk.wait_group 0;" ::: "memory");
      if (VR) asm volatile(ELECT
        "@p cp.async.bulk.shared::cluster.global.mbarrier::complete_tx::bytes.multicast::cluster [%0], [%1+1024], 4096, [%2], %3;\n"
        "@p cp.async.bulk.shared::cluster.global.mbarrier::complete_tx::bytes.multicast::cluster [%0+4096], [%1+6144], 4096, [%2], %3;}"
          :: "r"(sb + SM_VR + (par ^ 1) * 8192), "l"(REC(s + 1)), "r"(mbar + MB_KV + (par ^ 1) * 8), "h"((unsigned short)7) : "memory");
    };
    auto load_v = [&]() {
      if (s >= -1) mbar_wait(mbar + MB_KV + (par ^ 1) * 8, ((s + 1) >> 1) & 1);
#pragma unroll
      for (int i = 0; i < 4; i++) ldsm4(vf[i][0], vf[i][1], vf[i][2], vf[i][3], va + (par ^ 1) * 8192 + (i >> 1) * 2048 + (i & 1) * 256);
    };
    if (s >= 0) {
    uint32_t su[6], sw[6], vm[4];
#define LDSM2T(d, a) asm volatile("ldmatrix.sync.aligned.m8n8.x2.trans.shared.b16 {%0,%1}, [%2];" : "=r"(d[4]), "=r"(d[5]) : "r"(a) : "memory")
#define HADD4(a, b) { a[0] = hadd2(a[0], b[0]); a[1] = hadd2(a[1], b[1]); a[2] = hadd2(a[2], b[2]); a[3] = hadd2(a[3], b[3]); }
    bar_sync<9, 384>();
    PRB(0)
    {
      uint32_t qf[2][4], qg[2][4];
      float sa[4][4];
      if (j + (r & 2) < 2) {
        LDW(qf[0], l16 + SM_QK); LDW(qg[0], l16 + SM_QK + 3072); LDW(qf[1], l16 + SM_QK + 512); LDW(qg[1], l16 + SM_QK + 3584);
        HADD4(qf[0], qg[0]); HADD4(qf[1], qg[1]);
#pragma unroll
        for (int i = 0; i < 4; i++) mmaZ(sa[i], kf[i], qf[i >> 1][(i & 1) * 2], qf[i >> 1][(i & 1) * 2 + 1]);
        const uint32_t t0 = pack_bf16((sa[0][0] + sa[1][0]) + (sa[2][0] + sa[3][0]), (sa[0][1] + sa[1][1]) + (sa[2][1] + sa[3][1]));
        const uint32_t t1 = pack_bf16((sa[0][2] + sa[1][2]) + (sa[2][2] + sa[3][2]), (sa[0][3] + sa[1][3]) + (sa[2][3] + sa[3][3]));
        stas32<0>(ps[0], t0, pb[0]); stas32<0>(ps[1], t0, pb[1]); stas32<128>(ps[0], t1, pb[0]); stas32<128>(ps[1], t1, pb[1]);
        sts32(own, t0); sts32(own + 128, t1);
      } else if (!VR) {
        LDW(qf[0], wr16 + SM_QK - 1024); LDW(qg[0], wr16 + SM_QK + 2048); LDW(qf[1], ka); LDW(qg[1], ka + 1024);
        HADD4(qf[0], qg[0]); HADD4(qf[1], qg[1]);
        mmaZ(sa[0], qf[1], qf[0][0], qf[0][1]); mmaZ(sa[1], qf[1], qf[0][2], qf[0][3]);
        const uint32_t t0 = pack_bf16(sa[0][0] + sa[1][2], sa[0][1] + sa[1][3]);
        stas32<0>(ps[0], t0, pb[0]); stas32<0>(ps[1], t0, pb[1]);
        sts32(own, t0);
      } else {
        ldsm4(qf[0][0], qf[0][1], qf[0][2], qf[0][3], wr16 + SM_QK); ldsm4(qg[0][0], qg[0][1], qg[0][2], qg[0][3], l16 + (j ^ 2) * 512 + SM_QK + 2048);
        HADD4(qf[0], qg[0]);
        sts128(wr16 + SM_VM, qf[0][0], qf[0][1], qf[0][2], qf[0][3]);
#pragma unroll
        for (int i = 0; i < 2; i++)
          asm volatile("st.async.weak.shared::cluster.mbarrier::complete_tx::bytes.v4.b32 [%0], {%1,%2,%3,%4}, [%5];" :: "r"(ps[i]), "r"(qf[0][0]), "r"(qf[0][1]), "r"(qf[0][2]), "r"(qf[0][3]), "r"(pb[i]) : "memory");
      }
      PRB(1)
      VERDICT(0);
      if (VR) { if (VPOS == 1 && j == 2) v_load(); mbar_wait(mbar + MB_QK, par); }
      LDW(su, l16 + SM_SC + (r & 1) * 1024); LDSM2T(su, l16 + SM_SC + 512 + (r & 1) * 1024);
      if (!VR) mbar_wait(mbar + MB_QK, par);
      PRB(2)
      LDW(sw, l16 + SM_SC + 1024 - (r & 1) * 1024); LDSM2T(sw, l16 + SM_SC + 1536 - (r & 1) * 1024);
      su[4] = hadd2(su[4], su[5]);
    }
    {
      HADD4(su, sw); su[4] = hadd2(su[4], hadd2(sw[4], sw[5]));
      uint32_t m = hmax2(hmax2(hmax2(su[0], su[1]), hmax2(su[2], su[3])), su[4]);
      const uint32_t m1 = __shfl_xor_sync(~0u, m, 1), m2 = __shfl_xor_sync(~0u, m, 2), m3 = __shfl_xor_sync(~0u, m, 3);
      float t[10];
#pragma unroll
      for (int i = 0; i < 5; i++) { t[2 * i] = bf_lo(su[i]) * sc2; t[2 * i + 1] = bf_hi(su[i]) * sc2; }
      {
        asm volatile("" : "+f"(t[0]), "+f"(t[1]), "+f"(t[2]), "+f"(t[3]), "+f"(t[4]), "+f"(t[5]), "+f"(t[6]), "+f"(t[7]), "+f"(t[8]), "+f"(t[9]));
        mbar_wait(mbar + MB_V, par | (r >> 1)); bar_arrive<2, 384>(); lds128(vm, wr16 + SM_VM);
      }
      t[PINT] = __uint_as_float(lop3<0xF8>(__float_as_uint(t[PINT]), vm[0], p.zero));
      m = hmax2(hmax2(m, m1), hmax2(m2, m3));
      const float mx = fmaxf(bf_lo(m), bf_hi(m));
#define EX(i) ex2(fmaf(mx, -sc2, t[i]))
      float o1[2][4], z[4];
      const uint32_t P0 = pack_bf16(EX(0), EX(1)), P1 = pack_bf16(EX(2), EX(3));
      mmaZ(o1[0], vf[0], P0, P1); mmaZ(o1[1], vf[1], P0, P1); mma16816z(z, ones, ones, ones, ones, P0, P1);
      const float e4 = EX(4), e5 = EX(5);
      const uint32_t P2 = pack_bf16(e4, e5), P3 = pack_bf16(EX(6), EX(7));
      mmaA(o1[0], vf[2], P2, P3); mmaA(o1[1], vf[3], P2, P3); mma16816(z, ones, ones, ones, ones, P2, P3);
      const uint32_t Pm = pack_bf16(EX(8), EX(9));
      mma1688(o1[0], vm[0], vm[1], Pm); mma1688(o1[1], vm[2], vm[3], Pm); mma1688(z, ones, ones, Pm);
      asm volatile("stmatrix.sync.aligned.m8n8.x4.shared.b16 [%0], {%1,%2,%3,%4};" :: "r"(wr16 + SM_OX),
        "r"(pack_bf16(o1[0][0], o1[0][1])), "r"(pack_bf16(o1[0][2], o1[0][3])), "r"(pack_bf16(o1[1][0], o1[1][1])), "r"(pack_bf16(o1[1][2], o1[1][3])) : "memory");
      if (j == 3) asm volatile("st.shared.v2.f32 [%0], {%1,%2};" :: "r"(l16 + SM_OX + 2048), "f"(z[0]), "f"(z[1]) : "memory");
    }
    bar_arrive<3, 384>();
    PRB(3)
    if (j == 3) asm volatile(ELECT "@p mbarrier.arrive.expect_tx.shared.b64 _, [%0+%4], %2;\n@p mbarrier.arrive.expect_tx.shared.b64 _, [%1], 8192;\n"
      "@p mbarrier.arrive.expect_tx.shared.b64 _, [%0+%5], 10368;\nsetp.ne.and.u32 p, %3, 2, p;\n@p mbarrier.arrive.expect_tx.shared.b64 _, [%0+%6], 2048;}"
        :: "r"(mbar), "r"(mbar + MB_KV + par * 8), "r"(VR ? 1536 : 768), "r"(r), "n"(MB_QK), "n"(MB_A), "n"(MB_V) : "memory");
    }
    uint32_t T3, c3;
    asm volatile("ld.shared.v2.b32 {%0,%1}, [%2];" : "=r"(T3), "=r"(c3) : "r"(mbar + MB_TK) : "memory");
    {
      const uint32_t now = gt32(), lim = now + c3 + p.gap;
      if ((int)(T3 - now) > 20000) T3 = now;
      advance(T3, lim, p.slack);
    }
    if (s >= 0) m_store(s);
    if (j + (r & 2) < 2) {
#pragma unroll
      for (int i = 0; i < 4; i++) LDW(kf[i], ka + i * 256);
    } else {
#pragma unroll
      for (int i = 0; i < 16; i++) kf[i >> 2][i & 3] = 0;
    }
    int used = 0;
    if (j == 2 && s >= -1) { if (VPOS != 1 || !VR || s < 0) v_load(); used = ld_relaxed(fl + 24); }
    if (VPOS == 1) load_v();
    bar_arrive<11, 384>();
    if (is_red) {
      const uint32_t expect = ((s >> 1) & 1) ^ 1, rb = mbar + MB_R + j * 8, stg = SM_AT + 28672 + j * 4096, s1 = ka | (s & p.zero);
      char* w0 = (char*)comm + (x3_slot(s + 1) + bline + (l16 & 511) / 4);
      asm volatile("" : "+l"(w0));
      uint32_t T2 = T3 - c3;
      if (s < 0) asm volatile("bar.arrive 12, %0;" :: "r"((h & 1) ? 320 : 352) : "memory");
      else {
#pragma unroll 1
        for (int nth = 0;; nth++) {
          wait_gt(T2);
          PRB(4)
          asm volatile(ELECT "@p cp.async.bulk.shared::cluster.global.mbarrier::complete_tx::bytes [%0], [%1], 4096, [%2];\n@p mbarrier.arrive.expect_tx.shared.b64 _, [%2], 4096;}"
            :: "r"(sb + stg), "l"(comm + (inbox + par * (256 * 4096))), "r"(rb) : "memory");
          mbar_wait(rb, rph & 1); rph++;
          uint32_t x[8][4], f[4];
          float ra[4][4];
#pragma unroll
          for (int i = 0; i < 8; i++) ldsm4(x[i][0], x[i][1], x[i][2], x[i][3], l16 + stg + i * 512);
#pragma unroll
          for (int i = 0; i < 4; i++) f[i] = lds32(own + i * 1024);
#pragma unroll
          for (int i = 0; i < 8; i++) { if (i < 4) mmaZ(ra[i], x[i], ka, s1); else mmaA(ra[i & 3], x[i], ka, s1); }
          const uint32_t ok = __all_sync(~0u, lop3<0xA8>(lop3<0x7E>(f[0], f[1], expect), lop3<0x7E>(f[2], f[3], expect), 1) == 0) || nth == POLL_LIMIT;
          const uint32_t v = pack_bf16(((ra[0][0] + ra[0][2]) + (ra[1][0] + ra[1][2])) + ((ra[2][0] + ra[2][2]) + (ra[3][0] + ra[3][2])), ((ra[0][1] + ra[0][3]) + (ra[1][1] + ra[1][3])) + ((ra[2][1] + ra[2][3]) + (ra[3][1] + ra[3][3])));
          asm volatile("{.reg .pred p, q; setp.ne.u32 p, %2, 0; setp.eq.u32 q, %4, 0; @q bar.arrive 12, %3; @p st.relaxed.gpu.global.u32 [%0], %1; @p st.relaxed.gpu.global.u32 [%0+4096], %1; @p bar.arrive 15, %5;}"
            :: "l"(w0), "r"(v), "r"(ok), "r"(lop3<0xF8>((h & 1) ? 320 : 352, __float_as_uint(ra[3][0]), p.zero)), "r"(nth), "r"((h & 1) ? 96 : 128) : "memory");
          if (ok) break;
          if (nth == 0) {
            char* c = (char*)comm + (x3_slot(s + 1) + 1920);
            asm volatile(ELECT "@p red.relaxed.gpu.global.max.s32 [%0], %1;\n@p red.relaxed.gpu.global.max.s32 [%0+4096], %1;}" :: "l"(c), "r"(lds32(mbar + MB_TAB + 8) + 1) : "memory");
          }
          if (!IMM || nth) { T2 += p.slack; advance(T2, gt32() - TOLQ, p.slack); }
        }
        PRB(5)
        w0 = (char*)((uint64_t)w0 ^ (1 << 20));
        st_relaxed(w0, 0xFFFFFFFFu); st_relaxed(w0 + 4096, 0xFFFFFFFFu);
      }
#pragma unroll
      for (int i = 0; i < 16; i++) kf[i >> 2][i & 3] = 0;
    }
#pragma unroll 1
    for (int guard = 0;; guard++) {
      if (j == 3 && s >= 0) {
        if (VR && guard == 0) { asm volatile("bar.sync 15, %0;" :: "r"((h & 1) ? 96 : 128) : "memory"); sts32(mbar + MB_TAB, 0); }
        advance(T3, gt32() - (VR ? TOLV : TOLQ), p.slack);
        wait_gt(T3);
        asm volatile(ELECT
          "@p cp.async.bulk.shared::cluster.global.mbarrier::complete_tx::bytes [%0+-128], [%2+1920], 2176, [%1];\n"
          "@p cp.async.bulk.shared::cluster.global.mbarrier::complete_tx::bytes [%0+2048], [%2+16384], 4096, [%1];\n"
          "@p cp.async.bulk.shared::cluster.global.mbarrier::complete_tx::bytes [%0+6144], [%2+32768], 4096, [%1];}"
          :: "r"(sb + SM_MEMT), "r"(mbar + MB_A), "l"(comm + (x3_slot(s + 1) + side * 4096)) : "memory");
      }
      PRB(6)
      if (VPOS == 0) load_v();
      uint32_t m = 0, ok;
      if (j < 2) {
        if (s + 3 < NSEG) mbar_wait(mbar + MB_X + (par ^ 1) * 8, ((s + 3) >> 1) & 1);
        if (s >= 0) {
          mbar_wait(mbar + MB_A, att & 1);
#pragma unroll
          for (int i = 0; i < 5; i++) m = max(m, lds32(l16 + (l16 & 511) + (l16 & 448) / 16 + (j * 1024 + SM_MEMT + i * 2048)));
        }
      } else if (guard == 0) {
        bar_sync<14, 320>();
        if (j == 2) {
#pragma unroll 1
          for (int g2 = 0; __any_sync(~0u, used + QRING < s + 3) && g2 < POLL_LIMIT && !DBGF(16); g2++) used = ld_relaxed(fl + 24);
          asm volatile("fence.proxy.async.shared::cta;" ::: "memory");
          if (s + 2 < NSEG && !DBGF(64)) asm volatile(ELECT "@p cp.async.bulk.global.shared::cta.bulk_group [%0], [%1], 10240;\ncp.async.bulk.commit_group;}" :: "l"(REC(s + 2)), "r"(sb + SM_ST) : "memory");
        } else if (XPOS == 0 && s + 4 < NSEG) { if (s >= 0) wait_gt(T3 + 192); x_load(p, sb, s + 4); }
      }
      if (VPOS == 2) load_v();
      att++;
      asm volatile("{.reg .pred p; setp.ne.u32 p, %1, 0xffffffff; bar.red.and.pred p, 13, 128, p; selp.u32 %0, 1, 0, p;}" : "=r"(ok) : "r"(m) : "memory");
      if (__all_sync(~0u, ok) || guard == POLL_LIMIT) break;
      bar_arrive<9, 384>();
      VERDICT(1);
      if (j == 3) asm volatile(ELECT "@p mbarrier.arrive.expect_tx.shared.b64 _, [%0], 10368;}" :: "r"(mbar + MB_A) : "memory");
      T3 += p.slack;
    }
    PRB(7)
    if (j == 3) {
      if (XPOS == 1 && s + 4 < NSEG) x_load(p, sb, s + 4);
      if (s >= 0) {
        const int seen = lds32(sb + SM_MEMT - 128), had = lds32(mbar + MB_TAB + 8), cnt = max(seen, had + (s < FIRSTN));
        sts32(mbar + MB_TAB + 8, cnt); sts32(mbar + MB_TK, T3 + p.period + (cnt - had) * (p.xlate + p.extra)); sts32(mbar + MB_TK + 4, cnt > had ? p.c3 + p.extra : p.c3);
      }
      st_relaxed(fl + r * 8, (((s < 0 ? T3 - p.period : T3) >> 5) << 7) | (s + 2));
      if (s == -2) asm volatile(ELECT "@p mbarrier.arrive.shared.b64 _, [%0];}" :: "r"(mbar + MB_A) : "memory");
      if (s < 0) TL(18);
    }
  }
  bar_sync<9, 384>();
  m_store(NSEG - 1);
  VERDICT(0);
  TL(19);
  if (__all_sync(~0u, lds32(mbar + MB_TAB + 4) == 0)) bar_arrive<1, 384>();
  if (is_red) {
    uint32_t* wpoi = (uint32_t*)(comm + (x3_slot(2) + bline + (l16 & 511) / 4));
    st_relaxed(wpoi, 0xFFFFFFFFu); st_relaxed(wpoi + 1024, 0xFFFFFFFFu);
#pragma unroll 1
    for (int i = 0; i < 8; i++) stg128((char*)comm + (inbox + 256 * 4096 + i * 512 + (l16 & 511)), 0, 0, 0, 0);
    __threadfence();
  }
#undef VR
}

__global__ void __launch_bounds__(384, 1) rec_kernel(const __grid_constant__ RecParams p) {
  extern __shared__ __align__(1024) char smem_raw[];
  const uint32_t sb = (smem_u32(smem_raw) + 1023) & ~1023u;
  char* smem = smem_raw + (sb - smem_u32(smem_raw));
  const int tid = threadIdx.x;
  const uint32_t mbar = sb + SM_BAR;
  pdl_launch();
  if (!p.helper) {
    if (tid == 32 || tid == 96) l2_prefetch((tid == 32 ? p.wi : p.wr) + blockIdx.x * 6848, 13696);
    if (tid == 64 && blockIdx.x < 12) l2_prefetch(g_tab + TB_F32 * 4 + blockIdx.x * 256, 1024);
  }
#pragma unroll 1
  for (int L = p.layer; L < 2; L++) {
    {
    const int w = __shfl_sync(~0u, tid >> 5, 0), bid = blockIdx.x + (L & p.zero), h = bid / 3, r = bid % 3;
    TL(0);
    if (tid == 0) {
#pragma unroll 1
      for (int i = 0; i < 14; i++) {
        if (L > p.layer) asm volatile("mbarrier.inval.shared.b64 [%0];" :: "r"(mbar + i * 8) : "memory");
        mbar_init(mbar + i * 8, 1);
      }
      asm volatile("fence.mbarrier_init.release.cluster;" ::: "memory");
      asm volatile("fence.proxy.async.shared::cta;" ::: "memory");
      mbar_expect(mbar + MB_QK, r == 2 ? 1536 : 768); mbar_expect(mbar + MB_V, 2048);
      mbar_expect(mbar + MB_KV, 8192); mbar_expect(mbar + MB_KV + 8, 8192);
      if (L == 0) { sts32(mbar + MB_PRB, 60000); sts32(mbar + MB_PRB + 4, 60000); }
      sts32(mbar + MB_TK, gt32() + 50000); sts32(mbar + MB_TK + 4, p.c3 + p.extra); sts32(mbar + MB_TAB + 4, L); sts32(mbar + MB_TAB + 8, L * 1000);
      mbar_expect(mbar + MB_IA, L ? 0 : 163840); mbar_expect(mbar + MB_IC, r == 2 ? 32768 : 65536);
    }
    const int v = bid + p.helper * 96;
    const bool prep = L == 0 && v >= 86;
    if (prep && v < 118 && tid == 0) {
      mbar_expect(mbar + 8, 2 * 41088);
      bulk_g2s(sb + SM_WS, p.wr + (v - 86) * 64 * 321, 41088, mbar + 8); bulk_g2s(sb + SM_WS + 41088, p.wi + (v - 86) * 64 * 321, 41088, mbar + 8);
    }
    __syncwarp();
    a_layer(p.a[L], smem + SM_WST, v, w, [&](int u) {
        if (u == -1 && prep) {
          const int o = (v - 86) * 384 + tid, pg = 160 + ((o >> 8) & 15) + ((o >> 12) & 1) * 64 + (o >> 13) * 256;
          const uint32_t c = (pg & 2) ? 0u : ~0u;
          if (o < 64 * 256) stg128((uint4*)p.comm + pg * 256 + (o & 255), c, c, c, c);
          if (v < 118) { mbar_wait(mbar + 8, 0); filter_prep((uint32_t*)p.a[0].WT, sb + SM_WS, v - 86); }
          asm volatile("fence.proxy.async.shared::cta;" ::: "memory");
          TL(20);
          __syncthreads();
        }
        if (u == 0 && prep && tid == 256) { red_release(p.a[0].sync + SY_W); TL(21); }
        auto w_load = [&](int i) {
          asm volatile(ELECT "@p cp.async.bulk.tensor.2d.shared::cluster.global.mbarrier::complete_tx::bytes [%0], [%1, {%3, %4}], [%2];}"
            :: "r"(sb + SM_WS + ((0x3102 >> (4 * (i & 3))) & 3) * 40960 + (i >> 2) * 8192), "l"(&p.tmW[r == 2 ? 2 : i & 1]), "r"(mbar + MB_IA), "r"(h * 128 + (r == 2 ? i & 1 : r) * 64), "r"((i & 2) * 160 + (i >> 2) * 64) : "memory");
        };
        const int b0 = (WPLAN >> (4 * u + 4)) & 15, n = ((WPLAN >> (4 * u + 8)) & 15) - b0;
        if (n > 0 && w + L * 12 + p.helper * 12 < 4 * n) w_load(4 * b0 + w);
        if (u == OPF && w < 4 && r + p.helper * 2 < 2)
          asm volatile(ELECT "@p cp.async.bulk.prefetch.tensor.2d.L2.global [%0, {%1, %2}];}" :: "l"(&p.tmWo), "r"(r * 256 + 128 + (w >> 1) * 64), "r"(h * 128 + (w & 1) * 64) : "memory");
        if (u == 4 && w == 4 && !p.helper) wo_load(p, sb, h, r, 0);
      });
    if (p.helper) {
      return;
    }
    __syncwarp();
    }
    L = __shfl_sync(~0u, lds32(mbar + MB_TAB + 4), 0);
    const int w = __shfl_sync(~0u, tid >> 5, 0), bid = blockIdx.x + (L & p.zero), h = bid / 3, r = bid % 3;
    if (w < 8) {
      asm volatile("setmaxnreg.inc.sync.aligned.u32 216;");
      if (r < 2) rec_gemm_warps<false>(p, sb, h, r, L, w); else rec_gemm_warps<true>(p, sb, h, r, L, w);
      asm volatile("setmaxnreg.dec.sync.aligned.u32 168;");
    } else {
      asm volatile("setmaxnreg.dec.sync.aligned.u32 72;");
      const int side = rec_attn_setup(p, sb, h, r, L, w - 8);
      rec_attn_warps(p, sb, smem, h, r, side, L, w - 8);
      asm volatile("setmaxnreg.inc.sync.aligned.u32 168;");
    }
    asm volatile("barrier.cluster.arrive.relaxed.aligned; barrier.cluster.wait.aligned;" ::: "memory");
    L = __shfl_sync(~0u, lds32(mbar + MB_TAB + 4), 0);
    if (tid < 32) TL_DUMP(L * 166 + blockIdx.x, tid);
    __syncthreads();
  }
}

constexpr int PERIOD = 1984, C3 = 480, SLACK = 768, XLATE = 64, GAP = 128;
static int PH[9] = {256, 704, 3, 1280, 96, 62, 5600, 60, 768};
__device__ __align__(128) uint32_t g_Z1[96 * 7680], g_ZT[640 * 1024];
__device__ __align__(128) uint32_t g_WT[321 * 2048];
__device__ bf16 g_x1[S_ * D_], g_x2[S_ * D_], g_hN[S_ * D_];
__device__ __align__(128) uint4 g_QKV[QRING * 32 * 30720 / 16], g_O[ORING * 32 * 8192 / 16];
__device__ __align__(128) uint4 g_part[PRING * 32 * 8960 / 16];
__device__ __align__(128) uint32_t g_sync[256];
__device__ uint32_t g_comm[(4 << 20) / 4];

typedef CUresult (*EncodeFn)(CUtensorMap*, CUtensorMapDataType, cuuint32_t, void*, const cuuint64_t*, const cuuint64_t*, const cuuint32_t*, const cuuint32_t*,
                             CUtensorMapInterleave, CUtensorMapSwizzle, CUtensorMapL2promotion, CUtensorMapFloatOOBfill);
static void make_map(EncodeFn fn, CUtensorMap* m, const void* base, uint64_t cols, uint64_t rows, uint32_t bc, uint32_t br) {
  cuuint64_t dims[2] = {cols, rows}, strides[1] = {cols * 2}; cuuint32_t box[2] = {bc, br}, es[2] = {1, 1};
  fn(m, CU_TENSOR_MAP_DATA_TYPE_BFLOAT16, 2, (void*)base, dims, strides, box, es, CU_TENSOR_MAP_INTERLEAVE_NONE, CU_TENSOR_MAP_SWIZZLE_128B, CU_TENSOR_MAP_L2_PROMOTION_L2_256B, CU_TENSOR_MAP_FLOAT_OOB_FILL_NONE);
}
template <typename T> static T* sym(T& s) { void* p; cudaGetSymbolAddress(&p, s); return (T*)p; }

template <typename... KA, typename... A> static void launch(void (*k)(KA...), int grid, int block, int smem, bool pdl, int cluster, A... a) {
  cudaLaunchConfig_t cfg = {};
  cfg.gridDim = dim3(grid); cfg.blockDim = dim3(block); cfg.dynamicSmemBytes = smem; cfg.stream = cudaStreamPerThread;
  cudaLaunchAttribute at[2]; int n = 0;
  if (pdl) { at[n].id = cudaLaunchAttributeProgrammaticStreamSerialization; at[n].val.programmaticStreamSerializationAllowed = 1; n++; }
  if (cluster > 1) { at[n].id = cudaLaunchAttributeClusterDimension; at[n].val.clusterDim.x = cluster; at[n].val.clusterDim.y = 1; at[n].val.clusterDim.z = 1; n++; }
  cfg.attrs = at; cfg.numAttrs = n;
  cudaLaunchKernelEx(&cfg, k, KA(a)...);
}

extern "C" void kernel_launch(void* const* d_in, const int* in_sizes, int n_in, void* d_out, int out_size) {
  const bf16 *x = (const bf16*)d_in[0], *wr = (const bf16*)d_in[1], *wi = (const bf16*)d_in[2], *mem0 = (const bf16*)d_in[4];
  const bf16 *Wq = (const bf16*)d_in[5], *Wk = (const bf16*)d_in[6], *Wv = (const bf16*)d_in[7], *Wo = (const bf16*)d_in[8];
  bf16* out = (bf16*)d_out;
  uint32_t *Z1 = (uint32_t*)sym(g_Z1), *ZT = (uint32_t*)sym(g_ZT), *WT = (uint32_t*)sym(g_WT);
  bf16 *x1 = (bf16*)sym(g_x1), *x2 = (bf16*)sym(g_x2), *hN = (bf16*)sym(g_hN);
  char *QKV = (char*)sym(g_QKV), *part = (char*)sym(g_part);
  uint32_t* comm = (uint32_t*)(((uint64_t)sym(g_comm) + (2 << 20) - 1) & ~(uint64_t)((2 << 20) - 1));
  EncodeFn enc = nullptr; cudaDriverEntryPointQueryResult qr;
  cudaGetDriverEntryPoint("cuTensorMapEncodeTiled", (void**)&enc, cudaEnableDefault, &qr);
  CUtensorMap tmW[3], tmWo, tmX, tmP;
  { cuuint64_t dims[3] = {64, PRING * 32, 70}, strides[2] = {8960, 128}; cuuint32_t box[3] = {64, 32, 2}, es[3] = {1, 1, 1};
    enc(&tmP, CU_TENSOR_MAP_DATA_TYPE_BFLOAT16, 3, part, dims, strides, box, es, CU_TENSOR_MAP_INTERLEAVE_NONE, CU_TENSOR_MAP_SWIZZLE_128B, CU_TENSOR_MAP_L2_PROMOTION_NONE, CU_TENSOR_MAP_FLOAT_OOB_FILL_NONE); }
  { cuuint64_t dims[3] = {64, 2048, 10}, strides[2] = {1280, 128}; cuuint32_t box[3] = {64, 32, 10}, es[3] = {1, 1, 1};
    enc(&tmX, CU_TENSOR_MAP_DATA_TYPE_BFLOAT16, 3, hN, dims, strides, box, es, CU_TENSOR_MAP_INTERLEAVE_NONE, CU_TENSOR_MAP_SWIZZLE_128B, CU_TENSOR_MAP_L2_PROMOTION_L2_256B, CU_TENSOR_MAP_FLOAT_OOB_FILL_NONE); }
  make_map(enc, &tmW[0], Wq, 4096, 640, 64, 64); make_map(enc, &tmW[1], Wk, 4096, 640, 64, 64); make_map(enc, &tmW[2], Wv, 4096, 640, 64, 64);
  make_map(enc, &tmWo, Wo, 640, 4096, 64, 64);
  int dbgf = 0;
  cudaFuncSetAttribute(side_kernel, cudaFuncAttributeMaxDynamicSharedMemorySize, SD_SMEM);
  cudaFuncSetAttribute(rec_kernel, cudaFuncAttributeMaxDynamicSharedMemorySize, REC_SMEM);
  uint32_t* sy = (uint32_t*)sym(g_sync);
  RecParams rp = {{tmW[0], tmW[1], tmW[2]}, tmWo, tmX, {{x, Z1, ZT, WT, x1, hN, sy, nullptr, 45, 1}, {x2, Z1, ZT, WT, x1, hN, sy + 128, (dbgf & 16) ? nullptr : comm + FL_ROW, 0, 0}},
                  mem0, wr, wi, QKV, comm, 0x4000004000010000ull, PERIOD, C3, SLACK, XLATE, PH[4], PH[6], GAP, 0, 0, 0, dbgf, nullptr, nullptr};
  launch(rec_kernel, 96, 384, REC_SMEM, false, 3, rp);
  for (int L = 0; L < 2; L++) {
    rp.helper = 1; rp.layer = L;
    launch(rec_kernel, 35, 384, REC_SMEM, true, 1, rp);
    SideParams sp = {tmWo, tmP, QKV, (char*)sym(g_O), part, x1, L == 0 ? x2 : out, comm + L * 1024, sy + L * 128, rp.dhi, L == 0, rp.period, PH[0], PH[1], PH[2], PH[3], PH[5], PH[7], PH[8], dbgf};
    launch(side_kernel, 36, 512, SD_SMEM, true, 1, sp);
  }
}
```

```cpp
#include <cuda_runtime.h>
#include <cuda_bf16.h>
#include <cuda.h>
#include <stdint.h>
typedef __nv_bfloat16 bf16;
constexpr int S_ = 2048, D_ = 640, H_ = 32, DH = 128, NSEG = 64;

__device__ __forceinline__ uint32_t smem_u32(const void* p) { return (uint32_t)__cvta_generic_to_shared(p); }
__device__ __forceinline__ uint32_t pack_bf16(float lo, float hi) { uint32_t r; asm("cvt.rn.bf16x2.f32 %0, %1, %2;" : "=r"(r) : "f"(hi), "f"(lo)); return r; }
__device__ __forceinline__ float bf_lo(uint32_t v) { return __uint_as_float(v << 16); }
__device__ __forceinline__ float bf_hi(uint32_t v) { return __uint_as_float(v & 0xFFFF0000u); }
__device__ __forceinline__ void ldsm4t(uint32_t& r0, uint32_t& r1, uint32_t& r2, uint32_t& r3, uint32_t a) {
  asm volatile("ldmatrix.sync.aligned.m8n8.x4.trans.shared.b16 {%0,%1,%2,%3}, [%4];" : "=r"(r0), "=r"(r1), "=r"(r2), "=r"(r3) : "r"(a) : "memory");
}
__device__ __forceinline__ void ldsm4(uint32_t& r0, uint32_t& r1, uint32_t& r2, uint32_t& r3, uint32_t a) {
  asm volatile("ldmatrix.sync.aligned.m8n8.x4.shared.b16 {%0,%1,%2,%3}, [%4];" : "=r"(r0), "=r"(r1), "=r"(r2), "=r"(r3) : "r"(a) : "memory");
}
__device__ __forceinline__ void mma16816(float* d, uint32_t a0, uint32_t a1, uint32_t a2, uint32_t a3, uint32_t b0, uint32_t b1) {
  asm volatile("mma.sync.aligned.m16n8k16.row.col.f32.bf16.bf16.f32 {%0,%1,%2,%3}, {%4,%5,%6,%7}, {%8,%9}, {%0,%1,%2,%3};"
    : "+f"(d[0]), "+f"(d[1]), "+f"(d[2]), "+f"(d[3]) : "r"(a0), "r"(a1), "r"(a2), "r"(a3), "r"(b0), "r"(b1));
}
__device__ __forceinline__ void mma16816z(float* d, uint32_t a0, uint32_t a1, uint32_t a2, uint32_t a3, uint32_t b0, uint32_t b1) {
  asm volatile("mma.sync.aligned.m16n8k16.row.col.f32.bf16.bf16.f32 {%0,%1,%2,%3}, {%4,%5,%6,%7}, {%8,%9}, {%10,%10,%10,%10};"
    : "=f"(d[0]), "=f"(d[1]), "=f"(d[2]), "=f"(d[3]) : "r"(a0), "r"(a1), "r"(a2), "r"(a3), "r"(b0), "r"(b1), "f"(0.f));
}
__device__ __forceinline__ void mma1688z(float* d, uint32_t a0, uint32_t a1, uint32_t b0) {
  asm volatile("mma.sync.aligned.m16n8k8.row.col.f32.bf16.bf16.f32 {%0,%1,%2,%3}, {%4,%5}, {%6}, {%7,%7,%7,%7};"
    : "=f"(d[0]), "=f"(d[1]), "=f"(d[2]), "=f"(d[3]) : "r"(a0), "r"(a1), "r"(b0), "f"(0.f));
}
__device__ __forceinline__ void mma1688(float* d, uint32_t a0, uint32_t a1, uint32_t b0) {
  asm volatile("mma.sync.aligned.m16n8k8.row.col.f32.bf16.bf16.f32 {%0,%1,%2,%3}, {%4,%5}, {%6}, {%0,%1,%2,%3};"
    : "+f"(d[0]), "+f"(d[1]), "+f"(d[2]), "+f"(d[3]) : "r"(a0), "r"(a1), "r"(b0));
}
__device__ __forceinline__ void mmaA(float* d, const uint32_t* a, uint32_t b0, uint32_t b1) { mma16816(d, a[0], a[1], a[2], a[3], b0, b1); }
__device__ __forceinline__ void mmaZ(float* d, const uint32_t* a, uint32_t b0, uint32_t b1) { mma16816z(d, a[0], a[1], a[2], a[3], b0, b1); }
__device__ __forceinline__ uint32_t movm(uint32_t a) { uint32_t d; asm volatile("movmatrix.sync.aligned.m8n8.trans.b16 %0, %1;" : "=r"(d) : "r"(a)); return d; }
__device__ __forceinline__ void cp_async16(uint32_t dst, const void* src) { asm volatile("cp.async.cg.shared.global [%0], [%1], 16;" :: "r"(dst), "l"(src) : "memory"); }
__device__ __forceinline__ void cp_commit() { asm volatile("cp.async.commit_group;" ::: "memory"); }
template <int N> __device__ __forceinline__ void cp_wait() { asm volatile("cp.async.wait_group %0;" :: "n"(N) : "memory"); }
__device__ __forceinline__ void lds128(uint32_t* r, uint32_t a) { asm volatile("ld.shared.v4.b32 {%0,%1,%2,%3}, [%4];" : "=r"(r[0]), "=r"(r[1]), "=r"(r[2]), "=r"(r[3]) : "r"(a) : "memory"); }
__device__ __forceinline__ void sts128(uint32_t a, uint32_t r0, uint32_t r1, uint32_t r2, uint32_t r3) { asm volatile("st.shared.v4.b32 [%0], {%1,%2,%3,%4};" :: "r"(a), "r"(r0), "r"(r1), "r"(r2), "r"(r3) : "memory"); }
__device__ __forceinline__ void stg128(void* p, uint32_t r0, uint32_t r1, uint32_t r2, uint32_t r3) { asm volatile("st.global.v4.b32 [%0], {%1,%2,%3,%4};" :: "l"(p), "r"(r0), "r"(r1), "r"(r2), "r"(r3) : "memory"); }
template <int ID, int N> __device__ __forceinline__ void bar_sync() { asm volatile("bar.sync %0, %1;" :: "n"(ID), "n"(N) : "memory"); }
template <int ID, int N> __device__ __forceinline__ void bar_arrive() { asm volatile("bar.arrive %0, %1;" :: "n"(ID), "n"(N) : "memory"); }
__device__ __forceinline__ void mbar_wait(uint32_t bar, uint32_t parity) {
  asm volatile("{\n.reg .pred p, pq;\n.reg .u32 n;\nmov.u32 n, 0;\nLW%=:\nmbarrier.try_wait.parity.shared::cta.b64 p, [%0], %1;\n@p bra.uni LD%=;\nadd.u32 n, n, 1;\nsetp.lt.u32 pq, n, 1000000;\n@pq bra.uni LW%=;\nLD%=:\n}" :: "r"(bar), "r"(parity) : "memory");
}
#define mbar_wait_long mbar_wait
__device__ __forceinline__ void mbar_init(uint32_t bar, int n) { asm volatile("mbarrier.init.shared.b64 [%0], %1;" :: "r"(bar), "r"(n) : "memory"); }
__device__ __forceinline__ void mbar_expect(uint32_t bar, int bytes) { asm volatile("mbarrier.arrive.expect_tx.shared.b64 _, [%0], %1;" :: "r"(bar), "r"(bytes) : "memory"); }
__device__ __forceinline__ void mbar_arrive(uint32_t bar) { asm volatile("mbarrier.arrive.shared.b64 _, [%0];" :: "r"(bar) : "memory"); }
__device__ __forceinline__ void l2_prefetch(const void* p, int bytes) { asm volatile("cp.async.bulk.prefetch.L2.global [%0], %1;" :: "l"(p), "r"(bytes) : "memory"); }
__device__ __forceinline__ float ex2(float x) { float y; asm("ex2.approx.ftz.f32 %0, %1;" : "=f"(y) : "f"(x)); return y; }
__device__ __forceinline__ void pdl_wait() { asm volatile("griddepcontrol.wait;" ::: "memory"); }
__device__ __forceinline__ void pdl_launch() { asm volatile("griddepcontrol.launch_dependents;" ::: "memory"); }
__device__ __forceinline__ uint32_t hadd2(uint32_t a, uint32_t b) { uint32_t r; asm("add.rn.bf16x2 %0, %1, %2;" : "=r"(r) : "r"(a), "r"(b)); return r; }
__device__ __forceinline__ void sched_fence() { asm volatile("{\n.reg .pred p;\n.reg .u32 t;\nLF%=:\nmov.u32 t, %%clock;\nsetp.eq.u32 p, t, %0;\n@p bra.uni LF%=;\n}" :: "n"(12345) : "memory"); }
#define TL(k)
#define TL_DUMP(slot, t)

constexpr int TB_F16 = 0, TB_640 = 64, TB_F40 = 384, TB_F32 = 784, TB_512 = 1040, TB_2048 = 1296;
__device__ __align__(128) const uint32_t g_tab[6208] = {
0x3f803f80,0xbf803f80,0x3f803f80,0xbf803f80,0x3f803f80,0xbf803f80,0x3f803f80,0xbf803f80,0x3f803f80,0xbf803f80,0x3f803f80,0xbf803f80,0x3f803f80,0xbf803f80,0x3f803f80,0xbf803f80,
0x3f6d3f80,0xbf6d3f80,0xbf6dbf80,0x3f6dbf80,0x3ec43f35,0xbec43f35,0xbec4bf35,0x3ec4bf35,0xbec40000,0x3ec40000,0x3ec40000,0xbec40000,0xbf6dbf35,0x3f6dbf35,0x3f6d3f35,0xbf6d3f35,
0x3f353f80,0xbf353f80,0x3f353f80,0xbf353f80,0xbf350000,0x3f350000,0xbf350000,0x3f350000,0xbf35bf80,0x3f35bf80,0xbf35bf80,0x3f35bf80,0x3f350000,0xbf350000,0x3f350000,0xbf350000,
0x3ec43f80,0xbec43f80,0xbec4bf80,0x3ec4bf80,0xbf6dbf35,0x3f6dbf35,0x3f6d3f35,0xbf6d3f35,0x3f6d0000,0xbf6d0000,0xbf6d0000,0x3f6d0000,0xbec43f35,0x3ec43f35,0x3ec4bf35,0xbec4bf35,
0x3f80,0x3f80,0x3f80,0x3f80,0xbf80,0xbf80,0xbf80,0xbf80,0x3f80,0x3f80,0x3f80,0x3f80,0xbf80,0xbf80,0xbf80,0xbf80,
0xbec43f80,0x3ec43f80,0x3ec4bf80,0xbec4bf80,0x3f6dbf35,0xbf6dbf35,0xbf6d3f35,0x3f6d3f35,0xbf6d0000,0x3f6d0000,0x3f6d0000,0xbf6d0000,0x3ec43f35,0xbec43f35,0xbec4bf35,0x3ec4bf35,
0xbf353f80,0x3f353f80,0xbf353f80,0x3f353f80,0x3f350000,0xbf350000,0x3f350000,0xbf350000,0x3f35bf80,0xbf35bf80,0x3f35bf80,0xbf35bf80,0xbf350000,0x3f350000,0xbf350000,0x3f350000,
0xbf6d3f80,0x3f6d3f80,0x3f6dbf80,0xbf6dbf80,0xbec43f35,0x3ec43f35,0x3ec4bf35,0xbec4bf35,0x3ec40000,0xbec40000,0xbec40000,0x3ec40000,0x3f6dbf35,0xbf6dbf35,0xbf6d3f35,0x3f6d3f35,
0x80008000,0x80008000,0x80008000,0x80008000,0x80008000,0x80008000,0x80008000,0x80008000,0x80008000,0x80008000,0x80008000,0x80008000,0x80008000,0x80008000,0x80008000,0x80008000,
0xbec48000,0x3ec48000,0x3ec48000,0xbec48000,0xbf6dbf35,0x3f6dbf35,0x3f6d3f35,0xbf6d3f35,0xbf6dbf80,0x3f6dbf80,0x3f6d3f80,0xbf6d3f80,0xbec4bf35,0x3ec4bf35,0x3ec43f35,0xbec43f35,
0xbf358000,0x3f358000,0xbf358000,0x3f358000,0xbf35bf80,0x3f35bf80,0xbf35bf80,0x3f35bf80,0x3f358000,0xbf358000,0x3f358000,0xbf358000,0x3f353f80,0xbf353f80,0x3f353f80,0xbf353f80,
0xbf6d8000,0x3f6d8000,0x3f6d8000,0xbf6d8000,0x3ec4bf35,0xbec4bf35,0xbec43f35,0x3ec43f35,0x3ec43f80,0xbec43f80,0xbec4bf80,0x3ec4bf80,0xbf6dbf35,0x3f6dbf35,0x3f6d3f35,0xbf6d3f35,
0xbf808000,0x3f808000,0xbf808000,0x3f808000,0x3f808000,0xbf808000,0x3f808000,0xbf808000,0xbf808000,0x3f808000,0xbf808000,0x3f808000,0x3f808000,0xbf808000,0x3f808000,0xbf808000,
0xbf6d8000,0x3f6d8000,0x3f6d8000,0xbf6d8000,0x3ec43f35,0xbec43f35,0xbec4bf35,0x3ec4bf35,0x3ec4bf80,0xbec4bf80,0xbec43f80,0x3ec43f80,0xbf6d3f35,0x3f6d3f35,0x3f6dbf35,0xbf6dbf35,
0xbf358000,0x3f358000,0xbf358000,0x3f358000,0xbf353f80,0x3f353f80,0xbf353f80,0x3f353f80,0x3f358000,0xbf358000,0x3f358000,0xbf358000,0x3f35bf80,0xbf35bf80,0x3f35bf80,0xbf35bf80,
0xbec48000,0x3ec48000,0x3ec48000,0xbec48000,0xbf6d3f35,0x3f6d3f35,0x3f6dbf35,0xbf6dbf35,0xbf6d3f80,0x3f6d3f80,0x3f6dbf80,0xbf6dbf80,0xbec43f35,0x3ec43f35,0x3ec4bf35,0xbec4bf35,
0x3f800000,0x3f800000,0x3f800000,0x3f7f35f9,0x3f800000,0x3f800000,0x3f7cd925,0x3f78ed3c,0x3f800000,0x3f800000,0x3f737871,0x3f6c835e,0x3f800000,0x3f800000,0x3f641901,0x3f5a46a0,
0x3f800000,0x3f7ffcd7,0x3f800000,0x3f7f0059,0x3f7ff35e,0x3f7fe394,0x3f7c0361,0x3f770f11,0x3f7fcd79,0x3f7fb10f,0x3f702d4f,0x3f676bd8,0x3f7f8e56,0x3f7f654e,0x3f5cdc29,0x3f50935b,
0x3f800000,0x3f7ff35e,0x3f800000,0x3f7ec46d,0x3f7fcd79,0x3f7f8e56,0x3f7b14be,0x3f74fa0b,0x3f7f35f9,0x3f7ec46d,0x3f6c835e,0x3f61c598,0x3f7e39bc,0x3f7d95f4,0x3f54db31,0x3f45e403,
0x3f800000,0x3f7fe394,0x3f800000,0x3f7e8238,0x3f7f8e56,0x3f7f0059,0x3f7a0d54,0x3f72ae9e,0x3f7e39bc,0x3f7d3aac,0x3f687c12,0x3f5b941a,0x3f7c0361,0x3f7a9421,0x3f4c1d35,0x3f3a4582,
0x3f800000,0x3f7fcd79,0x3f800000,0x3f7e39bc,0x3f7f35f9,0x3f7e39bc,0x3f78ed3c,0x3f702d4f,0x3f7cd925,0x3f7b14be,0x3f641901,0x3f54db31,0x3f78ed3c,0x3f766377,0x3f42a9f7,0x3f2dc5e3,
0x3f800000,0x3f7fb10f,0x3f800000,0x3f7deafa,0x3f7ec46d,0x3f7d3aac,0x3f77b493,0x3f6d76aa,0x3f7b14be,0x3f7853f8,0x3f5f5be6,0x3f4d9f02,0x3f74fa0b,0x3f710908,0x3f3889dc,0x3f207440,
0x3f800000,0x3f7f8e56,0x3f800000,0x3f7d95f4,0x3f7e39bc,0x3f7c0361,0x3f766377,0x3f6a8b4b,0x3f78ed3c,0x3f74fa0b,0x3f5a46a0,0x3f45e403,0x3f702d4f,0x3f6a8b4b,0x3f2dc5e3,0x3f1260b2,
0x3f800000,0x3f7f654e,0x3f800000,0x3f7d3aac,0x3f7d95f4,0x3f7a9421,0x3f74fa0b,0x3f676bd8,0x3f766377,0x3f710908,0x3f54db31,0x3f3daef9,0x3f6a8b4b,0x3f62f219,0x3f226799,0x3f039c3d,
0x3f800000,0x3f800000,0x3f4f1bbd,0x3f42a9f7,0x3f800000,0x3f800000,0x3f3504f3,0x3f26423a,0x3f800000,0x3f800000,0x3f167918,0x3f05c277,0x3f800000,0x3f800000,0x3ee87171,0x3ec3ef15,
0x3f7f35f9,0x3f7f0059,0x3f42a9f7,0x3f333bc6,0x3f7ec46d,0x3f7e8238,0x3f226799,0x3f104f0e,0x3f7e39bc,0x3f7deafa,0x3efa2c90,0x3ed1c759,0x3f7d95f4,0x3f7d3aac,0x3ea7bf25,0x3e78cfcc,
0x3f7cd925,0x3f7c0361,0x3f3504f3,0x3f226799,0x3f7b14be,0x3f7a0d54,0x3f0e39da,0x3ef15aea,0x3f78ed3c,0x3f77b493,0x3ec3ef15,0x3e94a031,0x3f766377,0x3f74fa0b,0x3e47c5c2,0x3dc8bd36,
0x3f78ed3c,0x3f770f11,0x3f26423a,0x3f104f0e,0x3f74fa0b,0x3f72ae9e,0x3ef15aea,0x3ebf47d7,0x3f702d4f,0x3f6d76aa,0x3e8afa3e,0x3e2a1c3f,0x3f6a8b4b,0x3f676bd8,0x3d712283,0xbd48fb30,
0x3f737871,0x3f702d4f,0x3f167918,0x3efa2c90,0x3f6c835e,0x3f687c12,0x3ec3ef15,0x3e8afa3e,0x3f641901,0x3f5f5be6,0x3e20305b,0x3d20cee7,0x3f5a46a0,0x3f54db31,0xbda0af2a,0xbe47c5c2,
0x3f6c835e,0x3f676bd8,0x3f05c277,0x3ed1c759,0x3f61c598,0x3f5b941a,0x3e94a031,0x3e2a1c3f,0x3f54db31,0x3f4d9f02,0x3d20cee7,0xbdb4b86a,0x3f45e403,0x3f3daef9,0xbe5b73dc,0xbeac7cd4,
0x3f641901,0x3f5cdc29,0x3ee87171,0x3ea7bf25,0x3f54db31,0x3f4c1d35,0x3e47c5c2,0x3d712283,0x3f42a9f7,0x3f3889dc,0xbda0af2a,0xbe5b73dc,0x3f2dc5e3,0x3f226799,0xbeb13641,0xbef15aea,
0x3f5a46a0,0x3f50935b,0x3ec3ef15,0x3e78cfcc,0x3f45e403,0x3f3a4582,0x3dc8bd36,0xbd48fb30,0x3f2dc5e3,0x3f207440,0xbe47c5c2,0xbeac7cd4,0x3f1260b2,0x3f039c3d,0xbef15aea,0xbf187fc0,
0x3f800000,0x3f800000,0x3e9e377a,0x3e6f0c4d,0x3f800000,0x3f800000,0x3e20305b,0x3da0af2a,0x3f800000,0x3f800000,0,0xbda0af2a,0x3f800000,0x3f800000,0xbe20305b,0xbe6f0c4d,
0x3f7cd925,0x3f7c7160,0x3e20305b,0x3d8ca1f2,0x3f7c0361,0x3f7b8f2a,0xbca0d6d6,0xbddcbd0d,0x3f7b14be,0x3f7a9421,0xbe47c5c2,0xbe8fcefe,0x3f7a0d54,0x3f79805c,0xbeba9be1,0xbee3f40d,
0x3f737871,0x3f71decf,0,0xbdc8bd36,0x3f702d4f,0x3f6e641a,0xbe47c5c2,0xbe94a031,0x3f6c835e,0x3f6a8b4b,0xbec3ef15,0xbef15aea,0x3f687c12,0x3f6655e7,0xbf0e39da,0xbf226799,
0x3f641901,0x3f609384,0xbe20305b,0xbe862210,0x3f5cdc29,0x3f58f3c4,0xbeba9be1,0xbeece91a,0x3f54db31,0x3f50935b,0xbf0e39da,0xbf2456f1,0x3f4c1d35,0x3f4779bc,0xbf3889dc,0xbf4a965e,
0x3f4f1bbd,0x3f490a88,0xbe9e377a,0xbed65a92,0x3f42a9f7,0x3f3bfc8f,0xbf05c277,0xbf1e7cf1,0x3f3504f3,0x3f2dc5e3,0xbf3504f3,0xbf490a88,0x3f26423a,0x3f1e7cf1,0xbf5a46a0,0xbf687c12,
0x3f3504f3,0x3f2beb4a,0xbee87171,0xbf104f0e,0x3f226799,0x3f187fc0,0xbf2a0c73,0xbf4105b8,0x3f0e39da,0x3f039c3d,0xbf54db31,0xbf653a48,0x3ef15aea,0x3edae880,0xbf71decf,0xbf7a9421,
0x3f167918,0x3f0a04f8,0xbf167918,0xbf316e2c,0x3efa2c90,0x3edf7108,0xbf490a88,0xbf5cdc29,0x3ec3ef15,0x3ea7bf25,0xbf6c835e,0xbf77b493,0x3e8afa3e,0x3e5b73dc,0xbf7e39bc,0xbf7ff35e,
0x3ee87171,0x3ec8917e,0xbf3504f3,0xbf4d9f02,0x3ea7bf25,0x3e862210,0xbf61c598,0xbf710908,0x3e47c5c2,0x3e0255f4,0xbf7b14be,0xbf7fb10f,0x3d712283,0xbc20d8d2,0xbf7ec46d,0xbf7853f8,
0x3f800000,0x3f800000,0xbe9e377a,0xbec3ef15,0x3f800000,0x3f800000,0xbee87171,0xbf05c277,0x3f800000,0x3f800000,0xbf167918,0xbf26423a,0x3f800000,0x3f800000,0xbf3504f3,0xbf42a9f7,
0x3f78ed3c,0x3f7853f8,0xbf05c277,0xbf187fc0,0x3f77b493,0x3f770f11,0xbf2a0c73,0xbf3a4582,0x3f766377,0x3f75b1c9,0xbf490a88,0xbf563e03,0x3f74fa0b,0x3f743c41,0xbf61c598,0xbf6b8a3d,
0x3f641901,0x3f61c598,0xbf3504f3,0xbf45e403,0x3f5f5be6,0x3f5cdc29,0xbf54db31,0xbf61c598,0x3f5a46a0,0x3f579b8c,0xbf6c835e,0xbf74fa0b,0x3f54db31,0x3f5205d4,0xbf7b14be,0xbf7ec46d,
0x3f42a9f7,0x3f3daef9,0xbf5a46a0,0xbf676bd8,0x3f3889dc,0x3f333bc6,0xbf71decf,0xbf79805c,0x3f2dc5e3,0x3f28296a,0xbf7e39bc,0xbf7ffcd7,0x3f226799,0x3f1c81b9,0xbf7ec46d,0xbf7a9421,
0x3f167918,0x3f0e39da,0xbf737871,0xbf7b14be,0x3f05c277,0x3efa2c90,0xbf7f35f9,0xbf7fcd79,0x3ee87171,0x3ed65a92,0xbf7cd925,0xbf766377,0x3ec3ef15,0x3eb13641,0xbf6c835e,0xbf5f5be6,
0x3ec3ef15,0x3eac7cd4,0xbf7f35f9,0xbf7fb10f,0x3e94a031,0x3e78cfcc,0xbf7c0361,0xbf743c41,0x3e47c5c2,0x3e164083,0xbf687c12,0xbf58f3c4,0x3dc8bd36,0x3d48fb30,0xbf45e403,0xbf2f9c32,
0x3e20305b,0x3dc8bd36,0xbf7cd925,0xbf74fa0b,0x3d20cee7,0xbca0d6d6,0xbf687c12,0xbf579b8c,0xbda0af2a,0xbe0c4cf7,0xbf42a9f7,0xbf2a0c73,0xbe47c5c2,0xbe814693,0xbf0e39da,0xbedf7108,
0xbda0af2a,0xbe164083,0xbf6c835e,0xbf5b941a,0xbe5b73dc,0xbe8fcefe,0xbf45e403,0xbf2beb4a,0xbeb13641,0xbed1c759,0xbf0e39da,0xbedae880,0xbef15aea,0xbf07e565,0xbe94a031,0xbe164083,
0x3f800000,0x3f800000,0xbf4f1bbd,0xbf5a46a0,0x3f800000,0x3f800000,0xbf641901,0xbf6c835e,0x3f800000,0x3f800000,0xbf737871,0xbf78ed3c,0x3f800000,0x3f800000,0xbf7cd925,0xbf7f35f9,
0x3f737871,0x3f72ae9e,0xbf737871,0xbf79805c,0x3f71decf,0x3f710908,0xbf7d95f4,0xbf7fb10f,0x3f702d4f,0x3f6f4ba8,0xbf7fcd79,0xbf7deafa,0x3f6e641a,0x3f6d76aa,0xbf7a0d54,0xbf743c41,
0x3f4f1bbd,0x3f4c1d35,0xbf800000,0xbf7ec46d,0x3f490a88,0x3f45e403,0xbf7b14be,0xbf74fa0b,0x3f42a9f7,0x3f3f5cb5,0xbf6c835e,0xbf61c598,0x3f3bfc8f,0x3f3889dc,0xbf54db31,0xbf45e403,
0x3f167918,0x3f104f0e,0xbf737871,0xbf698690,0x3f0a04f8,0x3f039c3d,0xbf5cdc29,0xbf4d9f02,0x3efa2c90,0x3eece91a,0xbf3bfc8f,0xbf28296a,0x3edf7108,0x3ed1c759,0xbf1260b2,0xbef5c6c5,
0x3e9e377a,0x3e8afa3e,0xbf4f1bbd,0xbf3bfc8f,0x3e6f0c4d,0x3e47c5c2,0xbf26423a,0xbf0e39da,0x3e20305b,0x3df0b772,0xbee87171,0xbeb13641,0x3da0af2a,0x3d20cee7,0xbe6f0c4d,0xbdf0b772,
0,0xbd48fb30,0xbf167918,0xbef5c6c5,0xbdc8bd36,0xbe164083,0xbeba9be1,0xbe78cfcc,0xbe47c5c2,0xbe78cfcc,0xbdf0b772,0x3c20d8d2,0xbe94a031,0xbeac7cd4,0x3e0c4cf7,0x3e862210,
0xbe9e377a,0xbeba9be1,0xbe9e377a,0xbe3403f1,0xbed65a92,0xbef15aea,0xbd20cee7,0x3dc8bd36,0xbf05c277,0xbf1260b2,0x3e6f0c4d,0x3eba9be1,0xbf1e7cf1,0xbf2a0c73,0x3efa2c90,0x3f1a82a4,
0xbf167918,0xbf2456f1,0,0x3e164083,0xbf316e2c,0xbf3daef9,0x3e94a031,0x3edae880,0xbf490a88,0xbf53731f,0x3f0e39da,0x3f2beb4a,0xbf5cdc29,0xbf653a48,0x3f45e403,0x3f5b941a,
0x80000000,0x80000000,0x80000000,0xbda0af2a,0x80000000,0x80000000,0xbe20305b,0xbe6f0c4d,0x80000000,0x80000000,0xbe9e377a,0xbec3ef15,0x80000000,0x80000000,0xbee87171,0xbf05c277,
0x80000000,0xbc20d8d2,0x80000000,0xbdb4b86a,0xbca0d6d6,0xbcf13d4c,0xbe3403f1,0xbe862210,0xbd20cee7,0xbd48fb30,0xbeb13641,0xbedae880,0xbd712283,0xbd8ca1f2,0xbf0172c3,0xbf146eba,
0x80000000,0xbca0d6d6,0x80000000,0xbdc8bd36,0xbd20cee7,0xbd712283,0xbe47c5c2,0xbe94a031,0xbda0af2a,0xbdc8bd36,0xbec3ef15,0xbef15aea,0xbdf0b772,0xbe0c4cf7,0xbf0e39da,0xbf226799,
0x80000000,0xbcf13d4c,0x80000000,0xbddcbd0d,0xbd712283,0xbdb4b86a,0xbe5b73dc,0xbea2fd52,0xbdf0b772,0xbe164083,0xbed65a92,0xbf039c3d,0xbe3403f1,0xbe519f65,0xbf1a82a4,0xbf2f9c32,
0x80000000,0xbd20cee7,0x80000000,0xbdf0b772,0xbda0af2a,0xbdf0b772,0xbe6f0c4d,0xbeb13641,0xbe20305b,0xbe47c5c2,0xbee87171,0xbf0e39da,0xbe6f0c4d,0xbe8afa3e,0xbf26423a,0xbf3bfc8f,
0x80000000,0xbd48fb30,0x80000000,0xbe0255f4,0xbdc8bd36,0xbe164083,0xbe814693,0xbebf47d7,0xbe47c5c2,0xbe78cfcc,0xbefa2c90,0xbf187fc0,0xbe94a031,0xbeac7cd4,0xbf316e2c,0xbf4779bc,
0x80000000,0xbd712283,0x80000000,0xbe0c4cf7,0xbdf0b772,0xbe3403f1,0xbe8afa3e,0xbecd2ef3,0xbe6f0c4d,0xbe94a031,0xbf05c277,0xbf226799,0xbeb13641,0xbecd2ef3,0xbf3bfc8f,0xbf5205d4,
0x80000000,0xbd8ca1f2,0x80000000,0xbe164083,0xbe0c4cf7,0xbe519f65,0xbe94a031,0xbedae880,0xbe8afa3e,0xbeac7cd4,0xbf0e39da,0xbf2beb4a,0xbecd2ef3,0xbeece91a,0xbf45e403,0xbf5b941a,
0x80000000,0x80000000,0xbf167918,0xbf26423a,0x80000000,0x80000000,0xbf3504f3,0xbf42a9f7,0x80000000,0x80000000,0xbf4f1bbd,0xbf5a46a0,0x80000000,0x80000000,0xbf641901,0xbf6c835e,
0xbda0af2a,0xbdb4b86a,0xbf26423a,0xbf36c9a9,0xbdc8bd36,0xbddcbd0d,0xbf45e403,0xbf53731f,0xbdf0b772,0xbe0255f4,0xbf5f5be6,0xbf698690,0xbe0c4cf7,0xbe164083,0xbf71decf,0xbf7853f8,
0xbe20305b,0xbe3403f1,0xbf3504f3,0xbf45e403,0xbe47c5c2,0xbe5b73dc,0xbf54db31,0xbf61c598,0xbe6f0c4d,0xbe814693,0xbf6c835e,0xbf74fa0b,0xbe8afa3e,0xbe94a031,0xbf7b14be,0xbf7ec46d,
0xbe6f0c4d,0xbe862210,0xbf42a9f7,0xbf53731f,0xbe94a031,0xbea2fd52,0xbf61c598,0xbf6d76aa,0xbeb13641,0xbebf47d7,0xbf766377,0xbf7c7160,0xbecd2ef3,0xbedae880,0xbf7f8e56,0xbf7fb10f,
0xbe9e377a,0xbeb13641,0xbf4f1bbd,0xbf5f5be6,0xbec3ef15,0xbed65a92,0xbf6c835e,0xbf766377,0xbee87171,0xbefa2c90,0xbf7cd925,0xbf7fcd79,0xbf05c277,0xbf0e39da,0xbf7f35f9,0xbf7b14be,
0xbec3ef15,0xbedae880,0xbf5a46a0,0xbf698690,0xbef15aea,0xbf039c3d,0xbf74fa0b,0xbf7c7160,0xbf0e39da,0xbf187fc0,0xbf7fcd79,0xbf7f0059,0xbf226799,0xbf2beb4a,0xbf7a0d54,0xbf710908,
0xbee87171,0xbf0172c3,0xbf641901,0xbf71decf,0xbf0e39da,0xbf1a82a4,0xbf7b14be,0xbf7f8e56,0xbf26423a,0xbf316e2c,0xbf7f35f9,0xbf7a0d54,0xbf3bfc8f,0xbf45e403,0xbf702d4f,0xbf61c598,
0xbf05c277,0xbf146eba,0xbf6c835e,0xbf7853f8,0xbf226799,0xbf2f9c32,0xbf7ec46d,0xbf7fb10f,0xbf3bfc8f,0xbf4779bc,0xbf7b14be,0xbf710908,0xbf5205d4,0xbf5b941a,0xbf61c598,0xbf4d9f02,
0x80000000,0x80000000,0xbf737871,0xbf78ed3c,0x80000000,0x80000000,0xbf7cd925,0xbf7f35f9,0x80000000,0x80000000,0xbf800000,0xbf7f35f9,0x80000000,0x80000000,0xbf7cd925,0xbf78ed3c,
0xbe20305b,0xbe2a1c3f,0xbf7cd925,0xbf7f654e,0xbe3403f1,0xbe3de731,0xbf7ff35e,0xbf7e8238,0xbe47c5c2,0xbe519f65,0xbf7b14be,0xbf75b1c9,0xbe5b73dc,0xbe6542e9,0xbf6e641a,0xbf653a48,
0xbe9e377a,0xbea7bf25,0xbf800000,0xbf7ec46d,0xbeb13641,0xbeba9be1,0xbf7b14be,0xbf74fa0b,0xbec3ef15,0xbecd2ef3,0xbf6c835e,0xbf61c598,0xbed65a92,0xbedf7108,0xbf54db31,0xbf45e403,
0xbee87171,0xbef5c6c5,0xbf7cd925,0xbf770f11,0xbf0172c3,0xbf07e565,0xbf6e641a,0xbf62f219,0xbf0e39da,0xbf146eba,0xbf54db31,0xbf444969,0xbf1a82a4,0xbf207440,0xbf316e2c,0xbf1c81b9,
0xbf167918,0xbf1e7cf1,0xbf737871,0xbf687c12,0xbf26423a,0xbf2dc5e3,0xbf5a46a0,0xbf490a88,0xbf3504f3,0xbf3bfc8f,0xbf3504f3,0xbf1e7cf1,0xbf42a9f7,0xbf490a88,0xbf05c277,0xbed65a92,
0xbf3504f3,0xbf3daef9,0xbf641901,0xbf53731f,0xbf45e403,0xbf4d9f02,0xbf3f5cb5,0xbf28296a,0xbf54db31,0xbf5b941a,0xbf0e39da,0xbee3f40d,0xbf61c598,0xbf676bd8,0xbea7bf25,0xbe519f65,
0xbf4f1bbd,0xbf579b8c,0xbf4f1bbd,0xbf3889dc,0xbf5f5be6,0xbf6655e7,0xbf1e7cf1,0xbf0172c3,0xbf6c835e,0xbf71decf,0xbec3ef15,0xbe814693,0xbf766377,0xbf7a0d54,0xbdf0b772,0x3ca0d6d6,
0xbf641901,0xbf6b8a3d,0xbf3504f3,0xbf187fc0,0xbf71decf,0xbf770f11,0xbef15aea,0xbeac7cd4,0xbf7b14be,0xbf7deafa,0xbe47c5c2,0xbd48fb30,0xbf7f8e56,0xbf7ffcd7,0x3dc8bd36,0x3e78cfcc,
0x80000000,0x80000000,0xbf737871,0xbf6c835e,0x80000000,0x80000000,0xbf641901,0xbf5a46a0,0x80000000,0x80000000,0xbf4f1bbd,0xbf42a9f7,0x80000000,0x80000000,0xbf3504f3,0xbf26423a,
0xbe6f0c4d,0xbe78cfcc,0xbf5a46a0,0xbf4d9f02,0xbe814693,0xbe862210,0xbf3f5cb5,0xbf2f9c32,0xbe8afa3e,0xbe8fcefe,0xbf1e7cf1,0xbf0c2124,0xbe94a031,0xbe996dba,0xbef15aea,0xbec8917e,
0xbee87171,0xbef15aea,0xbf3504f3,0xbf226799,0xbefa2c90,0xbf0172c3,0xbf0e39da,0xbef15aea,0xbf05c277,0xbf0a04f8,0xbec3ef15,0xbe94a031,0xbf0e39da,0xbf1260b2,0xbe47c5c2,0xbdc8bd36,
0xbf26423a,0xbf2beb4a,0xbf05c277,0xbedae880,0xbf316e2c,0xbf36c9a9,0xbea7bf25,0xbe6542e9,0xbf3bfc8f,0xbf4105b8,0xbdf0b772,0xbc20d8d2,0xbf45e403,0xbf4a965e,0x3dc8bd36,0x3e519f65,
0xbf4f1bbd,0xbf54db31,0xbe9e377a,0xbe47c5c2,0xbf5a46a0,0xbf5f5be6,0xbda0af2a,0x3d20cee7,0xbf641901,0xbf687c12,0x3e20305b,0x3e8afa3e,0xbf6c835e,0xbf702d4f,0x3ec3ef15,0x3efa2c90,
0xbf6c835e,0xbf710908,0xbda0af2a,0x3d48fb30,0xbf74fa0b,0xbf7853f8,0x3e3403f1,0x3e996dba,0xbf7b14be,0xbf7d3aac,0x3ed65a92,0x3f07e565,0xbf7ec46d,0xbf7fb10f,0x3f226799,0x3f3a4582,
0xbf7cd925,0xbf7ec46d,0x3e20305b,0x3e94a031,0xbf7fcd79,0xbf7ff35e,0x3ed65a92,0x3f0a04f8,0xbf7f35f9,0xbf7d95f4,0x3f26423a,0x3f3f5cb5,0xbf7b14be,0xbf77b493,0x3f54db31,0x3f6655e7,
0xbf7f35f9,0xbf7d3aac,0x3ec3ef15,0x3f039c3d,0xbf7a0d54,0xbf75b1c9,0x3f226799,0x3f3daef9,0xbf702d4f,0xbf698690,0x3f54db31,0x3f676bd8,0xbf61c598,0xbf58f3c4,0x3f74fa0b,0x3f7d3aac,
0x80000000,0x80000000,0xbf167918,0xbf05c277,0x80000000,0x80000000,0xbee87171,0xbec3ef15,0x80000000,0x80000000,0xbe9e377a,0xbe6f0c4d,0x80000000,0x80000000,0xbe20305b,0xbda0af2a,
0xbe9e377a,0xbea2fd52,0xbe9e377a,0xbe6542e9,0xbea7bf25,0xbeac7cd4,0xbe0c4cf7,0xbd48fb30,0xbeb13641,0xbeb5eb4f,0x3d20cee7,0x3e0255f4,0xbeba9be1,0xbebf47d7,0x3e5b73dc,0x3e996dba,
0xbf167918,0xbf1a82a4,0x80000000,0x3dc8bd36,0xbf1e7cf1,0xbf226799,0x3e47c5c2,0x3e94a031,0xbf26423a,0xbf2a0c73,0x3ec3ef15,0x3ef15aea,0xbf2dc5e3,0xbf316e2c,0x3f0e39da,0x3f226799,
0xbf4f1bbd,0xbf53731f,0x3e9e377a,0x3ed1c759,0xbf579b8c,0xbf5b941a,0x3f0172c3,0x3f187fc0,0xbf5f5be6,0xbf62f219,0x3f2dc5e3,0x3f4105b8,0xbf6655e7,0xbf698690,0x3f5205d4,0x3f609384,
0xbf737871,0xbf766377,0x3f167918,0x3f2dc5e3,0xbf78ed3c,0xbf7b14be,0x3f42a9f7,0x3f54db31,0xbf7cd925,0xbf7e39bc,0x3f641901,0x3f702d4f,0xbf7f35f9,0xbf7fcd79,0x3f78ed3c,0x3f7e39bc,
0xbf800000,0xbf7fb10f,0x3f4f1bbd,0x3f609384,0xbf7ec46d,0xbf7d3aac,0x3f6e641a,0x3f7853f8,0xbf7b14be,0xbf7853f8,0x3f7e39bc,0x3f7ffcd7,0xbf74fa0b,0xbf710908,0x3f7d95f4,0x3f770f11,
0xbf737871,0xbf6e641a,0x3f737871,0x3f7c0361,0xbf687c12,0xbf61c598,0x3f7fcd79,0x3f7ec46d,0xbf5a46a0,0xbf5205d4,0x3f78ed3c,0x3f6e641a,0xbf490a88,0xbf3f5cb5,0x3f5f5be6,0x3f4c1d35,
0xbf4f1bbd,0xbf444969,0x3f800000,0x3f7d3aac,0xbf3889dc,0xbf2beb4a,0x3f74fa0b,0x3f676bd8,0xbf1e7cf1,0xbf104f0e,0x3f54db31,0x3f3daef9,0xbf0172c3,0xbee3f40d,0x3f226799,0x3f039c3d,
0x3f803f80,0,0x3f803f80,0,0x3f803f80,0,0x3f803f80,0,0x3f7d3f80,0x3e200000,0x3f643f73,0x3ee83e9e,0x3f353f4f,0x3f353f16,0x3ee83f16,0x3f643f4f,
0x3f733f80,0x3e9e0000,0x3f163f4f,0x3f4f3f16,0x3e9e,0x3f803f73,0xbf16be9e,0x3f4f3f73,0x3f643f80,0x3ee80000,0x3e203f16,0x3f7d3f4f,0xbf35be9e,0x3f353f73,0xbf7dbf73,0xbe203e9e,
0x3f4f3f80,0x3f160000,0xbe9e3e9e,0x3f733f73,0xbf80bf4f,0x3f16,0xbe9ebf4f,0xbf73bf16,0x3f353f80,0x3f350000,0xbf350000,0x3f353f80,0xbf35bf80,0xbf350000,0x3f350000,0xbf35bf80,
0x3f163f80,0x3f4f0000,0xbf73be9e,0x3e9e3f73,0xbf4f,0xbf80bf16,0x3f733f4f,0x3e9ebf16,0x3ee83f80,0x3f640000,0xbf7dbf16,0xbe203f4f,0x3f35be9e,0xbf35bf73,0x3e203f73,0x3f7d3e9e,
0x3e9e3f80,0x3f730000,0xbf4fbf4f,0xbf163f16,0x3f803e9e,0xbf73,0xbf4f3e9e,0x3f163f73,0x3e203f80,0x3f7d0000,0xbee8bf73,0xbf643e9e,0x3f353f4f,0x3f35bf16,0xbf64bf16,0xbee83f4f,
0x3f80,0x3f800000,0xbf80,0xbf800000,0x3f80,0x3f800000,0xbf80,0xbf800000,0xbe203f80,0x3f7d0000,0x3ee8bf73,0xbf64be9e,0xbf353f4f,0x3f353f16,0x3f64bf16,0xbee8bf4f,
0xbe9e3f80,0x3f730000,0x3f4fbf4f,0xbf16bf16,0xbf803e9e,0x3f73,0x3f4f3e9e,0x3f16bf73,0xbee83f80,0x3f640000,0x3f7dbf16,0xbe20bf4f,0xbf35be9e,0xbf353f73,0xbe203f73,0x3f7dbe9e,
0xbf163f80,0x3f4f0000,0x3f73be9e,0x3e9ebf73,0xbf4f,0xbf803f16,0xbf733f4f,0x3e9e3f16,0xbf353f80,0x3f350000,0x3f350000,0x3f35bf80,0x3f35bf80,0xbf350000,0xbf350000,0xbf353f80,
0xbf4f3f80,0x3f160000,0x3e9e3e9e,0x3f73bf73,0x3f80bf4f,0xbf16,0x3e9ebf4f,0xbf733f16,0xbf643f80,0x3ee80000,0xbe203f16,0x3f7dbf4f,0x3f35be9e,0x3f35bf73,0x3f7dbf73,0xbe20be9e,
0xbf733f80,0x3e9e0000,0xbf163f4f,0x3f4fbf16,0x3e9e,0x3f80bf73,0x3f16be9e,0x3f4fbf73,0xbf7d3f80,0x3e200000,0xbf643f73,0x3ee8be9e,0xbf353f4f,0x3f35bf16,0xbee83f16,0x3f64bf4f,
0xbf803f80,0,0xbf803f80,0,0xbf803f80,0,0xbf803f80,0,0xbf7d3f80,0xbe200000,0xbf643f73,0xbee83e9e,0xbf353f4f,0xbf353f16,0xbee83f16,0xbf643f4f,
0xbf733f80,0xbe9e0000,0xbf163f4f,0xbf4f3f16,0x3e9e,0xbf803f73,0x3f16be9e,0xbf4f3f73,0xbf643f80,0xbee80000,0xbe203f16,0xbf7d3f4f,0x3f35be9e,0xbf353f73,0x3f7dbf73,0x3e203e9e,
0xbf4f3f80,0xbf160000,0x3e9e3e9e,0xbf733f73,0x3f80bf4f,0x3f16,0x3e9ebf4f,0x3f73bf16,0xbf353f80,0xbf350000,0x3f350000,0xbf353f80,0x3f35bf80,0x3f350000,0xbf350000,0x3f35bf80,
0xbf163f80,0xbf4f0000,0x3f73be9e,0xbe9e3f73,0xbf4f,0x3f80bf16,0xbf733f4f,0xbe9ebf16,0xbee83f80,0xbf640000,0x3f7dbf16,0x3e203f4f,0xbf35be9e,0x3f35bf73,0xbe203f73,0xbf7d3e9e,
0xbe9e3f80,0xbf730000,0x3f4fbf4f,0x3f163f16,0xbf803e9e,0xbf73,0x3f4f3e9e,0xbf163f73,0xbe203f80,0xbf7d0000,0x3ee8bf73,0x3f643e9e,0xbf353f4f,0xbf35bf16,0x3f64bf16,0x3ee83f4f,
0x3f80,0xbf800000,0xbf80,0x3f800000,0x3f80,0xbf800000,0xbf80,0x3f800000,0x3e203f80,0xbf7d0000,0xbee8bf73,0x3f64be9e,0x3f353f4f,0xbf353f16,0xbf64bf16,0x3ee8bf4f,
0x3e9e3f80,0xbf730000,0xbf4fbf4f,0x3f16bf16,0x3f803e9e,0x3f73,0xbf4f3e9e,0xbf16bf73,0x3ee83f80,0xbf640000,0xbf7dbf16,0x3e20bf4f,0x3f35be9e,0x3f353f73,0x3e203f73,0xbf7dbe9e,
0x3f163f80,0xbf4f0000,0xbf73be9e,0xbe9ebf73,0xbf4f,0x3f803f16,0x3f733f4f,0xbe9e3f16,0x3f353f80,0xbf350000,0xbf350000,0xbf35bf80,0xbf35bf80,0x3f350000,0x3f350000,0x3f353f80,
0x3f4f3f80,0xbf160000,0xbe9e3e9e,0xbf73bf73,0xbf80bf4f,0xbf16,0xbe9ebf4f,0x3f733f16,0x3f643f80,0xbee80000,0x3e203f16,0xbf7dbf4f,0xbf35be9e,0xbf35bf73,0xbf7dbf73,0x3e20be9e,
0x3f733f80,0xbe9e0000,0x3f163f4f,0xbf4fbf16,0x3e9e,0xbf80bf73,0xbf16be9e,0xbf4fbf73,0x3f7d3f80,0xbe200000,0x3f643f73,0xbee8be9e,0x3f353f4f,0xbf35bf16,0x3ee83f16,0xbf64bf4f,
0x3f803f80,0,0x3f803f80,0,0x3f803f80,0,0x3f803f80,0,0x3e203e9e,0x3f7d3f73,0xbe200000,0x3f7d3f80,0xbee8be9e,0x3f643f73,0xbf35bf16,0x3f353f4f,
0xbf73bf4f,0x3e9e3f16,0xbf73bf80,0xbe9e0000,0xbf16bf4f,0xbf4fbf16,0xbe9e,0xbf80bf73,0xbee8bf4f,0xbf64bf16,0x3ee80000,0xbf64bf80,0x3f7d3f4f,0xbe20bf16,0x3f353f73,0x3f353e9e,
0x3f4f3e9e,0xbf16bf73,0x3f4f3f80,0x3f160000,0xbe9e3e9e,0x3f733f73,0xbf80bf4f,0x3f16,0x3f353f80,0x3f350000,0xbf350000,0x3f353f80,0xbf35bf80,0xbf350000,0x3f350000,0xbf35bf80,
0xbf163e9e,0x3f4f3f73,0xbf16bf80,0xbf4f0000,0x3f733e9e,0xbe9ebf73,0x3f4f,0x3f803f16,0xbf64bf4f,0xbee83f16,0x3f640000,0xbee8bf80,0xbe203f4f,0x3f7d3f16,0xbf35bf73,0xbf353e9e,
0x3e9ebf4f,0xbf73bf16,0x3e9e3f80,0x3f730000,0xbf4fbf4f,0xbf163f16,0x3f803e9e,0xbf73,0x3f7d3e9e,0x3e20bf73,0xbf7d0000,0x3e203f80,0x3f64be9e,0xbee8bf73,0xbf353f16,0x3f353f4f,
0x3f80,0x3f800000,0xbf80,0xbf800000,0x3f80,0x3f800000,0xbf80,0xbf800000,0xbf7d3e9e,0x3e203f73,0x3f7d0000,0x3e20bf80,0xbf64be9e,0xbee83f73,0x3f353f16,0x3f35bf4f,
0xbe9ebf4f,0xbf733f16,0xbe9e3f80,0x3f730000,0x3f4fbf4f,0xbf16bf16,0xbf803e9e,0x3f73,0x3f64bf4f,0xbee8bf16,0xbf640000,0xbee83f80,0x3e203f4f,0x3f7dbf16,0x3f35bf73,0xbf35be9e,
0x3f163e9e,0x3f4fbf73,0x3f16bf80,0xbf4f0000,0xbf733e9e,0xbe9e3f73,0x3f4f,0x3f80bf16,0xbf353f80,0x3f350000,0x3f350000,0x3f35bf80,0x3f35bf80,0xbf350000,0xbf350000,0xbf353f80,
0xbf4f3e9e,0xbf163f73,0xbf4f3f80,0x3f160000,0x3e9e3e9e,0x3f73bf73,0x3f80bf4f,0xbf16,0x3ee8bf4f,0xbf643f16,0xbee80000,0xbf643f80,0xbf7d3f4f,0xbe203f16,0xbf353f73,0x3f35be9e,
0x3f73bf4f,0x3e9ebf16,0x3f73bf80,0xbe9e0000,0x3f16bf4f,0xbf4f3f16,0xbe9e,0xbf803f73,0xbe203e9e,0x3f7dbf73,0x3e200000,0x3f7dbf80,0x3ee8be9e,0x3f64bf73,0x3f35bf16,0x3f35bf4f,
0xbf803f80,0,0xbf803f80,0,0xbf803f80,0,0xbf803f80,0,0xbe203e9e,0xbf7d3f73,0x3e200000,0xbf7d3f80,0x3ee8be9e,0xbf643f73,0x3f35bf16,0xbf353f4f,
0x3f73bf4f,0xbe9e3f16,0x3f73bf80,0x3e9e0000,0x3f16bf4f,0x3f4fbf16,0xbe9e,0x3f80bf73,0x3ee8bf4f,0x3f64bf16,0xbee80000,0x3f64bf80,0xbf7d3f4f,0x3e20bf16,0xbf353f73,0xbf353e9e,
0xbf4f3e9e,0x3f16bf73,0xbf4f3f80,0xbf160000,0x3e9e3e9e,0xbf733f73,0x3f80bf4f,0x3f16,0xbf353f80,0xbf350000,0x3f350000,0xbf353f80,0x3f35bf80,0x3f350000,0xbf350000,0x3f35bf80,
0x3f163e9e,0xbf4f3f73,0x3f16bf80,0x3f4f0000,0xbf733e9e,0x3e9ebf73,0x3f4f,0xbf803f16,0x3f64bf4f,0x3ee83f16,0xbf640000,0x3ee8bf80,0x3e203f4f,0xbf7d3f16,0x3f35bf73,0x3f353e9e,
0xbe9ebf4f,0x3f73bf16,0xbe9e3f80,0xbf730000,0x3f4fbf4f,0x3f163f16,0xbf803e9e,0xbf73,0xbf7d3e9e,0xbe20bf73,0x3f7d0000,0xbe203f80,0xbf64be9e,0x3ee8bf73,0x3f353f16,0xbf353f4f,
0x3f80,0xbf800000,0xbf80,0x3f800000,0x3f80,0xbf800000,0xbf80,0x3f800000,0x3f7d3e9e,0xbe203f73,0xbf7d0000,0xbe20bf80,0x3f64be9e,0x3ee83f73,0xbf353f16,0xbf35bf4f,
0x3e9ebf4f,0x3f733f16,0x3e9e3f80,0xbf730000,0xbf4fbf4f,0x3f16bf16,0x3f803e9e,0x3f73,0xbf64bf4f,0x3ee8bf16,0x3f640000,0x3ee83f80,0xbe203f4f,0xbf7dbf16,0xbf35bf73,0x3f35be9e,
0xbf163e9e,0xbf4fbf73,0xbf16bf80,0x3f4f0000,0x3f733e9e,0x3e9e3f73,0x3f4f,0xbf80bf16,0x3f353f80,0xbf350000,0xbf350000,0xbf35bf80,0xbf35bf80,0x3f350000,0x3f350000,0x3f353f80,
0x3f4f3e9e,0x3f163f73,0x3f4f3f80,0xbf160000,0xbe9e3e9e,0xbf73bf73,0xbf80bf4f,0xbf16,0xbee8bf4f,0x3f643f16,0x3ee80000,0x3f643f80,0x3f7d3f4f,0x3e203f16,0x3f353f73,0xbf35be9e,
0xbf73bf4f,0xbe9ebf16,0xbf73bf80,0x3e9e0000,0xbf16bf4f,0x3f4f3f16,0xbe9e,0x3f803f73,0x3e203e9e,0xbf7dbf73,0xbe200000,0xbf7dbf80,0xbee8be9e,0xbf64bf73,0xbf35bf16,0xbf35bf4f,
0x3f803f80,0,0x3f803f80,0,0x3f803f80,0,0x3f803f80,0,0xbf64bf4f,0x3ee83f16,0xbf7dbf73,0x3e203e9e,0xbf7dbf80,0xbe200000,0xbf64bf73,0xbee8be9e,
0x3f163e9e,0xbf4fbf73,0x3f733f4f,0xbe9ebf16,0x3f733f80,0x3e9e0000,0x3f163f4f,0x3f4f3f16,0xbe203e9e,0x3f7d3f73,0xbf64bf16,0x3ee83f4f,0xbf64bf80,0xbee80000,0xbe20bf16,0xbf7dbf4f,
0xbe9ebf4f,0xbf73bf16,0x3f4f3e9e,0xbf16bf73,0x3f4f3f80,0x3f160000,0xbe9e3e9e,0x3f733f73,0x3f353f80,0x3f350000,0xbf350000,0x3f353f80,0xbf35bf80,0xbf350000,0x3f350000,0xbf35bf80,
0xbf73bf4f,0xbe9e3f16,0x3f16be9e,0xbf4fbf73,0x3f163f80,0x3f4f0000,0xbf73be9e,0x3e9e3f73,0x3f7d3e9e,0xbe20bf73,0xbee83f16,0x3f643f4f,0xbee8bf80,0xbf640000,0x3f7d3f16,0x3e20bf4f,
0xbf4f3e9e,0x3f163f73,0x3e9ebf4f,0xbf73bf16,0x3e9e3f80,0x3f730000,0xbf4fbf4f,0xbf163f16,0x3ee8bf4f,0xbf64bf16,0xbe203f73,0x3f7d3e9e,0xbe20bf80,0xbf7d0000,0x3ee83f73,0x3f64be9e,
0x3f80,0x3f800000,0xbf80,0xbf800000,0x3f80,0x3f800000,0xbf80,0xbf800000,0xbee8bf4f,0xbf643f16,0x3e203f73,0x3f7dbe9e,0x3e20bf80,0xbf7d0000,0xbee83f73,0x3f643e9e,
0x3f4f3e9e,0x3f16bf73,0xbe9ebf4f,0xbf733f16,0xbe9e3f80,0x3f730000,0x3f4fbf4f,0xbf16bf16,0xbf7d3e9e,0xbe203f73,0x3ee83f16,0x3f64bf4f,0x3ee8bf80,0xbf640000,0xbf7d3f16,0x3e203f4f,
0x3f73bf4f,0xbe9ebf16,0xbf16be9e,0xbf4f3f73,0xbf163f80,0x3f4f0000,0x3f73be9e,0x3e9ebf73,0xbf353f80,0x3f350000,0x3f350000,0x3f35bf80,0x3f35bf80,0xbf350000,0xbf350000,0xbf353f80,
0x3e9ebf4f,0xbf733f16,0xbf4f3e9e,0xbf163f73,0xbf4f3f80,0x3f160000,0x3e9e3e9e,0x3f73bf73,0x3e203e9e,0x3f7dbf73,0x3f64bf16,0x3ee8bf4f,0x3f64bf80,0xbee80000,0x3e20bf16,0xbf7d3f4f,
0xbf163e9e,0xbf4f3f73,0xbf733f4f,0xbe9e3f16,0xbf733f80,0x3e9e0000,0xbf163f4f,0x3f4fbf16,0x3f64bf4f,0x3ee8bf16,0x3f7dbf73,0x3e20be9e,0x3f7dbf80,0xbe200000,0x3f64bf73,0xbee83e9e,
0xbf803f80,0,0xbf803f80,0,0xbf803f80,0,0xbf803f80,0,0x3f64bf4f,0xbee83f16,0x3f7dbf73,0xbe203e9e,0x3f7dbf80,0x3e200000,0x3f64bf73,0x3ee8be9e,
0xbf163e9e,0x3f4fbf73,0xbf733f4f,0x3e9ebf16,0xbf733f80,0xbe9e0000,0xbf163f4f,0xbf4f3f16,0x3e203e9e,0xbf7d3f73,0x3f64bf16,0xbee83f4f,0x3f64bf80,0x3ee80000,0x3e20bf16,0x3f7dbf4f,
0x3e9ebf4f,0x3f73bf16,0xbf4f3e9e,0x3f16bf73,0xbf4f3f80,0xbf160000,0x3e9e3e9e,0xbf733f73,0xbf353f80,0xbf350000,0x3f350000,0xbf353f80,0x3f35bf80,0x3f350000,0xbf350000,0x3f35bf80,
0x3f73bf4f,0x3e9e3f16,0xbf16be9e,0x3f4fbf73,0xbf163f80,0xbf4f0000,0x3f73be9e,0xbe9e3f73,0xbf7d3e9e,0x3e20bf73,0x3ee83f16,0xbf643f4f,0x3ee8bf80,0x3f640000,0xbf7d3f16,0xbe20bf4f,
0x3f4f3e9e,0xbf163f73,0xbe9ebf4f,0x3f73bf16,0xbe9e3f80,0xbf730000,0x3f4fbf4f,0x3f163f16,0xbee8bf4f,0x3f64bf16,0x3e203f73,0xbf7d3e9e,0x3e20bf80,0x3f7d0000,0xbee83f73,0xbf64be9e,
0x3f80,0xbf800000,0xbf80,0x3f800000,0x3f80,0xbf800000,0xbf80,0x3f800000,0x3ee8bf4f,0x3f643f16,0xbe203f73,0xbf7dbe9e,0xbe20bf80,0x3f7d0000,0x3ee83f73,0xbf643e9e,
0xbf4f3e9e,0xbf16bf73,0x3e9ebf4f,0x3f733f16,0x3e9e3f80,0xbf730000,0xbf4fbf4f,0x3f16bf16,0x3f7d3e9e,0x3e203f73,0xbee83f16,0xbf64bf4f,0xbee8bf80,0x3f640000,0x3f7d3f16,0xbe203f4f,
0xbf73bf4f,0x3e9ebf16,0x3f16be9e,0x3f4f3f73,0x3f163f80,0xbf4f0000,0xbf73be9e,0xbe9ebf73,0x3f353f80,0xbf350000,0xbf350000,0xbf35bf80,0xbf35bf80,0x3f350000,0x3f350000,0x3f353f80,
0xbe9ebf4f,0x3f733f16,0x3f4f3e9e,0x3f163f73,0x3f4f3f80,0xbf160000,0xbe9e3e9e,0xbf73bf73,0xbe203e9e,0xbf7dbf73,0xbf64bf16,0xbee8bf4f,0xbf64bf80,0x3ee80000,0xbe20bf16,0x3f7d3f4f,
0x3f163e9e,0x3f4f3f73,0x3f733f4f,0x3e9e3f16,0x3f733f80,0xbe9e0000,0x3f163f4f,0xbf4fbf16,0xbf64bf4f,0xbee8bf16,0xbf7dbf73,0xbe20be9e,0xbf7dbf80,0x3e200000,0xbf64bf73,0x3ee83e9e,
0x3f803f80,0,0x3f803f80,0,0x3f803f80,0,0x3f803f80,0,0xbf35bf4f,0xbf35bf16,0xbee8bf16,0xbf64bf4f,0xbe20be9e,0xbf7dbf73,0x3e200000,0xbf7dbf80,
0x3e9e,0x3f803f73,0xbf16be9e,0x3f4f3f73,0xbf73bf4f,0x3e9e3f16,0xbf73bf80,0xbe9e0000,0x3f353e9e,0xbf35bf73,0x3f7d3f73,0x3e20be9e,0x3ee83f4f,0x3f643f16,0xbee80000,0x3f643f80,
0xbf80bf4f,0x3f16,0xbe9ebf4f,0xbf73bf16,0x3f4f3e9e,0xbf16bf73,0x3f4f3f80,0x3f160000,0x3f353f80,0x3f350000,0xbf350000,0x3f353f80,0xbf35bf80,0xbf350000,0x3f350000,0xbf35bf80,
0xbf4f,0xbf80bf16,0x3f733f4f,0x3e9ebf16,0xbf163e9e,0x3f4f3f73,0xbf16bf80,0xbf4f0000,0xbf353e9e,0x3f353f73,0xbe20bf73,0xbf7dbe9e,0x3f643f4f,0x3ee8bf16,0xbf640000,0x3ee83f80,
0x3f803e9e,0xbf73,0xbf4f3e9e,0x3f163f73,0x3e9ebf4f,0xbf73bf16,0x3e9e3f80,0x3f730000,0xbf35bf4f,0xbf353f16,0x3f643f16,0x3ee8bf4f,0xbf7dbe9e,0xbe203f73,0x3f7d0000,0xbe20bf80,
0x3f80,0x3f800000,0xbf80,0xbf800000,0x3f80,0x3f800000,0xbf80,0xbf800000,0x3f35bf4f,0xbf35bf16,0xbf643f16,0x3ee83f4f,0x3f7dbe9e,0xbe20bf73,0xbf7d0000,0xbe203f80,
0xbf803e9e,0x3f73,0x3f4f3e9e,0x3f16bf73,0xbe9ebf4f,0xbf733f16,0xbe9e3f80,0x3f730000,0x3f353e9e,0x3f35bf73,0x3e20bf73,0xbf7d3e9e,0xbf643f4f,0x3ee83f16,0x3f640000,0x3ee8bf80,
0xbf4f,0xbf803f16,0xbf733f4f,0x3e9e3f16,0x3f163e9e,0x3f4fbf73,0x3f16bf80,0xbf4f0000,0xbf353f80,0x3f350000,0x3f350000,0x3f35bf80,0x3f35bf80,0xbf350000,0xbf350000,0xbf353f80,
0x3f80bf4f,0xbf16,0x3e9ebf4f,0xbf733f16,0xbf4f3e9e,0xbf163f73,0xbf4f3f80,0x3f160000,0xbf353e9e,0xbf353f73,0xbf7d3f73,0x3e203e9e,0xbee83f4f,0x3f64bf16,0x3ee80000,0x3f64bf80,
0x3e9e,0x3f80bf73,0x3f16be9e,0x3f4fbf73,0x3f73bf4f,0x3e9ebf16,0x3f73bf80,0xbe9e0000,0x3f35bf4f,0xbf353f16,0x3ee8bf16,0xbf643f4f,0x3e20be9e,0xbf7d3f73,0xbe200000,0xbf7d3f80,
0xbf803f80,0,0xbf803f80,0,0xbf803f80,0,0xbf803f80,0,0x3f35bf4f,0x3f35bf16,0x3ee8bf16,0x3f64bf4f,0x3e20be9e,0x3f7dbf73,0xbe200000,0x3f7dbf80,
0x3e9e,0xbf803f73,0x3f16be9e,0xbf4f3f73,0x3f73bf4f,0xbe9e3f16,0x3f73bf80,0x3e9e0000,0xbf353e9e,0x3f35bf73,0xbf7d3f73,0xbe20be9e,0xbee83f4f,0xbf643f16,0x3ee80000,0xbf643f80,
0x3f80bf4f,0x3f16,0x3e9ebf4f,0x3f73bf16,0xbf4f3e9e,0x3f16bf73,0xbf4f3f80,0xbf160000,0xbf353f80,0xbf350000,0x3f350000,0xbf353f80,0x3f35bf80,0x3f350000,0xbf350000,0x3f35bf80,
0xbf4f,0x3f80bf16,0xbf733f4f,0xbe9ebf16,0x3f163e9e,0xbf4f3f73,0x3f16bf80,0x3f4f0000,0x3f353e9e,0xbf353f73,0x3e20bf73,0x3f7dbe9e,0xbf643f4f,0xbee8bf16,0x3f640000,0xbee83f80,
0xbf803e9e,0xbf73,0x3f4f3e9e,0xbf163f73,0xbe9ebf4f,0x3f73bf16,0xbe9e3f80,0xbf730000,0x3f35bf4f,0x3f353f16,0xbf643f16,0xbee8bf4f,0x3f7dbe9e,0x3e203f73,0xbf7d0000,0x3e20bf80,
0x3f80,0xbf800000,0xbf80,0x3f800000,0x3f80,0xbf800000,0xbf80,0x3f800000,0xbf35bf4f,0x3f35bf16,0x3f643f16,0xbee83f4f,0xbf7dbe9e,0x3e20bf73,0x3f7d0000,0x3e203f80,
0x3f803e9e,0x3f73,0xbf4f3e9e,0xbf16bf73,0x3e9ebf4f,0x3f733f16,0x3e9e3f80,0xbf730000,0xbf353e9e,0xbf35bf73,0xbe20bf73,0x3f7d3e9e,0x3f643f4f,0xbee83f16,0xbf640000,0xbee8bf80,
0xbf4f,0x3f803f16,0x3f733f4f,0xbe9e3f16,0xbf163e9e,0xbf4fbf73,0xbf16bf80,0x3f4f0000,0x3f353f80,0xbf350000,0xbf350000,0xbf35bf80,0xbf35bf80,0x3f350000,0x3f350000,0x3f353f80,
0xbf80bf4f,0xbf16,0xbe9ebf4f,0x3f733f16,0x3f4f3e9e,0x3f163f73,0x3f4f3f80,0xbf160000,0x3f353e9e,0x3f353f73,0x3f7d3f73,0xbe203e9e,0x3ee83f4f,0xbf64bf16,0xbee80000,0xbf64bf80,
0x3e9e,0xbf80bf73,0xbf16be9e,0xbf4fbf73,0xbf73bf4f,0xbe9ebf16,0xbf73bf80,0x3e9e0000,0xbf35bf4f,0x3f353f16,0xbee8bf16,0x3f643f4f,0xbe20be9e,0x3f7d3f73,0x3e200000,0x3f7d3f80,
0x3f803f80,0,0x3f803f80,0,0x3f803f80,0,0x3f803f80,0,0x3ee83e9e,0xbf64bf73,0x3f353f16,0xbf35bf4f,0x3f643f4f,0xbee8bf16,0x3f7d3f73,0xbe20be9e,
0xbf16bf4f,0xbf4fbf16,0xbe9e,0xbf80bf73,0x3f163e9e,0xbf4fbf73,0x3f733f4f,0xbe9ebf16,0xbf7dbf4f,0x3e203f16,0xbf35bf73,0xbf35be9e,0x3e20be9e,0xbf7dbf73,0x3f643f16,0xbee8bf4f,
0xbe9e3e9e,0x3f733f73,0xbf80bf4f,0x3f16,0xbe9ebf4f,0xbf73bf16,0x3f4f3e9e,0xbf16bf73,0x3f353f80,0x3f350000,0xbf350000,0x3f353f80,0xbf35bf80,0xbf350000,0x3f350000,0xbf35bf80,
0x3f733e9e,0xbe9ebf73,0x3f4f,0x3f803f16,0xbf73bf4f,0xbe9e3f16,0x3f16be9e,0xbf4fbf73,0x3e20bf4f,0xbf7dbf16,0x3f353f73,0x3f35be9e,0xbf7dbe9e,0x3e203f73,0x3ee8bf16,0xbf64bf4f,
0xbf4fbf4f,0xbf163f16,0x3f803e9e,0xbf73,0xbf4f3e9e,0x3f163f73,0x3e9ebf4f,0xbf73bf16,0xbf643e9e,0x3ee83f73,0x3f35bf16,0xbf35bf4f,0xbee83f4f,0x3f643f16,0x3e20bf73,0xbf7dbe9e,
0x3f80,0x3f800000,0xbf80,0xbf800000,0x3f80,0x3f800000,0xbf80,0xbf800000,0x3f643e9e,0x3ee8bf73,0xbf35bf16,0xbf353f4f,0x3ee83f4f,0x3f64bf16,0xbe20bf73,0xbf7d3e9e,
0x3f4fbf4f,0xbf16bf16,0xbf803e9e,0x3f73,0x3f4f3e9e,0x3f16bf73,0xbe9ebf4f,0xbf733f16,0xbe20bf4f,0xbf7d3f16,0xbf353f73,0x3f353e9e,0x3f7dbe9e,0x3e20bf73,0xbee8bf16,0xbf643f4f,
0xbf733e9e,0xbe9e3f73,0x3f4f,0x3f80bf16,0x3f73bf4f,0xbe9ebf16,0xbf16be9e,0xbf4f3f73,0xbf353f80,0x3f350000,0x3f350000,0x3f35bf80,0x3f35bf80,0xbf350000,0xbf350000,0xbf353f80,
0x3e9e3e9e,0x3f73bf73,0x3f80bf4f,0xbf16,0x3e9ebf4f,0xbf733f16,0xbf4f3e9e,0xbf163f73,0x3f7dbf4f,0x3e20bf16,0x3f35bf73,0xbf353e9e,0xbe20be9e,0xbf7d3f73,0xbf643f16,0xbee83f4f,
0x3f16bf4f,0xbf4f3f16,0xbe9e,0xbf803f73,0xbf163e9e,0xbf4f3f73,0xbf733f4f,0xbe9e3f16,0xbee83e9e,0xbf643f73,0xbf353f16,0xbf353f4f,0xbf643f4f,0xbee83f16,0xbf7d3f73,0xbe203e9e,
0xbf803f80,0,0xbf803f80,0,0xbf803f80,0,0xbf803f80,0,0xbee83e9e,0x3f64bf73,0xbf353f16,0x3f35bf4f,0xbf643f4f,0x3ee8bf16,0xbf7d3f73,0x3e20be9e,
0x3f16bf4f,0x3f4fbf16,0xbe9e,0x3f80bf73,0xbf163e9e,0x3f4fbf73,0xbf733f4f,0x3e9ebf16,0x3f7dbf4f,0xbe203f16,0x3f35bf73,0x3f35be9e,0xbe20be9e,0x3f7dbf73,0xbf643f16,0x3ee8bf4f,
0x3e9e3e9e,0xbf733f73,0x3f80bf4f,0x3f16,0x3e9ebf4f,0x3f73bf16,0xbf4f3e9e,0x3f16bf73,0xbf353f80,0xbf350000,0x3f350000,0xbf353f80,0x3f35bf80,0x3f350000,0xbf350000,0x3f35bf80,
0xbf733e9e,0x3e9ebf73,0x3f4f,0xbf803f16,0x3f73bf4f,0x3e9e3f16,0xbf16be9e,0x3f4fbf73,0xbe20bf4f,0x3f7dbf16,0xbf353f73,0xbf35be9e,0x3f7dbe9e,0xbe203f73,0xbee8bf16,0x3f64bf4f,
0x3f4fbf4f,0x3f163f16,0xbf803e9e,0xbf73,0x3f4f3e9e,0xbf163f73,0xbe9ebf4f,0x3f73bf16,0x3f643e9e,0xbee83f73,0xbf35bf16,0x3f35bf4f,0x3ee83f4f,0xbf643f16,0xbe20bf73,0x3f7dbe9e,
0x3f80,0xbf800000,0xbf80,0x3f800000,0x3f80,0xbf800000,0xbf80,0x3f800000,0xbf643e9e,0xbee8bf73,0x3f35bf16,0x3f353f4f,0xbee83f4f,0xbf64bf16,0x3e20bf73,0x3f7d3e9e,
0xbf4fbf4f,0x3f16bf16,0x3f803e9e,0x3f73,0xbf4f3e9e,0xbf16bf73,0x3e9ebf4f,0x3f733f16,0x3e20bf4f,0x3f7d3f16,0x3f353f73,0xbf353e9e,0xbf7dbe9e,0xbe20bf73,0x3ee8bf16,0x3f643f4f,
0x3f733e9e,0x3e9e3f73,0x3f4f,0xbf80bf16,0xbf73bf4f,0x3e9ebf16,0x3f16be9e,0x3f4f3f73,0x3f353f80,0xbf350000,0xbf350000,0xbf35bf80,0xbf35bf80,0x3f350000,0x3f350000,0x3f353f80,
0xbe9e3e9e,0xbf73bf73,0xbf80bf4f,0xbf16,0xbe9ebf4f,0x3f733f16,0x3f4f3e9e,0x3f163f73,0xbf7dbf4f,0xbe20bf16,0xbf35bf73,0x3f353e9e,0x3e20be9e,0x3f7d3f73,0x3f643f16,0x3ee83f4f,
0xbf16bf4f,0x3f4f3f16,0xbe9e,0x3f803f73,0x3f163e9e,0x3f4f3f73,0x3f733f4f,0x3e9e3f16,0x3ee83e9e,0x3f643f73,0x3f353f16,0x3f353f4f,0x3f643f4f,0x3ee83f16,0x3f7d3f73,0x3e203e9e,
0x3f803f80,0x3f80,0xbf803f80,0x3f80,0x3f803f80,0xbf80,0xbf803f80,0xbf80,0x3f803f80,0x3f80,0xbf803f80,0x3f80,0x3f803f80,0xbf80,0xbf803f80,0xbf80,
0x3f7b3f80,0xbe483f80,0xbf7b3f80,0x3e483f80,0x3f553f6d,0x3f0ebf6d,0xbf553f6d,0xbf0ebf6d,0x3f0e3f35,0xbf553f35,0xbf0e3f35,0x3f553f35,0x3e483ec4,0x3f7bbec4,0xbe483ec4,0xbf7bbec4,
0x3f6d3f80,0xbec43f80,0xbf6d3f80,0x3ec43f80,0x3ec43f35,0x3f6dbf35,0xbec43f35,0xbf6dbf35,0xbec40000,0xbf6d0000,0x3ec40000,0x3f6d0000,0xbf6dbf35,0x3ec43f35,0x3f6dbf35,0xbec43f35,
0x3f553f80,0xbf0e3f80,0xbf553f80,0x3f0e3f80,0xbe483ec4,0x3f7bbec4,0x3e483ec4,0xbf7bbec4,0xbf7bbf35,0xbe48bf35,0x3f7bbf35,0x3e48bf35,0xbf0ebf6d,0xbf553f6d,0x3f0ebf6d,0x3f553f6d,
0x3f353f80,0xbf353f80,0xbf353f80,0x3f353f80,0xbf350000,0x3f350000,0x3f350000,0xbf350000,0xbf35bf80,0x3f35bf80,0x3f35bf80,0xbf35bf80,0x3f350000,0xbf350000,0xbf350000,0x3f350000,
0x3f0e3f80,0xbf553f80,0xbf0e3f80,0x3f553f80,0xbf7bbec4,0x3e483ec4,0x3f7bbec4,0xbe483ec4,0x3e48bf35,0x3f7bbf35,0xbe48bf35,0xbf7bbf35,0x3f553f6d,0x3f0ebf6d,0xbf553f6d,0xbf0ebf6d,
0x3ec43f80,0xbf6d3f80,0xbec43f80,0x3f6d3f80,0xbf6dbf35,0xbec43f35,0x3f6dbf35,0x3ec43f35,0x3f6d0000,0x3ec40000,0xbf6d0000,0xbec40000,0xbec43f35,0x3f6dbf35,0x3ec43f35,0xbf6dbf35,
0x3e483f80,0xbf7b3f80,0xbe483f80,0x3f7b3f80,0xbf0ebf6d,0xbf553f6d,0x3f0ebf6d,0x3f553f6d,0x3f553f35,0xbf0e3f35,0xbf553f35,0x3f0e3f35,0xbf7bbec4,0xbe483ec4,0x3f7bbec4,0x3e483ec4,
0x3f803f80,0x3f80,0xbf803f80,0x3f80,0x3f803f80,0xbf80,0xbf803f80,0xbf80,0x3f803f80,0x3f80,0xbf803f80,0x3f80,0x3f803f80,0xbf80,0xbf803f80,0xbf80,
0xbe480000,0xbf7b0000,0x3e480000,0x3f7b0000,0xbf0ebec4,0x3f553ec4,0x3f0ebec4,0xbf553ec4,0xbf55bf35,0xbf0ebf35,0x3f55bf35,0x3f0ebf35,0xbf7bbf6d,0x3e483f6d,0x3f7bbf6d,0xbe483f6d,
0xbf6dbf80,0x3ec4bf80,0x3f6dbf80,0xbec4bf80,0xbec4bf35,0xbf6d3f35,0x3ec4bf35,0x3f6d3f35,0x3ec40000,0x3f6d0000,0xbec40000,0xbf6d0000,0x3f6d3f35,0xbec4bf35,0xbf6d3f35,0x3ec4bf35,
0x3f0e0000,0x3f550000,0xbf0e0000,0xbf550000,0x3f7b3f6d,0x3e48bf6d,0xbf7b3f6d,0xbe48bf6d,0x3e483f35,0xbf7b3f35,0xbe483f35,0x3f7b3f35,0xbf55bec4,0x3f0e3ec4,0x3f55bec4,0xbf0e3ec4,
0x3f353f80,0xbf353f80,0xbf353f80,0x3f353f80,0xbf350000,0x3f350000,0x3f350000,0xbf350000,0xbf35bf80,0x3f35bf80,0x3f35bf80,0xbf35bf80,0x3f350000,0xbf350000,0xbf350000,0x3f350000,
0xbf550000,0xbf0e0000,0x3f550000,0x3f0e0000,0xbe48bf6d,0xbf7b3f6d,0x3e48bf6d,0x3f7b3f6d,0x3f7b3f35,0xbe483f35,0xbf7b3f35,0x3e483f35,0xbf0e3ec4,0x3f55bec4,0x3f0e3ec4,0xbf55bec4,
0xbec4bf80,0x3f6dbf80,0x3ec4bf80,0xbf6dbf80,0x3f6d3f35,0x3ec4bf35,0xbf6d3f35,0xbec4bf35,0xbf6d0000,0xbec40000,0x3f6d0000,0x3ec40000,0x3ec4bf35,0xbf6d3f35,0xbec4bf35,0x3f6d3f35,
0x3f7b0000,0x3e480000,0xbf7b0000,0xbe480000,0xbf553ec4,0x3f0ebec4,0x3f553ec4,0xbf0ebec4,0x3f0ebf35,0x3f55bf35,0xbf0ebf35,0xbf55bf35,0xbe483f6d,0x3f7bbf6d,0x3e483f6d,0xbf7bbf6d,
0x3f803f80,0x3f80,0xbf803f80,0x3f80,0x3f803f80,0xbf80,0xbf803f80,0xbf80,0x3f803f80,0x3f80,0xbf803f80,0x3f80,0x3f803f80,0xbf80,0xbf803f80,0xbf80,
0xbf7bbf80,0x3e48bf80,0x3f7bbf80,0xbe48bf80,0xbf55bf6d,0xbf0e3f6d,0x3f55bf6d,0x3f0e3f6d,0xbf0ebf35,0x3f55bf35,0x3f0ebf35,0xbf55bf35,0xbe48bec4,0xbf7b3ec4,0x3e48bec4,0x3f7b3ec4,
0x3f6d3f80,0xbec43f80,0xbf6d3f80,0x3ec43f80,0x3ec43f35,0x3f6dbf35,0xbec43f35,0xbf6dbf35,0xbec40000,0xbf6d0000,0x3ec40000,0x3f6d0000,0xbf6dbf35,0x3ec43f35,0x3f6dbf35,0xbec43f35,
0xbf55bf80,0x3f0ebf80,0x3f55bf80,0xbf0ebf80,0x3e48bec4,0xbf7b3ec4,0xbe48bec4,0x3f7b3ec4,0x3f7b3f35,0x3e483f35,0xbf7b3f35,0xbe483f35,0x3f0e3f6d,0x3f55bf6d,0xbf0e3f6d,0xbf55bf6d,
0x3f353f80,0xbf353f80,0xbf353f80,0x3f353f80,0xbf350000,0x3f350000,0x3f350000,0xbf350000,0xbf35bf80,0x3f35bf80,0x3f35bf80,0xbf35bf80,0x3f350000,0xbf350000,0xbf350000,0x3f350000,
0xbf0ebf80,0x3f55bf80,0x3f0ebf80,0xbf55bf80,0x3f7b3ec4,0xbe48bec4,0xbf7b3ec4,0x3e48bec4,0xbe483f35,0xbf7b3f35,0x3e483f35,0x3f7b3f35,0xbf55bf6d,0xbf0e3f6d,0x3f55bf6d,0x3f0e3f6d,
0x3ec43f80,0xbf6d3f80,0xbec43f80,0x3f6d3f80,0xbf6dbf35,0xbec43f35,0x3f6dbf35,0x3ec43f35,0x3f6d0000,0x3ec40000,0xbf6d0000,0xbec40000,0xbec43f35,0x3f6dbf35,0x3ec43f35,0xbf6dbf35,
0xbe48bf80,0x3f7bbf80,0x3e48bf80,0xbf7bbf80,0x3f0e3f6d,0x3f55bf6d,0xbf0e3f6d,0xbf55bf6d,0xbf55bf35,0x3f0ebf35,0x3f55bf35,0xbf0ebf35,0x3f7b3ec4,0x3e48bec4,0xbf7b3ec4,0xbe48bec4,
0x3f803f80,0x3f80,0xbf803f80,0x3f80,0x3f803f80,0xbf80,0xbf803f80,0xbf80,0x3f803f80,0x3f80,0xbf803f80,0x3f80,0x3f803f80,0xbf80,0xbf803f80,0xbf80,
0x3e480000,0x3f7b0000,0xbe480000,0xbf7b0000,0x3f0e3ec4,0xbf55bec4,0xbf0e3ec4,0x3f55bec4,0x3f553f35,0x3f0e3f35,0xbf553f35,0xbf0e3f35,0x3f7b3f6d,0xbe48bf6d,0xbf7b3f6d,0x3e48bf6d,
0xbf6dbf80,0x3ec4bf80,0x3f6dbf80,0xbec4bf80,0xbec4bf35,0xbf6d3f35,0x3ec4bf35,0x3f6d3f35,0x3ec40000,0x3f6d0000,0xbec40000,0xbf6d0000,0x3f6d3f35,0xbec4bf35,0xbf6d3f35,0x3ec4bf35,
0xbf0e0000,0xbf550000,0x3f0e0000,0x3f550000,0xbf7bbf6d,0xbe483f6d,0x3f7bbf6d,0x3e483f6d,0xbe48bf35,0x3f7bbf35,0x3e48bf35,0xbf7bbf35,0x3f553ec4,0xbf0ebec4,0xbf553ec4,0x3f0ebec4,
0x3f353f80,0xbf353f80,0xbf353f80,0x3f353f80,0xbf350000,0x3f350000,0x3f350000,0xbf350000,0xbf35bf80,0x3f35bf80,0x3f35bf80,0xbf35bf80,0x3f350000,0xbf350000,0xbf350000,0x3f350000,
0x3f550000,0x3f0e0000,0xbf550000,0xbf0e0000,0x3e483f6d,0x3f7bbf6d,0xbe483f6d,0xbf7bbf6d,0xbf7bbf35,0x3e48bf35,0x3f7bbf35,0xbe48bf35,0x3f0ebec4,0xbf553ec4,0xbf0ebec4,0x3f553ec4,
0xbec4bf80,0x3f6dbf80,0x3ec4bf80,0xbf6dbf80,0x3f6d3f35,0x3ec4bf35,0xbf6d3f35,0xbec4bf35,0xbf6d0000,0xbec40000,0x3f6d0000,0x3ec40000,0x3ec4bf35,0xbf6d3f35,0xbec4bf35,0x3f6d3f35,
0xbf7b0000,0xbe480000,0x3f7b0000,0x3e480000,0x3f55bec4,0xbf0e3ec4,0xbf55bec4,0x3f0e3ec4,0xbf0e3f35,0xbf553f35,0x3f0e3f35,0x3f553f35,0x3e48bf6d,0xbf7b3f6d,0xbe48bf6d,0x3f7b3f6d,
0,0x3f800000,0,0xbf800000,0,0xbf800000,0,0x3f800000,0,0x3f800000,0,0xbf800000,0,0xbf800000,0,0x3f800000,
0x3e480000,0x3f7b0000,0xbe480000,0xbf7b0000,0x3f0e3ec4,0xbf55bec4,0xbf0e3ec4,0x3f55bec4,0x3f553f35,0x3f0e3f35,0xbf553f35,0xbf0e3f35,0x3f7b3f6d,0xbe48bf6d,0xbf7b3f6d,0x3e48bf6d,
0x3ec40000,0x3f6d0000,0xbec40000,0xbf6d0000,0x3f6d3f35,0xbec4bf35,0xbf6d3f35,0x3ec4bf35,0x3f6d3f80,0xbec43f80,0xbf6d3f80,0x3ec43f80,0x3ec43f35,0x3f6dbf35,0xbec43f35,0xbf6dbf35,
0x3f0e0000,0x3f550000,0xbf0e0000,0xbf550000,0x3f7b3f6d,0x3e48bf6d,0xbf7b3f6d,0xbe48bf6d,0x3e483f35,0xbf7b3f35,0xbe483f35,0x3f7b3f35,0xbf55bec4,0x3f0e3ec4,0x3f55bec4,0xbf0e3ec4,
0x3f350000,0x3f350000,0xbf350000,0xbf350000,0x3f353f80,0x3f35bf80,0xbf353f80,0xbf35bf80,0xbf350000,0xbf350000,0x3f350000,0x3f350000,0xbf35bf80,0xbf353f80,0x3f35bf80,0x3f353f80,
0x3f550000,0x3f0e0000,0xbf550000,0xbf0e0000,0x3e483f6d,0x3f7bbf6d,0xbe483f6d,0xbf7bbf6d,0xbf7bbf35,0x3e48bf35,0x3f7bbf35,0xbe48bf35,0x3f0ebec4,0xbf553ec4,0xbf0ebec4,0x3f553ec4,
0x3f6d0000,0x3ec40000,0xbf6d0000,0xbec40000,0xbec43f35,0x3f6dbf35,0x3ec43f35,0xbf6dbf35,0xbec4bf80,0x3f6dbf80,0x3ec4bf80,0xbf6dbf80,0x3f6d3f35,0x3ec4bf35,0xbf6d3f35,0xbec4bf35,
0x3f7b0000,0x3e480000,0xbf7b0000,0xbe480000,0xbf553ec4,0x3f0ebec4,0x3f553ec4,0xbf0ebec4,0x3f0ebf35,0x3f55bf35,0xbf0ebf35,0xbf55bf35,0xbe483f6d,0x3f7bbf6d,0x3e483f6d,0xbf7bbf6d,
0,0x3f800000,0,0xbf800000,0,0xbf800000,0,0x3f800000,0,0x3f800000,0,0xbf800000,0,0xbf800000,0,0x3f800000,
0x3f7b3f80,0xbe483f80,0xbf7b3f80,0x3e483f80,0x3f553f6d,0x3f0ebf6d,0xbf553f6d,0xbf0ebf6d,0x3f0e3f35,0xbf553f35,0xbf0e3f35,0x3f553f35,0x3e483ec4,0x3f7bbec4,0xbe483ec4,0xbf7bbec4,
0xbec40000,0xbf6d0000,0x3ec40000,0x3f6d0000,0xbf6dbf35,0x3ec43f35,0x3f6dbf35,0xbec43f35,0xbf6dbf80,0x3ec4bf80,0x3f6dbf80,0xbec4bf80,0xbec4bf35,0xbf6d3f35,0x3ec4bf35,0x3f6d3f35,
0xbf55bf80,0x3f0ebf80,0x3f55bf80,0xbf0ebf80,0x3e48bec4,0xbf7b3ec4,0xbe48bec4,0x3f7b3ec4,0x3f7b3f35,0x3e483f35,0xbf7b3f35,0xbe483f35,0x3f0e3f6d,0x3f55bf6d,0xbf0e3f6d,0xbf55bf6d,
0x3f350000,0x3f350000,0xbf350000,0xbf350000,0x3f353f80,0x3f35bf80,0xbf353f80,0xbf35bf80,0xbf350000,0xbf350000,0x3f350000,0x3f350000,0xbf35bf80,0xbf353f80,0x3f35bf80,0x3f353f80,
0x3f0e3f80,0xbf553f80,0xbf0e3f80,0x3f553f80,0xbf7bbec4,0x3e483ec4,0x3f7bbec4,0xbe483ec4,0x3e48bf35,0x3f7bbf35,0xbe48bf35,0xbf7bbf35,0x3f553f6d,0x3f0ebf6d,0xbf553f6d,0xbf0ebf6d,
0xbf6d0000,0xbec40000,0x3f6d0000,0x3ec40000,0x3ec4bf35,0xbf6d3f35,0xbec4bf35,0x3f6d3f35,0x3ec43f80,0xbf6d3f80,0xbec43f80,0x3f6d3f80,0xbf6dbf35,0xbec43f35,0x3f6dbf35,0x3ec43f35,
0xbe48bf80,0x3f7bbf80,0x3e48bf80,0xbf7bbf80,0x3f0e3f6d,0x3f55bf6d,0xbf0e3f6d,0xbf55bf6d,0xbf55bf35,0x3f0ebf35,0x3f55bf35,0xbf0ebf35,0x3f7b3ec4,0x3e48bec4,0xbf7b3ec4,0xbe48bec4,
0,0x3f800000,0,0xbf800000,0,0xbf800000,0,0x3f800000,0,0x3f800000,0,0xbf800000,0,0xbf800000,0,0x3f800000,
0xbe480000,0xbf7b0000,0x3e480000,0x3f7b0000,0xbf0ebec4,0x3f553ec4,0x3f0ebec4,0xbf553ec4,0xbf55bf35,0xbf0ebf35,0x3f55bf35,0x3f0ebf35,0xbf7bbf6d,0x3e483f6d,0x3f7bbf6d,0xbe483f6d,
0x3ec40000,0x3f6d0000,0xbec40000,0xbf6d0000,0x3f6d3f35,0xbec4bf35,0xbf6d3f35,0x3ec4bf35,0x3f6d3f80,0xbec43f80,0xbf6d3f80,0x3ec43f80,0x3ec43f35,0x3f6dbf35,0xbec43f35,0xbf6dbf35,
0xbf0e0000,0xbf550000,0x3f0e0000,0x3f550000,0xbf7bbf6d,0xbe483f6d,0x3f7bbf6d,0x3e483f6d,0xbe48bf35,0x3f7bbf35,0x3e48bf35,0xbf7bbf35,0x3f553ec4,0xbf0ebec4,0xbf553ec4,0x3f0ebec4,
0x3f350000,0x3f350000,0xbf350000,0xbf350000,0x3f353f80,0x3f35bf80,0xbf353f80,0xbf35bf80,0xbf350000,0xbf350000,0x3f350000,0x3f350000,0xbf35bf80,0xbf353f80,0x3f35bf80,0x3f353f80,
0xbf550000,0xbf0e0000,0x3f550000,0x3f0e0000,0xbe48bf6d,0xbf7b3f6d,0x3e48bf6d,0x3f7b3f6d,0x3f7b3f35,0xbe483f35,0xbf7b3f35,0x3e483f35,0xbf0e3ec4,0x3f55bec4,0x3f0e3ec4,0xbf55bec4,
0x3f6d0000,0x3ec40000,0xbf6d0000,0xbec40000,0xbec43f35,0x3f6dbf35,0x3ec43f35,0xbf6dbf35,0xbec4bf80,0x3f6dbf80,0x3ec4bf80,0xbf6dbf80,0x3f6d3f35,0x3ec4bf35,0xbf6d3f35,0xbec4bf35,
0xbf7b0000,0xbe480000,0x3f7b0000,0x3e480000,0x3f55bec4,0xbf0e3ec4,0xbf55bec4,0x3f0e3ec4,0xbf0e3f35,0xbf553f35,0x3f0e3f35,0x3f553f35,0x3e48bf6d,0xbf7b3f6d,0xbe48bf6d,0x3f7b3f6d,
0,0x3f800000,0,0xbf800000,0,0xbf800000,0,0x3f800000,0,0x3f800000,0,0xbf800000,0,0xbf800000,0,0x3f800000,
0xbf7bbf80,0x3e48bf80,0x3f7bbf80,0xbe48bf80,0xbf55bf6d,0xbf0e3f6d,0x3f55bf6d,0x3f0e3f6d,0xbf0ebf35,0x3f55bf35,0x3f0ebf35,0xbf55bf35,0xbe48bec4,0xbf7b3ec4,0x3e48bec4,0x3f7b3ec4,
0xbec40000,0xbf6d0000,0x3ec40000,0x3f6d0000,0xbf6dbf35,0x3ec43f35,0x3f6dbf35,0xbec43f35,0xbf6dbf80,0x3ec4bf80,0x3f6dbf80,0xbec4bf80,0xbec4bf35,0xbf6d3f35,0x3ec4bf35,0x3f6d3f35,
0x3f553f80,0xbf0e3f80,0xbf553f80,0x3f0e3f80,0xbe483ec4,0x3f7bbec4,0x3e483ec4,0xbf7bbec4,0xbf7bbf35,0xbe48bf35,0x3f7bbf35,0x3e48bf35,0xbf0ebf6d,0xbf553f6d,0x3f0ebf6d,0x3f553f6d,
0x3f350000,0x3f350000,0xbf350000,0xbf350000,0x3f353f80,0x3f35bf80,0xbf353f80,0xbf35bf80,0xbf350000,0xbf350000,0x3f350000,0x3f350000,0xbf35bf80,0xbf353f80,0x3f35bf80,0x3f353f80,
0xbf0ebf80,0x3f55bf80,0x3f0ebf80,0xbf55bf80,0x3f7b3ec4,0xbe48bec4,0xbf7b3ec4,0x3e48bec4,0xbe483f35,0xbf7b3f35,0x3e483f35,0x3f7b3f35,0xbf55bf6d,0xbf0e3f6d,0x3f55bf6d,0x3f0e3f6d,
0xbf6d0000,0xbec40000,0x3f6d0000,0x3ec40000,0x3ec4bf35,0xbf6d3f35,0xbec4bf35,0x3f6d3f35,0x3ec43f80,0xbf6d3f80,0xbec43f80,0x3f6d3f80,0xbf6dbf35,0xbec43f35,0x3f6dbf35,0x3ec43f35,
0x3e483f80,0xbf7b3f80,0xbe483f80,0x3f7b3f80,0xbf0ebf6d,0xbf553f6d,0x3f0ebf6d,0x3f553f6d,0x3f553f35,0xbf0e3f35,0xbf553f35,0x3f0e3f35,0xbf7bbec4,0xbe483ec4,0x3f7bbec4,0x3e483ec4,
0x3f800000,0x3f800000,0x3f800000,0x3f7ec46d,0x3f800000,0x3f800000,0x3f7b14be,0x3f74fa0b,0x3f800000,0x3f800000,0x3f6c835e,0x3f61c598,0x3f800000,0x3f800000,0x3f54db31,0x3f45e403,
0x3f800000,0x3f7ffb11,0x3f800000,0x3f7e70b0,0x3f7fec43,0x3f7fd397,0x3f79c79d,0x3f721352,0x3f7fb10f,0x3f7f84ab,0x3f676bd8,0x3f59f26a,0x3f7f4e6d,0x3f7f0e58,0x3f49d112,0x3f373a23,
0x3f800000,0x3f7fec43,0x3f800000,0x3f7e1324,0x3f7fb10f,0x3f7f4e6d,0x3f7853f8,0x3f6ed89e,0x3f7ec46d,0x3f7e1324,0x3f61c598,0x3f514d3d,0x3f7d3aac,0x3f7c3b28,0x3f3daef9,0x3f273656,
0x3f800000,0x3f7fd397,0x3f800000,0x3f7dabcc,0x3f7f4e6d,0x3f7e70b0,0x3f76ba07,0x3f6b4b0c,0x3f7d3aac,0x3f7baccd,0x3f5b941a,0x3f47de65,0x3f79c79d,0x3f778bc5,0x3f3085bb,0x3f15f6d9,
0x3f800000,0x3f7fb10f,0x3f800000,0x3f7d3aac,0x3f7ec46d,0x3f7d3aac,0x3f74fa0b,0x3f676bd8,0x3f7b14be,0x3f7853f8,0x3f54db31,0x3f3daef9,0x3f74fa0b,0x3f710908,0x3f226799,0x3f039c3d,
0x3f800000,0x3f7f84ab,0x3f800000,0x3f7cbfc9,0x3f7e1324,0x3f7baccd,0x3f731447,0x3f633c5a,0x3f7853f8,0x3f740bdd,0x3f4d9f02,0x3f32c8c9,0x3f6ed89e,0x3f68bf3c,0x3f13682a,0x3ee0924f,
0x3f800000,0x3f7f4e6d,0x3f800000,0x3f7c3b28,0x3f7d3aac,0x3f79c79d,0x3f710908,0x3f5ebe05,0x3f74fa0b,0x3f6ed89e,0x3f45e403,0x3f273656,0x3f676bd8,0x3f5ebe05,0x3f039c3d,0x3eb8442a,
0x3f800000,0x3f7f0e58,0x3f800000,0x3f7baccd,0x3f7c3b28,0x3f778bc5,0x3f6ed89e,0x3f59f26a,0x3f710908,0x3f68bf3c,0x3f3daef9,0x3f1b02c6,0x3f5ebe05,0x3f531849,0x3ee63375,0x3e8e9a22,
0x3f800000,0x3f800000,0x3f3504f3,0x3f226799,0x3f800000,0x3f800000,0x3f0e39da,0x3ef15aea,0x3f800000,0x3f800000,0x3ec3ef15,0x3e94a031,0x3f800000,0x3f800000,0x3e47c5c2,0x3dc8bd36,
0x3f7ec46d,0x3f7e70b0,0x3f226799,0x3f0b9a6b,0x3f7e1324,0x3f7dabcc,0x3ee63375,0x3eb263ef,0x3f7d3aac,0x3f7cbfc9,0x3e78cfcc,0x3e09cf86,0x3f7c3b28,0x3f7baccd,0x3cc90ab0,0xbdafb680,
0x3f7b14be,0x3f79c79d,0x3f0e39da,0x3ee63375,0x3f7853f8,0x3f76ba07,0x3eac7cd4,0x3e605c13,0x3f74fa0b,0x3f731447,0x3dc8bd36,0xbcc90ab0,0x3f710908,0x3f6ed89e,0xbe164083,0xbe888e93,
0x3f74fa0b,0x3f721352,0x3ef15aea,0x3eb263ef,0x3f6ed89e,0x3f6b4b0c,0x3e605c13,0x3dafb680,0x3f676bd8,0x3f633c5a,0xbd48fb30,0xbe3b6ecf,0x3f5ebe05,0x3f59f26a,0xbea09ae5,0xbee0924f,
0x3f6c835e,0x3f676bd8,0x3ec3ef15,0x3e78cfcc,0x3f61c598,0x3f5b941a,0x3dc8bd36,0xbd48fb30,0x3f54db31,0x3f4d9f02,0xbe47c5c2,0xbeac7cd4,0x3f45e403,0x3f3daef9,0xbef15aea,0xbf187fc0,
0x3f61c598,0x3f59f26a,0x3e94a031,0x3e09cf86,0x3f514d3d,0x3f47de65,0xbcc90ab0,0xbe3b6ecf,0x3f3daef9,0x3f32c8c9,0xbeac7cd4,0xbef6e0cb,0x3f273656,0x3f1b02c6,0xbf1d7fd1,0xbf3b8f3b,
0x3f54db31,0x3f49d112,0x3e47c5c2,0x3cc90ab0,0x3f3daef9,0x3f3085bb,0xbe164083,0xbea09ae5,0x3f226799,0x3f13682a,0xbef15aea,0xbf1d7fd1,0x3f039c3d,0x3ee63375,0xbf3daef9,0xbf584853,
0x3f45e403,0x3f373a23,0x3dc8bd36,0xbdafb680,0x3f273656,0x3f15f6d9,0xbe888e93,0xbee0924f,0x3f039c3d,0x3ee0924f,0xbf187fc0,0xbf3b8f3b,0x3eb8442a,0x3e8e9a22,0xbf584853,0xbf6db293,
0x3f800000,0x3f800000,0,0xbdc8bd36,0x3f800000,0x3f800000,0xbe47c5c2,0xbe94a031,0x3f800000,0x3f800000,0xbec3ef15,0xbef15aea,0x3f800000,0x3f800000,0xbf0e39da,0xbf226799,
0x3f7b14be,0x3f7a7302,0xbe47c5c2,0xbe9aa086,0x3f79c79d,0x3f791298,0xbecf7bca,0xbf00e7e4,0x3f7853f8,0x3f778bc5,0xbf187fc0,0xbf2e3bde,0x3f76ba07,0x3f75dec6,0xbf41d870,0xbf531849,
0x3f6c835e,0x3f6a09a7,0xbec3ef15,0xbefc5d27,0x3f676bd8,0x3f64aa59,0xbf187fc0,0xbf3085bb,0x3f61c598,0x3f5ebe05,0xbf45e403,0xbf584853,0x3f5b941a,0x3f584853,0xbf676bd8,0xbf731447,
0x3f54db31,0x3f4f7a1f,0xbf0e39da,0xbf299415,0x3f49d112,0x3f43e200,0xbf41d870,0xbf5695e5,0x3f3daef9,0x3f373a23,0xbf676bd8,0xbf740bdd,0x3f3085bb,0x3f299415,0xbf7c3b28,0xbf7fd397,
0x3f3504f3,0x3f2beb4a,0xbf3504f3,0xbf4d9f02,0x3f226799,0x3f187fc0,0xbf61c598,0xbf710908,0x3f0e39da,0x3f039c3d,0xbf7b14be,0xbf7fb10f,0x3ef15aea,0x3edae880,0xbf7ec46d,0xbf7853f8,
0x3f0e39da,0x3f00e7e4,0xbf54db31,0xbf68bf3c,0x3ee63375,0x3ec9b953,0xbf76ba07,0xbf7e70b0,0x3eac7cd4,0x3e8e9a22,0xbf7fb10f,0xbf7a7302,0x3e605c13,0x3e22abb6,0xbf6ed89e,0xbf5d2d53,
0x3ec3ef15,0x3ea09ae5,0xbf6c835e,0xbf79c79d,0x3e78cfcc,0x3e2f10a2,0xbf7fb10f,0xbf7e1324,0x3dc8bd36,0x3cc90ab0,0xbf74fa0b,0xbf64aa59,0xbd48fb30,0xbdfab273,0xbf4d9f02,0xbf3085bb,
0x3e47c5c2,0x3de1bc2e,0xbf7b14be,0xbf7ffb11,0x3cc90ab0,0xbd7b2b74,0xbf7c3b28,0xbf6ff573,0xbe164083,0xbe6c9a7f,0xbf5b941a,0xbf3fc767,0xbea09ae5,0xbec9b953,0xbf1d7fd1,0xbeebcbbb,
0x3f800000,0x3f800000,0xbf3504f3,0xbf45e403,0x3f800000,0x3f800000,0xbf54db31,0xbf61c598,0x3f800000,0x3f800000,0xbf6c835e,0xbf74fa0b,0x3f800000,0x3f800000,0xbf7b14be,0xbf7ec46d,
0x3f74fa0b,0x3f740bdd,0xbf61c598,0xbf6db293,0x3f731447,0x3f721352,0xbf76ba07,0xbf7cbfc9,0x3f710908,0x3f6ff573,0xbf7fb10f,0xbf7f84ab,0x3f6ed89e,0x3f6db293,0xbf7c3b28,0xbf75dec6,
0x3f54db31,0x3f514d3d,0xbf7b14be,0xbf7f4e6d,0x3f4d9f02,0x3f49d112,0xbf7fb10f,0xbf7c3b28,0x3f45e403,0x3f41d870,0xbf74fa0b,0xbf6a09a7,0x3f3daef9,0x3f396842,0xbf5b941a,0xbf49d112,
0x3f226799,0x3f1b02c6,0xbf7ec46d,0xbf791298,0x3f13682a,0x3f0b9a6b,0xbf6ed89e,0xbf604621,0x3f039c3d,0x3ef6e0cb,0xbf4d9f02,0xbf373a23,0x3ee63375,0x3ed53641,0xbf1d7fd1,0xbf00e7e4,
0x3ec3ef15,0x3eac7cd4,0xbf6c835e,0xbf5b941a,0x3e94a031,0x3e78cfcc,0xbf45e403,0xbf2beb4a,0x3e47c5c2,0x3e164083,0xbf0e39da,0xbedae880,0x3dc8bd36,0x3d48fb30,0xbe94a031,0xbe164083,
0x3dc8bd36,0x3d16c32c,0xbf45e403,0xbf299415,0xbcc90ab0,0xbdafb680,0xbf08f59b,0xbec9b953,0xbe164083,0xbe541501,0xbe78cfcc,0xbdafb680,0xbe888e93,0xbea68f12,0x3d96a905,0x3e6c9a7f,
0xbe47c5c2,0xbe888e93,0xbf0e39da,0xbecf7bca,0xbeac7cd4,0xbecf7bca,0xbe78cfcc,0xbd96a905,0xbef15aea,0xbf08f59b,0x3dc8bd36,0x3e888e93,0xbf187fc0,0xbf273656,0x3edae880,0x3f13682a,
0xbef15aea,0xbf0b9a6b,0xbe94a031,0xbde1bc2e,0xbf1d7fd1,0xbf2e3bde,0x3d96a905,0x3e827dc0,0xbf3daef9,0xbf4bbbf8,0x3edae880,0x3f15f6d9,0xbf584853,0xbf633c5a,0x3f396842,0x3f5695e5,
0,0,0,0x3dc8bd36,0,0,0x3e47c5c2,0x3e94a031,0,0,0x3ec3ef15,0x3ef15aea,0,0,0x3f0e39da,0x3f226799,
0,0x3c490e90,0,0x3de1bc2e,0x3cc90ab0,0x3d16c32c,0x3e605c13,0x3ea68f12,0x3d48fb30,0x3d7b2b74,0x3edae880,0x3f064b82,0x3d96a905,0x3dafb680,0x3f1d7fd1,0x3f32c8c9,
0,0x3cc90ab0,0,0x3dfab273,0x3d48fb30,0x3d96a905,0x3e78cfcc,0x3eb8442a,0x3dc8bd36,0x3dfab273,0x3ef15aea,0x3f13682a,0x3e164083,0x3e2f10a2,0x3f2beb4a,0x3f41d870,
0,0x3d16c32c,0,0x3e09cf86,0x3d96a905,0x3de1bc2e,0x3e888e93,0x3ec9b953,0x3e164083,0x3e3b6ecf,0x3f039c3d,0x3f1ff6cb,0x3e605c13,0x3e827dc0,0x3f396842,0x3f4f7a1f,
0,0x3d48fb30,0,0x3e164083,0x3dc8bd36,0x3e164083,0x3e94a031,0x3edae880,0x3e47c5c2,0x3e78cfcc,0x3f0e39da,0x3f2beb4a,0x3e94a031,0x3eac7cd4,0x3f45e403,0x3f5b941a,
0,0x3d7b2b74,0,0x3e22abb6,0x3dfab273,0x3e3b6ecf,0x3ea09ae5,0x3eebcbbb,0x3e78cfcc,0x3e9aa086,0x3f187fc0,0x3f373a23,0x3eb8442a,0x3ed53641,0x3f514d3d,0x3f660f88,
0,0x3d96a905,0,0x3e2f10a2,0x3e164083,0x3e605c13,0x3eac7cd4,0x3efc5d27,0x3e94a031,0x3eb8442a,0x3f226799,0x3f41d870,0x3edae880,0x3efc5d27,0x3f5b941a,0x3f6ed89e,
0,0x3dafb680,0,0x3e3b6ecf,0x3e2f10a2,0x3e827dc0,0x3eb8442a,0x3f064b82,0x3eac7cd4,0x3ed53641,0x3f2beb4a,0x3f4bbbf8,0x3efc5d27,0x3f10d3cd,0x3f64aa59,0x3f75dec6,
0,0,0x3f3504f3,0x3f45e403,0,0,0x3f54db31,0x3f61c598,0,0,0x3f6c835e,0x3f74fa0b,0,0,0x3f7b14be,0x3f7ec46d,
0x3dc8bd36,0x3de1bc2e,0x3f45e403,0x3f5695e5,0x3dfab273,0x3e09cf86,0x3f64aa59,0x3f6ff573,0x3e164083,0x3e22abb6,0x3f7853f8,0x3f7dabcc,0x3e2f10a2,0x3e3b6ecf,0x3f7fec43,0x3f7f0e58,
0x3e47c5c2,0x3e605c13,0x3f54db31,0x3f64aa59,0x3e78cfcc,0x3e888e93,0x3f710908,0x3f79c79d,0x3e94a031,0x3ea09ae5,0x3f7ec46d,0x3f7fec43,0x3eac7cd4,0x3eb8442a,0x3f7d3aac,0x3f76ba07,
0x3e94a031,0x3ea68f12,0x3f61c598,0x3f6ff573,0x3eb8442a,0x3ec9b953,0x3f79c79d,0x3f7f0e58,0x3edae880,0x3eebcbbb,0x3f7fb10f,0x3f7baccd,0x3efc5d27,0x3f064b82,0x3f731447,0x3f660f88,
0x3ec3ef15,0x3edae880,0x3f6c835e,0x3f7853f8,0x3ef15aea,0x3f039c3d,0x3f7ec46d,0x3f7fb10f,0x3f0e39da,0x3f187fc0,0x3f7b14be,0x3f710908,0x3f226799,0x3f2beb4a,0x3f61c598,0x3f4d9f02,
0x3ef15aea,0x3f064b82,0x3f74fa0b,0x3f7dabcc,0x3f13682a,0x3f1ff6cb,0x3f7fec43,0x3f7baccd,0x3f2beb4a,0x3f373a23,0x3f710908,0x3f604621,0x3f41d870,0x3f4bbbf8,0x3f49d112,0x3f2e3bde,
0x3f0e39da,0x3f1d7fd1,0x3f7b14be,0x3f7fec43,0x3f2beb4a,0x3f396842,0x3f7d3aac,0x3f731447,0x3f45e403,0x3f514d3d,0x3f61c598,0x3f49d112,0x3f5b941a,0x3f64aa59,0x3f2beb4a,0x3f08f59b,
0x3f226799,0x3f32c8c9,0x3f7ec46d,0x3f7f0e58,0x3f41d870,0x3f4f7a1f,0x3f76ba07,0x3f660f88,0x3f5b941a,0x3f660f88,0x3f4d9f02,0x3f2e3bde,0x3f6ed89e,0x3f75dec6,0x3f08f59b,0x3ebe1d4a,
0,0,0x3f800000,0x3f7ec46d,0,0,0x3f7b14be,0x3f74fa0b,0,0,0x3f6c835e,0x3f61c598,0,0,0x3f54db31,0x3f45e403,
0x3e47c5c2,0x3e541501,0x3f7b14be,0x3f740bdd,0x3e605c13,0x3e6c9a7f,0x3f6a09a7,0x3f5d2d53,0x3e78cfcc,0x3e827dc0,0x3f4d9f02,0x3f3b8f3b,0x3e888e93,0x3e8e9a22,0x3f273656,0x3f10d3cd,
0x3ec3ef15,0x3ecf7bca,0x3f6c835e,0x3f5ebe05,0x3edae880,0x3ee63375,0x3f4d9f02,0x3f396842,0x3ef15aea,0x3efc5d27,0x3f226799,0x3f08f59b,0x3f039c3d,0x3f08f59b,0x3edae880,0x3ea09ae5,
0x3f0e39da,0x3f15f6d9,0x3f54db31,0x3f3fc767,0x3f1d7fd1,0x3f24d225,0x3f273656,0x3f0b9a6b,0x3f2beb4a,0x3f32c8c9,0x3edae880,0x3e9aa086,0x3f396842,0x3f3fc767,0x3e2f10a2,0x3d16c32c,
0x3f3504f3,0x3f3daef9,0x3f3504f3,0x3f187fc0,0x3f45e403,0x3f4d9f02,0x3ef15aea,0x3eac7cd4,0x3f54db31,0x3f5b941a,0x3e47c5c2,0x3d48fb30,0x3f61c598,0x3f676bd8,0xbdc8bd36,0xbe78cfcc,
0x3f54db31,0x3f5d2d53,0x3f0e39da,0x3ed53641,0x3f64aa59,0x3f6b4b0c,0x3e888e93,0x3de1bc2e,0x3f710908,0x3f75dec6,0xbd48fb30,0xbe541501,0x3f79c79d,0x3f7cbfc9,0xbeb8442a,0xbf00e7e4,
0x3f6c835e,0x3f731447,0x3ec3ef15,0x3e605c13,0x3f7853f8,0x3f7c3b28,0x3d48fb30,0xbdfab273,0x3f7ec46d,0x3f7fec43,0xbe94a031,0xbee63375,0x3f7fb10f,0x3f7e1324,0xbf187fc0,0xbf396842,
0x3f7b14be,0x3f7e70b0,0x3e47c5c2,0x3c490e90,0x3f7fec43,0x3f7f84ab,0xbe2f10a2,0xbeb263ef,0x3f7d3aac,0x3f791298,0xbf039c3d,0xbf299415,0x3f731447,0x3f6b4b0c,0xbf49d112,0xbf633c5a,
0,0,0x3f3504f3,0x3f226799,0,0,0x3f0e39da,0x3ef15aea,0,0,0x3ec3ef15,0x3e94a031,0,0,0x3e47c5c2,0x3dc8bd36,
0x3e94a031,0x3e9aa086,0x3ef15aea,0x3ebe1d4a,0x3ea09ae5,0x3ea68f12,0x3e888e93,0x3e22abb6,0x3eac7cd4,0x3eb263ef,0x3d48fb30,0xbd7b2b74,0x3eb8442a,0x3ebe1d4a,0xbe2f10a2,0xbe8e9a22,
0x3f0e39da,0x3f13682a,0x3e47c5c2,0x3d96a905,0x3f187fc0,0x3f1d7fd1,0xbd48fb30,0xbe2f10a2,0x3f226799,0x3f273656,0xbe94a031,0xbecf7bca,0x3f2beb4a,0x3f3085bb,0xbf039c3d,0xbf1d7fd1,
0x3f45e403,0x3f4bbbf8,0xbdc8bd36,0xbe6c9a7f,0x3f514d3d,0x3f5695e5,0xbeb8442a,0xbef6e0cb,0x3f5b941a,0x3f604621,0xbf187fc0,0xbf32c8c9,0x3f64aa59,0x3f68bf3c,0xbf49d112,0xbf5d2d53,
0x3f6c835e,0x3f710908,0xbec3ef15,0xbf039c3d,0x3f74fa0b,0x3f7853f8,0xbf226799,0xbf3daef9,0x3f7b14be,0x3f7d3aac,0xbf54db31,0xbf676bd8,0x3f7ec46d,0x3f7fb10f,0xbf74fa0b,0xbf7d3aac,
0x3f7ec46d,0x3f7fd397,0xbf226799,0xbf3fc767,0x3f7fec43,0x3f7f0e58,0xbf584853,0xbf6b4b0c,0x3f7d3aac,0x3f7a7302,0xbf7853f8,0xbf7f0e58,0x3f76ba07,0x3f721352,0xbf7f4e6d,0xbf791298,
0x3f7b14be,0x3f76ba07,0xbf54db31,0xbf6a09a7,0x3f710908,0x3f6a09a7,0xbf7853f8,0xbf7f4e6d,0x3f61c598,0x3f584853,0xbf7ec46d,0xbf76ba07,0x3f4d9f02,0x3f41d870,0xbf676bd8,0xbf514d3d,
0x3f61c598,0x3f5695e5,0xbf74fa0b,0xbf7e70b0,0x3f49d112,0x3f3b8f3b,0xbf7f4e6d,0xbf778bc5,0x3f2beb4a,0x3f1b02c6,0xbf676bd8,0xbf4f7a1f,0x3f08f59b,0x3eebcbbb,0xbf3085bb,0xbf0b9a6b,
0x3f800000,0x3f7fffb1,0x3f7ffec4,0x3f7ffd39,0x3f7ffb11,0x3f7ff84a,0x3f7ff4e6,0x3f7ff0e3,0x3f7fec43,0x3f7fe705,0x3f7fe129,0x3f7fdaaf,0x3f7fd397,0x3f7fcbe2,0x3f7fc38f,0x3f7fba9e,
0x3f7fb10f,0x3f7fa6e3,0x3f7f9c18,0x3f7f90b1,0x3f7f84ab,0x3f7f7808,0x3f7f6ac7,0x3f7f5ce9,0x3f7f4e6d,0x3f7f3f54,0x3f7f2f9d,0x3f7f1f49,0x3f7f0e58,0x3f7efcc9,0x3f7eea9d,0x3f7ed7d4,
0x3f7ec46d,0x3f7eb069,0x3f7e9bc9,0x3f7e868b,0x3f7e70b0,0x3f7e5a38,0x3f7e4323,0x3f7e2b72,0x3f7e1324,0x3f7dfa38,0x3f7de0b1,0x3f7dc68c,0x3f7dabcc,0x3f7d906e,0x3f7d7474,0x3f7d57de,
0x3f7d3aac,0x3f7d1cdd,0x3f7cfe73,0x3f7cdf6c,0x3f7cbfc9,0x3f7c9f8a,0x3f7c7eb0,0x3f7c5d3a,0x3f7c3b28,0x3f7c187a,0x3f7bf531,0x3f7bd14d,0x3f7baccd,0x3f7b87b2,0x3f7b61fc,0x3f7b3bab,
0x3f7b14be,0x3f7aed37,0x3f7ac516,0x3f7a9c59,0x3f7a7302,0x3f7a4910,0x3f7a1e84,0x3f79f35e,0x3f79c79d,0x3f799b43,0x3f796e4e,0x3f7940c0,0x3f791298,0x3f78e3d6,0x3f78b47b,0x3f788486,
0x3f7853f8,0x3f7822d1,0x3f77f110,0x3f77beb7,0x3f778bc5,0x3f77583a,0x3f772417,0x3f76ef5b,0x3f76ba07,0x3f76841b,0x3f764d97,0x3f76167a,0x3f75dec6,0x3f75a67b,0x3f756d97,0x3f75341d,
0x3f74fa0b,0x3f74bf62,0x3f748422,0x3f74484b,0x3f740bdd,0x3f73ced9,0x3f73913f,0x3f73530e,0x3f731447,0x3f72d4eb,0x3f7294f8,0x3f725470,0x3f721352,0x3f71d19f,0x3f718f57,0x3f714c7a,
0x3f710908,0x3f70c501,0x3f708066,0x3f703b37,0x3f6ff573,0x3f6faf1b,0x3f6f6830,0x3f6f20b0,0x3f6ed89e,0x3f6e8ff8,0x3f6e46be,0x3f6dfcf2,0x3f6db293,0x3f6d67a1,0x3f6d1c1d,0x3f6cd007,
0x3f6c835e,0x3f6c3624,0x3f6be858,0x3f6b99fb,0x3f6b4b0c,0x3f6afb8c,0x3f6aab7b,0x3f6a5ad9,0x3f6a09a7,0x3f69b7e4,0x3f696591,0x3f6912ae,0x3f68bf3c,0x3f686b39,0x3f6816a8,0x3f67c187,
0x3f676bd8,0x3f671599,0x3f66becc,0x3f666771,0x3f660f88,0x3f65b710,0x3f655e0b,0x3f650479,0x3f64aa59,0x3f644fac,0x3f63f473,0x3f6398ac,0x3f633c5a,0x3f62df7b,0x3f628210,0x3f62241a,
0x3f61c598,0x3f61668a,0x3f6106f2,0x3f60a6cf,0x3f604621,0x3f5fe4e9,0x3f5f8327,0x3f5f20db,0x3f5ebe05,0x3f5e5aa6,0x3f5df6be,0x3f5d924d,0x3f5d2d53,0x3f5cc7d1,0x3f5c61c7,0x3f5bfb34,
0x3f5b941a,0x3f5b2c79,0x3f5ac450,0x3f5a5ba0,0x3f59f26a,0x3f5988ad,0x3f591e6a,0x3f58b3a1,0x3f584853,0x3f57dc7f,0x3f577026,0x3f570348,0x3f5695e5,0x3f5627fe,0x3f55b993,0x3f554aa4,
0x3f54db31,0x3f546b3b,0x3f53fac3,0x3f5389c7,0x3f531849,0x3f52a649,0x3f5233c6,0x3f51c0c2,0x3f514d3d,0x3f50d937,0x3f5064af,0x3f4fefa8,0x3f4f7a1f,0x3f4f0417,0x3f4e8d90,0x3f4e1689,
0x3f4d9f02,0x3f4d26fd,0x3f4cae79,0x3f4c3578,0x3f4bbbf8,0x3f4b41fa,0x3f4ac77f,0x3f4a4c87,0x3f49d112,0x3f495521,0x3f48d8b3,0x3f485bca,0x3f47de65,0x3f476085,0x3f46e22a,0x3f466354,
0x3f45e403,0x3f456439,0x3f44e3f5,0x3f446337,0x3f43e200,0x3f436051,0x3f42de29,0x3f425b89,0x3f41d870,0x3f4154e1,0x3f40d0da,0x3f404c5c,0x3f3fc767,0x3f3f41fc,0x3f3ebc1b,0x3f3e35c5,
0x3f3daef9,0x3f3d27b8,0x3f3ca003,0x3f3c17d9,0x3f3b8f3b,0x3f3b0629,0x3f3a7ca4,0x3f39f2ac,0x3f396842,0x3f38dd65,0x3f385216,0x3f37c655,0x3f373a23,0x3f36ad7f,0x3f36206c,0x3f3592e7,
0x3f3504f3,0x3f34768f,0x3f33e7bc,0x3f33587a,0x3f32c8c9,0x3f3238aa,0x3f31a81d,0x3f311722,0x3f3085bb,0x3f2ff3e6,0x3f2f61a5,0x3f2ecef7,0x3f2e3bde,0x3f2da859,0x3f2d1469,0x3f2c800f,
0x3f2beb4a,0x3f2b561b,0x3f2ac082,0x3f2a2a80,0x3f299415,0x3f28fd41,0x3f286605,0x3f27ce61,0x3f273656,0x3f269de3,0x3f26050a,0x3f256bcb,0x3f24d225,0x3f24381a,0x3f239da9,0x3f2302d3,
0x3f226799,0x3f21cbfb,0x3f212ff9,0x3f209393,0x3f1ff6cb,0x3f1f599f,0x3f1ebc12,0x3f1e1e22,0x3f1d7fd1,0x3f1ce11f,0x3f1c420c,0x3f1ba299,0x3f1b02c6,0x3f1a6293,0x3f19c200,0x3f19210f,
0x3f187fc0,0x3f17de12,0x3f173c07,0x3f16999f,0x3f15f6d9,0x3f1553b7,0x3f14b039,0x3f140c5f,0x3f13682a,0x3f12c39a,0x3f121eb0,0x3f11796b,0x3f10d3cd,0x3f102dd5,0x3f0f8784,0x3f0ee0db,
0x3f0e39da,0x3f0d9281,0x3f0cead0,0x3f0c42c9,0x3f0b9a6b,0x3f0af1b7,0x3f0a48ad,0x3f099f4e,0x3f08f59b,0x3f084b92,0x3f07a136,0x3f06f686,0x3f064b82,0x3f05a02c,0x3f04f484,0x3f044889,
0x3f039c3d,0x3f02ef9f,0x3f0242b1,0x3f019573,0x3f00e7e4,0x3f003a06,0x3eff17b2,0x3efdbabb,0x3efc5d27,0x3efafef7,0x3ef9a02d,0x3ef840c8,0x3ef6e0cb,0x3ef58035,0x3ef41f07,0x3ef2bd43,
0x3ef15aea,0x3eeff7fb,0x3eee9479,0x3eed3063,0x3eebcbbb,0x3eea6681,0x3ee900b7,0x3ee79a5d,0x3ee63375,0x3ee4cbfe,0x3ee363fa,0x3ee1fb6a,0x3ee0924f,0x3edf28a9,0x3eddbe79,0x3edc53c1,
0x3edae880,0x3ed97cb9,0x3ed8106b,0x3ed6a399,0x3ed53641,0x3ed3c867,0x3ed25a09,0x3ed0eb2a,0x3ecf7bca,0x3ece0bea,0x3ecc9b8b,0x3ecb2aae,0x3ec9b953,0x3ec8477c,0x3ec6d529,0x3ec5625c,
0x3ec3ef15,0x3ec27b55,0x3ec1071e,0x3ebf926f,0x3ebe1d4a,0x3ebca7af,0x3ebb31a0,0x3eb9bb1e,0x3eb8442a,0x3eb6ccc3,0x3eb554ec,0x3eb3dca5,0x3eb263ef,0x3eb0eacb,0x3eaf713a,0x3eadf73c,
0x3eac7cd4,0x3eab0201,0x3ea986c4,0x3ea80b1f,0x3ea68f12,0x3ea5129f,0x3ea395c5,0x3ea21887,0x3ea09ae5,0x3e9f1cdf,0x3e9d9e78,0x3e9c1faf,0x3e9aa086,0x3e9920fe,0x3e97a117,0x3e9620d2,
0x3e94a031,0x3e931f35,0x3e919ddd,0x3e901c2c,0x3e8e9a22,0x3e8d17c0,0x3e8b9507,0x3e8a11f7,0x3e888e93,0x3e870ada,0x3e8586ce,0x3e840270,0x3e827dc0,0x3e80f8c0,0x3e7ee6e1,0x3e7bdba4,
0x3e78cfcc,0x3e75c35a,0x3e72b651,0x3e6fa8b2,0x3e6c9a7f,0x3e698bba,0x3e667c66,0x3e636c83,0x3e605c13,0x3e5d4b1a,0x3e5a3997,0x3e57278f,0x3e541501,0x3e5101f1,0x3e4dee60,0x3e4ada4f,
0x3e47c5c2,0x3e44b0b9,0x3e419b37,0x3e3e853e,0x3e3b6ecf,0x3e3857ec,0x3e354098,0x3e3228d4,0x3e2f10a2,0x3e2bf804,0x3e28defc,0x3e25c58c,0x3e22abb6,0x3e1f917b,0x3e1c76de,0x3e195be0,
0x3e164083,0x3e1324ca,0x3e1008b7,0x3e0cec4a,0x3e09cf86,0x3e06b26e,0x3e039502,0x3e007745,0x3dfab273,0x3df475c0,0x3dee3876,0x3de7fa9a,0x3de1bc2e,0x3ddb7d37,0x3dd53db9,0x3dcefdb7,
0x3dc8bd36,0x3dc27c39,0x3dbc3ac3,0x3db5f8da,0x3dafb680,0x3da973ba,0x3da3308c,0x3d9cecf9,0x3d96a905,0x3d9064b4,0x3d8a200a,0x3d83db0a,0x3d7b2b74,0x3d6ea038,0x3d621469,0x3d55880e,
0x3d48fb30,0x3d3c6dd5,0x3d2fe007,0x3d2351cb,0x3d16c32c,0x3d0a342f,0x3cfb49ba,0x3ce22a7a,0x3cc90ab0,0x3cafea69,0x3c96c9b6,0x3c7b514b,0x3c490e90,0x3c16cb58,0x3bc90f88,0x3b490fc6,
0,0x3b490fc6,0x3bc90f88,0x3c16cb58,0x3c490e90,0x3c7b514b,0x3c96c9b6,0x3cafea69,0x3cc90ab0,0x3ce22a7a,0x3cfb49ba,0x3d0a342f,0x3d16c32c,0x3d2351cb,0x3d2fe007,0x3d3c6dd5,
0x3d48fb30,0x3d55880e,0x3d621469,0x3d6ea038,0x3d7b2b74,0x3d83db0a,0x3d8a200a,0x3d9064b4,0x3d96a905,0x3d9cecf9,0x3da3308c,0x3da973ba,0x3dafb680,0x3db5f8da,0x3dbc3ac3,0x3dc27c39,
0x3dc8bd36,0x3dcefdb7,0x3dd53db9,0x3ddb7d37,0x3de1bc2e,0x3de7fa9a,0x3dee3876,0x3df475c0,0x3dfab273,0x3e007745,0x3e039502,0x3e06b26e,0x3e09cf86,0x3e0cec4a,0x3e1008b7,0x3e1324ca,
0x3e164083,0x3e195be0,0x3e1c76de,0x3e1f917b,0x3e22abb6,0x3e25c58c,0x3e28defc,0x3e2bf804,0x3e2f10a2,0x3e3228d4,0x3e354098,0x3e3857ec,0x3e3b6ecf,0x3e3e853e,0x3e419b37,0x3e44b0b9,
0x3e47c5c2,0x3e4ada4f,0x3e4dee60,0x3e5101f1,0x3e541501,0x3e57278f,0x3e5a3997,0x3e5d4b1a,0x3e605c13,0x3e636c83,0x3e667c66,0x3e698bba,0x3e6c9a7f,0x3e6fa8b2,0x3e72b651,0x3e75c35a,
0x3e78cfcc,0x3e7bdba4,0x3e7ee6e1,0x3e80f8c0,0x3e827dc0,0x3e840270,0x3e8586ce,0x3e870ada,0x3e888e93,0x3e8a11f7,0x3e8b9507,0x3e8d17c0,0x3e8e9a22,0x3e901c2c,0x3e919ddd,0x3e931f35,
0x3e94a031,0x3e9620d2,0x3e97a117,0x3e9920fe,0x3e9aa086,0x3e9c1faf,0x3e9d9e78,0x3e9f1cdf,0x3ea09ae5,0x3ea21887,0x3ea395c5,0x3ea5129f,0x3ea68f12,0x3ea80b1f,0x3ea986c4,0x3eab0201,
0x3eac7cd4,0x3eadf73c,0x3eaf713a,0x3eb0eacb,0x3eb263ef,0x3eb3dca5,0x3eb554ec,0x3eb6ccc3,0x3eb8442a,0x3eb9bb1e,0x3ebb31a0,0x3ebca7af,0x3ebe1d4a,0x3ebf926f,0x3ec1071e,0x3ec27b55,
0x3ec3ef15,0x3ec5625c,0x3ec6d529,0x3ec8477c,0x3ec9b953,0x3ecb2aae,0x3ecc9b8b,0x3ece0bea,0x3ecf7bca,0x3ed0eb2a,0x3ed25a09,0x3ed3c867,0x3ed53641,0x3ed6a399,0x3ed8106b,0x3ed97cb9,
0x3edae880,0x3edc53c1,0x3eddbe79,0x3edf28a9,0x3ee0924f,0x3ee1fb6a,0x3ee363fa,0x3ee4cbfe,0x3ee63375,0x3ee79a5d,0x3ee900b7,0x3eea6681,0x3eebcbbb,0x3eed3063,0x3eee9479,0x3eeff7fb,
0x3ef15aea,0x3ef2bd43,0x3ef41f07,0x3ef58035,0x3ef6e0cb,0x3ef840c8,0x3ef9a02d,0x3efafef7,0x3efc5d27,0x3efdbabb,0x3eff17b2,0x3f003a06,0x3f00e7e4,0x3f019573,0x3f0242b1,0x3f02ef9f,
0x3f039c3d,0x3f044889,0x3f04f484,0x3f05a02c,0x3f064b82,0x3f06f686,0x3f07a136,0x3f084b92,0x3f08f59b,0x3f099f4e,0x3f0a48ad,0x3f0af1b7,0x3f0b9a6b,0x3f0c42c9,0x3f0cead0,0x3f0d9281,
0x3f0e39da,0x3f0ee0db,0x3f0f8784,0x3f102dd5,0x3f10d3cd,0x3f11796b,0x3f121eb0,0x3f12c39a,0x3f13682a,0x3f140c5f,0x3f14b039,0x3f1553b7,0x3f15f6d9,0x3f16999f,0x3f173c07,0x3f17de12,
0x3f187fc0,0x3f19210f,0x3f19c200,0x3f1a6293,0x3f1b02c6,0x3f1ba299,0x3f1c420c,0x3f1ce11f,0x3f1d7fd1,0x3f1e1e22,0x3f1ebc12,0x3f1f599f,0x3f1ff6cb,0x3f209393,0x3f212ff9,0x3f21cbfb,
0x3f226799,0x3f2302d3,0x3f239da9,0x3f24381a,0x3f24d225,0x3f256bcb,0x3f26050a,0x3f269de3,0x3f273656,0x3f27ce61,0x3f286605,0x3f28fd41,0x3f299415,0x3f2a2a80,0x3f2ac082,0x3f2b561b,
0x3f2beb4a,0x3f2c800f,0x3f2d1469,0x3f2da859,0x3f2e3bde,0x3f2ecef7,0x3f2f61a5,0x3f2ff3e6,0x3f3085bb,0x3f311722,0x3f31a81d,0x3f3238aa,0x3f32c8c9,0x3f33587a,0x3f33e7bc,0x3f34768f,
0x3f3504f3,0x3f3592e7,0x3f36206c,0x3f36ad7f,0x3f373a23,0x3f37c655,0x3f385216,0x3f38dd65,0x3f396842,0x3f39f2ac,0x3f3a7ca4,0x3f3b0629,0x3f3b8f3b,0x3f3c17d9,0x3f3ca003,0x3f3d27b8,
0x3f3daef9,0x3f3e35c5,0x3f3ebc1b,0x3f3f41fc,0x3f3fc767,0x3f404c5c,0x3f40d0da,0x3f4154e1,0x3f41d870,0x3f425b89,0x3f42de29,0x3f436051,0x3f43e200,0x3f446337,0x3f44e3f5,0x3f456439,
0x3f45e403,0x3f466354,0x3f46e22a,0x3f476085,0x3f47de65,0x3f485bca,0x3f48d8b3,0x3f495521,0x3f49d112,0x3f4a4c87,0x3f4ac77f,0x3f4b41fa,0x3f4bbbf8,0x3f4c3578,0x3f4cae79,0x3f4d26fd,
0x3f4d9f02,0x3f4e1689,0x3f4e8d90,0x3f4f0417,0x3f4f7a1f,0x3f4fefa8,0x3f5064af,0x3f50d937,0x3f514d3d,0x3f51c0c2,0x3f5233c6,0x3f52a649,0x3f531849,0x3f5389c7,0x3f53fac3,0x3f546b3b,
0x3f54db31,0x3f554aa4,0x3f55b993,0x3f5627fe,0x3f5695e5,0x3f570348,0x3f577026,0x3f57dc7f,0x3f584853,0x3f58b3a1,0x3f591e6a,0x3f5988ad,0x3f59f26a,0x3f5a5ba0,0x3f5ac450,0x3f5b2c79,
0x3f5b941a,0x3f5bfb34,0x3f5c61c7,0x3f5cc7d1,0x3f5d2d53,0x3f5d924d,0x3f5df6be,0x3f5e5aa6,0x3f5ebe05,0x3f5f20db,0x3f5f8327,0x3f5fe4e9,0x3f604621,0x3f60a6cf,0x3f6106f2,0x3f61668a,
0x3f61c598,0x3f62241a,0x3f628210,0x3f62df7b,0x3f633c5a,0x3f6398ac,0x3f63f473,0x3f644fac,0x3f64aa59,0x3f650479,0x3f655e0b,0x3f65b710,0x3f660f88,0x3f666771,0x3f66becc,0x3f671599,
0x3f676bd8,0x3f67c187,0x3f6816a8,0x3f686b39,0x3f68bf3c,0x3f6912ae,0x3f696591,0x3f69b7e4,0x3f6a09a7,0x3f6a5ad9,0x3f6aab7b,0x3f6afb8c,0x3f6b4b0c,0x3f6b99fb,0x3f6be858,0x3f6c3624,
0x3f6c835e,0x3f6cd007,0x3f6d1c1d,0x3f6d67a1,0x3f6db293,0x3f6dfcf2,0x3f6e46be,0x3f6e8ff8,0x3f6ed89e,0x3f6f20b0,0x3f6f6830,0x3f6faf1b,0x3f6ff573,0x3f703b37,0x3f708066,0x3f70c501,
0x3f710908,0x3f714c7a,0x3f718f57,0x3f71d19f,0x3f721352,0x3f725470,0x3f7294f8,0x3f72d4eb,0x3f731447,0x3f73530e,0x3f73913f,0x3f73ced9,0x3f740bdd,0x3f74484b,0x3f748422,0x3f74bf62,
0x3f74fa0b,0x3f75341d,0x3f756d97,0x3f75a67b,0x3f75dec6,0x3f76167a,0x3f764d97,0x3f76841b,0x3f76ba07,0x3f76ef5b,0x3f772417,0x3f77583a,0x3f778bc5,0x3f77beb7,0x3f77f110,0x3f7822d1,
0x3f7853f8,0x3f788486,0x3f78b47b,0x3f78e3d6,0x3f791298,0x3f7940c0,0x3f796e4e,0x3f799b43,0x3f79c79d,0x3f79f35e,0x3f7a1e84,0x3f7a4910,0x3f7a7302,0x3f7a9c59,0x3f7ac516,0x3f7aed37,
0x3f7b14be,0x3f7b3bab,0x3f7b61fc,0x3f7b87b2,0x3f7baccd,0x3f7bd14d,0x3f7bf531,0x3f7c187a,0x3f7c3b28,0x3f7c5d3a,0x3f7c7eb0,0x3f7c9f8a,0x3f7cbfc9,0x3f7cdf6c,0x3f7cfe73,0x3f7d1cdd,
0x3f7d3aac,0x3f7d57de,0x3f7d7474,0x3f7d906e,0x3f7dabcc,0x3f7dc68c,0x3f7de0b1,0x3f7dfa38,0x3f7e1324,0x3f7e2b72,0x3f7e4323,0x3f7e5a38,0x3f7e70b0,0x3f7e868b,0x3f7e9bc9,0x3f7eb069,
0x3f7ec46d,0x3f7ed7d4,0x3f7eea9d,0x3f7efcc9,0x3f7f0e58,0x3f7f1f49,0x3f7f2f9d,0x3f7f3f54,0x3f7f4e6d,0x3f7f5ce9,0x3f7f6ac7,0x3f7f7808,0x3f7f84ab,0x3f7f90b1,0x3f7f9c18,0x3f7fa6e3,
0x3f7fb10f,0x3f7fba9e,0x3f7fc38f,0x3f7fcbe2,0x3f7fd397,0x3f7fdaaf,0x3f7fe129,0x3f7fe705,0x3f7fec43,0x3f7ff0e3,0x3f7ff4e6,0x3f7ff84a,0x3f7ffb11,0x3f7ffd39,0x3f7ffec4,0x3f7fffb1,
};

__device__ __forceinline__ int tid_here() { return __shfl_xor_sync(~0u, (int)threadIdx.x, 0); }
__device__ __forceinline__ void ld_tab(uint32_t* d, int chunk) { asm volatile("ld.global.v4.u32 {%0,%1,%2,%3}, [%4];" : "=r"(d[0]), "=r"(d[1]), "=r"(d[2]), "=r"(d[3]) : "l"((const uint4*)g_tab + chunk) : "memory"); }
__device__ __forceinline__ void ld_tab(float* d, int chunk) { asm volatile("ld.global.v4.f32 {%0,%1,%2,%3}, [%4];" : "=f"(d[0]), "=f"(d[1]), "=f"(d[2]), "=f"(d[3]) : "l"((const uint4*)g_tab + chunk) : "memory"); }
__device__ __forceinline__ void fft640(uint32_t plane, uint32_t tab, int lane, const uint32_t* fr, const uint32_t* fi, const float (*tc)[4], const float (*ts)[4], float (*xr)[4], float (*xi)[4]) {
  uint32_t A1[5][4], nfi[4];
#pragma unroll
  for (int i = 0; i < 4; i++) nfi[i] = fi[i] ^ 0x80008000u;
  const uint32_t la = plane + (lane >> 4) * 1280 + (lane & 15) * 80;
#pragma unroll
  for (int j = 0; j < 5; j++) {
    uint32_t r0, r1, i0, i1; ldsm4t(r0, r1, i0, i1, la + j * 16);
    float yr[4], yi[4];
    mmaZ(yr, fr, r0, r1); mmaZ(yi, fi, r0, r1); mmaA(yr, nfi, i0, i1); mmaA(yi, fr, i0, i1);
    float zr[4], zi[4];
#pragma unroll
    for (int e = 0; e < 4; e++) { zr[e] = yr[e] * tc[j][e] - yi[e] * ts[j][e]; zi[e] = yr[e] * ts[j][e] + yi[e] * tc[j][e]; }
    A1[j][0] = pack_bf16(zr[0], zr[1]); A1[j][1] = pack_bf16(zr[2], zr[3]); A1[j][2] = pack_bf16(zi[0], zi[1]); A1[j][3] = pack_bf16(zi[2], zi[3]);
  }
#pragma unroll
  for (int t = 0; t < 5; t++) {
    uint32_t A2[4] = {A1[t][2], A1[t][3], A1[t][0] ^ 0x80008000u, A1[t][1] ^ 0x80008000u};
#pragma unroll
    for (int u = 0; u < 5; u++) {
      uint32_t b0, b1; asm volatile("ld.shared.v2.b32 {%0,%1}, [%2];" : "=r"(b0), "=r"(b1) : "r"(tab + (t * 5 + u) * 256 + lane * 8));
      if (t == 0) { mmaZ(xr[u], A1[t], b0, b1); mmaZ(xi[u], A2, b0, b1); } else { mmaA(xr[u], A1[t], b0, b1); mmaA(xi[u], A2, b0, b1); }
    }
  }
}
__device__ __forceinline__ void ln_row(float* v) {
  float s = 0.f, q = 0.f;
#pragma unroll
  for (int i = 0; i < 20; i++) { s += v[i]; q = fmaf(v[i], v[i], q); }
#pragma unroll
  for (int o = 16; o; o >>= 1) { s += __shfl_xor_sync(~0u, s, o); q += __shfl_xor_sync(~0u, q, o); }
  const float mean = s * (1.f / D_), rs = rsqrtf(fmaxf(fmaf(-mean, mean, q * (1.f / D_)), 0.f) + 1e-5f), nb = -mean * rs;
#pragma unroll
  for (int i = 0; i < 20; i++) v[i] = fmaf(v[i], rs, nb);
}

#define TLBASE (1024 + 896)
struct AParams { const bf16* x; uint32_t *Z1, *Z2; const uint32_t* WT; bf16 *x1, *hN; uint32_t* sync; const uint32_t* rowdone; int nw; uint32_t tag; };
constexpr int SY_1 = 0, SY_2 = 32, SY_3 = 64, SY_W = 96;
__device__ __forceinline__ void red_release(uint32_t* p) { asm volatile("red.release.gpu.global.add.u32 [%0], 1;" :: "l"(p) : "memory"); }
__device__ __forceinline__ void red_relaxed(uint32_t* p) { asm volatile("red.relaxed.gpu.global.add.u32 [%0], 1;" :: "l"(p) : "memory"); }
__device__ __forceinline__ void spin_count(const uint32_t* p, uint32_t n) {
  uint32_t v; int guard = 0;
#pragma unroll 1
  do { asm volatile("ld.relaxed.gpu.global.u32 %0, [%1];" : "=r"(v) : "l"(p) : "memory"); } while (v < n && ++guard < 400000);
}

__device__ __forceinline__ void filter_prep(uint32_t* WT, uint32_t sm, int k2) {
  const int tid = threadIdx.x, r = (tid >> 5) & 3;
  const uint32_t src = sm + (8 * (tid & 3) + r) * 642;
#pragma unroll 2
  for (int f = (tid >> 7) * 8 + ((tid & 31) >> 2); f < 321; f += 24) {
    uint32_t v[4];
#pragma unroll
    for (int i = 0; i < 4; i++) {
      unsigned short lo, hi;
      const uint32_t a = src + f * 2 + ((i >> 1) * 4 + (i & 1) * 32) * 642;
      asm volatile("ld.shared.u16 %0, [%1];" : "=h"(lo) : "r"(a)); asm volatile("ld.shared.u16 %0, [%1];" : "=h"(hi) : "r"(a + 41088));
      v[i] = lo | ((uint32_t)hi << 16);
    }
    stg128(WT + f * 2048 + k2 * 64 + r * 16 + (tid & 3) * 4, v[0], v[1], v[2], v[3]);
  }
}

template <typename F> __device__ __forceinline__ void a_phase2(const AParams& a, float* buf, int f, F hook) {
  const int t0 = tid_here(), tid = (t0 + (t0 >> 7) * 32) & 127  , lane = tid & 31, w = tid >> 5, g = lane >> 2, q = lane & 3, barid = 5 + (t0 >> 7);
  const int f2 = (640 - f) % 640;
#define WGBAR() asm volatile("bar.sync %0, 128;" :: "r"(barid) : "memory")
  uint32_t fr[4], fi[4], nfi[4], br[4][4], bi[4][4];
  float tc[4][4], ts[4][4], wc[4], ws[4];
  ld_tab(wc, TB_2048 + tid); ld_tab(ws, TB_2048 + 128 + tid); ld_tab(fr, TB_F16 + lane); ld_tab(fi, TB_F16 + 32 + lane);
#pragma unroll
  for (int j = 0; j < 4; j++) { ld_tab(tc[j], TB_512 + j * 32 + lane); ld_tab(ts[j], TB_512 + 128 + j * 32 + lane); }
  if (tid == 32 && !a.nw) l2_prefetch(a.WT + f * 2048, 8192);
  const uint32_t* zs[4];
#pragma unroll
  for (int j = 0; j < 4; j++) { const int m = j * 256 + 2 * tid; zs[j] = a.Z1 + (j == 3 && w == 3 && !a.nw ? 86 * 7680 + (m / 4 - 240) * 2560 + m % 4 : (m / 12) * 7680 + m % 12); }
  const int st3 = w == 3 && !a.nw ? 4 : 12;
  if (tid == 0) spin_count(a.sync + SY_1, 80);
  WGBAR();
  if (w == 3) { spin_count(a.sync + SY_1 + 16, a.nw ? 6 : 16); TL(6); }
  const uint32_t sbuf = smem_u32(buf);
  {
    uint2 P[4], Q[4];
#pragma unroll 1
    for (int guard = 0; guard < 100000; guard++) {
      uint32_t bad = 0;
#pragma unroll
      for (int j = 0; j < 4; j++) {
        asm volatile("ld.relaxed.gpu.global.v2.u32 {%0,%1}, [%2];" : "=r"(P[j].x), "=r"(P[j].y) : "l"(zs[j] + f * (j == 3 ? st3 : 12)) : "memory");
        asm volatile("ld.relaxed.gpu.global.v2.u32 {%0,%1}, [%2];" : "=r"(Q[j].x), "=r"(Q[j].y) : "l"(zs[j] + f2 * (j == 3 ? st3 : 12)) : "memory");
      }
#pragma unroll
      for (int j = 0; j < 4; j++) bad |= (P[j].x ^ a.tag) | (Q[j].x ^ a.tag);
      if (__all_sync(~0u, !(bad & 1))) break;
    }
    float ur[4][4], ui[4][4];
#pragma unroll
    for (int i = 0; i < 4; i++) {
      float ar[4], ai[4];
#pragma unroll
      for (int j = 0; j < 4; j++) {
        const uint32_t p = (i >> 1) ? P[j].y : P[j].x, z = (i >> 1) ? Q[j].y : Q[j].x;
        if (!(i & 1)) { ar[j] = bf_lo(p) + bf_lo(z); ai[j] = bf_hi(p) - bf_hi(z); }
        else { ar[j] = bf_hi(p) + bf_hi(z); ai[j] = bf_lo(z) - bf_lo(p); }
      }
      const float s0r = ar[0] + ar[2], s0i = ai[0] + ai[2], d0r = ar[0] - ar[2], d0i = ai[0] - ai[2];
      const float s1r = ar[1] + ar[3], s1i = ai[1] + ai[3], d1r = ar[1] - ar[3], d1i = ai[1] - ai[3];
      ur[0][i] = s0r + s1r; ui[0][i] = s0i + s1i;
      const float vr[3] = {d0r + d1i, s0r - s1r, d0r - d1i}, vi[3] = {d0i - d1r, s0i - s1i, d0i + d1r};
      const float c2 = wc[i] * wc[i] - ws[i] * ws[i], s2 = 2.f * wc[i] * ws[i];
      const float twc[4] = {1.f, wc[i], c2, c2 * wc[i] - s2 * ws[i]}, tws[4] = {0.f, ws[i], s2, s2 * wc[i] + c2 * ws[i]};
#pragma unroll
      for (int r = 1; r < 4; r++) { const float c = twc[r], s = tws[r]; ur[r][i] = vr[r - 1] * c + vi[r - 1] * s; ui[r][i] = vi[r - 1] * c - vr[r - 1] * s; }
    }
    const uint32_t o = sbuf + (tid >> 3) * 80 + (tid & 7) * 8;
#pragma unroll
    for (int r = 0; r < 4; r++) {
      asm volatile("st.shared.v2.b32 [%0], {%1,%2};" :: "r"(o + r * 5120), "r"(pack_bf16(ur[r][0], ur[r][1])), "r"(pack_bf16(ur[r][2], ur[r][3])) : "memory");
      asm volatile("st.shared.v2.b32 [%0], {%1,%2};" :: "r"(o + r * 5120 + 1280), "r"(pack_bf16(ui[r][0], ui[r][1])), "r"(pack_bf16(ui[r][2], ui[r][3])) : "memory");
    }
  }
#pragma unroll
  for (int j = 0; j < 4; j++) { ld_tab(br[j], TB_F32 + j * 32 + lane); ld_tab(bi[j], TB_F32 + 128 + j * 32 + lane); }
  if (a.nw) { if (tid == 0) spin_count(a.sync + SY_W, a.nw); WGBAR(); }
  uint2 wt[8];
#pragma unroll
  for (int i = 0; i < 8; i++) wt[i] = __ldcg((const uint2*)(a.WT + f * 2048 + ((i >> 1) * 8 + 2 * q + (i & 1)) * 64 + w * 16 + g * 2));
  WGBAR();
  hook(1);
  TL(7);
  {
    uint32_t A1[4][4], A2[4][4];
#pragma unroll
    for (int i = 0; i < 4; i++) nfi[i] = fi[i] ^ 0x80008000u;
    const uint32_t la = sbuf + w * 5120 + (lane >> 4) * 1280 + (lane & 15) * 80;
#pragma unroll
    for (int j = 0; j < 4; j++) {
      uint32_t r0, r1, i0, i1; ldsm4t(r0, r1, i0, i1, la + j * 16);
      float yr[4], yi[4];
      mmaZ(yr, fr, r0, r1); mmaZ(yi, fi, r0, r1); mmaA(yr, nfi, i0, i1); mmaA(yi, fr, i0, i1);
      float zr[4], zi[4];
#pragma unroll
      for (int e = 0; e < 4; e++) { zr[e] = yr[e] * tc[j][e] + yi[e] * ts[j][e]; zi[e] = yi[e] * tc[j][e] - yr[e] * ts[j][e]; }
      A1[j][0] = pack_bf16(zr[0], zr[1]); A1[j][1] = pack_bf16(zr[2], zr[3]); A1[j][2] = pack_bf16(zi[0], zi[1]); A1[j][3] = pack_bf16(zi[2], zi[3]);
      A2[j][0] = A1[j][2]; A2[j][1] = A1[j][3]; A2[j][2] = A1[j][0] ^ 0x80008000u; A2[j][3] = A1[j][1] ^ 0x80008000u;
    }
    float xr[4][4], xi[4][4];
#pragma unroll
    for (int t = 0; t < 4; t++)
#pragma unroll
      for (int u = 0; u < 4; u++) {
        if (t == 0) { mmaZ(xr[u], A1[t], br[t][u], bi[t][u]); mmaZ(xi[u], A2[t], br[t][u], bi[t][u]); } else { mmaA(xr[u], A1[t], br[t][u], bi[t][u]); mmaA(xi[u], A2[t], br[t][u], bi[t][u]); }
      }
#pragma unroll
    for (int u = 0; u < 4; u++) {
      const uint32_t wv[4] = {wt[2 * u].x, wt[2 * u + 1].x, wt[2 * u].y, wt[2 * u + 1].y};
      float zr[4], zi[4];
#pragma unroll
      for (int e = 0; e < 4; e++) { const float c = bf_lo(wv[e]), b = bf_hi(wv[e]); zr[e] = xr[u][e] * c - xi[u][e] * b; zi[e] = xr[u][e] * b + xi[u][e] * c; }
      A2[u][2] = pack_bf16(zr[0], zr[1]); A2[u][3] = pack_bf16(zr[2], zr[3]); A2[u][0] = pack_bf16(zi[0], zi[1]); A2[u][1] = pack_bf16(zi[2], zi[3]);
      A1[u][0] = A2[u][2]; A1[u][1] = A2[u][3]; A1[u][2] = A2[u][0] ^ 0x80008000u; A1[u][3] = A2[u][1] ^ 0x80008000u;
    }
#pragma unroll
    for (int t = 0; t < 4; t++)
#pragma unroll
      for (int u = 0; u < 4; u++) {
        if (t == 0) { mmaZ(xr[u], A1[t], br[t][u], bi[t][u]); mmaZ(xi[u], A2[t], br[t][u], bi[t][u]); } else { mmaA(xr[u], A1[t], br[t][u], bi[t][u]); mmaA(xi[u], A2[t], br[t][u], bi[t][u]); }
      }
    __syncwarp();
    float* pl = buf + w * 1280;
    const float nrm = 0.5f / (2048.f * 640.f);
#pragma unroll
    for (int j = 0; j < 4; j++) {
      float zr[4], zi[4];
#pragma unroll
      for (int e = 0; e < 4; e++) { zr[e] = xr[j][e] * tc[j][e] - xi[j][e] * ts[j][e]; zi[e] = xi[j][e] * tc[j][e] + xr[j][e] * ts[j][e]; }
      const uint32_t r0 = movm(pack_bf16(zr[0], zr[1])), r1 = movm(pack_bf16(zr[2], zr[3])), i0 = movm(pack_bf16(zi[0], zi[1])), i1 = movm(pack_bf16(zi[2], zi[3]));
      float yr[4], yi[4];
      mmaZ(yr, fr, r0, r1); mmaZ(yi, nfi, r0, r1); mmaA(yr, fi, i0, i1); mmaA(yi, fr, i0, i1);
      *(float2*)(pl + g * 40 + 8 * j + 2 * q) = make_float2(yr[0] * nrm, yr[1] * nrm); *(float2*)(pl + (g + 8) * 40 + 8 * j + 2 * q) = make_float2(yr[2] * nrm, yr[3] * nrm);
      *(float2*)(pl + 640 + g * 40 + 8 * j + 2 * q) = make_float2(yi[0] * nrm, yi[1] * nrm); *(float2*)(pl + 640 + (g + 8) * 40 + 8 * j + 2 * q) = make_float2(yi[2] * nrm, yi[3] * nrm);
    }
  }
  ld_tab(wc, TB_2048 + tid); ld_tab(ws, TB_2048 + 128 + tid);
  WGBAR();
  hook(2);
  TL(8);
  {
    float4 Ur[4], Ui[4];
#pragma unroll
    for (int r = 0; r < 4; r++) { Ur[r] = *(const float4*)(buf + r * 1280 + (tid >> 3) * 40 + (tid & 7) * 4); Ui[r] = *(const float4*)(buf + r * 1280 + 640 + (tid >> 3) * 40 + (tid & 7) * 4); }
    float yr[4][4], yi[4][4];
#pragma unroll
    for (int i = 0; i < 4; i++) {
      float ar[4], ai[4];
      const float c2 = wc[i] * wc[i] - ws[i] * ws[i], s2 = 2.f * wc[i] * ws[i];
      const float twc[4] = {1.f, wc[i], c2, c2 * wc[i] - s2 * ws[i]}, tws[4] = {0.f, ws[i], s2, s2 * wc[i] + c2 * ws[i]};
#pragma unroll
      for (int r = 0; r < 4; r++) {
        const float a = i == 0 ? Ur[r].x : i == 1 ? Ur[r].y : i == 2 ? Ur[r].z : Ur[r].w, b = i == 0 ? Ui[r].x : i == 1 ? Ui[r].y : i == 2 ? Ui[r].z : Ui[r].w;
        if (r == 0) { ar[r] = a; ai[r] = b; } else { const float c = twc[r], s = tws[r]; ar[r] = a * c - b * s; ai[r] = b * c + a * s; }
      }
      const float s0r = ar[0] + ar[2], s0i = ai[0] + ai[2], d0r = ar[0] - ar[2], d0i = ai[0] - ai[2];
      const float s1r = ar[1] + ar[3], s1i = ai[1] + ai[3], d1r = ar[1] - ar[3], d1i = ai[1] - ai[3];
      yr[0][i] = s0r + s1r; yi[0][i] = s0i + s1i; yr[2][i] = s0r - s1r; yi[2][i] = s0i - s1i;
      yr[1][i] = d0r - d1i; yi[1][i] = d0i + d1r; yr[3][i] = d0r + d1i; yi[3][i] = d0i - d1r;
    }
    const float im = (f == f2) ? 0.f : 1.f;
#pragma unroll
    for (int j = 0; j < 4; j++) {
      *(uint2*)(a.Z2 + f * 1024 + j * 256 + 2 * tid) = make_uint2((pack_bf16(yr[j][0] - im * yi[j][1], yr[j][1] + im * yi[j][0]) & ~1u) | a.tag, pack_bf16(yr[j][2] - im * yi[j][3], yr[j][3] + im * yi[j][2]));
      if (f != f2) *(uint2*)(a.Z2 + f2 * 1024 + j * 256 + 2 * tid) = make_uint2((pack_bf16(yr[j][0] + yi[j][1], yr[j][1] - yi[j][0]) & ~1u) | a.tag, pack_bf16(yr[j][2] + yi[j][3], yr[j][3] - yi[j][2]));
    }
  }
  TL(9);
}

constexpr int KA_TR_STRIDE = 804;
template <typename F> __device__ __forceinline__ void a_layer(const AParams& a, char* scratch, int v, int w, F hook) {
  const int tid = tid_here(), lane = tid & 31;
  uint32_t raw[2][10], fr[4], fi[4];
  float tc[5][4], ts[5][4];
  const int np = a.nw ? (v < 86 ? 12 : 0) : v < 80 ? 12 : v < 96 ? 4 : 0;
  bool act = w < np;
  int m = !act ? v * 4 + w : np == 4 ? 640 + v * 4 + w : min(v * 12 + w, 1023);
  uint32_t* buf = (uint32_t*)(scratch + 6400) + (w & 3) * KA_TR_STRIDE + (w >> 2) * 3244;
  auto load_rows = [&]() {
    const int lane = tid_here() & 31;
#pragma unroll
    for (int i = 0; i < 10; i++) asm volatile("ld.relaxed.gpu.global.v2.u32 {%0,%1}, [%2];" : "=r"(raw[i / 5][2 * (i % 5)]), "=r"(raw[i / 5][2 * (i % 5) + 1]) : "l"(a.x + (size_t)(2 * m) * D_ + i * 128 + lane * 4) : "memory");
  };
  uint32_t t[2][4];
  auto load_tabs = [&]() {
    const int tid = tid_here(), lane = tid & 31;
    ld_tab(t[0], TB_F40 + (tid & 255)); ld_tab(t[1], TB_F40 + 144 + (tid & 255));
    ld_tab(fr, TB_F16 + lane); ld_tab(fi, TB_F16 + 32 + lane);
#pragma unroll
    for (int j = 0; j < 5; j++) { ld_tab(tc[j], TB_640 + j * 32 + lane); ld_tab(ts[j], TB_640 + 160 + j * 32 + lane); }
  };
  auto store_tabs = [&]() {
    const int tid = tid_here();
    sts128(smem_u32(scratch) + (tid & 255) * 16, t[0][0], t[0][1], t[0][2], t[0][3]); sts128(smem_u32(scratch) + 2304 + (tid & 255) * 16, t[1][0], t[1][1], t[1][2], t[1][3]);
  };
  if (a.rowdone) {
    load_tabs(); store_tabs();
    if (act) spin_count(a.rowdone + (m >> 4) * 32, 32);
#pragma unroll 1
    for (int guard = 0; guard < 20000; guard++) {
      load_rows();
      uint32_t mx = 0;
#pragma unroll
      for (int i = 0; i < 10; i++) mx = max(mx, raw[i / 5][2 * (i % 5)]);
      if (__all_sync(~0u, mx != ~0u)) break;
    }
  }
  else { load_rows(); load_tabs(); store_tabs(); }
  __syncthreads();
  hook(-1);
  TL(1);
#pragma unroll 1
  for (int it = 0;; it++) {
    if (act) {
#pragma unroll
      for (int r = 0; r < 2; r++) {
        float x[20];
#pragma unroll
        for (int i = 0; i < 10; i++) { x[2 * i] = bf_lo(raw[r][i]); x[2 * i + 1] = bf_hi(raw[r][i]); }
        ln_row(x);
#pragma unroll
        for (int i = 0; i < 10; i++) raw[r][i] = pack_bf16(x[2 * i], x[2 * i + 1]);
      }
    }
    if (it) break;
    if (act) {
#pragma unroll
      for (int i = 0; i < 10; i++) *(uint2*)(buf + i * 64 + lane * 2) = make_uint2(raw[i / 5][2 * (i % 5)], raw[i / 5][2 * (i % 5) + 1]);
      __syncwarp();
    }
    TL(2);
#pragma unroll 1
    for (int ph = 0;; ph++) {
      if (act) {
        float xr[5][4], xi[5][4];
        const int lane = tid_here() & 31, g = lane >> 2, q = lane & 3;
        fft640(smem_u32(buf), smem_u32(scratch), lane, fr, fi, tc, ts, xr, xi);
        __syncwarp();
#pragma unroll
        for (int u = 0; u < 5; u++)
#pragma unroll
          for (int e = 0; e < 4; e++) { const int f = g + 8 * (e >> 1) + 16 * (8 * u + 2 * q + (e & 1)); buf[f + 8 * (f >> 5)] = pack_bf16(xr[u][e], xi[u][e]); }
        __syncwarp();
      }
      if (ph) break;
      __syncthreads();
      TL(3);
      const int t1 = tid_here(), f0 = t1 / 3, part = t1 % 3;
      if (np == 12) {
        const uint32_t* src = (const uint32_t*)(scratch + 6400) + part * 3244 + f0 + 8 * (f0 >> 5);
        uint32_t ov[5][4];
#pragma unroll
        for (int i = 0; i < 5; i++)
#pragma unroll
          for (int k = 0; k < 4; k++) ov[i][k] = src[k * KA_TR_STRIDE + i * 160];
#pragma unroll
        for (int i = 0; i < 5; i++) stg128(a.Z1 + v * 7680 + (i * 384 + t1) * 4, (ov[i][0] & ~1u) | a.tag, ov[i][1], (ov[i][2] & ~1u) | a.tag, ov[i][3]);
      } else if (np) {
#pragma unroll
        for (int i = 0; i < 2; i++) {
          const int f = min(i * 384 + t1, 639);
          const uint32_t* src = (const uint32_t*)(scratch + 6400) + f + 8 * (f >> 5);
          stg128(a.Z1 + 86 * 7680 + (v - 80) * 2560 + f * 4, src[0] & ~1u, src[KA_TR_STRIDE], src[2 * KA_TR_STRIDE] & ~1u, src[3 * KA_TR_STRIDE]);
        }
      }
      TL(4);
      __syncthreads();
      if (tid == 32 && act) { if (v >= 80) __threadfence(); red_relaxed(a.sync + SY_1 + (v < 80 ? 0 : 16)); TL(5); }
      hook(0);
      const int f = (w >> 2) * 131 + v;
      if (f < 321) a_phase2(a, (float*)(scratch + (w >> 2) * 20480), f, hook);
      asm volatile("fence.proxy.async.shared::cta;" ::: "memory");
      __syncthreads();
      if (tid == 32) red_relaxed(a.sync + SY_2);
      hook(3);
      if (w >= 8 || v >= 128) return;
      const int job = (v + 32) & 127;
      act = true; m = job * 8 + w;
      scratch += 32768; buf = (uint32_t*)(scratch + 6400);
      {
        load_rows(); load_tabs();
        if (tid == 0) { spin_count(a.sync + SY_2, 131); TL(10); }
        bar_sync<5, 256>();
        uint4 za[3], zb[3];
        const int tid = tid_here();
#pragma unroll 1
        for (int guard = 0; guard < 100000; guard++) {
          uint32_t bad = 0;
#pragma unroll
          for (int i = 0; i < 3; i++) {
            const uint32_t* s = a.Z2 + (i * 256 + (tid & (i < 2 ? 254 : 126))) * 1024 + job * 8 + (tid & 1) * 4;
            asm volatile("ld.relaxed.gpu.global.v4.u32 {%0,%1,%2,%3}, [%4];" : "=r"(za[i].x), "=r"(za[i].y), "=r"(za[i].z), "=r"(za[i].w) : "l"(s) : "memory");
            asm volatile("ld.relaxed.gpu.global.v4.u32 {%0,%1,%2,%3}, [%4];" : "=r"(zb[i].x), "=r"(zb[i].y), "=r"(zb[i].z), "=r"(zb[i].w) : "l"(s + 1024) : "memory");
          }
#pragma unroll
          for (int i = 0; i < 3; i++) bad |= (za[i].x ^ a.tag) | (zb[i].x ^ a.tag) | (za[i].z ^ a.tag) | (zb[i].z ^ a.tag);
          if (__all_sync(~0u, !(bad & 1))) break;
        }
#pragma unroll
        for (int i = 0; i < 3; i++) if (i < 2 || tid < 128) {
          const uint4 c = za[i], b = zb[i];
          uint32_t* d = buf + (tid & 1) * 4 * KA_TR_STRIDE + i * 128 + (tid >> 1);
          d[320] = __byte_perm(c.x, b.x, 0x5410); d[0] = __byte_perm(c.x, b.x, 0x7632); d += KA_TR_STRIDE;
          d[320] = __byte_perm(c.y, b.y, 0x5410); d[0] = __byte_perm(c.y, b.y, 0x7632); d += KA_TR_STRIDE;
          d[320] = __byte_perm(c.z, b.z, 0x5410); d[0] = __byte_perm(c.z, b.z, 0x7632); d += KA_TR_STRIDE;
          d[320] = __byte_perm(c.w, b.w, 0x5410); d[0] = __byte_perm(c.w, b.w, 0x7632);
        }
        store_tabs();
        bar_sync<5, 256>();
        hook(4);
        TL(11);
      }
      buf += w * KA_TR_STRIDE;
    }
    {
      TL(12);
      const int lane = tid_here() & 31;
#pragma unroll
      for (int i = 0; i < 5; i++) {
        const uint4 y = *(const uint4*)(buf + i * 160 + lane * 4 + 8 * (lane >> 3));
        raw[0][2 * i] = hadd2(raw[0][2 * i], __byte_perm(y.x, y.y, 0x7632)); raw[0][2 * i + 1] = hadd2(raw[0][2 * i + 1], __byte_perm(y.z, y.w, 0x7632));
        raw[1][2 * i] = hadd2(raw[1][2 * i], __byte_perm(y.x, y.y, 0x5410)); raw[1][2 * i + 1] = hadd2(raw[1][2 * i + 1], __byte_perm(y.z, y.w, 0x5410));
      }
#pragma unroll
      for (int i = 0; i < 10; i++) *(uint2*)(a.x1 + (size_t)(2 * m) * D_ + i * 128 + lane * 4) = make_uint2(raw[i / 5][2 * (i % 5)], raw[i / 5][2 * (i % 5) + 1]);
    }
  }
  {
#pragma unroll
    for (int i = 0; i < 10; i++) *(uint2*)(a.hN + (size_t)(2 * m) * D_ + i * 128 + lane * 4) = make_uint2(raw[i / 5][2 * (i % 5)], raw[i / 5][2 * (i % 5) + 1]);
    TL(13);
    if (v < 96) bar_arrive<6, 320>();
    else {
      bar_sync<5, 256>();
      if (tid == 0) { __threadfence(); if (v < 100) red_relaxed(a.sync + SY_3 + 16); red_relaxed(a.sync + SY_3); TL(14); }
    }
  }
}

__device__ __forceinline__ void tma2d(uint32_t dst, const CUtensorMap* tm, int c0, int c1, uint32_t bar) {
  asm volatile("cp.async.bulk.tensor.2d.shared::cluster.global.mbarrier::complete_tx::bytes [%0], [%1, {%3, %4}], [%2];" :: "r"(dst), "l"(tm), "r"(bar), "r"(c0), "r"(c1) : "memory");
}
__device__ __forceinline__ void bulk_g2s(uint32_t dst, const void* src, int bytes, uint32_t bar) {
  asm volatile("cp.async.bulk.shared::cluster.global.mbarrier::complete_tx::bytes [%0], [%1], %2, [%3];" :: "r"(dst), "l"(src), "r"(bytes), "r"(bar) : "memory");
}
__device__ __forceinline__ uint64_t desc128(uint32_t a) { return (uint64_t)((a & 0x3FFFF) >> 4) | (1ull << 16) | (64ull << 32) | (1ull << 62); }
#define WG_FENCE() asm volatile("wgmma.fence.sync.aligned;" ::: "memory")
#define WG_COMMIT() asm volatile("wgmma.commit_group.sync.aligned;" ::: "memory")
#define WG_WAIT(n) asm volatile("wgmma.wait_group.sync.aligned " #n ";" ::: "memory")
__device__ __forceinline__ void wg_rs_n64(float* d, const uint32_t* a, uint64_t db, int acc) {
  asm volatile("{.reg .pred p; setp.ne.b32 p, %37, 0;\n"
    "wgmma.mma_async.sync.aligned.m64n64k16.f32.bf16.bf16 {%0,%1,%2,%3,%4,%5,%6,%7,%8,%9,%10,%11,%12,%13,%14,%15,%16,%17,%18,%19,%20,%21,%22,%23,%24,%25,%26,%27,%28,%29,%30,%31}, {%32,%33,%34,%35}, %36, p, 1, 1, 0;}"
    : "+f"(d[0]), "+f"(d[1]), "+f"(d[2]), "+f"(d[3]), "+f"(d[4]), "+f"(d[5]), "+f"(d[6]), "+f"(d[7]), "+f"(d[8]), "+f"(d[9]), "+f"(d[10]), "+f"(d[11]), "+f"(d[12]), "+f"(d[13]), "+f"(d[14]), "+f"(d[15]),
      "+f"(d[16]), "+f"(d[17]), "+f"(d[18]), "+f"(d[19]), "+f"(d[20]), "+f"(d[21]), "+f"(d[22]), "+f"(d[23]), "+f"(d[24]), "+f"(d[25]), "+f"(d[26]), "+f"(d[27]), "+f"(d[28]), "+f"(d[29]), "+f"(d[30]), "+f"(d[31])
    : "r"(a[0]), "r"(a[1]), "r"(a[2]), "r"(a[3]), "l"(db), "r"(acc));
}
__device__ __forceinline__ void wg_rs_n32(float* d, const uint32_t* a, uint64_t db, int acc) {
  asm volatile("{.reg .pred p; setp.ne.b32 p, %21, 0;\n"
    "wgmma.mma_async.sync.aligned.m64n32k16.f32.bf16.bf16 {%0,%1,%2,%3,%4,%5,%6,%7,%8,%9,%10,%11,%12,%13,%14,%15}, {%16,%17,%18,%19}, %20, p, 1, 1, 0;}"
    : "+f"(d[0]), "+f"(d[1]), "+f"(d[2]), "+f"(d[3]), "+f"(d[4]), "+f"(d[5]), "+f"(d[6]), "+f"(d[7]), "+f"(d[8]), "+f"(d[9]), "+f"(d[10]), "+f"(d[11]), "+f"(d[12]), "+f"(d[13]), "+f"(d[14]), "+f"(d[15])
    : "r"(a[0]), "r"(a[1]), "r"(a[2]), "r"(a[3]), "l"(db), "r"(acc));
}
__device__ __forceinline__ void wg_ss_n40_tt(float* d, uint64_t da, uint64_t db, int acc) {
  asm volatile("{.reg .pred p; setp.ne.b32 p, %22, 0;\n"
    "wgmma.mma_async.sync.aligned.m64n40k16.f32.bf16.bf16 {%0,%1,%2,%3,%4,%5,%6,%7,%8,%9,%10,%11,%12,%13,%14,%15,%16,%17,%18,%19}, %20, %21, p, 1, 1, 1, 1;}"
    : "+f"(d[0]), "+f"(d[1]), "+f"(d[2]), "+f"(d[3]), "+f"(d[4]), "+f"(d[5]), "+f"(d[6]), "+f"(d[7]), "+f"(d[8]), "+f"(d[9]), "+f"(d[10]), "+f"(d[11]), "+f"(d[12]), "+f"(d[13]), "+f"(d[14]), "+f"(d[15]),
      "+f"(d[16]), "+f"(d[17]), "+f"(d[18]), "+f"(d[19])
    : "l"(da), "l"(db), "r"(acc));
}
__device__ __forceinline__ void wg_ss_n32_ta(float* d, uint64_t da, uint64_t db, int acc) {
  asm volatile("{.reg .pred p; setp.ne.b32 p, %18, 0;\n"
    "wgmma.mma_async.sync.aligned.m64n32k16.f32.bf16.bf16 {%0,%1,%2,%3,%4,%5,%6,%7,%8,%9,%10,%11,%12,%13,%14,%15}, %16, %17, p, 1, 1, 1, 0;}"
    : "+f"(d[0]), "+f"(d[1]), "+f"(d[2]), "+f"(d[3]), "+f"(d[4]), "+f"(d[5]), "+f"(d[6]), "+f"(d[7]), "+f"(d[8]), "+f"(d[9]), "+f"(d[10]), "+f"(d[11]), "+f"(d[12]), "+f"(d[13]), "+f"(d[14]), "+f"(d[15])
    : "l"(da), "l"(db), "r"(acc));
}
__device__ __forceinline__ uint64_t desc_ns(uint32_t a, uint32_t lbo, uint32_t sbo) { return (uint64_t)((a & 0x3FFFF) >> 4) | ((uint64_t)(lbo >> 4) << 16) | ((uint64_t)(sbo >> 4) << 32); }
__device__ __forceinline__ void wait_count(const uint32_t* p, uint32_t n) {
  uint32_t v; int guard = 0;
#pragma unroll 1
  while (true) { asm volatile("ld.relaxed.gpu.global.u32 %0, [%1];" : "=r"(v) : "l"(p) : "memory"); if (__all_sync(~0u, v >= n) || ++guard > 200000) break; }
}

constexpr int SD_WS = 0, SD_REC = 16384, SD_O = SD_REC + 2 * 30720, SD_OI = SD_O + 2 * 8192, SD_OUT = SD_OI + 2 * 40960, SD_FIN = SD_OUT + 8192, SD_BAR = SD_FIN + 10240;
constexpr int SD_SMEM = SD_BAR + 512 + 1024;
#undef TLBASE
#define TLBASE (1024 + SD_BAR + 256)
#define QRING 4
constexpr int ORING = 8, PRING = 2 * ORING;
constexpr int FL_MEM = 162 * 1024, FL_RDY = 166 * 1024, FL_SM = 170 * 1024, FL_ROW = 174 * 1024;
struct SideParams { CUtensorMap tmWo, tmP; const char* QKV; char *O, *part; const bf16* x1; bf16* out; uint32_t *comm, *sync; uint64_t dhi; int first, period, phase, win, lag, tmem, last, early, tlast, dbgf; };
#define DBGF(m) false
#define ELECT "{.reg .pred p; elect.sync _|p, 0xffffffff;\n"
#define ATS(i)
__global__ void __launch_bounds__(512, 1) side_kernel(const __grid_constant__ SideParams p) {
  extern __shared__ __align__(1024) char smem_raw[];
  const uint32_t sb = (smem_u32(smem_raw) + 1023) & ~1023u, wfull = sb + SD_BAR, rland = wfull + 8, ofull = wfull + 16, ofree = wfull + 32,
    ifull = wfull + 48, ifree = wfull + 64, rfull = wfull + 80, rfree = wfull + 96, fdone = wfull + 112, ffull = wfull + 128;
  const int tid = threadIdx.x, lane = tid & 31, w = __shfl_sync(~0u, tid >> 5, 0);
  if (!DBGF(16)) pdl_launch();
  if (tid == 0) {
    spin_count(p.sync + SY_3, 128);
    uint32_t sm, mate; asm("mov.u32 %0, %%smid;" : "=r"(sm));
    asm volatile("ld.relaxed.gpu.global.u32 %0, [%1];" : "=r"(mate) : "l"(p.comm + FL_SM - (p.first ^ 1) * 1024 + (sm ^ 1)) : "memory");
    const uint32_t n = atomicAdd(p.comm + FL_SM + 512 + (mate ? 8 : 0), 1);
    asm volatile("st.shared.b32 [%0], %1;" :: "r"(fdone + 12), "r"(mate ? 35 - n : n) : "memory");
  }
  __syncthreads();
  int h; asm volatile("ld.shared.b32 %0, [%1];" : "=r"(h) : "r"(fdone + 12) : "memory");
  h = __shfl_sync(~0u, h, 0);
  if (h == 35) return;
  const int cb = h % 5, ks = h / 5, h0 = ks < 4 ? 5 * ks : 4 + 4 * ks, nh = ks < 4 ? 5 : 4;
  const int nseg = DBGF(16) ? 0 : NSEG;
  auto since = [&](uint32_t ref) { uint32_t now; asm volatile("mov.u32 %0, %%globaltimer_lo;" : "=r"(now) :: "memory"); return (int)((now - ((ref >> 7) << 5)) << 2) >> 2; };
  auto gate = [&](int s) {
#pragma unroll 1
    for (int guard = 0; guard < 4000; guard++) {
      uint32_t ref; asm volatile("ld.volatile.shared.b32 %0, [%1];" : "=r"(ref) : "r"(fdone + 4) : "memory");
      const int n = ref & 127;
      if (n >= p.last || n > s + p.lag || (uint32_t)(since(ref) + 4 * p.period - p.phase) % p.period <= p.win) break;
    }
  };
  TL(0);
  if (tid == 0) {
    mbar_init(wfull, 1); mbar_init(rland, 1); mbar_init(ffull, 1);
    for (int i = 0; i < 2; i++) { mbar_init(ofull + i * 8, 2); mbar_init(ofree + i * 8, 1); mbar_init(ifull + i * 8, 1); mbar_init(ifree + i * 8, 8); mbar_init(rfull + i * 8, 1); mbar_init(rfree + i * 8, 4); }
    asm volatile("st.shared.v2.b32 [%0], {%1,%1};" :: "r"(fdone), "r"(0) : "memory");
    asm volatile("fence.proxy.async.shared::cta;" ::: "memory");
    mbar_expect(wfull, nh * 32768);
#pragma unroll 1
    for (int b = 0; b < 4 * nh; b++) tma2d(sb + ((b + 2) % 20) * 8192, &p.tmWo, cb * 128 + (b & 1) * 64, h0 * 128 + (b >> 1) * 64, wfull);
  }
  __syncthreads();
  if (w < 8) {
    asm volatile("setmaxnreg.inc.sync.aligned.u32 192;");
    const int c = w >> 2, mg = w & 3;
    const uint32_t boxoff = (((lane >> 4) << 3) + (lane & 7)) * 128 + (((2 * mg + ((lane >> 3) & 1)) ^ (lane & 7)) << 4);
    uint32_t A[36][4];
    mbar_wait(wfull, 0);
#pragma unroll
    for (int f = 0; f < 36; f++) ldsm4t(A[f][0], A[f][1], A[f][2], A[f][3], sb + 16384 + c * 8192 + boxoff + (f >> 2) * 16384 + (f & 3) * 2048);
    asm volatile("fence.proxy.async.shared::cta;" ::: "memory");
    bar_sync<1, 320>();
    TL(1);
    const uint32_t oa = sb + SD_OUT + c * 4096 + boxoff;
    const uint32_t ca = sb + SD_OI + tid * 32 + (lane & 4) * 4, tm = lane < 4 ? 0x00010001u : 0u;
    uint32_t wp = 1;
#pragma unroll 1
    for (int s = 0; s < nseg; s++) {
      const int b = s & 1;
      const uint64_t db = p.dhi + (uint32_t)(((sb + SD_OI) >> 4) + b * 2560), da = p.dhi + (uint32_t)(((sb + SD_WS) >> 4) + c * 512);
#define D128(x) (x)
      float acc[16];
      mbar_wait_long(ifull + b * 8, (s >> 1) & 1);
#pragma unroll 1
      for (int guard = 0; guard < 20000; guard++) {
        uint32_t bad = 0, ok;
#pragma unroll
        for (int i = 0; i < 5; i++) if (i < 4 || nh == 5) { uint32_t v; asm volatile("ld.shared.b32 %0, [%1];" : "=r"(v) : "r"(ca + b * 40960 + i * 8192) : "memory"); bad |= v ^ (s / ORING + 1); }
        asm volatile("{.reg .pred p; setp.eq.u32 p, %1, 0; bar.red.and.pred p, 5, 256, p; selp.u32 %0, 1, 0, p;}" : "=r"(ok) : "r"(bad & 1) : "memory");
        if (__all_sync(~0u, ok)) break;
        if (w == 0) {
          asm volatile("fence.proxy.async.shared::cta;" ::: "memory");
          asm volatile(ELECT "@p mbarrier.arrive.expect_tx.shared.b64 _, [%2], %3;\n@p cp.async.bulk.shared::cluster.global.mbarrier::complete_tx::bytes [%0], [%1], %3, [%2];}"
            :: "r"(sb + SD_OI + b * 40960), "l"(p.O + (size_t)((s % ORING) * 32 + h0) * 8192), "r"(wfull), "r"(nh * 8192) : "memory");
        }
        mbar_wait_long(wfull, wp); wp ^= 1;
      }
      if (s == NSEG - 2 && h < 32) mbar_wait_long(ofull + 8, 1);
      ATS(0)
      WG_FENCE();
#pragma unroll
      for (int k = 0; k < 32; k++) wg_rs_n32(acc, A[k], D128(db + (k >> 2) * 256 + (k & 3) * 2), k);
      if (nh == 5) {
#pragma unroll
        for (int k = 32; k < 36; k++) wg_rs_n32(acc, A[k], D128(db + 2048 + (k & 3) * 2), 1);
#pragma unroll
        for (int k = 0; k < 4; k++) wg_ss_n32_ta(acc, D128(da + k * 128), D128(db + 2304 + k * 2), 1);
      }
      WG_COMMIT();
      bar_sync<2, 256>();
      WG_WAIT(0);
      ATS(1)
      if (lane == 0) mbar_arrive(ifree + b * 8);
      const uint32_t tg = (s / PRING) & 1 ? 0u : tm;
#define TAG(x) (((x) & ~tm) | tg)
#pragma unroll
      for (int u = 0; u < 2; u++)
        asm volatile("stmatrix.sync.aligned.m8n8.x4.trans.shared.b16 [%0], {%1,%2,%3,%4};" :: "r"(oa + u * 2048),
          "r"(TAG(pack_bf16(acc[8 * u], acc[8 * u + 1]))), "r"(TAG(pack_bf16(acc[8 * u + 2], acc[8 * u + 3]))), "r"(TAG(pack_bf16(acc[8 * u + 4], acc[8 * u + 5]))), "r"(TAG(pack_bf16(acc[8 * u + 6], acc[8 * u + 7]))) : "memory");
      asm volatile("fence.proxy.async.shared::cta;" ::: "memory");
      if (w > 0) bar_arrive<4, 256>();
      else {
        bar_sync<4, 256>();
        asm volatile(ELECT "@p cp.async.bulk.tensor.3d.global.shared::cta.bulk_group [%0, {%2, %3, %4}], [%1];\n"
          "cp.async.bulk.commit_group;\ncp.async.bulk.wait_group 0;\n@p red.relaxed.gpu.global.add.u32 [%5], 1;}"
          :: "l"(&p.tmP), "r"(sb + SD_OUT), "r"(0), "r"((s % PRING) * 32), "r"(ks * 10 + cb * 2), "l"(p.comm + FL_RDY + s * 16 + 8) : "memory");
        ATS(2)
      }
    }
    TL(5);
  } else if (w < 12) {
    asm volatile("setmaxnreg.dec.sync.aligned.u32 72;");
    const int a = w - 8, g = lane >> 2, q = lane & 3;
    const float sc2 = 0.08838834764831845f * 1.4426950408889634f;
#pragma unroll 1
    for (int s = 0; s < (h < 32 ? nseg : 0); s++) {
      const int b = s & 1;
      const uint32_t rec = sb + SD_REC + b * 30720;
      mbar_wait_long(rfull + b * 8, (s >> 1) & 1);
      ATS(1)
      if (s == 0) TL(2);
      uint32_t P[3][4]; float inv[2];
      {
        float sc[20];
        const uint64_t dq = desc_ns(rec + 1024, 128, 1024), dk = desc_ns(rec + 5120, 128, 1024);
        WG_FENCE();
#pragma unroll
        for (int k = 0; k < 8; k++) wg_ss_n40_tt(sc, dq + (k >> 2) * 640 + (k & 3) * 16, dk + (k >> 2) * 640 + (k & 3) * 16, k);
        WG_COMMIT(); WG_WAIT(0);
        ATS(2)
#pragma unroll
        for (int rh = 0; rh < 2; rh++) {
          const int row = 16 * a + 8 * rh + g;
          float v[5][2], mx = -3.0e38f;
#pragma unroll
          for (int n = 0; n < 5; n++)
#pragma unroll
            for (int e = 0; e < 2; e++) {
              const bool ok = n == 0 || (8 * (n - 1) + 2 * q + e) <= row;
              v[n][e] = ok ? sc[4 * n + 2 * rh + e] * sc2 : -1.0e9f * 1.4426950408889634f; mx = fmaxf(mx, v[n][e]);
            }
          mx = fmaxf(mx, __shfl_xor_sync(~0u, mx, 1)); mx = fmaxf(mx, __shfl_xor_sync(~0u, mx, 2));
          float sum = 0.f;
#pragma unroll
          for (int n = 0; n < 5; n++) { const float e0 = ex2(v[n][0] - mx), e1 = ex2(v[n][1] - mx); sum += e0 + e1; P[n >> 1][(n & 1) * 2 + rh] = pack_bf16(e0, e1); }
          P[2][2 + rh] = 0u;
          sum += __shfl_xor_sync(~0u, sum, 1); sum += __shfl_xor_sync(~0u, sum, 2);
          asm("rcp.approx.ftz.f32 %0, %1;" : "=f"(inv[rh]) : "f"(sum));
        }
      }
      ATS(3)
      mbar_wait_long(ofree + b * 8, ((s >> 1) & 1) ^ 1);
      ATS(4)
      const uint32_t od = sb + SD_O + b * 8192 + (16 * a + (lane & 15)) * 128, tm = q == 0, tg = (s / ORING) & 1 ? 0u : tm;
#pragma unroll 1
      for (int hf = 0; hf < 2; hf++) {
        float o[32];
        const uint64_t dv = desc_ns(rec + 20480 + hf * 5120, 1024, 128);
        WG_FENCE();
        wg_rs_n64(o, P[0], dv, 0); wg_rs_n64(o, P[1], dv + 128, 1); wg_rs_n64(o, P[2], desc_ns(rec + 20480 + hf * 5120 + 4096, 0, 128), 1);
        WG_COMMIT(); WG_WAIT(0);
        if (a < 2) {
#pragma unroll
          for (int n = 0; n < 8; n += 2) {
            const float* x = o + 4 * n;
            asm volatile("stmatrix.sync.aligned.m8n8.x4.shared.b16 [%0], {%1,%2,%3,%4};" :: "r"(od + hf * 4096 + (((n + (lane >> 4)) ^ (lane & 7)) << 4)),
              "r"(TAG(pack_bf16(x[0] * inv[0], x[1] * inv[0]))), "r"(TAG(pack_bf16(x[2] * inv[1], x[3] * inv[1]))), "r"(TAG(pack_bf16(x[4] * inv[0], x[5] * inv[0]))), "r"(TAG(pack_bf16(x[6] * inv[1], x[7] * inv[1]))) : "memory");
          }
        }
      }
      if (a < 2) {
        asm volatile("fence.proxy.async.shared::cta;" ::: "memory");
        __syncwarp();
        if (lane == 0) mbar_arrive(ofull + b * 8);
      }
      if (lane == 0) mbar_arrive(rfree + b * 8);
      ATS(5)
    }
    TL(3);
  } else {
    asm volatile("setmaxnreg.dec.sync.aligned.u32 56;");
    if (w == 13) {
      bar_sync<1, 320>();
#pragma unroll 1
      for (int s = 0; s < nseg; s++) {
        mbar_wait_long(ifree + (s & 1) * 8, ((s >> 1) & 1) ^ 1);
        wait_count(p.comm + FL_RDY + s * 16 + ks, nh);
        gate(s + 2);
        ATS(0)
        asm volatile(ELECT "@p mbarrier.arrive.expect_tx.shared.b64 _, [%2], %3;\n@p cp.async.bulk.shared::cluster.global.mbarrier::complete_tx::bytes [%0], [%1], %3, [%2];}"
          :: "r"(sb + SD_OI + (s & 1) * 40960), "l"(p.O + (size_t)((s % ORING) * 32 + h0) * 8192), "r"(ifull + (s & 1) * 8), "r"(nh * 8192) : "memory");
      }
    } else if (h >= 32 && w < 15) {
    } else if (w == 12) {
#pragma unroll 1
      for (int s = 0; s < nseg; s++) {
        mbar_wait_long(ofull + (s & 1) * 8, (s >> 1) & 1);
        int fin, guard = 0;
        do { asm volatile("ld.volatile.shared.b32 %0, [%1];" : "=r"(fin) : "r"(fdone) : "memory"); } while (fin + ORING <= s && ++guard < 1000000);
        ATS(0)
        asm volatile(ELECT "@p cp.async.bulk.global.shared::cta.bulk_group [%0], [%1], 8192;\n"
          "cp.async.bulk.commit_group;\ncp.async.bulk.wait_group 0;\n@p mbarrier.arrive.shared.b64 _, [%3];\n@p red.relaxed.gpu.global.add.u32 [%2], 1;}"
          :: "l"(p.O + (size_t)((s % ORING) * 32 + h) * 8192), "r"(sb + SD_O + (s & 1) * 8192), "l"(p.comm + FL_RDY + s * 16 + (h < 20 ? h / 5 : (h - 4) >> 2)), "r"(ofree + (s & 1) * 8) : "memory");
        ATS(1)
      }
      TL(4);
    } else if (w == 14) {
      if (DBGF(16)) pdl_wait(); else
      mbar_wait_long(ofull, 0);
      uint32_t fp = 0;
      if (p.first) {
#pragma unroll 1
        for (int i = 0; i < 20; i++) *(uint2*)(p.out + (size_t)((NSEG - 4 + i / 5) * 32 + h) * D_ + (i % 5) * 128 + lane * 4) = make_uint2(~0u, ~0u);
      }
#pragma unroll 1
      for (int s = 0; s < nseg; s++) {
        asm volatile("fence.proxy.async.shared::cta;" ::: "memory");
        __syncwarp();
        asm volatile(ELECT "@p mbarrier.arrive.expect_tx.shared.b64 _, [%2], 10240;\n@p cp.async.bulk.shared::cluster.global.mbarrier::complete_tx::bytes [%0], [%1], 1280, [%2];}"
          :: "r"(sb + SD_FIN + 8960), "l"(p.x1 + (size_t)(s * 32 + h) * D_), "r"(ffull) : "memory");
        wait_count(p.comm + FL_RDY + s * 16 + 8, 35);
        ATS(0)
        uint32_t y[5][2];
#pragma unroll 1
        for (int tries = 0; tries < 20000; tries++) {
          asm volatile(ELECT "@p cp.async.bulk.shared::cluster.global.mbarrier::complete_tx::bytes [%0], [%1], 8960, [%2];}"
            :: "r"(sb + SD_FIN), "l"(p.part + (size_t)((s % PRING) * 32 + h) * 8960), "r"(ffull) : "memory");
          mbar_wait_long(ffull, fp); fp ^= 1;
          ATS(1)
          uint32_t bad = 0;
#pragma unroll
          for (int i = 0; i < 5; i++) {
            uint32_t v[8][2];
#pragma unroll
            for (int u = 0; u < 8; u++) asm volatile("ld.shared.v2.b32 {%0,%1}, [%2];" : "=r"(v[u][0]), "=r"(v[u][1]) : "r"(sb + SD_FIN + u * 1280 + i * 256 + lane * 8) : "memory");
#pragma unroll
            for (int u = 0; u < 7; u++) bad |= v[u][0] ^ (s / PRING + 1);
#pragma unroll
            for (int k = 0; k < 2; k++)
              y[i][k] = hadd2(v[7][k], pack_bf16(((bf_lo(v[0][k]) + bf_lo(v[1][k])) + (bf_lo(v[2][k]) + bf_lo(v[3][k]))) + ((bf_lo(v[4][k]) + bf_lo(v[5][k])) + bf_lo(v[6][k])),
                                                 ((bf_hi(v[0][k]) + bf_hi(v[1][k])) + (bf_hi(v[2][k]) + bf_hi(v[3][k]))) + ((bf_hi(v[4][k]) + bf_hi(v[5][k])) + bf_hi(v[6][k]))));
          }
          if (__all_sync(~0u, !(bad & ~lane & 1))) break;
          asm volatile("fence.proxy.async.shared::cta;" ::: "memory");
          __syncwarp();
          asm volatile(ELECT "@p mbarrier.arrive.expect_tx.shared.b64 _, [%0], 8960;}" :: "r"(ffull) : "memory");
        }
#pragma unroll
        for (int i = 0; i < 5; i++) *(uint2*)(p.out + (size_t)(s * 32 + h) * D_ + i * 128 + lane * 4) = make_uint2(y[i][0], y[i][1]);
        asm volatile("st.volatile.shared.b32 [%0], %1;" :: "r"(fdone), "r"(s + 1) : "memory");
        __syncwarp();
        if (lane == 0 && p.first) { if (s < NSEG - 4) __threadfence(); red_relaxed(p.comm + FL_ROW + s * 32); if (s == NSEG - 1) __threadfence(); }
        ATS(2)
      }
    } else {
      uint32_t lp = 0, known = 0;
      bar_sync<1, 320>();
#pragma unroll 1
      for (int s = 0; s < nseg; s++) {
        const int b = s & 1;
        const uint32_t rec = sb + SD_REC + b * 30720;
        if (h < 32) mbar_wait_long(rfree + b * 8, ((s >> 1) & 1) ^ 1);
        uint32_t f = ~0u;
#pragma unroll 1
        for (int guard = 0; guard < 100000; guard++) {
          if (lane < 3) asm volatile("ld.relaxed.gpu.global.u32 %0, [%1];" : "=r"(f) : "l"(p.comm + FL_MEM + (h & 31) * 32 + lane * 8) : "memory");
          known = __reduce_min_sync(~0u, f & 127);
          if (known > (uint32_t)s) break;
        }
        f = __shfl_sync(~0u, f, 0);
        if (lane == 0) asm volatile("st.volatile.shared.b32 [%0], %1;" :: "r"(fdone + 4), "r"(f) : "memory");
        if (h >= 32) continue;
        __syncwarp();
        const char* src = p.QKV + (size_t)((s % QRING) * 32 + h) * 30720;
#pragma unroll 1
        for (int tries = 0; tries < 20000; tries++) {
          if ((f & 127) == s + 1 && tries == (s >= p.early)) { const int t = s == NSEG - 1 ? p.tlast : p.tmem; for (int guard = 0; since(f) < t && guard < 4000; guard++) {} }
          if (tries == 0 || s < p.early) gate(s);
          ATS(0)
          asm volatile("fence.proxy.async.shared::cta;" ::: "memory");
          __syncwarp();
          if (tries == 0) asm volatile(ELECT "@p mbarrier.arrive.expect_tx.shared.b64 _, [%2], 30720;\n@p cp.async.bulk.shared::cluster.global.mbarrier::complete_tx::bytes [%0], [%1], 30720, [%2];}" :: "r"(rec), "l"(src), "r"(rland) : "memory");
          else asm volatile(ELECT "@p mbarrier.arrive.expect_tx.shared.b64 _, [%2], 4096;\n"
            "@p cp.async.bulk.shared::cluster.global.mbarrier::complete_tx::bytes [%0+5120], [%1+5120], 1024, [%2];\n@p cp.async.bulk.shared::cluster.global.mbarrier::complete_tx::bytes [%0+15360], [%1+15360], 1024, [%2];\n"
            "@p cp.async.bulk.shared::cluster.global.mbarrier::complete_tx::bytes [%0+20480], [%1+20480], 1024, [%2];\n@p cp.async.bulk.shared::cluster.global.mbarrier::complete_tx::bytes [%0+25600], [%1+25600], 1024, [%2];}"
            :: "r"(rec), "l"(src), "r"(rland) : "memory");
          mbar_wait_long(rland, lp); lp ^= 1;
          uint32_t mx = 0;
#pragma unroll
          for (int k = 0; k < 4; k++) { uint32_t v; asm volatile("ld.shared.b32 %0, [%1];" : "=r"(v) : "r"(rec + (k == 0 ? 5120 : 10240 + k * 5120) + lane * 32 + (lane >> 2) * 4) : "memory"); mx = max(mx, v); }
          if (__all_sync(~0u, mx != ~0u)) break;
        }
        if (lane == 0) { mbar_arrive(rfull + b * 8); asm volatile("st.relaxed.gpu.global.u32 [%0], %1;" :: "l"(p.comm + FL_MEM + h * 32 + 24), "r"(s + 1) : "memory"); }
      }
    }
    if (w == 14) { TL(6); __syncwarp(); TL_DUMP((p.first ^ 1) * 166 + 131 + h, lane); }
    if (!p.first && tid == 448 && h == 0) { for (int i = 0; i < 16; i++) p.sync[i * 16 - 128] = 0; }
  }
}

__device__ __forceinline__ uint32_t ld_relaxed(const void* p) { uint32_t v; asm volatile("ld.relaxed.gpu.global.u32 %0, [%1];" : "=r"(v) : "l"(p) : "memory"); return v; }
__device__ __forceinline__ void st_relaxed(void* p, uint32_t v) { asm volatile("st.relaxed.gpu.global.u32 [%0], %1;" :: "l"(p), "r"(v) : "memory"); }
__device__ __forceinline__ void st_relaxed_if(void* p, uint32_t v, uint32_t c) { asm volatile("{.reg .pred p; setp.ne.u32 p, %2, 0; @p st.relaxed.gpu.global.u32 [%0], %1;}" :: "l"(p), "r"(v), "r"(c) : "memory"); }
__device__ __forceinline__ uint32_t clk32() { uint32_t c; asm volatile("mov.u32 %0, %%clock;" : "=r"(c) :: "memory"); return c; }
__device__ __forceinline__ uint32_t gt32() { uint64_t c; asm volatile("mov.u64 %0, %%globaltimer;" : "=l"(c) :: "memory"); return (uint32_t)c; }
__device__ __forceinline__ void wait_gt(uint32_t T) {
  asm volatile("{\n.reg .pred p;\n.reg .u64 t;\n.reg .u32 lo, hi;\nLG%=:\nmov.u64 t, %%globaltimer;\nmov.b64 {lo, hi}, t;\nsub.u32 lo, lo, %0;\nsetp.lt.s32 p, lo, 0;\n@p bra.uni LG%=;\n}" :: "r"(T) : "memory");
}
__device__ __forceinline__ void advance(uint32_t& T, uint32_t lim, uint32_t step) {
  asm volatile("{\n.reg .pred p;\n.reg .s32 d;\nLA%=:\nsub.s32 d, %1, %0;\nsetp.gt.s32 p, d, 0;\n@p add.u32 %0, %0, %2;\n@p bra.uni LA%=;\n}" : "+r"(T) : "r"(lim), "r"(step));
}
template <int LUT> __device__ __forceinline__ uint32_t lop3(uint32_t a, uint32_t b, uint32_t c) { uint32_t r; asm("lop3.b32 %0, %1, %2, %3, %4;" : "=r"(r) : "r"(a), "r"(b), "r"(c), "n"(LUT)); return r; }
__device__ __forceinline__ uint32_t ldsm1t(uint32_t a) { uint32_t r; asm volatile("ldmatrix.sync.aligned.m8n8.x1.trans.shared.b16 {%0}, [%1];" : "=r"(r) : "r"(a) : "memory"); return r; }
__device__ __forceinline__ uint32_t hmax2(uint32_t a, uint32_t b) { uint32_t r; asm("max.bf16x2 %0, %1, %2;" : "=r"(r) : "r"(a), "r"(b)); return r; }
__device__ __forceinline__ uint32_t lds32(uint32_t a) { uint32_t v; asm volatile("ld.shared.b32 %0, [%1];" : "=r"(v) : "r"(a) : "memory"); return v; }
__device__ __forceinline__ void sts32(uint32_t a, uint32_t v) { asm volatile("st.shared.b32 [%0], %1;" :: "r"(a), "r"(v) : "memory"); }
__device__ __forceinline__ uint32_t mapa(uint32_t a, int rank) { uint32_t r; asm("mapa.shared::cluster.u32 %0, %1, %2;" : "=r"(r) : "r"(a), "r"(rank)); return r; }
template <int OFF> __device__ __forceinline__ void stas32(uint32_t a, uint32_t v, uint32_t bar) {
  asm volatile("st.async.weak.shared::cluster.mbarrier::complete_tx::bytes.b32 [%0+%3], %1, [%2];" :: "r"(a), "r"(v), "r"(bar), "n"(OFF) : "memory");
}
#define OPAQUE(x) x = __shfl_sync(~0u, x, lane)
#define CLUSTER_SYNC() asm volatile("barrier.cluster.arrive.release.aligned; barrier.cluster.wait.acquire.aligned;" ::: "memory")

constexpr int SM_BAR = 0;
constexpr int SM_WO = 2048;
constexpr int SM_VR = 43008;
constexpr int SM_RED = 59392;
constexpr int SM_AT = 67584;
constexpr int SM_MEMT = 108672;
constexpr int SM_QK = 119040;
constexpr int SM_SC = 123136;
constexpr int SM_OX = 125184;
constexpr int SM_VM = 127744;
constexpr int SM_ST = 139264;
constexpr int SM_X = 149504;
constexpr int SM_WST = 2048;
constexpr int SM_WS = 67584;
constexpr int REC_SMEM = 231424 + 1024;
constexpr int MB_A = 0, MB_QK = 24, MB_R = 32, MB_V = 56, MB_KV = 64, MB_X = 80, MB_IA = 96, MB_IC = 104, MB_TK = 112, MB_PRB = 120, MB_DP = 128, MB_TAB = 256, MB_T2 = 512;
#define NTQ 10
#define NTV 4
#define NB0 4
#define PINK 14
#define NB1 7
#define PINT 5
#define WPLAN 0x5542110
#define OPF 3
#define XPOS 1
#define W0K 4
#define NLATE 1
#define VPOS 0
#define XK 2
#define IMM 1
#define FIRSTN 1
#define VMERGE 0
#define NBV 4
#define ALT 0
#define PINB -1
#define GATEK 3
#define TOLQ 96
#define TOLV 160
constexpr int POLL_LIMIT = 20000;
constexpr int CM_X3 = 160, CM_MISC = 172;
__device__ __forceinline__ uint32_t x3_slot(int slot) { return (CM_X3 + (slot & 1) * 64 + (slot & 2) * 128) * 4096; }
__device__ __forceinline__ int near_page(int pg, int side) { return pg + ((__popc(pg & 0xB3) ^ side) & 1); }
__device__ __forceinline__ int mem_line(int jb) { const int ks = jb >> 1, c = ks >= 20, kk = ks - 20 * c; return (kk >> 2) * 16 + c * 8 + (kk & 3) * 2 + (jb & 1); }

struct RecParams {
  CUtensorMap tmW[3], tmWo, tmX;
  AParams a[2];
  const bf16 *mem0, *wr, *wi;
  char* QKV;
  uint32_t* comm;
  uint64_t dhi;
  int period, c3, slack, xlate, extra, start, gap, zero, helper, layer, dbgf;
  uint32_t *dbg, *log;
};
#define PRB(k)
#define LDW(d, a) ldsm4t(d[0], d[1], d[2], d[3], a)

#undef TLBASE
#define TLBASE (1024 + 896)
#define PRBASE (mbar + w * 16)
#define PRIMM 1024
#define PROFF 0
template <bool VR>
__device__ __forceinline__ void rec_gemm_warps(const RecParams& p, const uint32_t sb, const int h, const int r, const int L, const int w) {
  const int tid = tid_here(), lane = tid & 31;
  const int mg = w & 3, c = w >> 2;
  constexpr int NT = VR ? NTV : NTQ, NW = VR ? 8 : 16, NF = 4, NBG = VR ? NBV : NB0;
  uint32_t R[20][4], P[20][4], Wr[NW - NT][4];
  const uint32_t mbar = sb + SM_BAR;
  uint32_t l16 = lane * 16, lm = (lane >> 4) * 1024 + (lane & 15) * 16;
  OPAQUE(l16); OPAQUE(lm);
#define wl16 (l16 + (sb + w * 512))
  {
    const uint32_t boxoff = (((lane >> 4) << 3) + (lane & 7)) * 128 + (((2 * mg + ((lane >> 3) & 1)) ^ (lane & 7)) << 4);
    mbar_wait(mbar + MB_IA, 0);
    TL(15);
    const uint32_t wa = sb + SM_WS + c * 40960 + boxoff;
#pragma unroll
    for (int k = 0; k < 20; k++) LDW(R[k], wa + 81920 + k * 2048);
    bar_arrive<4, 288>();
#pragma unroll
    for (int k = 0; k < 20; k++) LDW(P[k], wa + k * 2048);
    bar_sync<2, 256>();
#pragma unroll
    for (int i = 0; i < NT; i++) sts128(wl16 + SM_AT + i * 4096, P[i][0], P[i][1], P[i][2], P[i][3]);
    mbar_wait(mbar + MB_IC, 0);
    TL(16);
    const uint32_t woa = sb + SM_WST + c * 16384 + boxoff;
#pragma unroll
    for (int i = 0; i < NW; i++) {
      const uint32_t a = woa + (VR ? i * 2048 : (i & 1) * 32768 + (i >> 1) * 2048);
      if (i >= NF && i < NF + NW - NT) LDW(Wr[i - NF], a); else LDW(P[i < NF ? i : i - (NW - NT)], a);
    }
    asm volatile("fence.proxy.async.shared::cta;" ::: "memory");
    bar_sync<1, 384>();
#pragma unroll
    for (int i = 0; i < NT; i++) sts128(wl16 + SM_WO + i * 4096, P[i][0], P[i][1], P[i][2], P[i][3]);
    asm volatile("barrier.cluster.arrive.relaxed.aligned; barrier.cluster.wait.aligned;" ::: "memory");
  }
#define LDT(i) lds128(P[i], wl16 + SM_AT + (i) * 4096)
#define WGX(acc, A, ks, sc) wg_rs_n32(acc, A[ks], d##A + (((ks) >> 2) * 256 + ((ks) & 3) * 2), sc)
  float tb[16];
  constexpr int KW = VR ? 20 - W0K : 20;
  auto stream0 = [&](int n) {
    const uint64_t dP = p.dhi + (uint32_t)(((sb + SM_X + c * 20480) >> 4) + (n & 1) * 2560 + ((n + 1) & p.zero));
    WG_FENCE();
#pragma unroll
    for (int k = KW; k < 20; k++) WGX(tb, P, k, k - KW);
    WG_COMMIT();
  };
  auto stream = [&](int n) {
    float ta[16];
    const uint64_t dR = p.dhi + (uint32_t)(((sb + SM_X + c * 20480) >> 4) + (n & 1) * 2560), dP = dR + (uint32_t)(~n & p.zero);
    WG_FENCE();
    constexpr int NE = NT - (VR ? NLATE : 4);
#pragma unroll
    for (int k = 0; k < 20; k++) { WGX(ta, R, k, k); if ((k & 1) && k / 2 < NE) LDT(k / 2); }
    WG_COMMIT();
#define GATE(i) if (VR && (i) == GATEK) { if (GATEK) WG_COMMIT(); asm volatile("bar.sync 12, %0;" :: "r"((h & 1) ? 320 : 352) : "memory"); WG_FENCE(); }
    constexpr int K2 = VR ? NT + XK : 16;
#pragma unroll
    for (int k = K2; k < KW; k++) { GATE(k - K2); WGX(tb, P, k, KW < 20 || k > K2); }
    WG_COMMIT();
    WG_WAIT(1);
#pragma unroll
    for (int i = 0; i < 2; i++)
      sts128(l16 + (sb + (w ^ 4) * 512) + SM_RED + i * 4096, pack_bf16(ta[8 * i], ta[8 * i + 1]), pack_bf16(ta[8 * i + 2], ta[8 * i + 3]), pack_bf16(ta[8 * i + 4], ta[8 * i + 5]), pack_bf16(ta[8 * i + 6], ta[8 * i + 7]));
#pragma unroll
    for (int i = NE; i < NT; i++) LDT(i);
#pragma unroll
    for (int k = NT; k < K2; k++) { GATE(KW - K2 + k - NT); WGX(tb, P, k, 1); }
    WG_FENCE();
#pragma unroll
    for (int k = 0; k < NE; k++) WGX(tb, P, k, 1);
    bar_sync<11, 384>();
    uint32_t o[2][4];
    lds128(o[0], wl16 + SM_RED); lds128(o[1], wl16 + SM_RED + 4096);
    WG_FENCE();
#pragma unroll
    for (int k = NE; k < NT; k++) WGX(tb, P, k, 1);
    WG_COMMIT();
    WG_WAIT(0);
#pragma unroll
    for (int i = 0; i < 2; i++)
      asm volatile("stmatrix.sync.aligned.m8n8.x4.shared.b16 [%0], {%1,%2,%3,%4};" :: "r"(lm + (sb + (c ^ 1) * 5120 + mg * 256) + SM_ST + 1024 + i * 2048),
        "r"(hadd2(pack_bf16(tb[8 * i], tb[8 * i + 1]), o[i][0])), "r"(hadd2(pack_bf16(tb[8 * i + 2], tb[8 * i + 3]), o[i][1])),
        "r"(hadd2(pack_bf16(tb[8 * i + 4], tb[8 * i + 5]), o[i][2])), "r"(hadd2(pack_bf16(tb[8 * i + 6], tb[8 * i + 7]), o[i][3])) : "memory");
    bar_arrive<14, 320>();
  };
  int s = -2, att = 0;
#pragma unroll 1
  while (true) {
    if (s >= 0) {
    uint32_t B[10][4], Wf[NT][4], dp[4];
    float ap[2][4], ar[2][4];
#define LDO(i, base) lds128(Wf[i], (base) + SM_WO + (i) * 4096)
#define LDB(k2) ldsm4t(B[k2][0], B[k2][1], B[k2][2], B[k2][3], l16 + (sb + c * 1024) + SM_MEMT + ((k2) >> 1) * 2048 + ((k2) & 1) * 512)
#define BK(k) B[(k) >> 1][((k) & 1) * 2], B[(k) >> 1][((k) & 1) * 2 + 1]
    mbar_wait(mbar + MB_A, att & 1);
    PRB(0)
    LDB(0); LDB(1);
#pragma unroll
    for (int k = 0; k < 20; k++) {
      if (!(k & 1) && k < 16) LDB(k / 2 + 2);
      if (k == PINK) {
        const uint32_t wb = lop3<0xF8>(l16, __float_as_uint(ap[0][0]), p.zero) + (sb + w * 512);
#pragma unroll
        for (int u = 0; u < NBG && u < NT; u++) LDO(u, wb);
      }
      if (k < 2) { mmaZ(ap[k], P[k], BK(k)); mmaZ(ar[k], R[k], BK(k)); } else { mmaA(ap[k & 1], P[k], BK(k)); mmaA(ar[k & 1], R[k], BK(k)); }
    }
    asm volatile("stmatrix.sync.aligned.m8n8.x4.shared.b16 [%0], {%1,%2,%3,%4};" :: "r"(lm + (sb + c * 2048 + mg * 256) + SM_QK),
      "r"(pack_bf16(ar[0][0] + ar[1][0], ar[0][1] + ar[1][1])), "r"(pack_bf16(ar[0][2] + ar[1][2], ar[0][3] + ar[1][3])),
      "r"(pack_bf16(ap[0][0] + ap[1][0], ap[0][1] + ap[1][1])), "r"(pack_bf16(ap[0][2] + ap[1][2], ap[0][3] + ap[1][3])) : "memory");
    bar_arrive<9, 384>();
    PRB(1)
    att++;
    uint32_t bad;
    asm volatile("{.reg .pred p; setp.ne.u32 p, 0, 0; bar.red.or.pred p, 8, 384, p; selp.u32 %0, 1, 0, p;}" : "=r"(bad) :: "memory");
    if (bad) {
#pragma unroll
      for (int i = 0; i < NT; i++) LDT(i);
      continue;
    }
    if (s == NSEG - 1) break;
    if (VR && VMERGE == 2) bar_arrive<2, 384>();
    if (KW < 20) stream0(s);
    lds128(dp, mbar + MB_DP + w * 16);
#pragma unroll
    for (int i = NBG; i < NT && (VR || i < NB1); i++) LDO(i, wl16);
    uint32_t fmask = (~(l16 | dp[0]) >> 4) & 1, bit = ((s >> 1) & 1) ? 0u : fmask;
    char* cb = (char*)p.comm + ((s & 1) * (256 * 4096) + (l16 >> 2));
    char *d0 = cb + dp[0], *d1 = cb + dp[1], *d2 = cb + dp[2], *d3 = cb + dp[3];
    if (VR) asm volatile("" : "+l"(d0), "+l"(d1), "+r"(bit), "+r"(fmask)); else asm volatile("" : "+l"(d0), "+l"(d1), "+l"(d2), "+l"(d3), "+r"(bit), "+r"(fmask));
    if (KW < 20) WG_WAIT(0);
    if (VR || VMERGE != 2) sched_fence();
    if (VR) { if (VMERGE != 2) bar_arrive<2, 384>(); }
    else {
      if (VMERGE == 2) mbar_wait(mbar + MB_V, s & 1);
      bar_sync<2, 384>();
#pragma unroll
      for (int i = NB1; i < NT; i++) LDO(i, wl16);
    }
    bar_sync<3, 384>();
    PRB(2)
    uint32_t ob[4][4];
    float z0, z1;
#pragma unroll
    for (int i = 0; i < 4; i++) LDW(ob[i], l16 + sb + SM_OX + i * 512);
    asm volatile("ld.shared.v2.f32 {%0,%1}, [%2];" : "=f"(z0), "=f"(z1) : "r"(l16 + sb + SM_OX + 2048) : "memory");
#define WO(i) ((i) >= NF && (i) < NF + NW - NT ? Wr[(i) >= NF && (i) < NF + NW - NT ? (i) - NF : 0] : Wf[(i) < NF ? (i) : (i) < NF + NW - NT ? 0 : (i) - (NW - NT)])
    float ga[4][4];
#pragma unroll
    for (int i = 0; i < NW; i++) {
      const int ks = VR ? i : i >> 1;
      if (i < 4) mmaZ(ga[i], WO(i), ob[ks >> 1][(ks & 1) * 2], ob[ks >> 1][(ks & 1) * 2 + 1]); else mmaA(ga[i & 3], WO(i), ob[ks >> 1][(ks & 1) * 2], ob[ks >> 1][(ks & 1) * 2 + 1]);
    }
    asm("rcp.approx.ftz.f32 %0, %0;" : "+f"(z0)); asm("rcp.approx.ftz.f32 %0, %0;" : "+f"(z1));
#pragma unroll
    for (int i = 0; i < 4; i++) { ga[0][i] += ga[2][i]; ga[1][i] += ga[3][i]; if (VR) ga[0][i] += ga[1][i]; }
#pragma unroll
    for (int t = 0; t < NW / 8; t++) {
      st_relaxed(t ? d2 : d0, lop3<0xF4>(bit, pack_bf16(ga[t][0] * z0, ga[t][1] * z1), fmask));
      st_relaxed(t ? d3 : d1, lop3<0xF4>(bit, pack_bf16(ga[t][2] * z0, ga[t][3] * z1), fmask));
    }
    PRB(3)
    } else { mbar_wait(mbar + MB_X + (s & 1) * 8, 0); if (KW < 20) { stream0(s); WG_WAIT(0); } }
    bar_sync<10, 256>();
    stream(s);
    PRB(4)
    s++;
  }
  if (__all_sync(~0u, lds32(mbar + MB_TAB + 4) == 0)) {
#pragma unroll
    for (int i = 0; i < NT; i++) LDT(i);
    bar_sync<1, 384>();
    const int ln = l16 >> 4;
    const uint32_t wa = sb + SM_WS + c * 40960 + (((ln >> 4) << 3) + (ln & 7)) * 128 + (((2 * mg + ((ln >> 3) & 1)) ^ (ln & 7)) << 4);
#pragma unroll
    for (int k = 0; k < 40; k++) {
      const uint32_t* f = k < 20 ? R[k % 20] : P[k % 20];
      asm volatile("stmatrix.sync.aligned.m8n8.x4.trans.shared.b16 [%0], {%1,%2,%3,%4};" :: "r"(wa + (k < 20 ? 81920 : 0) + (k % 20) * 2048), "r"(f[0]), "r"(f[1]), "r"(f[2]), "r"(f[3]) : "memory");
    }
  }
#undef wl16
}

#undef PRBASE
#undef PRIMM
#undef PROFF
#define PRBASE (mbar + j * 16)
#define PRIMM (1024 + 4)
#define PROFF 8
__device__ __forceinline__ void x_load(const RecParams& p, const uint32_t sb, int n) {
  if (DBGF(32)) { if ((threadIdx.x & 31) == 0) mbar_arrive(sb + SM_BAR + MB_X + (n & 1) * 8); return; }
  asm volatile(ELECT "@p mbarrier.arrive.expect_tx.shared.b64 _, [%2], 40960;\n"
    "@p cp.async.bulk.tensor.3d.shared::cluster.global.mbarrier::complete_tx::bytes [%0], [%1, {%3, %4, %3}], [%2];}"
      :: "r"(sb + SM_X + (n & 1) * 40960), "l"(&p.tmX), "r"(sb + SM_BAR + MB_X + (n & 1) * 8), "r"(0), "r"(n * 32) : "memory");
}
__device__ __forceinline__ void wo_load(const RecParams& p, const uint32_t sb, int h, int r, int i0) {
#pragma unroll 1
  for (int i = i0; i < i0 + 4; i++)
    asm volatile(ELECT "@p cp.async.bulk.tensor.2d.shared::cluster.global.mbarrier::complete_tx::bytes [%0], [%1, {%3, %4}], [%2];}"
      :: "r"(sb + SM_WST + i * 8192), "l"(&p.tmWo), "r"(sb + SM_BAR + MB_IC), "r"(r * 256 + (i >> 1) * 64), "r"(h * 128 + (i & 1) * 64) : "memory");
}
__device__ __forceinline__ int rec_attn_setup(const RecParams& p, const uint32_t sb, const int h, const int r, const int L, const int j) {
  const int ct = tid_here() - 256, lane = ct & 31;
  const uint32_t mbar = sb + SM_BAR;
  uint32_t* misc = p.comm + CM_MISC * 1024;
  if (lane == 0 && L == 0) {
#pragma unroll 1
    for (int it = 0; it < (j == 2 ? 40 : 12); it++) {
      const int pg = (it ^ j) & 1;
      uint32_t* a = misc + pg * 1024 + 128 + j * 192 + blockIdx.x * 2;
      const uint32_t t0 = clk32();
      uint32_t v; asm volatile("atom.relaxed.gpu.global.exch.b32 %0, [%1], %2;" : "=r"(v) : "l"(a), "r"(t0) : "memory");
      st_relaxed_if(a, 0, v == t0 + 1);
      asm volatile("red.shared.min.u32 [%0], %1;" :: "r"(mbar + MB_PRB + pg * 4), "r"(clk32() - t0) : "memory");
      const uint32_t b0 = lds32(mbar + MB_PRB), b1 = lds32(mbar + MB_PRB + 4);
      if (it >= 3 && min(b0, b1) < 380 && min(b0, b1) + 70 < max(b0, b1)) break;
    }
  }
  __syncwarp();
  if (ct == 32 && L == 0) { uint32_t sm; asm volatile("mov.u32 %0, %%smid;" : "=r"(sm)); st_relaxed(p.comm + FL_SM + sm, 1); }
  uint32_t m0[5][4];
#pragma unroll
  for (int i = 0; i < 20; i++) m0[i >> 2][i & 3] = *(const uint32_t*)(p.mem0 + (lane >> 2) * D_ + (j * 20 + i) * 8 + (lane & 3) * 2);
  if (j < 2) {
    bar_sync<6, 320>();
    if (j == 0) { if (lane == 0) { red_release(p.a[L].sync + SY_3); TL(14); } __syncwarp(); }
    else {
      if (r < 2) { asm volatile("fence.proxy.async.shared::cta;" ::: "memory"); wo_load(p, sb, h, r, 4); }
      if (lane == 0 && atomicAdd(p.a[L].sync + SY_W + 16, 1) == 95) st_relaxed(misc + 96 + L, (gt32() + p.start) & ~31u);
      __syncwarp();
    }
  }
  if (j == 3) {
    spin_count(p.a[L].sync + SY_3 + 16, 4);
    asm volatile("fence.proxy.async.global;" ::: "memory");
    bar_sync<4, 288>();
    asm volatile("fence.proxy.async.shared::cta;" ::: "memory");
    x_load(p, sb, 0); x_load(p, sb, 1);
    TL(17);
  }
  bar_sync<1, 384>();
  asm volatile("barrier.cluster.arrive.relaxed.aligned;" ::: "memory");
#pragma unroll
  for (int i = 0; i < 5; i++)
    asm volatile("stmatrix.sync.aligned.m8n8.x4.trans.shared.b16 [%0], {%1,%2,%3,%4};" :: "r"(sb + SM_MEMT + mem_line(j * 20 + i * 4) * 128 + lane * 16), "r"(m0[i][0]), "r"(m0[i][1]), "r"(m0[i][2]), "r"(m0[i][3]) : "memory");
  sts128(sb + SM_ST + (ct >> 6) * 5120 + (ct & 63) * 16, ~0u, ~0u, ~0u, ~0u);
  asm volatile("barrier.cluster.wait.aligned;" ::: "memory");
  const uint32_t b0 = lds32(mbar + MB_PRB), b1 = lds32(mbar + MB_PRB + 4);
  const int side = __shfl_sync(~0u, ((b1 < b0) ^ __popc(CM_MISC & 0xB3)) & 1, 0);
  if (r == 2 && j + (h & 1) < 3) st_relaxed(misc + (j < 2 ? 2 * h + j : 64 + (h >> 1)), side);
  if (j == 0) {
    const int job = 2 * (16 * r + (lane >> 2) + ((lane & 2) && r < 2 ? 8 : 0)) + (lane & 1);
    uint32_t v; int guard = 0;
#pragma unroll 1
    do { v = ld_relaxed(misc + job); } while (__any_sync(~0u, v == 0xFFFFFFFFu) && ++guard < 1000000);
    sts32(mbar + MB_DP + lane * 4, near_page(2 * job, v) * 4096 + h * 128);
  }
  if (j == 1) {
    if (lane == 0) {
      uint32_t v; int guard = 0;
#pragma unroll 1
      do { v = ld_relaxed(misc + 96 + L); } while (v == 0xFFFFFFFFu && ++guard < 1000000);
      sts32(mbar + MB_TK, v);
    }
    __syncwarp();
  }
  if (j == 3) { spin_count(p.a[L].sync + SY_3, 128); asm volatile("fence.proxy.async.global;" ::: "memory"); }
  return side;
}
__device__ __forceinline__ void rec_attn_warps(const RecParams& p, const uint32_t sb, char* smem, const int h, const int r, const int side, const int L, const int j) {
  const int lane = tid_here() & 31, mi = lane >> 3;
  const uint32_t mbar = sb + SM_BAR;
#define VR (r == 2)
#define is_red (j + (h & 1) < 3 * r - 3)
  uint32_t l16 = sb + lane * 16;
#define wr16 (l16 + j * 512)
#define L0 ((l16 & 511) == 0)
  uint32_t ka = VR ? (mi != (lane & 3) ? 0u : (lane & 4) ? 0x3F800000u : 0x00003F80u)
    : j < 2 ? sb + SM_ST + 6144 + (2 * j + (mi & 1)) * 1024 + ((mi >> 1) * 8 + (lane & 7)) * 16 : sb + SM_QK + j * 512 + ((mi & 1) * 16 + (mi >> 1) * 8 + (lane & 7)) * 16;
  uint32_t own = VR ? sb + SM_AT + 28672 + j * 4096 + lane * 32 + (lane & 12) * 2 : sb + SM_SC + r * 1024 + (j < 2 ? j * 256 : 256 + j * 128) + lane * 4;
  uint32_t va = sb + SM_VR + (j >> 1) * 4096 + (mi >> 1) * 1024 + ((j & 1) * 32 + (mi & 1) * 8 + (lane & 7)) * 16, ps[2], pb[2];
#pragma unroll
  for (int i = 0; i < 2; i++) {
    const int peer = VR ? (ALT ? i ^ (j & 1) : i) : i == 0 ? r ^ 1 : 2;
    ps[i] = mapa(VR ? wr16 + SM_VM : own, peer); pb[i] = mapa(mbar + (VR && VMERGE != 1 ? MB_V : MB_QK), peer);
    OPAQUE(ps[i]); OPAQUE(pb[i]);
  }
  OPAQUE(ka); OPAQUE(own); OPAQUE(va); OPAQUE(l16);
  const char* comm = (const char*)p.comm;
  const uint32_t ones = 0x3F803F80u;
  const float sc2 = 0.08838834764831845f * 1.4426950408889634f;
  uint32_t kf[4][4], vf[4][4];
#pragma unroll
  for (int i = 0; i < 16; i++) kf[i >> 2][i & 3] = vf[i >> 2][i & 3] = p.zero;
  char* const rec0 = p.QKV + (h * 3 + r) * 10240;
  uint32_t* const fl = p.comm + FL_MEM + (L * 32 + h) * 32;
#define REC(n) (rec0 + ((n) & (QRING - 1)) * (96 * 10240))
  auto m_store = [&](int n) {
    if (VR || j < 2) {
      const int jj = VR ? j : j + 2;
      uint32_t a[4], b[4]; lds128(a, l16 + jj * 512 + SM_QK); lds128(b, l16 + (jj ^ 2) * 512 + SM_QK + 2048);
      asm volatile("st.relaxed.gpu.global.v4.u32 [%0], {%1,%2,%3,%4};" :: "l"(REC(n) + ((jj >> 1) * 5120 + (j & 1) * 512) + (l16 & 511)),
        "r"(hadd2(a[0], b[0])), "r"(hadd2(a[1], b[1])), "r"(hadd2(a[2], b[2])), "r"(hadd2(a[3], b[3])) : "memory");
    }
  };
  int att = 1, rph = 0;
  const int jb = j < 2 ? 2 * h + j : 64 + (h >> 1), ln = mem_line(jb) + 16;
  const uint32_t inbox = near_page(2 * jb, side) * 4096, bline = (ln >> 5) * 16384 + (ln & 31) * 128;
#define VERDICT(bad) asm volatile("{.reg .pred p; setp.ne.u32 p, %0, 0; bar.red.or.pred p, 8, 384, p;}" :: "n"(bad) : "memory")
#pragma unroll 1
  for (int s = -2; s < NSEG - 1; s++) {
    const uint32_t par = s & 1;
    auto v_load = [&]() {
      asm volatile("cp.async.bulk.wait_group 0;" ::: "memory");
      if (VR) asm volatile(ELECT
        "@p cp.async.bulk.shared::cluster.global.mbarrier::complete_tx::bytes.multicast::cluster [%0], [%1+1024], 4096, [%2], %3;\n"
        "@p cp.async.bulk.shared::cluster.global.mbarrier::complete_tx::bytes.multicast::cluster [%0+4096], [%1+6144], 4096, [%2], %3;}"
          :: "r"(sb + SM_VR + (par ^ 1) * 8192), "l"(REC(s + 1)), "r"(mbar + MB_KV + (par ^ 1) * 8), "h"((unsigned short)7) : "memory");
    };
    auto load_v = [&]() {
      if (s >= -1) mbar_wait(mbar + MB_KV + (par ^ 1) * 8, ((s + 1) >> 1) & 1);
#pragma unroll
      for (int i = 0; i < 4; i++) ldsm4(vf[i][0], vf[i][1], vf[i][2], vf[i][3], va + (par ^ 1) * 8192 + (i >> 1) * 2048 + (i & 1) * 256);
    };
    if (s >= 0) {
    uint32_t su[6], sw[6], vm[4];
#define LDSM2T(d, a) asm volatile("ldmatrix.sync.aligned.m8n8.x2.trans.shared.b16 {%0,%1}, [%2];" : "=r"(d[4]), "=r"(d[5]) : "r"(a) : "memory")
#define HADD4(a, b) { a[0] = hadd2(a[0], b[0]); a[1] = hadd2(a[1], b[1]); a[2] = hadd2(a[2], b[2]); a[3] = hadd2(a[3], b[3]); }
    bar_sync<9, 384>();
    PRB(0)
    {
      uint32_t qf[2][4], qg[2][4];
      float sa[4][4];
      if (j + (r & 2) < 2) {
        LDW(qf[0], l16 + SM_QK); LDW(qg[0], l16 + SM_QK + 3072); LDW(qf[1], l16 + SM_QK + 512); LDW(qg[1], l16 + SM_QK + 3584);
        HADD4(qf[0], qg[0]); HADD4(qf[1], qg[1]);
#pragma unroll
        for (int i = 0; i < 4; i++) mmaZ(sa[i], kf[i], qf[i >> 1][(i & 1) * 2], qf[i >> 1][(i & 1) * 2 + 1]);
        const uint32_t t0 = pack_bf16((sa[0][0] + sa[1][0]) + (sa[2][0] + sa[3][0]), (sa[0][1] + sa[1][1]) + (sa[2][1] + sa[3][1]));
        const uint32_t t1 = pack_bf16((sa[0][2] + sa[1][2]) + (sa[2][2] + sa[3][2]), (sa[0][3] + sa[1][3]) + (sa[2][3] + sa[3][3]));
        stas32<0>(ps[0], t0, pb[0]); stas32<0>(ps[1], t0, pb[1]); stas32<128>(ps[0], t1, pb[0]); stas32<128>(ps[1], t1, pb[1]);
        sts32(own, t0); sts32(own + 128, t1);
      } else if (!VR) {
        LDW(qf[0], wr16 + SM_QK - 1024); LDW(qg[0], wr16 + SM_QK + 2048); LDW(qf[1], ka); LDW(qg[1], ka + 1024);
        HADD4(qf[0], qg[0]); HADD4(qf[1], qg[1]);
        mmaZ(sa[0], qf[1], qf[0][0], qf[0][1]); mmaZ(sa[1], qf[1], qf[0][2], qf[0][3]);
        const uint32_t t0 = pack_bf16(sa[0][0] + sa[1][2], sa[0][1] + sa[1][3]);
        stas32<0>(ps[0], t0, pb[0]); stas32<0>(ps[1], t0, pb[1]);
        sts32(own, t0);
      } else {
        ldsm4(qf[0][0], qf[0][1], qf[0][2], qf[0][3], wr16 + SM_QK); ldsm4(qg[0][0], qg[0][1], qg[0][2], qg[0][3], l16 + (j ^ 2) * 512 + SM_QK + 2048);
        HADD4(qf[0], qg[0]);
        sts128(wr16 + SM_VM, qf[0][0], qf[0][1], qf[0][2], qf[0][3]);
#pragma unroll
        for (int i = 0; i < 2; i++)
          asm volatile("st.async.weak.shared::cluster.mbarrier::complete_tx::bytes.v4.b32 [%0], {%1,%2,%3,%4}, [%5];" :: "r"(ps[i]), "r"(qf[0][0]), "r"(qf[0][1]), "r"(qf[0][2]), "r"(qf[0][3]), "r"(pb[i]) : "memory");
      }
      PRB(1)
      VERDICT(0);
      if (VR) { if (VPOS == 1 && j == 2) v_load(); mbar_wait(mbar + MB_QK, par); }
      LDW(su, l16 + SM_SC + (r & 1) * 1024); LDSM2T(su, l16 + SM_SC + 512 + (r & 1) * 1024);
      if (!VR) mbar_wait(mbar + MB_QK, par);
      PRB(2)
      LDW(sw, l16 + SM_SC + 1024 - (r & 1) * 1024); LDSM2T(sw, l16 + SM_SC + 1536 - (r & 1) * 1024);
      su[4] = hadd2(su[4], su[5]);
    }
    {
      HADD4(su, sw); su[4] = hadd2(su[4], hadd2(sw[4], sw[5]));
      uint32_t m = hmax2(hmax2(hmax2(su[0], su[1]), hmax2(su[2], su[3])), su[4]);
      const uint32_t m1 = __shfl_xor_sync(~0u, m, 1), m2 = __shfl_xor_sync(~0u, m, 2), m3 = __shfl_xor_sync(~0u, m, 3);
      float t[10];
#pragma unroll
      for (int i = 0; i < 5; i++) { t[2 * i] = bf_lo(su[i]) * sc2; t[2 * i + 1] = bf_hi(su[i]) * sc2; }
      {
        asm volatile("" : "+f"(t[0]), "+f"(t[1]), "+f"(t[2]), "+f"(t[3]), "+f"(t[4]), "+f"(t[5]), "+f"(t[6]), "+f"(t[7]), "+f"(t[8]), "+f"(t[9]));
        if (!VMERGE) mbar_wait(mbar + MB_V, par | (r >> 1));
        if (VMERGE == 2) bar_sync<2, 384>(); else bar_arrive<2, 384>();
        lds128(vm, wr16 + SM_VM);
      }
      t[PINT] = __uint_as_float(lop3<0xF8>(__float_as_uint(t[PINT]), vm[0], p.zero));
      m = hmax2(hmax2(m, m1), hmax2(m2, m3));
      const float mx = fmaxf(bf_lo(m), bf_hi(m));
#define EX(i) ex2(fmaf(mx, -sc2, t[i]))
      float o1[2][4], z[4];
      const uint32_t P0 = pack_bf16(EX(0), EX(1)), P1 = pack_bf16(EX(2), EX(3));
      mmaZ(o1[0], vf[0], P0, P1); mmaZ(o1[1], vf[1], P0, P1); mma16816z(z, ones, ones, ones, ones, P0, P1);
      const float e4 = EX(4), e5 = EX(5);
      const uint32_t P2 = pack_bf16(e4, e5), P3 = pack_bf16(EX(6), EX(7));
      mmaA(o1[0], vf[2], P2, P3); mmaA(o1[1], vf[3], P2, P3); mma16816(z, ones, ones, ones, ones, P2, P3);
      uint32_t Pm = pack_bf16(EX(8), EX(9));
      mma1688(o1[0], vm[0], vm[1], Pm); mma1688(o1[1], vm[2], vm[3], Pm); mma1688(z, ones, ones, Pm);
      asm volatile("stmatrix.sync.aligned.m8n8.x4.shared.b16 [%0], {%1,%2,%3,%4};" :: "r"(wr16 + SM_OX),
        "r"(pack_bf16(o1[0][0], o1[0][1])), "r"(pack_bf16(o1[0][2], o1[0][3])), "r"(pack_bf16(o1[1][0], o1[1][1])), "r"(pack_bf16(o1[1][2], o1[1][3])) : "memory");
      if (j == 3) asm volatile("st.shared.v2.f32 [%0], {%1,%2};" :: "r"(l16 + SM_OX + 2048), "f"(z[0]), "f"(z[1]) : "memory");
    }
    bar_arrive<3, 384>();
    PRB(3)
    if (j == 3) asm volatile(ELECT "@p mbarrier.arrive.expect_tx.shared.b64 _, [%0+%4], %2;\n@p mbarrier.arrive.expect_tx.shared.b64 _, [%1], 8192;\n"
      "@p mbarrier.arrive.expect_tx.shared.b64 _, [%0+%5], 10368;\nsetp.ne.and.u32 p, %3, 2, p;\n@p mbarrier.arrive.expect_tx.shared.b64 _, [%0+%6], 2048;}"
        :: "r"(mbar), "r"(mbar + MB_KV + par * 8), "r"(VR ? 1536 : VMERGE == 1 ? 2816 : 768), "r"(VMERGE == 1 ? 2 : r), "n"(MB_QK), "n"(MB_A), "n"(MB_V) : "memory");
    }
    uint32_t T3, c3;
    asm volatile("ld.shared.v2.b32 {%0,%1}, [%2];" : "=r"(T3), "=r"(c3) : "r"(mbar + MB_TK) : "memory");
    {
      const uint32_t now = gt32(), lim = now + c3 + p.gap;
      if ((int)(T3 - now) > 20000) T3 = now;
      advance(T3, lim, p.slack);
    }
    if (s >= 0) m_store(s);
    if (j + (r & 2) < 2) {
#pragma unroll
      for (int i = 0; i < 4; i++) LDW(kf[i], ka + i * 256);
    } else {
#pragma unroll
      for (int i = 0; i < 16; i++) kf[i >> 2][i & 3] = 0;
    }
    int used = 0;
    if (j == 2 && s >= -1) { if (VPOS != 1 || !VR || s < 0) v_load(); used = ld_relaxed(fl + 24); }
    if (VPOS == 1) load_v();
    bar_arrive<11, 384>();
    if (is_red) {
      const uint32_t expect = ((s >> 1) & 1) ^ 1, rb = mbar + MB_R + j * 8, stg = SM_AT + 28672 + j * 4096, s1 = ka | (s & p.zero);
      char* w0 = (char*)comm + (x3_slot(s + 1) + bline + (l16 & 511) / 4);
      asm volatile("" : "+l"(w0));
      uint32_t T2 = T3 - c3;
      if (s < 0) asm volatile("bar.arrive 12, %0;" :: "r"((h & 1) ? 320 : 352) : "memory");
      else {
#pragma unroll 1
        for (int nth = 0;; nth++) {
          wait_gt(T2);
          PRB(4)
          asm volatile(ELECT "@p cp.async.bulk.shared::cluster.global.mbarrier::complete_tx::bytes [%0], [%1], 4096, [%2];\n@p mbarrier.arrive.expect_tx.shared.b64 _, [%2], 4096;}"
            :: "r"(sb + stg), "l"(comm + (inbox + par * (256 * 4096))), "r"(rb) : "memory");
          mbar_wait(rb, rph & 1); rph++;
          uint32_t x[8][4], f[4];
          float ra[4][4];
#pragma unroll
          for (int i = 0; i < 8; i++) ldsm4(x[i][0], x[i][1], x[i][2], x[i][3], l16 + stg + i * 512);
#pragma unroll
          for (int i = 0; i < 4; i++) f[i] = lds32(own + i * 1024);
#pragma unroll
          for (int i = 0; i < 8; i++) { if (i < 4) mmaZ(ra[i], x[i], ka, s1); else mmaA(ra[i & 3], x[i], ka, s1); }
          const uint32_t ok = __all_sync(~0u, lop3<0xA8>(lop3<0x7E>(f[0], f[1], expect), lop3<0x7E>(f[2], f[3], expect), 1) == 0) || nth == POLL_LIMIT;
          const uint32_t v = pack_bf16(((ra[0][0] + ra[0][2]) + (ra[1][0] + ra[1][2])) + ((ra[2][0] + ra[2][2]) + (ra[3][0] + ra[3][2])), ((ra[0][1] + ra[0][3]) + (ra[1][1] + ra[1][3])) + ((ra[2][1] + ra[2][3]) + (ra[3][1] + ra[3][3])));
          asm volatile("{.reg .pred p, q; setp.ne.u32 p, %2, 0; setp.eq.u32 q, %4, 0; @q bar.arrive 12, %3; @p st.relaxed.gpu.global.u32 [%0], %1; @p st.relaxed.gpu.global.u32 [%0+4096], %1; @p bar.arrive 15, %5;}"
            :: "l"(w0), "r"(v), "r"(ok), "r"(lop3<0xF8>((h & 1) ? 320 : 352, __float_as_uint(ra[3][0]), p.zero)), "r"(nth), "r"((h & 1) ? 96 : 128) : "memory");
          if (ok) break;
          if (nth == 0) {
            char* c = (char*)comm + (x3_slot(s + 1) + 1920);
            asm volatile(ELECT "@p red.relaxed.gpu.global.max.s32 [%0], %1;\n@p red.relaxed.gpu.global.max.s32 [%0+4096], %1;}" :: "l"(c), "r"(lds32(mbar + MB_TAB + 8) + 1) : "memory");
          }
          if (!IMM || nth) { T2 += p.slack; advance(T2, gt32() - TOLQ, p.slack); }
        }
        PRB(5)
        w0 = (char*)((uint64_t)w0 ^ (1 << 20));
        st_relaxed(w0, 0xFFFFFFFFu); st_relaxed(w0 + 4096, 0xFFFFFFFFu);
      }
#pragma unroll
      for (int i = 0; i < 16; i++) kf[i >> 2][i & 3] = 0;
    }
#pragma unroll 1
    for (int guard = 0;; guard++) {
      if (j == 3 && s >= 0) {
        if (VR && guard == 0) { asm volatile("bar.sync 15, %0;" :: "r"((h & 1) ? 96 : 128) : "memory"); sts32(mbar + MB_TAB, 0); }
        advance(T3, gt32() - (VR ? TOLV : TOLQ), p.slack);
        wait_gt(T3);
        asm volatile(ELECT
          "@p cp.async.bulk.shared::cluster.global.mbarrier::complete_tx::bytes [%0+-128], [%2+1920], 2176, [%1];\n"
          "@p cp.async.bulk.shared::cluster.global.mbarrier::complete_tx::bytes [%0+2048], [%2+16384], 4096, [%1];\n"
          "@p cp.async.bulk.shared::cluster.global.mbarrier::complete_tx::bytes [%0+6144], [%2+32768], 4096, [%1];}"
          :: "r"(sb + SM_MEMT), "r"(mbar + MB_A), "l"(comm + (x3_slot(s + 1) + side * 4096)) : "memory");
      }
      PRB(6)
      if (VPOS == 0) load_v();
      uint32_t m = 0, ok;
      if (j < 2) {
        if (s + 3 < NSEG) mbar_wait(mbar + MB_X + (par ^ 1) * 8, ((s + 3) >> 1) & 1);
        if (s >= 0) {
          mbar_wait(mbar + MB_A, att & 1);
#pragma unroll
          for (int i = 0; i < 5; i++) m = max(m, lds32(l16 + (l16 & 511) + (l16 & 448) / 16 + (j * 1024 + SM_MEMT + i * 2048)));
        }
      } else if (guard == 0) {
        bar_sync<14, 320>();
        if (j == 2) {
#pragma unroll 1
          for (int g2 = 0; __any_sync(~0u, used + QRING < s + 3) && g2 < POLL_LIMIT && !DBGF(16); g2++) used = ld_relaxed(fl + 24);
          asm volatile("fence.proxy.async.shared::cta;" ::: "memory");
          if (s + 2 < NSEG && !DBGF(64)) asm volatile(ELECT "@p cp.async.bulk.global.shared::cta.bulk_group [%0], [%1], 10240;\ncp.async.bulk.commit_group;}" :: "l"(REC(s + 2)), "r"(sb + SM_ST) : "memory");
        } else if (XPOS == 0 && s + 4 < NSEG) { if (s >= 0) wait_gt(T3 + 192); x_load(p, sb, s + 4); }
      }
      if (VPOS == 2) load_v();
      att++;
      asm volatile("{.reg .pred p; setp.ne.u32 p, %1, 0xffffffff; bar.red.and.pred p, 13, 128, p; selp.u32 %0, 1, 0, p;}" : "=r"(ok) : "r"(m) : "memory");
      if (__all_sync(~0u, ok) || guard == POLL_LIMIT) break;
      bar_arrive<9, 384>();
      VERDICT(1);
      if (j == 3) asm volatile(ELECT "@p mbarrier.arrive.expect_tx.shared.b64 _, [%0], 10368;}" :: "r"(mbar + MB_A) : "memory");
      T3 += p.slack;
    }
    PRB(7)
    if (j == 3) {
      if (XPOS == 1 && s + 4 < NSEG) x_load(p, sb, s + 4);
      if (s >= 0) {
        const int seen = lds32(sb + SM_MEMT - 128), had = lds32(mbar + MB_TAB + 8), cnt = max(seen, had + (s < FIRSTN));
        sts32(mbar + MB_TAB + 8, cnt); sts32(mbar + MB_TK, T3 + p.period + (cnt - had) * (p.xlate + p.extra)); sts32(mbar + MB_TK + 4, cnt > had ? p.c3 + p.extra : p.c3);
      }
      st_relaxed(fl + r * 8, (((s < 0 ? T3 - p.period : T3) >> 5) << 7) | (s + 2));
      if (s == -2) asm volatile(ELECT "@p mbarrier.arrive.shared.b64 _, [%0];}" :: "r"(mbar + MB_A) : "memory");
      if (s < 0) TL(18);
    }
  }
  bar_sync<9, 384>();
  m_store(NSEG - 1);
  VERDICT(0);
  TL(19);
  if (__all_sync(~0u, lds32(mbar + MB_TAB + 4) == 0)) bar_arrive<1, 384>();
  if (is_red) {
    uint32_t* wpoi = (uint32_t*)(comm + (x3_slot(2) + bline + (l16 & 511) / 4));
    st_relaxed(wpoi, 0xFFFFFFFFu); st_relaxed(wpoi + 1024, 0xFFFFFFFFu);
#pragma unroll 1
    for (int i = 0; i < 8; i++) stg128((char*)comm + (inbox + 256 * 4096 + i * 512 + (l16 & 511)), 0, 0, 0, 0);
    __threadfence();
  }
#undef VR
}

__global__ void __launch_bounds__(384, 1) rec_kernel(const __grid_constant__ RecParams p) {
  extern __shared__ __align__(1024) char smem_raw[];
  const uint32_t sb = (smem_u32(smem_raw) + 1023) & ~1023u;
  char* smem = smem_raw + (sb - smem_u32(smem_raw));
  const int tid = threadIdx.x;
  const uint32_t mbar = sb + SM_BAR;
  pdl_launch();
  if (!p.helper) {
    if (tid == 32 || tid == 96) l2_prefetch((tid == 32 ? p.wi : p.wr) + blockIdx.x * 6848, 13696);
    if (tid == 64 && blockIdx.x < 12) l2_prefetch(g_tab + TB_F32 * 4 + blockIdx.x * 256, 1024);
  }
#pragma unroll 1
  for (int L = p.layer; L < 2; L++) {
    {
    const int w = __shfl_sync(~0u, tid >> 5, 0), bid = blockIdx.x + (L & p.zero), h = bid / 3, r = bid % 3;
    TL(0);
    if (tid == 0) {
#pragma unroll 1
      for (int i = 0; i < 14; i++) {
        if (L > p.layer) asm volatile("mbarrier.inval.shared.b64 [%0];" :: "r"(mbar + i * 8) : "memory");
        mbar_init(mbar + i * 8, 1);
      }
      asm volatile("fence.mbarrier_init.release.cluster;" ::: "memory");
      asm volatile("fence.proxy.async.shared::cta;" ::: "memory");
      mbar_expect(mbar + MB_QK, r == 2 ? 1536 : VMERGE == 1 ? 2816 : 768); mbar_expect(mbar + MB_V, 2048);
      mbar_expect(mbar + MB_KV, 8192); mbar_expect(mbar + MB_KV + 8, 8192);
      if (L == 0) { sts32(mbar + MB_PRB, 60000); sts32(mbar + MB_PRB + 4, 60000); }
      sts32(mbar + MB_TK, gt32() + 50000); sts32(mbar + MB_TK + 4, p.c3 + p.extra); sts32(mbar + MB_TAB + 4, L); sts32(mbar + MB_TAB + 8, L * 1000);
      mbar_expect(mbar + MB_IA, L ? 0 : 163840); mbar_expect(mbar + MB_IC, r == 2 ? 32768 : 65536);
    }
    const int v = bid + p.helper * 96;
    const bool prep = L == 0 && v >= 86;
    if (prep && v < 118 && tid == 0) {
      mbar_expect(mbar + 8, 2 * 41088);
      bulk_g2s(sb + SM_WS, p.wr + (v - 86) * 64 * 321, 41088, mbar + 8); bulk_g2s(sb + SM_WS + 41088, p.wi + (v - 86) * 64 * 321, 41088, mbar + 8);
    }
    __syncwarp();
    a_layer(p.a[L], smem + SM_WST, v, w, [&](int u) {
        if (u == -1 && prep) {
          const int o = (v - 86) * 384 + tid, pg = 160 + ((o >> 8) & 15) + ((o >> 12) & 1) * 64 + (o >> 13) * 256;
          const uint32_t c = (pg & 2) ? 0u : ~0u;
          if (o < 64 * 256) stg128((uint4*)p.comm + pg * 256 + (o & 255), c, c, c, c);
          if (v < 118) { mbar_wait(mbar + 8, 0); filter_prep((uint32_t*)p.a[0].WT, sb + SM_WS, v - 86); }
          asm volatile("fence.proxy.async.shared::cta;" ::: "memory");
          TL(20);
          __syncthreads();
        }
        if (u == 0 && prep && tid == 256) { red_release(p.a[0].sync + SY_W); TL(21); }
        auto w_load = [&](int i) {
          asm volatile(ELECT "@p cp.async.bulk.tensor.2d.shared::cluster.global.mbarrier::complete_tx::bytes [%0], [%1, {%3, %4}], [%2];}"
            :: "r"(sb + SM_WS + ((0x3102 >> (4 * (i & 3))) & 3) * 40960 + (i >> 2) * 8192), "l"(&p.tmW[r == 2 ? 2 : i & 1]), "r"(mbar + MB_IA), "r"(h * 128 + (r == 2 ? i & 1 : r) * 64), "r"((i & 2) * 160 + (i >> 2) * 64) : "memory");
        };
        const int b0 = (WPLAN >> (4 * u + 4)) & 15, n = ((WPLAN >> (4 * u + 8)) & 15) - b0;
        if (n > 0 && w + L * 12 + p.helper * 12 < 4 * n) w_load(4 * b0 + w);
        if (u == OPF && w < 4 && r + p.helper * 2 < 2)
          asm volatile(ELECT "@p cp.async.bulk.prefetch.tensor.2d.L2.global [%0, {%1, %2}];}" :: "l"(&p.tmWo), "r"(r * 256 + 128 + (w >> 1) * 64), "r"(h * 128 + (w & 1) * 64) : "memory");
        if (u == 4 && w == 4 && !p.helper) wo_load(p, sb, h, r, 0);
      });
    if (p.helper) {
      return;
    }
    __syncwarp();
    }
    L = __shfl_sync(~0u, lds32(mbar + MB_TAB + 4), 0);
    const int w = __shfl_sync(~0u, tid >> 5, 0), bid = blockIdx.x + (L & p.zero), h = bid / 3, r = bid % 3;
    if (w < 8) {
      asm volatile("setmaxnreg.inc.sync.aligned.u32 216;");
      if (r < 2) rec_gemm_warps<false>(p, sb, h, r, L, w); else rec_gemm_warps<true>(p, sb, h, r, L, w);
      asm volatile("setmaxnreg.dec.sync.aligned.u32 168;");
    } else {
      asm volatile("setmaxnreg.dec.sync.aligned.u32 72;");
      const int side = rec_attn_setup(p, sb, h, r, L, w - 8);
      rec_attn_warps(p, sb, smem, h, r, side, L, w - 8);
      asm volatile("setmaxnreg.inc.sync.aligned.u32 168;");
    }
    asm volatile("barrier.cluster.arrive.relaxed.aligned; barrier.cluster.wait.aligned;" ::: "memory");
    L = __shfl_sync(~0u, lds32(mbar + MB_TAB + 4), 0);
    if (tid < 32) TL_DUMP(L * 166 + blockIdx.x, tid);
    __syncthreads();
  }
}

constexpr int PERIOD = 1984, C3 = 480, SLACK = 768, XLATE = 64, GAP = 128;
static int PH[9] = {256, 704, 3, 1280, 96, 62, 5600, 60, 768};
__device__ __align__(128) uint32_t g_Z1[96 * 7680], g_ZT[640 * 1024];
__device__ __align__(128) uint32_t g_WT[321 * 2048];
__device__ bf16 g_x1[S_ * D_], g_x2[S_ * D_], g_hN[S_ * D_];
__device__ __align__(128) uint4 g_QKV[QRING * 32 * 30720 / 16], g_O[ORING * 32 * 8192 / 16];
__device__ __align__(128) uint4 g_part[PRING * 32 * 8960 / 16];
__device__ __align__(128) uint32_t g_sync[256];
__device__ uint32_t g_comm[(4 << 20) / 4];

typedef CUresult (*EncodeFn)(CUtensorMap*, CUtensorMapDataType, cuuint32_t, void*, const cuuint64_t*, const cuuint64_t*, const cuuint32_t*, const cuuint32_t*,
                             CUtensorMapInterleave, CUtensorMapSwizzle, CUtensorMapL2promotion, CUtensorMapFloatOOBfill);
static void make_map(EncodeFn fn, CUtensorMap* m, const void* base, uint64_t cols, uint64_t rows, uint32_t bc, uint32_t br) {
  cuuint64_t dims[2] = {cols, rows}, strides[1] = {cols * 2}; cuuint32_t box[2] = {bc, br}, es[2] = {1, 1};
  fn(m, CU_TENSOR_MAP_DATA_TYPE_BFLOAT16, 2, (void*)base, dims, strides, box, es, CU_TENSOR_MAP_INTERLEAVE_NONE, CU_TENSOR_MAP_SWIZZLE_128B, CU_TENSOR_MAP_L2_PROMOTION_L2_256B, CU_TENSOR_MAP_FLOAT_OOB_FILL_NONE);
}
template <typename T> static T* sym(T& s) { void* p; cudaGetSymbolAddress(&p, s); return (T*)p; }

template <typename... KA, typename... A> static void launch(void (*k)(KA...), int grid, int block, int smem, bool pdl, int cluster, A... a) {
  cudaLaunchConfig_t cfg = {};
  cfg.gridDim = dim3(grid); cfg.blockDim = dim3(block); cfg.dynamicSmemBytes = smem; cfg.stream = cudaStreamPerThread;
  cudaLaunchAttribute at[2]; int n = 0;
  if (pdl) { at[n].id = cudaLaunchAttributeProgrammaticStreamSerialization; at[n].val.programmaticStreamSerializationAllowed = 1; n++; }
  if (cluster > 1) { at[n].id = cudaLaunchAttributeClusterDimension; at[n].val.clusterDim.x = cluster; at[n].val.clusterDim.y = 1; at[n].val.clusterDim.z = 1; n++; }
  cfg.attrs = at; cfg.numAttrs = n;
  cudaLaunchKernelEx(&cfg, k, KA(a)...);
}

extern "C" void kernel_launch(void* const* d_in, const int* in_sizes, int n_in, void* d_out, int out_size) {
  const bf16 *x = (const bf16*)d_in[0], *wr = (const bf16*)d_in[1], *wi = (const bf16*)d_in[2], *mem0 = (const bf16*)d_in[4];
  const bf16 *Wq = (const bf16*)d_in[5], *Wk = (const bf16*)d_in[6], *Wv = (const bf16*)d_in[7], *Wo = (const bf16*)d_in[8];
  bf16* out = (bf16*)d_out;
  uint32_t *Z1 = (uint32_t*)sym(g_Z1), *ZT = (uint32_t*)sym(g_ZT), *WT = (uint32_t*)sym(g_WT);
  bf16 *x1 = (bf16*)sym(g_x1), *x2 = (bf16*)sym(g_x2), *hN = (bf16*)sym(g_hN);
  char *QKV = (char*)sym(g_QKV), *part = (char*)sym(g_part);
  uint32_t* comm = (uint32_t*)(((uint64_t)sym(g_comm) + (2 << 20) - 1) & ~(uint64_t)((2 << 20) - 1));
  EncodeFn enc = nullptr; cudaDriverEntryPointQueryResult qr;
  cudaGetDriverEntryPoint("cuTensorMapEncodeTiled", (void**)&enc, cudaEnableDefault, &qr);
  CUtensorMap tmW[3], tmWo, tmX, tmP;
  { cuuint64_t dims[3] = {64, PRING * 32, 70}, strides[2] = {8960, 128}; cuuint32_t box[3] = {64, 32, 2}, es[3] = {1, 1, 1};
    enc(&tmP, CU_TENSOR_MAP_DATA_TYPE_BFLOAT16, 3, part, dims, strides, box, es, CU_TENSOR_MAP_INTERLEAVE_NONE, CU_TENSOR_MAP_SWIZZLE_128B, CU_TENSOR_MAP_L2_PROMOTION_NONE, CU_TENSOR_MAP_FLOAT_OOB_FILL_NONE); }
  { cuuint64_t dims[3] = {64, 2048, 10}, strides[2] = {1280, 128}; cuuint32_t box[3] = {64, 32, 10}, es[3] = {1, 1, 1};
    enc(&tmX, CU_TENSOR_MAP_DATA_TYPE_BFLOAT16, 3, hN, dims, strides, box, es, CU_TENSOR_MAP_INTERLEAVE_NONE, CU_TENSOR_MAP_SWIZZLE_128B, CU_TENSOR_MAP_L2_PROMOTION_L2_256B, CU_TENSOR_MAP_FLOAT_OOB_FILL_NONE); }
  make_map(enc, &tmW[0], Wq, 4096, 640, 64, 64); make_map(enc, &tmW[1], Wk, 4096, 640, 64, 64); make_map(enc, &tmW[2], Wv, 4096, 640, 64, 64);
  make_map(enc, &tmWo, Wo, 640, 4096, 64, 64);
  int dbgf = 0;
  cudaFuncSetAttribute(side_kernel, cudaFuncAttributeMaxDynamicSharedMemorySize, SD_SMEM);
  cudaFuncSetAttribute(rec_kernel, cudaFuncAttributeMaxDynamicSharedMemorySize, REC_SMEM);
  uint32_t* sy = (uint32_t*)sym(g_sync);
  RecParams rp = {{tmW[0], tmW[1], tmW[2]}, tmWo, tmX, {{x, Z1, ZT, WT, x1, hN, sy, nullptr, 45, 1}, {x2, Z1, ZT, WT, x1, hN, sy + 128, (dbgf & 16) ? nullptr : comm + FL_ROW, 0, 0}},
                  mem0, wr, wi, QKV, comm, 0x4000004000010000ull, PERIOD, C3, SLACK, XLATE, PH[4], PH[6], GAP, 0, 0, 0, dbgf, nullptr, nullptr};
  launch(rec_kernel, 96, 384, REC_SMEM, false, 3, rp);
  for (int L = 0; L < 2; L++) {
    rp.helper = 1; rp.layer = L;
    launch(rec_kernel, 35, 384, REC_SMEM, true, 1, rp);
    SideParams sp = {tmWo, tmP, QKV, (char*)sym(g_O), part, x1, L == 0 ? x2 : out, comm + L * 1024, sy + L * 128, rp.dhi, L == 0, rp.period, PH[0], PH[1], PH[2], PH[3], PH[5], PH[7], PH[8], dbgf};
    launch(side_kernel, 36, 512, SD_SMEM, true, 1, sp);
  }
}
```
